```python
import torch

def _softmax(x, axis=-1):
    return torch.softmax(x, dim=axis)

def _gelu(x):
    return torch.nn.functional.gelu(x, approximate='tanh')

def _silu(x):
    return torch.nn.functional.silu(x)

def _sigmoid(x):
    return torch.sigmoid(x)

def _layernorm(x, axis=-1, eps=1e-05):
    m = x.mean(dim=axis, keepdim=True)
    v = x.var(dim=axis, keepdim=True, unbiased=False)
    return (x - m) / torch.sqrt(v + eps)

def _scatter_add(tgt, idx, src, axis=0):
    return tgt.clone().index_add_(axis, idx, src)

def _segment_sum(src, seg, n):
    out = torch.zeros((n,) + src.shape[1:], dtype=src.dtype)
    return out.index_add_(0, seg, src)

def _pad(x, pw):
    flat = tuple((v for pair in reversed(pw) for v in pair))
    return torch.nn.functional.pad(x, flat)
kernel_name = 'adaLN_cond__ssm_conv_s4d__moe_arch_mod__prompt'

def setup_inputs():

    _w = lambda a: (lambda t: t.to(torch.bfloat16) if t.is_floating_point() else t)(torch.as_tensor(a))

    def _A_setup():
        Bsz, L, D, N = (1, 2048, 576, 128)
        return {'u': _w((lambda *s: torch.randn(*s, dtype=torch.bfloat16) * 0.1)(Bsz, L, D)), 'log_A_real': _w((lambda *s: torch.randn(*s, dtype=torch.bfloat16) * 3.2)(D, N) * 0.5), 'A_imag': _w((lambda *s: torch.randn(*s, dtype=torch.bfloat16) * 0.4)(D, N) * 3.14), 'C_real': _w((lambda *s: torch.randn(*s, dtype=torch.bfloat16) * 0.8)(D, N) / N ** 0.5), 'C_imag': _w((lambda *s: torch.randn(*s, dtype=torch.bfloat16) * 0.8)(D, N) / N ** 0.5), 'log_dt': _w((lambda *s: torch.randn(*s, dtype=torch.bfloat16) * 0.4)(D) * 0.5 - 4.0), 'D_skip': _w((lambda *s: torch.randn(*s, dtype=torch.bfloat16) * 0.4)(D))}
    _A_in = _A_setup()

    def _B_setup():
        B, S, D, F, C = (1, 2048, 576, 4608, 8)
        return {'x': _w((lambda *s: torch.randn(*s, dtype=torch.bfloat16) * 0.1)(B, S, D)), 'w_r': _w((lambda *s: torch.randn(*s, dtype=torch.bfloat16) * 0.4)(D)), 'w_gate': _w((lambda *s: torch.randn(*s, dtype=torch.bfloat16) * 0.4)(D, F)), 'w_up': _w((lambda *s: torch.randn(*s, dtype=torch.bfloat16) * 0.4)(D, F)), 'w_down': _w((lambda *s: torch.randn(*s, dtype=torch.bfloat16) * 0.4)(F, D))}
    _B_in = _B_setup()
    return {'A_u': _A_in['u'], 'A_log_A_real': _A_in['log_A_real'], 'A_A_imag': _A_in['A_imag'], 'A_C_real': _A_in['C_real'], 'A_C_imag': _A_in['C_imag'], 'A_log_dt': _A_in['log_dt'], 'A_D_skip': _A_in['D_skip'], 'B_x': _B_in['x'], 'B_w_r': _B_in['w_r'], 'B_w_gate': _B_in['w_gate'], 'B_w_up': _B_in['w_up'], 'B_w_down': _B_in['w_down'], 'c': _w((lambda *s: torch.randn(*s, dtype=torch.bfloat16) * 0.2)(1, 576) * 8.0), 'w_mod': _w((lambda *s: torch.randn(*s, dtype=torch.bfloat16) * 0.2)(576, 6 * 576) * 576 ** (-0.5) * 8.0)}

def reference(A_u, A_log_A_real, A_A_imag, A_C_real, A_C_imag, A_log_dt, A_D_skip, B_x, B_w_r, B_w_gate, B_w_up, B_w_down, c, w_mod):

    def _A_ref(u, log_A_real, A_imag, C_real, C_imag, log_dt, D_skip):
        L = u.shape[1]
        dt = torch.exp(log_dt)
        A = -torch.exp(log_A_real) + 1j * A_imag
        C = (C_real + 1j * C_imag) * dt[:, None]
        pos = (lambda x, dt: x.to(dt))(torch.arange(L), log_dt.dtype)
        P = torch.exp((A * dt[:, None])[:, :, None] * pos[None, None, :])
        K = 2.0 * torch.einsum('dn,dnl->dl', C, P).real
        L2 = 2 * L
        u_t = (lambda x, *d: x.permute(*d))(u, 0, 2, 1)
        Kf = (lambda x, *a, **k: torch.fft.rfft(x.float(), *a, **k))(K, L2)
        Uf = (lambda x, *a, **k: torch.fft.rfft(x.float(), *a, **k))(u_t, L2)
        y = (lambda x, *a, **k: torch.fft.irfft(x, *a, **k).to(torch.bfloat16))(Uf * Kf[None, :, :], L2)[:, :, :L]
        y = (lambda x, *d: x.permute(*d))(y, 0, 2, 1)
        return y + u * D_skip[None, None, :]

    def _B_ref(x, w_r, w_gate, w_up, w_down):
        B, S, D = x.shape
        C = 8
        r = x @ w_r
        idx = torch.argsort(-r, axis=-1)[:, :C]
        idx_e = (lambda x, n, axis: torch.repeat_interleave(x, n, dim=axis))(idx.reshape(B, C, 1), D, axis=2)
        x_sel = (lambda x, i, axis: torch.take_along_dim(x, i, dim=axis))(x, idx_e, axis=1)
        g = _silu(x_sel @ w_gate)
        u = x_sel @ w_up
        y = g * u @ w_down
        r_sel = _sigmoid((lambda x, i, axis: torch.take_along_dim(x, i, dim=axis))(r, idx, axis=1))
        y = y * r_sel.reshape(B, C, 1)
        b_off = (torch.arange(B) * S).reshape(B, 1)
        flat_idx = (idx + b_off).reshape(B * C)
        zero = (x * 0.0).reshape(B * S, D)
        upd = _scatter_add(zero, flat_idx, y.reshape(B * C, D), axis=0)
        return x + upd.reshape(B, S, D)
    x = A_u
    mod = (_silu(c) @ w_mod).reshape(c.shape[0], 6, 1, -1)
    sa, ca, ga, sb, cb, gb = (mod[:, 0].clone(), mod[:, 1].clone(), mod[:, 2].clone(), mod[:, 3].clone(), mod[:, 4].clone(), mod[:, 5].clone())
    h = _layernorm(x, axis=-1) * (1 + ca) + sa
    x = x + ga * _A_ref(h, A_log_A_real, A_A_imag, A_C_real, A_C_imag, A_log_dt, A_D_skip)
    h = _layernorm(x, axis=-1) * (1 + cb) + sb
    x = x + gb * _B_ref(h, B_w_r, B_w_gate, B_w_up, B_w_down)
    return x
```

```cpp
#include <cuda_runtime.h>
#include <cuda.h>
#include <cuda_bf16.h>
#include <cuda_fp16.h>
#include <stdint.h>

namespace v5 {

#define L_ 2048
#define D_ 576
#define N_ 128
#define F_ 4608
#define G_ 120
#define NCL 15
#define NTHR 768
#define SPIN_MAX (1 << 18)

typedef __nv_bfloat16 bf16;

struct Scratch {
    float4 acc1[L_ + 8];
    float4 acc2[L_];
    uint4 h2c[128 * 72];
    uint2 part[NCL * 36 * 64];
    float4 rs[32 * 8];
};
#define NRST (L_ + 128 * 72 + NCL * 36 * 32 + 256)
static_assert(NRST == 240 * G_, "reset split");
__device__ __align__(1024) Scratch g_s;

#define OFF_WG 0
#define OFF_WU 46080
#define KSCR 3456
#define OFF_WM0 69120
#define OFF_STG OFF_WM0
#define OFF_MG2 86400
#define OFF_CH 92160
#define CHS 18688
#define ULBO 656
#define XO_U8 6272
#define XO_U16 10368
#define XO_ZA 5248
#define XO_ZB 8448
#define XO_ZC 11648
#define XO_ZD 13824
#define XO_TF 12416
#define XO_TD 16000
#define XO_K1024 18624
#define XO_DSK 18628
#define XO_KINV 18640
#define XO_KLAST 18656
#define XO_MBU 18672
#define OFF_X 185600
#define XG 672
#define XI(i) (((i) >> 1) * 5520 + ((i) & 1) * 2752)
#define XN(n) ((((n) >> 1) & 3) * XG + (2 * ((n) >> 3) + ((n) & 1)) * 80)
#define OFF_V 207616
#define VP 528
#define OFF_EK (OFF_V + 512)
#define OFF_WM2 OFF_V
#define OFF_MG1 (OFF_V + 17280)
#define OFF_SC (OFF_V + 19840)
#define OFF_C1 (OFF_V + 20640)
#define OFF_MISC 228736
#define OFF_WD OFF_CH
#define OFF_H2T (OFF_CH + 46080)
#define OFF_OUT (OFF_CH + 66560)
#define ROWP 584
#define OFF_H2S 0
#define OFF_FFR 9344
#define OFF_ACT 19584
#define OFF_RS 20480

enum { MB_WM2, MB_MG1, MB_MG2, MB_KEY, MB_V, MB_RS, MB_WG, MB_WU, MB_WD, MB_KEY2, MB_EK, MB_C2, MB_CW, MB_KD, MB_OUT, MB_N };

struct Misc {
    __align__(16) uint4 box[4 * 14];
    __align__(16) unsigned int key[256], cand[128];
    __align__(16) uint4 c2[20];
    __align__(16) unsigned int fin[12];
    unsigned int ga[8], wr[20];
    float cws[2];
    unsigned long long mbar[MB_N];
};
#define SMEM_TOTAL (OFF_MISC + (int)sizeof(Misc))
static_assert(SMEM_TOTAL <= 232448, "smem");

__device__ __forceinline__ float lo2f(uint32_t w) { return __uint_as_float(w << 16); }
__device__ __forceinline__ float hi2f(uint32_t w) { return __uint_as_float(w & 0xFFFF0000u); }
__device__ __forceinline__ uint32_t pack2(float lo, float hi) { uint32_t r; asm("cvt.rn.bf16x2.f32 %0, %1, %2;" : "=r"(r) : "f"(hi), "f"(lo)); return r; }
__device__ __forceinline__ float bfr(float x) { return __uint_as_float(pack2(0.f, x)); }
__device__ __forceinline__ uint32_t f2bits(float x) { return pack2(x, 0.f); }
__device__ __forceinline__ uint32_t packh(float lo, float hi) { uint32_t r; asm("cvt.rn.f16x2.f32 %0, %1, %2;" : "=r"(r) : "f"(hi), "f"(lo)); return r; }
__device__ __forceinline__ float frcp(float x) { float r; asm("rcp.approx.ftz.f32 %0, %1;" : "=f"(r) : "f"(x)); return r; }
__device__ __forceinline__ float fsqrt(float x) { float r; asm("sqrt.approx.f32 %0, %1;" : "=f"(r) : "f"(x)); return r; }
__device__ __forceinline__ float fex2(float x) { float r; asm("ex2.approx.ftz.f32 %0, %1;" : "=f"(r) : "f"(x)); return r; }
__device__ __forceinline__ float silu(float x) { return __fdividef(x, 1.0f + __expf(-x)); }
__device__ __forceinline__ uint32_t add2(uint32_t a, uint32_t b) { uint32_t r; asm("add.rn.bf16x2 %0, %1, %2;" : "=r"(r) : "r"(a), "r"(b)); return r; }
__device__ __forceinline__ uint32_t sub2(uint32_t a, uint32_t b) { uint32_t r; asm("sub.rn.bf16x2 %0, %1, %2;" : "=r"(r) : "r"(a), "r"(b)); return r; }
__device__ __forceinline__ uint32_t mul2(uint32_t a, uint32_t b) { uint32_t r; asm("mul.rn.bf16x2 %0, %1, %2;" : "=r"(r) : "r"(a), "r"(b)); return r; }
__device__ __forceinline__ uint32_t fma2(uint32_t a, uint32_t b, uint32_t c) { uint32_t r; asm("fma.rn.bf16x2 %0, %1, %2, %3;" : "=r"(r) : "r"(a), "r"(b), "r"(c)); return r; }
__device__ __forceinline__ uint32_t norm2(uint32_t x, uint32_t m, uint32_t rh, uint32_t rl) { const uint32_t d = sub2(x, m); return fma2(d, rh, mul2(d, rl)); }

__device__ __forceinline__ void mma_bf16(float* c, uint32_t a0, uint32_t a1, uint32_t a2, uint32_t a3, uint32_t b0, uint32_t b1) {
    asm volatile("mma.sync.aligned.m16n8k16.row.col.f32.bf16.bf16.f32 {%0,%1,%2,%3}, {%4,%5,%6,%7}, {%8,%9}, {%0,%1,%2,%3};\n"
                 : "+f"(c[0]), "+f"(c[1]), "+f"(c[2]), "+f"(c[3]) : "r"(a0), "r"(a1), "r"(a2), "r"(a3), "r"(b0), "r"(b1));
}
__device__ __forceinline__ void mma_f16(float* c, const uint32_t* a, uint32_t b0, uint32_t b1) {
    asm volatile("mma.sync.aligned.m16n8k16.row.col.f32.f16.f16.f32 {%0,%1,%2,%3}, {%4,%5,%6,%7}, {%8,%9}, {%0,%1,%2,%3};\n"
                 : "+f"(c[0]), "+f"(c[1]), "+f"(c[2]), "+f"(c[3]) : "r"(a[0]), "r"(a[1]), "r"(a[2]), "r"(a[3]), "r"(b0), "r"(b1));
}
__device__ __forceinline__ void ldsm_x4(uint32_t* r, uint32_t addr) {
    asm volatile("ldmatrix.sync.aligned.m8n8.x4.shared.b16 {%0,%1,%2,%3}, [%4];" : "=r"(r[0]), "=r"(r[1]), "=r"(r[2]), "=r"(r[3]) : "r"(addr) : "memory");
}
__device__ __forceinline__ void ldsm_x4_t(uint32_t* r, uint32_t addr) {
    asm volatile("ldmatrix.sync.aligned.m8n8.x4.trans.shared.b16 {%0,%1,%2,%3}, [%4];" : "=r"(r[0]), "=r"(r[1]), "=r"(r[2]), "=r"(r[3]) : "r"(addr) : "memory");
}
__device__ __forceinline__ void stsm_x4(uint32_t addr, uint32_t r0, uint32_t r1, uint32_t r2, uint32_t r3) {
    asm volatile("stmatrix.sync.aligned.m8n8.x4.shared.b16 [%0], {%1,%2,%3,%4};" ::"r"(addr), "r"(r0), "r"(r1), "r"(r2), "r"(r3) : "memory");
}
__device__ __forceinline__ void stsm_x4_t(uint32_t addr, uint32_t r0, uint32_t r1, uint32_t r2, uint32_t r3) {
    asm volatile("stmatrix.sync.aligned.m8n8.x4.trans.shared.b16 [%0], {%1,%2,%3,%4};" ::"r"(addr), "r"(r0), "r"(r1), "r"(r2), "r"(r3) : "memory");
}
__device__ __forceinline__ uint32_t movm(uint32_t a) { uint32_t r; asm volatile("movmatrix.sync.aligned.m8n8.trans.b16 %0, %1;" : "=r"(r) : "r"(a)); return r; }
__device__ __forceinline__ uint32_t lds32(uint32_t a) { uint32_t v; asm volatile("ld.shared.u32 %0, [%1];" : "=r"(v) : "r"(a)); return v; }
__device__ __forceinline__ void sts32(uint32_t a, uint32_t v) { asm volatile("st.shared.u32 [%0], %1;" ::"r"(a), "r"(v) : "memory"); }
__device__ __forceinline__ void sts16(uint32_t a, uint32_t v) { asm volatile("st.shared.u16 [%0], %1;" ::"r"(a), "h"((unsigned short)v) : "memory"); }
__device__ __forceinline__ void named_bar(int id, int n) { asm volatile("bar.sync %0, %1;" ::"r"(id), "r"(n) : "memory"); }
__device__ __forceinline__ void named_arrive(int id, int n) { asm volatile("bar.arrive %0, %1;" ::"r"(id), "r"(n) : "memory"); }
#define CBAR() asm volatile("bar.sync 0, 640;" ::: "memory")
#define PROXY_FENCE() asm volatile("fence.proxy.async.shared::cta;" ::: "memory")

#define D4(d, o) "+f"(d[o]), "+f"(d[o + 1]), "+f"(d[o + 2]), "+f"(d[o + 3])
__device__ __forceinline__ void wg32(float* d, uint32_t a0, uint32_t a1, uint32_t a2, uint32_t a3, uint64_t desc) {
    asm volatile("wgmma.mma_async.sync.aligned.m64n32k16.f32.bf16.bf16 {%0,%1,%2,%3,%4,%5,%6,%7,%8,%9,%10,%11,%12,%13,%14,%15}, {%16,%17,%18,%19}, %20, 1, 1, 1, 0;"
                 : D4(d, 0), D4(d, 4), D4(d, 8), D4(d, 12) : "r"(a0), "r"(a1), "r"(a2), "r"(a3), "l"(desc));
}
__device__ __forceinline__ void wg48(float* d, uint32_t a0, uint32_t a1, uint32_t a2, uint32_t a3, uint64_t desc) {
    asm volatile("wgmma.mma_async.sync.aligned.m64n48k16.f32.bf16.bf16 {%0,%1,%2,%3,%4,%5,%6,%7,%8,%9,%10,%11,%12,%13,%14,%15,%16,%17,%18,%19,%20,%21,%22,%23}, {%24,%25,%26,%27}, %28, 1, 1, 1, 0;"
                 : D4(d, 0), D4(d, 4), D4(d, 8), D4(d, 12), D4(d, 16), D4(d, 20) : "r"(a0), "r"(a1), "r"(a2), "r"(a3), "l"(desc));
}
#define O4(d, o) "=f"(d[o]), "=f"(d[o + 1]), "=f"(d[o + 2]), "=f"(d[o + 3])
__device__ __forceinline__ void wg32z(float* d, uint32_t a0, uint32_t a1, uint32_t a2, uint32_t a3, uint64_t desc) {
    asm volatile("wgmma.mma_async.sync.aligned.m64n32k16.f32.bf16.bf16 {%0,%1,%2,%3,%4,%5,%6,%7,%8,%9,%10,%11,%12,%13,%14,%15}, {%16,%17,%18,%19}, %20, 0, 1, 1, 0;"
                 : O4(d, 0), O4(d, 4), O4(d, 8), O4(d, 12) : "r"(a0), "r"(a1), "r"(a2), "r"(a3), "l"(desc));
}
__device__ __forceinline__ void wg48z(float* d, uint32_t a0, uint32_t a1, uint32_t a2, uint32_t a3, uint64_t desc) {
    asm volatile("wgmma.mma_async.sync.aligned.m64n48k16.f32.bf16.bf16 {%0,%1,%2,%3,%4,%5,%6,%7,%8,%9,%10,%11,%12,%13,%14,%15,%16,%17,%18,%19,%20,%21,%22,%23}, {%24,%25,%26,%27}, %28, 0, 1, 1, 0;"
                 : O4(d, 0), O4(d, 4), O4(d, 8), O4(d, 12), O4(d, 16), O4(d, 20) : "r"(a0), "r"(a1), "r"(a2), "r"(a3), "l"(desc));
}
#define WG_FENCE() asm volatile("wgmma.fence.sync.aligned;" ::: "memory")
#define WG_COMMIT() asm volatile("wgmma.commit_group.sync.aligned;" ::: "memory")
#define WG_WAIT(n) asm volatile("wgmma.wait_group.sync.aligned " #n ";" ::: "memory")
#define TQ(p, k) p[2 * (k) + 1], p[2 * (k) + 2], p[2 * (k)], p[2 * (k) + 1]

__device__ __forceinline__ uint4 ld_nc4(const void* p) { uint4 v; asm volatile("ld.global.nc.v4.u32 {%0,%1,%2,%3}, [%4];" : "=r"(v.x), "=r"(v.y), "=r"(v.z), "=r"(v.w) : "l"(p)); return v; }
__device__ __forceinline__ unsigned short ld_nc16(const void* p) { unsigned short v; asm volatile("ld.global.nc.u16 %0, [%1];" : "=h"(v) : "l"(p)); return v; }
__device__ __forceinline__ uint32_t ld_nc(const void* p) { uint32_t v; asm volatile("ld.global.nc.u32 %0, [%1];" : "=r"(v) : "l"(p)); return v; }
__device__ __forceinline__ uint32_t ld_rlx(const unsigned int* p) { uint32_t v; asm volatile("ld.relaxed.gpu.global.u32 %0, [%1];" : "=r"(v) : "l"(p) : "memory"); return v; }
__device__ __forceinline__ uint2 ld_rlx2(const void* p) { uint2 v; asm volatile("ld.relaxed.gpu.global.v2.u32 {%0,%1}, [%2];" : "=r"(v.x), "=r"(v.y) : "l"(p) : "memory"); return v; }
__device__ __forceinline__ uint4 ld_rlx4(const void* p) { uint4 v; asm volatile("ld.relaxed.gpu.global.v4.u32 {%0,%1,%2,%3}, [%4];" : "=r"(v.x), "=r"(v.y), "=r"(v.z), "=r"(v.w) : "l"(p) : "memory"); return v; }
__device__ __forceinline__ void st_rlx(unsigned int* p, uint32_t v) { asm volatile("st.relaxed.gpu.global.u32 [%0], %1;" ::"l"(p), "r"(v) : "memory"); }
__device__ __forceinline__ void st_rlx2(void* p, uint32_t a, uint32_t b) { asm volatile("st.relaxed.gpu.global.v2.u32 [%0], {%1,%2};" ::"l"(p), "r"(a), "r"(b) : "memory"); }
__device__ __forceinline__ void st_rlx4(void* p, uint4 v) { asm volatile("st.relaxed.gpu.global.v4.u32 [%0], {%1,%2,%3,%4};" ::"l"(p), "r"(v.x), "r"(v.y), "r"(v.z), "r"(v.w) : "memory"); }
__device__ __forceinline__ void red_inc(unsigned int* p) { asm volatile("red.relaxed.gpu.global.add.u32 [%0], 1;" ::"l"(p) : "memory"); }

__device__ __forceinline__ void mbar_init(uint32_t a, int cnt) { asm volatile("mbarrier.init.shared::cta.b64 [%0], %1;" ::"r"(a), "r"(cnt) : "memory"); }
__device__ __forceinline__ void mbar_expect(uint32_t a, uint32_t bytes) { asm volatile("mbarrier.arrive.expect_tx.shared::cta.b64 _, [%0], %1;" ::"r"(a), "r"(bytes) : "memory"); }
__device__ __forceinline__ void mbar_wait(uint32_t a, uint32_t parity) {
    uint32_t ok = 0;
    int it = 0;
    do {
        asm volatile("{\n.reg .pred p;\nmbarrier.try_wait.parity.shared::cta.b64 p, [%1], %2;\nselp.u32 %0, 1, 0, p;\n}" : "=r"(ok) : "r"(a), "r"(parity) : "memory");
    } while (!ok && ++it < SPIN_MAX);
}
__device__ __forceinline__ void tma2d(uint32_t dst, const CUtensorMap* tm, int c0, int c1, uint32_t mbar) {
    asm volatile("cp.async.bulk.tensor.2d.shared::cluster.global.mbarrier::complete_tx::bytes [%0], [%1, {%3, %4}], [%2];"
                 ::"r"(dst), "l"(tm), "r"(mbar), "r"(c0), "r"(c1) : "memory");
}
__device__ __forceinline__ void bulk_s2g(void* dst, uint32_t src, uint32_t bytes) {
    asm volatile("cp.async.bulk.global.shared::cta.bulk_group [%0], [%1], %2;" ::"l"(dst), "r"(src), "r"(bytes) : "memory");
}
__device__ __forceinline__ uint32_t ld_acq(const unsigned int* p) { uint32_t v; asm volatile("ld.acquire.gpu.global.u32 %0, [%1];" : "=r"(v) : "l"(p) : "memory"); return v; }
__device__ __forceinline__ void bulk_pf(const void* src, uint32_t bytes) { asm volatile("cp.async.bulk.prefetch.L2.global [%0], %1;" ::"l"(src), "r"(bytes) : "memory"); }

struct cplx { float x, y; };
__device__ __forceinline__ cplx cmul(cplx a, cplx b) { cplx r; r.x = a.x * b.x - a.y * b.y; r.y = a.x * b.y + a.y * b.x; return r; }
__device__ __forceinline__ cplx csq(cplx a) { cplx r; r.x = a.x * a.x - a.y * a.y; r.y = 2.0f * a.x * a.y; return r; }
__device__ __forceinline__ uint32_t hcm(uint32_t x, uint32_t y, uint32_t yp) {
    const __half2 X = *(const __half2*)&x, Y = *(const __half2*)&y, YP = *(const __half2*)&yp;
    const __half2 r = __hfma2(__high2half2(X), YP, __hmul2(__low2half2(X), Y));
    return *(const uint32_t*)&r;
}
__device__ __forceinline__ void ln_stats(float s1, float s2, float& meanb, float& rinv) {
    const float mean = s1 * (1.0f / D_);
    const float den = bfr(fsqrt(bfr(bfr(fmaxf(fmaf(-mean, mean, s2 * (1.0f / D_)), 0.f)) + 1e-5f)));
    meanb = bfr(mean);
    rinv = frcp(den);
}

__device__ __forceinline__ int fresh_tid() { int v; asm volatile("mov.u32 %0, %tid.x;" : "=r"(v)); return v - 128; }
__device__ __forceinline__ void mma_k8(float* c, uint32_t a0, uint32_t a1, uint32_t b0) {
    asm volatile("mma.sync.aligned.m16n8k8.row.col.f32.bf16.bf16.f32 {%0,%1,%2,%3}, {%4,%5}, {%6}, {%0,%1,%2,%3};\n"
                 : "+f"(c[0]), "+f"(c[1]), "+f"(c[2]), "+f"(c[3]) : "r"(a0), "r"(a1), "r"(b0));
}
__device__ __forceinline__ void ldsm_x2(uint32_t* r, uint32_t addr) {
    asm volatile("ldmatrix.sync.aligned.m8n8.x2.shared.b16 {%0,%1}, [%2];" : "=r"(r[0]), "=r"(r[1]) : "r"(addr) : "memory");
}
__device__ __forceinline__ void ldsm_x2_t(uint32_t* r, uint32_t addr) {
    asm volatile("ldmatrix.sync.aligned.m8n8.x2.trans.shared.b16 {%0,%1}, [%2];" : "=r"(r[0]), "=r"(r[1]) : "r"(addr) : "memory");
}
__device__ __forceinline__ void stsm_x2(uint32_t addr, uint32_t r0, uint32_t r1) {
    asm volatile("stmatrix.sync.aligned.m8n8.x2.shared.b16 [%0], {%1,%2};" ::"r"(addr), "r"(r0), "r"(r1) : "memory");
}
__device__ __forceinline__ uint4 lds128(uint32_t a) { uint4 v; asm volatile("ld.shared.v4.u32 {%0,%1,%2,%3}, [%4];" : "=r"(v.x), "=r"(v.y), "=r"(v.z), "=r"(v.w) : "r"(a) : "memory"); return v; }
__device__ __forceinline__ uint32_t mapa(uint32_t a, uint32_t r) { uint32_t o; asm("mapa.shared::cluster.u32 %0, %1, %2;" : "=r"(o) : "r"(a), "r"(r)); return o; }
__device__ __forceinline__ void sta4(uint32_t dst, uint4 v, uint32_t mb) {
    asm volatile("st.async.weak.shared::cluster.mbarrier::complete_tx::bytes.v4.b32 [%0], {%1,%2,%3,%4}, [%5];" ::"r"(dst), "r"(v.x), "r"(v.y), "r"(v.z), "r"(v.w), "r"(mb) : "memory");
}
__device__ __forceinline__ void sta2(uint32_t dst, uint32_t a, uint32_t b, uint32_t mb) {
    asm volatile("st.async.weak.shared::cluster.mbarrier::complete_tx::bytes.v2.b32 [%0], {%1,%2}, [%3];" ::"r"(dst), "r"(a), "r"(b), "r"(mb) : "memory");
}
__device__ __forceinline__ void mbar_arrive(uint32_t a) { asm volatile("mbarrier.arrive.shared::cta.b64 _, [%0];" ::"r"(a) : "memory"); }
__device__ __forceinline__ void red4(float4* p, float a, float b, float c) {
    asm volatile("red.relaxed.gpu.global.add.v4.f32 [%0], {%1,%2,%3,%4};" ::"l"(p), "f"(a), "f"(b), "f"(c), "f"(1.0f) : "memory");
}
__device__ __forceinline__ void red4p(bool on, float4* p, float a, float b, float c) {
    asm volatile("{\n.reg .pred q;\nsetp.ne.u32 q, %5, 0;\n@q red.relaxed.gpu.global.add.v4.f32 [%0], {%1,%2,%3,%4};\n}" ::"l"(p), "f"(a), "f"(b), "f"(c), "f"(1.0f), "r"((uint32_t)on) : "memory");
}
__device__ __forceinline__ float4 ld_rlx4f(const float4* p) { float4 v; asm volatile("ld.relaxed.gpu.global.v4.f32 {%0,%1,%2,%3}, [%4];" : "=f"(v.x), "=f"(v.y), "=f"(v.z), "=f"(v.w) : "l"(p) : "memory"); return v; }
__device__ __forceinline__ void tma5d_st(const CUtensorMap* tm, int c0, int c4, uint32_t src) {
    asm volatile("cp.async.bulk.tensor.5d.global.shared::cta.bulk_group [%0, {%2, %4, %4, %4, %3}], [%1];" ::"l"(tm), "r"(src), "r"(c0), "r"(c4), "r"(0) : "memory");
}
__device__ __forceinline__ void tma2d_pf(const CUtensorMap* tm, int c0, int c1) {
    asm volatile("cp.async.bulk.prefetch.tensor.2d.L2.global [%0, {%1, %2}];" ::"l"(tm), "r"(c0), "r"(c1) : "memory");
}
__device__ __forceinline__ void pace(int clk) {
    const long long c0 = clock64();
    int it = 0;
    while (clock64() - c0 < clk && ++it < 4096) { }
}
__device__ __forceinline__ uint32_t sign2(uint32_t a) { uint32_t r; asm("prmt.b32 %0, %1, 0, 0xBB99;" : "=r"(r) : "r"(a)); return r; }
#define MB(i) (sb + OFF_MISC + (uint32_t)offsetof(Misc, mbar) + 8 * (i))
__device__ __forceinline__ void conv_channel(unsigned char* sm, uint32_t rank) {
    Misc& M = *(Misc*)(sm + OFF_MISC);
    const uint32_t sb = (uint32_t)__cvta_generic_to_shared(sm);
    const int tid = fresh_tid(), lane = tid & 31, g = lane >> 2, t = lane & 3, lr = lane & 7, lm = lane >> 3;
    const int warp_ = __shfl_sync(0xffffffffu, tid >> 5, 0), wgi = warp_ >> 2, w = warp_ & 3;
    const uint32_t cb = sb + OFF_CH + wgi * CHS;
    float D[16];
    {
        {
            const uint32_t a8 = cb + lr * ULBO + (lm + 9) * 16 + w * 64, b8 = cb + XO_U8 + lm * 128 + lr * 16 + w * 512;
            const uint32_t a16 = cb + (((2 * lr) & 7) + (lm & 1)) * ULBO + (9 + (lr >> 2) + (lm & 2)) * 16 + w * 64;
            const uint32_t b16 = cb + XO_U16 + (lm & 1) * 512 + lr * 16 + (lm >> 1) * 128 + (w >> 1) * 1024 + (w & 1) * 256;
            uint32_t r[3][4];
            mbar_wait(cb + XO_MBU, 0);
            ldsm_x4_t(r[0], a8);
            ldsm_x4_t(r[1], a16);
            if (w < 2) ldsm_x4_t(r[2], a8 + 256);
            stsm_x4(b8, r[0][0], r[0][1], r[0][2], r[0][3]);
            stsm_x4(b16, r[1][0], r[1][1], r[1][2], r[1][3]);
            if (w < 2) stsm_x4(b8 + 2048, r[2][0], r[2][1], r[2][2], r[2][3]);
        }
        PROXY_FENCE();
        named_bar(1 + wgi, 128);
        {
            float Z8[24], Z16[16];
            const uint32_t pf = cb + XO_TF + (w >> 1) * 512 + (8 + 16 * (w & 1) + g - 2 * t) * 4;
            uint32_t p[13], q[9], z8[12];
#pragma unroll
            for (int s = 0; s < 13; s++) p[s] = lds32(pf + s * 32);
            const uint32_t d8 = ((((cb + XO_U8) & 0x3FFFF) >> 4) | ((128 >> 4) << 16));
#define DZ(o) (((uint64_t)(512 >> 4) << 32) | (uint64_t)(d8 + (o)))
            WG_FENCE();
#pragma unroll
            for (int e = 0; e < 6; e++) {
                if (e == 0) wg48z(Z8, TQ(p, e), DZ(16));
                else wg48(Z8, TQ(p, e), DZ(-(e >> 1) * 32 + (1 - (e & 1)) * 16));
            }
            WG_COMMIT();
            WG_WAIT(0);
#pragma unroll
            for (int s = 0; s < 9; s++) q[s] = lds32(pf + 1024 + s * 32);
#pragma unroll
            for (int i = 0; i < 12; i++) asm volatile("cvt.rn.bf16x2.f32 %0, %1, %2;" : "=r"(z8[i]) : "f"(Z8[2 * i + 1]), "f"(Z8[2 * i]));
            WG_FENCE();
#pragma unroll
            for (int e = 0; e < 4; e++) {
                if (e == 0) wg32z(Z16, TQ(q, e), DZ(256 + 16));
                else wg32(Z16, TQ(q, e), DZ(256 - (e >> 1) * 64 + (1 - (e & 1)) * 16));
            }
            WG_COMMIT();
            WG_WAIT(0);
            named_bar(1 + wgi, 128);
            const uint32_t za = cb + ((w >> 1) ? XO_ZB : XO_ZA) + lr * 400 + (1 + 2 * (w & 1) + (lm & 1) + 4 * (lm >> 1)) * 16;
#pragma unroll
            for (int i = 0; i < 3; i++) stsm_x4(za + i * 128, z8[4 * i], z8[4 * i + 1], z8[4 * i + 2], z8[4 * i + 3]);
            const int Cz = 2 * (16 * (w & 1) + 8 * (lm & 1) + lr) + (lm >> 1);
            const uint32_t zc = cb + ((w >> 1) ? XO_ZD : XO_ZC) + (Cz & 7) * 272 + (1 + (Cz >> 3)) * 16;
#pragma unroll
            for (int ob = 0; ob < 2; ob++) stsm_x4(zc + ob * 128, pack2(Z16[8 * ob], Z16[8 * ob + 1]), pack2(Z16[8 * ob + 2], Z16[8 * ob + 3]), pack2(Z16[8 * ob + 4], Z16[8 * ob + 5]), pack2(Z16[8 * ob + 6], Z16[8 * ob + 7]));
            if (lane < 8) *(uint4*)(sm + (cb - sb) + ((w < 2) ? (XO_ZA + w * 3200 + lane * 400) : (XO_ZC + (w - 2) * 2176 + lane * 272))) = make_uint4(0, 0, 0, 0);
        }
        {
#pragma unroll
            for (int i = 0; i < 16; i++) D[i] = 0.f;
            uint32_t pa = cb + XO_TD + (8 + 16 * w + g - 2 * t) * 4;
            uint32_t dlo = (((cb + 9 * 16) & 0x3FFFF) >> 4) | ((ULBO >> 4) << 16);
#define DS(o) (((uint64_t)(128 >> 4) << 32) | (uint64_t)(dlo + (o)))
#define KST (2 * (ULBO / 16))
            uint32_t pA[9], pB[9];
#pragma unroll
            for (int s = 0; s < 9; s++) pA[s] = lds32(pa + s * 32);
#pragma unroll 1
            for (int j = 0; j < 4; j++) {
                WG_FENCE();
#pragma unroll
                for (int q = 0; q < 4; q++) wg32(D, TQ(pA, q), DS((3 - q) * KST));
                WG_COMMIT();
                WG_WAIT(1);
#pragma unroll
                for (int s = 0; s < 9; s++) pB[s] = lds32(pa + 256 + s * 32);
                WG_FENCE();
#pragma unroll
                for (int q = 0; q < 4; q++) wg32(D, TQ(pB, q), DS((3 - q) * KST - 1));
                WG_COMMIT();
                WG_WAIT(1);
#pragma unroll
                for (int s = 0; s < 9; s++) pA[s] = lds32(pa + 512 + s * 32);
                dlo -= 2; pa += 512;
            }
            pB[1] = lds32(pa + 256 + 32); pB[2] = lds32(pa + 256 + 64);
            WG_FENCE();
#pragma unroll
            for (int q = 0; q < 4; q++) wg32(D, TQ(pA, q), DS((3 - q) * KST));
            wg32(D, pB[1], pB[2], pA[8], pB[1], DS(3 * KST - 1));
            WG_COMMIT();
        }
    }
    {
        named_bar(1 + wgi, 128);
        uint32_t u[2][4];
        {
            const uint4* pq = M.box + (6 + g - 2 * t);
            auto at = [&](int k, int pitch) { const int c = 2 * w + k; return cb + (c & 7) * pitch + (c < 0 ? 0 : 16) + lr * 16; };
            const int h1 = lm & 1;
            const uint32_t h2 = (lm >> 1) * 128;
            uint32_t bA[3][4], bB[2][4], bB3[2], bC[2][4], bD[2][4], bU[4], bU1[2];
            const uint32_t p0 = at(h1, 400) + XO_ZA;
            WG_WAIT(0);
            const uint4 m0 = pq[0], m1 = pq[14];
            ldsm_x4(bA[0], p0 + h2); ldsm_x4(bA[1], at(h1 - 2, 400) + XO_ZA + h2); ldsm_x4(bA[2], at(lm - 2, 400) + XO_ZA + 256);
            ldsm_x4(bB[0], p0 + 3200 + h2); ldsm_x2(bB3, p0 + 3200 + 256); ldsm_x4(bB[1], at(-1, 400) + XO_ZB + lm * 128);
            mma_bf16(D + 4, m0.x, m0.y, 0u, m0.x, bA[0][0], bA[0][1]);
            mma_bf16(D + 8, m0.x, m0.y, 0u, m0.x, bA[0][2], bA[0][3]);
            mma_bf16(D + 12, m0.x, m0.y, 0u, m0.x, bA[2][2], bA[2][3]);
            mma_bf16(D + 4, m0.z, 0u, m0.y, m0.z, bA[1][0], bA[1][1]);
            mma_bf16(D + 8, m0.z, 0u, m0.y, m0.z, bA[1][2], bA[1][3]);
            mma_bf16(D + 12, m0.z, 0u, m0.y, m0.z, bA[2][0], bA[2][1]);
            ldsm_x4(bC[0], at(h1 - 1, 272) + XO_ZC + h2); ldsm_x4(bC[1], at(h1 - 3, 272) + XO_ZC + h2);
            const uint4 m2 = pq[28];
            const uint32_t k2 = lds32(cb + XO_K1024), x0 = m2.w & k2, x8 = pq[42].x & k2;
            mma_bf16(D + 4, m0.w, m1.x, 0u, m0.w, bB[0][0], bB[0][1]);
            mma_bf16(D + 8, m0.w, m1.x, 0u, m0.w, bB[0][2], bB[0][3]);
            mma_bf16(D + 12, m0.w, m1.x, 0u, m0.w, bB3[0], bB3[1]);
            mma_k8(D + 4, m1.x, 0u, bB[1][0]);
            ldsm_x4(bD[0], at(h1, 272) + XO_ZD + h2); ldsm_x4(bD[1], at(h1 - 2, 272) + XO_ZD + h2);
            ldsm_x4(bU, at(h1, ULBO) + 128 + h2); ldsm_x2(bU1, at(-1, ULBO) + 128 + h1 * 128);
            ldsm_x4_t(u[0], cb + 2 * w * ULBO + 144 + lane * 16); ldsm_x4_t(u[1], cb + (2 * w + 1) * ULBO + 144 + lane * 16);
            const uint32_t dk2 = __byte_perm(lds32(cb + XO_DSK), 0, ((rank + wgi) & 1) ? 0x3232 : 0x1010);
#pragma unroll
            for (int c = 0; c < 2; c++) mma_bf16(D + 8 + 4 * c, m1.y, m1.z, 0u, m1.y, bC[0][2 * c], bC[0][2 * c + 1]);
#pragma unroll
            for (int c = 0; c < 2; c++) mma_bf16(D + 8 + 4 * c, m1.w, 0u, m1.z, m1.w, bC[1][2 * c], bC[1][2 * c + 1]);
#pragma unroll
            for (int c = 0; c < 2; c++) mma_bf16(D + 8 + 4 * c, m2.x, m2.y, 0u, m2.x, bD[0][2 * c], bD[0][2 * c + 1]);
#pragma unroll
            for (int i = 0; i < 8; i++) u[i >> 2][i & 3] = mul2(u[i >> 2][i & 3], dk2);
#pragma unroll
            for (int c = 0; c < 2; c++) mma_bf16(D + 8 + 4 * c, m2.z, 0u, m2.y, m2.z, bD[1][2 * c], bD[1][2 * c + 1]);
#pragma unroll
            for (int c = 0; c < 2; c++) mma_bf16(D + 8 + 4 * c, x0, x8, 0u, x0, bU[2 * c], bU[2 * c + 1]);
#pragma unroll
            for (int c = 0; c < 2; c++) mma_bf16(D + 8 + 4 * c, m1.x, 0u, x8, 0u, bB[1][1 + c], bU1[c]);
        }
        {
            mbar_wait(MB(MB_C2), 0);
            const uint32_t ga2 = M.ga[wgi];
#pragma unroll
            for (int h = 0; h < 2; h++) {
                const uint32_t rb = mapa(sb, 2 * w + h);
#pragma unroll
                for (int j = 0; j < 4; j++) u[h][j] = mul2(ga2, add2(pack2(D[4 * j + 2 * h], D[4 * j + 2 * h + 1]), u[h][j]));
                sta4(rb + OFF_V + (5 * rank + wgi) * VP + lane * 16, make_uint4(u[h][0], u[h][1], u[h][2], u[h][3]), rb + (MB(MB_V) - sb));
            }
        }
    }
}

#define WMD 400
#define PU 1200
#define PD 400
#define LN1POS 1
#define SLOT(key) (((~(key) >> 2) & 0x78u) | ((key) & 7u))
#define ROW(key) (((~(key) << 2) & 0xE0u) | ((~(key) >> 7) & 24u) | ((~(key) >> 11) & 6u) | ((~(key) >> 9) & 1u))
#define CE(a, b) { const uint32_t hi_ = max(a, b); b = min(a, b); a = hi_; }
#define POP(k, m) if (k.x == m) { k.x = k.y; k.y = k.z; k.z = k.w; k.w = 0u; }
#define GW(w) (17 - (w))
#define CL_ARRIVE() asm volatile("barrier.cluster.arrive.relaxed.aligned;" ::: "memory")
#define CL_WAIT() asm volatile("barrier.cluster.wait.aligned;" ::: "memory")
__global__ void __cluster_dims__(8, 1, 1) __launch_bounds__(NTHR, 1)
clus_kernel(const bf16* __restrict__ x, const bf16* __restrict__ logAr, const bf16* __restrict__ Aim, const bf16* __restrict__ Cr, const bf16* __restrict__ Ci,
            const bf16* __restrict__ logdt, const bf16* __restrict__ c_in, Scratch* __restrict__ S, const bf16* __restrict__ Dskip,
            const bf16* __restrict__ w_r, const bf16* __restrict__ w_mod, bf16* __restrict__ out,
            const __grid_constant__ CUtensorMap tm_wm, const __grid_constant__ CUtensorMap tm_wg,
            const __grid_constant__ CUtensorMap tm_wu, const __grid_constant__ CUtensorMap tm_wd, const __grid_constant__ CUtensorMap tm_out) {
    extern __shared__ __align__(1024) unsigned char sm[];
    Misc& M = *(Misc*)(sm + OFF_MISC);
    const uint32_t sb = (uint32_t)__cvta_generic_to_shared(sm);
    const int tid = threadIdx.x < 128 ? threadIdx.x + 640 : threadIdx.x - 128, warp = __shfl_sync(0xffffffffu, tid >> 5, 0), lane = tid & 31;
    const int g = lane >> 2, t = lane & 3, lr = lane & 7, lm = lane >> 3;
    const int wgi = warp >> 2, w = warp & 3;
    const int b = blockIdx.x, cl = b >> 3, rk = b & 7;
    auto mod_ld = [&](uint32_t (*a)[4], uint32_t s0, uint32_t s1, int i) {
        const uint32_t wa = sb + ((lm & 1) ? s1 : s0) + (lr + 8 * (lm >> 1)) * 80 + i * 16;
#pragma unroll
        for (int ks = 0; ks < 4; ks++) ldsm_x4_t(a[ks], wa + ks * 1280);
        ldsm_x2_t(a[4], wa + 5120);
    };
    auto mod_mma2 = [&](float* d, float* e, uint32_t (*a)[4], uint32_t (*c)[4], const uint32_t* bs) {
        mma_k8(d, a[4][0], a[4][1], bs[8]); mma_k8(e, c[4][0], c[4][1], bs[8]);
#pragma unroll
        for (int ks = 0; ks < 4; ks++) {
            mma_bf16(d, a[ks][0], a[ks][1], a[ks][2], a[ks][3], bs[2 * ks], bs[2 * ks + 1]);
            mma_bf16(e, c[ks][0], c[ks][1], c[ks][2], c[ks][3], bs[2 * ks], bs[2 * ks + 1]);
        }
    };
    auto mod_st = [&](const float* d, uint32_t dst, int mb) {
#pragma unroll
        for (int h = 0; h < 2; h++) {
            const uint32_t rb = mapa(sb, t + 4 * h);
            sta2(rb + dst + g * 8, __float_as_uint(d[0]), __float_as_uint(d[2]), rb + (MB(mb) - sb));
        }
    };
    if (wgi == 5) {
        CL_ARRIVE();
        const uint32_t c_a = ld_nc((const uint32_t*)c_in + 36 * rk + lane), c_b = ld_nc((const uint32_t*)c_in + 36 * rk + 32 + t);
        {
            pace(WMD);
            const char* wp = (const char*)(w_mod + (72 * rk + 18 * w) * (6 * D_) + 40 * cl);
#pragma unroll
            for (int i = 0; i < 3; i++) {
                const uint32_t c = lane + 32 * i, row = (c * 205) >> 10;
                const char* p = wp + (row * (12 * D_ - 80) + 16 * c);
                if (c < 90) {
                    asm volatile("cp.async.cg.shared.global [%0], [%1], 16;" ::"r"(sb + OFF_WM0 + 1440 * w + 16 * c), "l"(p) : "memory");
                    asm volatile("cp.async.cg.shared.global [%0], [%1], 16;" ::"r"(sb + OFF_WM0 + 5760 + 1440 * w + 16 * c), "l"(p + 2 * D_) : "memory");
                }
            }
            if (w == 3 && lane < 20)
                asm volatile("cp.async.ca.shared.global [%0], [%1], 4, %2;" ::"r"(sb + OFF_MISC + (uint32_t)offsetof(Misc, c2) + 12 + 16 * lane), "l"((const uint32_t*)w_r + min(20 * cl + lane, D_ / 2 - 1)),
                             "r"(20 * cl + lane < D_ / 2 ? 4 : 0) : "memory");
            asm volatile("cp.async.commit_group;" ::: "memory");
        }
        auto gsum = [&](uint32_t a, int pitch) {
            float4 s = make_float4(0.f, 0.f, 0.f, 0.f);
#pragma unroll
            for (int i = 0; i < 8; i++) { const float4 q = *(const float4*)(sm + a + i * pitch); s.x += q.x; s.y += q.y; s.z += q.z; s.w += q.w; }
            return make_uint2(pack2(s.x, s.z), pack2(s.y, s.w));
        };
        auto one_plus = [&](uint32_t v) { return pack2(1.0f + lo2f(v), 1.0f + hi2f(v)); };
        {
            uint32_t bs[9], a[5][4], c[5][4];
            float d[4] = {0.f, 0.f, 0.f, 0.f}, e[4] = {0.f, 0.f, 0.f, 0.f};
            const uint32_t sc = pack2(silu(lo2f(c_a)), silu(hi2f(c_a)));
            bs[8] = pack2(silu(lo2f(c_b)), silu(hi2f(c_b)));
            if (w == 2) { sts32(sb + OFF_SC + 4 * lane, sc); sts32(sb + OFF_SC + 128 + 4 * t, bs[8]); }
#pragma unroll
            for (int ks = 0; ks < 8; ks++) bs[ks] = __shfl_sync(0xffffffffu, sc, 4 * ks + t);
            CL_WAIT();
            asm volatile("cp.async.wait_group 0;" ::: "memory");
            named_bar(10, 128);
            mod_ld(a, OFF_WM0 + 5760, OFF_WM0, w);
            mod_ld(c, OFF_WM0 + 5760, OFF_WM0, 4);
            mod_mma2(d, e, a, c, bs);
            mod_st(d, OFF_MG1 + rk * 320 + 64 * w, MB_MG1);
            if (w == 1) mod_st(e, OFF_MG1 + rk * 320 + 256, MB_MG1);
        }
#define RESET() _Pragma("unroll") for (int i = 0; i < 8; i++) if (i < 7 || lane < 16) st_rlx4((uint4*)S->acc2 + 240 * b + 32 * i + lane, make_uint4(0, 0, 0, 0))
        {
            const int n0 = 8 * w + ((3 - rk) & 3), n1 = (n0 + 4 + t) & 31, rot = (rk + 2 * w) % 5;
            const float4* ap = &S->acc1[256 * rk + 8 * (n0 + t) + g];
            const float4* aq = &S->acc1[256 * rk + 8 * n1 + g];
            named_bar(9, 640);
            if (w == 2 && lane == 0) {
#pragma unroll
                for (int i = 2; i < 6; i++) tma2d(sb + (i == 5 ? OFF_WM0 + 11520 : OFF_WM2 + (i - 2) * 5760), &tm_wm, i * D_ + 40 * cl, 72 * rk, MB(MB_WM2));
            }
            __syncwarp();
            if (w == 3) mbar_wait(MB(MB_MG1), 0);
            float4 pa = ld_rlx4f(ap), pb = ld_rlx4f(aq);
            if (w == 3) {
                const uint2 v = gsum(OFF_MG1 + 16 * min(lane, 19), 320);
                const uint32_t c1 = one_plus(v.x);
                if (lane < 20) *(uint4*)(sm + OFF_C1 + 16 * lane) = make_uint4(__byte_perm(c1, 0, 0x1010), __byte_perm(v.y, 0, 0x1010), __byte_perm(c1, 0, 0x3232), __byte_perm(v.y, 0, 0x3232));
                __syncwarp();
                named_arrive(10, 128);
            }
            uint32_t xq[2][5][4];
            uint2 cc[5];
            const uint32_t xa = sb + OFF_X + XI(2 * lm + (lr & 1)) + XN(n0 + (lr >> 1)), xb = sb + OFF_X + XI(2 * lm + (lr & 1)) + XN((n0 + 4 + (lr >> 1)) & 31);
            uint32_t ua[5];
            const uint32_t ub = mapa(sb, 0) + OFF_CH, us = mapa(sb, 1) - mapa(sb, 0) - 5 * CHS;
#pragma unroll
            for (int j = 0; j < 5; j++) {
                const int jj = j + rot - (j + rot >= 5 ? 5 : 0), ch = 8 * jj + g, d = (ch * 13) >> 6;
                ldsm_x4_t(xq[0][j], xa + 16 * jj);
                ua[j] = ub + ch * CHS + d * us;
                if (cl == 14 && jj >= 2) ua[j] = sb + OFF_STG + 2048;
            }
#pragma unroll 1
            for (int it = 0; it < SPIN_MAX && (pa.w != (float)NCL || pb.w != (float)NCL); it++) { pa = ld_rlx4f(ap); pb = ld_rlx4f(aq); }
            __syncwarp();
            float m0, r0, m1, r1;
            ln_stats(pa.x, pa.y, m0, r0);
            ln_stats(pb.x, pb.y, m1, r1);
            const uint32_t rh = pack2(r0, r1), rl = pack2(r0 - lo2f(rh), r1 - hi2f(rh));
            const uint32_t stage = sb + OFF_STG + w * 512;
            stsm_x4_t(stage + lane * 16, pack2(m0, m1), rh, rl, rl);
            __syncwarp();
            if (w != 3) named_bar(10, 128);
#pragma unroll
            for (int j = 0; j < 5; j++) {
                const int jj = j + rot - (j + rot >= 5 ? 5 : 0);
                cc[j] = *(const uint2*)(sm + OFF_C1 + 64 * jj + 8 * g);
                ldsm_x4_t(xq[1][j], xb + 16 * jj);
            }
#pragma unroll
            for (int q = 0; q < 2; q++) {
                const uint4 sm_ = lds128(stage + (2 * t + q) * 16), sh = lds128(stage + 128 + (2 * t + q) * 16), sl = lds128(stage + 256 + (2 * t + q) * 16);
                const uint32_t no = rk * ULBO + (9 + (q ? n1 : n0 + t)) * 16;
#pragma unroll
                for (int j = 0; j < 5; j++) {
                    const uint32_t v0 = add2(mul2(norm2(xq[q][j][0], sm_.x, sh.x, sl.x), cc[j].x), cc[j].y), v1 = add2(mul2(norm2(xq[q][j][1], sm_.y, sh.y, sl.y), cc[j].x), cc[j].y);
                    const uint32_t v2 = add2(mul2(norm2(xq[q][j][2], sm_.z, sh.z, sl.z), cc[j].x), cc[j].y), v3 = add2(mul2(norm2(xq[q][j][3], sm_.w, sh.w, sl.w), cc[j].x), cc[j].y);
                    asm volatile("{\n.reg .pred p;\nsetp.ge.u32 p, %6, 0x1000000;\n"
                                 "@p st.async.weak.shared::cluster.mbarrier::complete_tx::bytes.v4.b32 [%0], {%1,%2,%3,%4}, [%5];\n"
                                 "@!p st.shared.v4.b32 [%0], {%1,%2,%3,%4};\n}"
                                 ::"r"(ua[j] + no), "r"(v0), "r"(v1), "r"(v2), "r"(v3), "r"(ua[j] + XO_MBU), "r"(ua[j] ^ sb) : "memory");
                }
            }
            __syncwarp();
            if (lane < 5) mbar_arrive(sb + OFF_CH + XO_MBU + lane * CHS);
        }
        asm volatile("setmaxnreg.dec.sync.aligned.u32 40;");
        if (w) named_arrive(11, 128); else named_bar(11, 128);
        if (w == 0) {
            const int lane = fresh_tid() & 31;
            mbar_wait(MB(MB_KD), 0);
            PROXY_FENCE();
            if (lane == 0) {
#pragma unroll
                for (int i = 0; i < 3; i++) tma2d(sb + OFF_WG + i * 15360, &tm_wg, 40 * b, 192 * i, MB(MB_WG));
                mbar_wait(MB(MB_C2), 0);
                PROXY_FENCE();
#pragma unroll 1
                for (int i = 0; i < 3; i++) { pace(PU); tma2d(sb + OFF_WU + i * 15360, &tm_wu, 40 * b, 192 * i, MB(MB_WU)); }
#pragma unroll 1
                for (int i = 0; i < 9; i++) { pace(PD); tma2d_pf(&tm_wd, 64 * i, 40 * b); }
            }
            __syncwarp();
            mbar_wait(MB(MB_KD), 1);
            PROXY_FENCE();
            if (lane < 9) tma2d(sb + OFF_WD + lane * 5120, &tm_wd, 64 * lane, 40 * b, MB(MB_WD));
            __syncwarp();
        } else if (w == 1) {
            const int lane = fresh_tid() & 31;
            RESET();
            asm volatile("fence.acq_rel.gpu;" ::: "memory");
            __syncwarp();
            if (lane == 0) asm volatile("red.relaxed.gpu.global.add.f32 [%0], %1;" ::"l"(&S->acc1[L_].z), "f"(1.0f) : "memory");
        } else if (w == 2) {
            if ((fresh_tid() & 31) == 0) {
                float4 v;
                int it = 0;
                mbar_wait(MB(MB_WU), 0);
                do { v = ld_rlx4f(&S->acc1[L_]); } while (++it < SPIN_MAX && (v.z != (float)G_ || v.w != (float)NCL));
                M.cws[0] = v.x; M.cws[1] = v.y;
                mbar_arrive(MB(MB_CW));
            }
        } else {
            const int lane = fresh_tid() & 31, l20 = min(lane, 19);
            mbar_wait(MB(MB_MG2), 0);
            const uint2 v = gsum(OFF_MG2 + 16 * l20, 640), u = gsum(OFF_MG2 + 320 + 16 * l20, 640);
            const uint32_t wr = lane < 20 ? M.c2[lane].w : 0u, cb1 = one_plus(v.x), cw = mul2(cb1, wr);
            if (lane < 20) {
                M.c2[lane] = make_uint4(cb1, v.y, u.x, cw);
                M.wr[lane] = wr;
                unsigned e;
                asm volatile("mov.u32 %0, %cluster_ctarank;" : "=r"(e));
                e = 2 * lane - 5 * e;
                if (e < 5u) M.ga[e] = __byte_perm(u.y, 0, 0x1010);
                if (e + 1u < 5u) M.ga[e + 1u] = __byte_perm(u.y, 0, 0x3232);
            }
            __syncwarp();
            if (lane == 0) mbar_arrive(MB(MB_C2));
            if (rk == 0) {
                float a = lo2f(cw) + hi2f(cw), s = lo2f(v.y) * lo2f(wr) + hi2f(v.y) * hi2f(wr);
#pragma unroll
                for (int o = 16; o; o >>= 1) { a += __shfl_xor_sync(0xffffffffu, a, o); s += __shfl_xor_sync(0xffffffffu, s, o); }
                if (lane == 0) red4(&S->acc1[L_], a, s, 0.f);
            }
        }
        {
        const int lane = fresh_tid() & 31, g = lane >> 2, t = lane & 3, lr = lane & 7, lm = lane >> 3;
        uint32_t aw[5];
        __syncwarp();
        mbar_wait(MB(MB_C2), 0);
#pragma unroll
        for (int j = 0; j < 5; j++) aw[j] = M.wr[4 * j + t];
        const int ph = w >> 1, lst = 2 * rk + (w & 1);
        const uint32_t rb = mapa(sb, lr);
        uint4* dst = &S->h2c[(8 * lst + 4 * ph + t) * 72 + 5 * cl + g];
        named_bar(6, 768);
        uint4 k = *(const uint4*)&M.key[128 * (w & 1) + 4 * lane];
        CE(k.x, k.y); CE(k.z, k.w); CE(k.x, k.z); CE(k.y, k.w); CE(k.y, k.z);
        uint32_t m[4];
#pragma unroll 1
        for (int q = 0; q <= ph; q++) {
#pragma unroll
            for (int rnd = 0; rnd < 4; rnd++) {
                m[rnd] = __reduce_max_sync(0xffffffffu, k.x);
                POP(k, m[rnd]);
            }
        }
#pragma unroll
        for (int rnd = 0; rnd < 4; rnd++) m[rnd] |= 4 * ph + rnd;
        const uint32_t cd = rb + OFF_MISC + (uint32_t)offsetof(Misc, cand) + (16 * ph + lst) * 16;
        if (lane < 8) sta4(cd, make_uint4(m[0], m[1], m[2], m[3]), rb + ((ph ? MB(MB_KEY2) : MB(MB_KEY)) - sb));
        const uint32_t mine = (t & 2) ? ((t & 1) ? m[3] : m[2]) : ((t & 1) ? m[1] : m[0]);
        const uint32_t ra = sb + OFF_H2T + ROW(mine) * 80;
        uint32_t bq[6];
        float rr[4] = {0.f, 0.f, 0.f, 0.f};
        named_bar(7, 640);
        const uint4 a = lds128(ra + 16 * g);
        ldsm_x4(bq, ra + 16 * lm); ldsm_x2(bq + 4, ra + 64);
        if (g < (cl < 14 ? 5 : 2)) st_rlx4(dst, make_uint4(~a.x, ~a.y, ~a.z, ~a.w));
        mma_bf16(rr, aw[0], aw[0], aw[1], aw[1], bq[0], bq[1]); mma_bf16(rr, aw[2], aw[2], aw[3], aw[3], bq[2], bq[3]); mma_k8(rr, aw[4], aw[4], bq[4]);
        float4* p = &S->rs[8 * (16 * ph + lst)];
        if (lane < 2) red4(p + lane, rr[0], 1.0f, rr[1]);
        float4 e0 = ld_rlx4f(p), e1 = ld_rlx4f(p + 1);
        uint32_t col = 0, m8 = 0;
        if (w == 1) {
            mbar_wait(MB(MB_KEY), 0);
            mbar_wait(MB(MB_KEY2), 0);
            k = *(const uint4*)&M.cand[4 * lane];
            if (b == 0 && lane == 0) st_rlx4(&S->acc1[L_], make_uint4(0, 0, 0, 0));
#pragma unroll
            for (int rnd = 0; rnd < 8; rnd++) {
                m8 = __reduce_max_sync(0xffffffffu, k.x);
                POP(k, m8);
                if (lr == rnd) col = m8;
            }
        }
#pragma unroll 1
        for (int it = 0; it < SPIN_MAX && (e0.w != (float)NCL || e1.w != (float)NCL); it++) { e0 = ld_rlx4f(p); e1 = ld_rlx4f(p + 1); }
        {
            const uint32_t r0 = pack2(e0.x, e0.z), r1 = pack2(e1.x, e1.z);
            const uint32_t o0 = r0 ^ (sign2(r0) | 0x80008000u), o1 = r1 ^ (sign2(r1) | 0x80008000u);
            if (lane < 8) sta4(rb + OFF_EK + (16 * ph + lst) * VP, make_uint4((o0 << 16) | (m[0] & 0x3FFFu), (o0 & 0xFFFF0000u) | (m[1] & 0x3FFFu), (o1 << 16) | (m[2] & 0x3FFFu), (o1 & 0xFFFF0000u) | (m[3] & 0x3FFFu)),
                               rb + (MB(MB_EK) - sb));
        }
        if (w == 0) {
            named_bar(8, 64);
            if (lane == 0) {
                PROXY_FENCE();
                tma5d_st(&tm_out, 40 * cl, 8 * rk, sb + OFF_OUT);
                asm volatile("cp.async.bulk.commit_group;" ::: "memory");
                asm volatile("cp.async.bulk.wait_group 0;" ::: "memory");
                mbar_arrive(MB(MB_OUT));
            }
        } else if (w == 1) {
            const uint4 k0 = *(const uint4*)&M.cand[4 * lane];
            mbar_wait(MB(MB_EK), 0);
            k = lds128(sb + OFF_EK + lane * VP);
            col = lds32(sb + OFF_EK + (((col & 4u) << 2) | ((~col >> 5) & 15u)) * VP + (col & 3u) * 4);
            const uint32_t lo = min(min(k0.x >= m8 ? k.x : ~0u, k0.y >= m8 ? k.y : ~0u), min(k0.z >= m8 ? k.z : ~0u, k0.w >= m8 ? k.w : ~0u));
            const uint32_t hi = max(max(k0.x >= m8 ? 0u : k.x, k0.y >= m8 ? 0u : k.y), max(k0.z >= m8 ? 0u : k.z, k0.w >= m8 ? 0u : k.w));
            const bool redo = __reduce_max_sync(0xffffffffu, hi) > __reduce_min_sync(0xffffffffu, lo);
            if (redo) {
                CE(k.x, k.y); CE(k.z, k.w); CE(k.x, k.z); CE(k.y, k.w); CE(k.y, k.z);
#pragma unroll 1
                for (int rnd = 0; rnd < 8; rnd++) {
                    m8 = __reduce_max_sync(0xffffffffu, k.x);
                    POP(k, m8);
                    if (lr == rnd) col = m8;
                }
            }
            if (lane < 9) M.fin[lane] = lane < 8 ? col : redo;
            __syncwarp();
            named_arrive(12, 672);
        }
        }
    } else {
    if (warp != 19) CL_ARRIVE();
    const int chn = 40 * cl + 5 * rk + wgi;
    const bool has_ch = chn < D_;
    const uint32_t cb = sb + OFF_CH + wgi * CHS;
    unsigned short r_ldt = 0, r_lar = 0, r_aim = 0, r_cr = 0, r_ci = 0;
    {
        const int n = min(chn, D_ - 1) * N_ + (tid & 127);
        r_ldt = ld_nc16((const unsigned short*)logdt + min(chn, D_ - 1));
        r_lar = ld_nc16((const unsigned short*)logAr + n);
        r_aim = ld_nc16((const unsigned short*)Aim + n);
        r_cr = ld_nc16((const unsigned short*)Cr + n);
        r_ci = ld_nc16((const unsigned short*)Ci + n);
    }
    if (warp == 19) {
        if (lane == 0) asm volatile("prefetch.tensormap [%0];" ::"l"(&tm_wm) : "memory");
        const uint32_t lo = 90u | (10u << 8) | (20u << 16) | (1u << 24), hi = (cl == 14 ? 32u : 80u) | ((rk < 4 ? 40u : 32u) << 8) | (180u << 16) | (180u << 24);
        const uint32_t tx = lane < 8 ? (((lane & 4 ? hi : lo) >> (8 * (lane & 3))) & 255u) : lane == 8 ? 180u : lane < 11 ? lane - 8u : 14u;
        if (lane == 0) {
#pragma unroll
            for (int i = 0; i < MB_N; i++) mbar_init(MB(i), i == MB_KD ? 20 : 1);
#pragma unroll
            for (int i = 0; i < 5; i++) mbar_init(sb + OFF_CH + XO_MBU + i * CHS, 5);
        }
        __syncwarp();
        if (lane < 16) mbar_expect(lane < MB_C2 ? MB(lane) : sb + OFF_CH + XO_MBU + (lane - MB_C2) * CHS, tx << 8);
        asm volatile("fence.mbarrier_init.release.cluster;" ::: "memory");
        __syncwarp();
        CL_ARRIVE();
    }
    if (warp < 16) {
        const char* xp = (const char*)(x + (128 * warp + 8 * rk) * D_ + 40 * cl);
#pragma unroll
        for (int i = 0; i < 3; i++) {
            const uint32_t c = lane + 32 * i, row = (c * 205) >> 10, hi = c >= 40;
            if (c < 80) asm volatile("cp.async.cg.shared.global [%0], [%1], 16, %2;" ::"r"(sb + OFF_X + XN(2 * warp) + XI(row & 7) + 80 * (hi - row) + 16 * c), "l"(xp + (row * (2 * D_ - 80) + 16 * c + hi * (56 * 2 * D_))),
                                     "r"((cl < 14 || c - 5 * row < 2) ? 16 : 0) : "memory");
        }
    }
    if ((tid & 127) == 32) asm volatile("cp.async.ca.shared.global [%0], [%1], 4;" ::"r"(cb + XO_DSK), "l"((const uint32_t*)Dskip + (min(chn, D_ - 1) >> 1)) : "memory");
    asm volatile("cp.async.commit_group;" ::: "memory");
    auto mod2 = [&]() {
        if (wgi == 4) {
            uint32_t bs[9], a[5][4], c[5][4];
            float d[4] = {0.f, 0.f, 0.f, 0.f}, e[4] = {0.f, 0.f, 0.f, 0.f}, f[4] = {0.f, 0.f, 0.f, 0.f};
            mbar_wait(MB(MB_MG1), 0);
#pragma unroll
            for (int ks = 0; ks < 9; ks++) bs[ks] = lds32(sb + OFF_SC + 16 * ks + 4 * t);
            mbar_wait(MB(MB_WM2), 0);
            mod_ld(a, OFF_WM2 + 11520, OFF_WM2 + 5760, w);
            mod_ld(c, OFF_WM0 + 11520, OFF_WM2, w);
            mod_mma2(d, e, a, c, bs);
            mod_ld(a, (w & 1) ? OFF_WM0 + 11520 : OFF_WM2 + 11520, (w & 1) ? OFF_WM2 : OFF_WM2 + 5760, 4);
            mod_st(d, OFF_MG2 + rk * 640 + 64 * w, MB_MG2);
            mod_st(e, OFF_MG2 + rk * 640 + 320 + 64 * w, MB_MG2);
            d[0] = d[1] = d[2] = d[3] = 0.f;
            mma_k8(d, a[4][0], a[4][1], bs[8]);
#pragma unroll
            for (int ks = 0; ks < 4; ks++) mma_bf16((ks & 1) ? d : f, a[ks][0], a[ks][1], a[ks][2], a[ks][3], bs[2 * ks], bs[2 * ks + 1]);
            d[0] += f[0]; d[2] += f[2];
            if (w < 2) mod_st(d, OFF_MG2 + rk * 640 + 320 * w + 256, MB_MG2);
            __syncwarp();
        }
    };
    auto ln1 = [&]() {
        if (warp < 16) {
            uint32_t a[10];
            const uint32_t xa = sb + OFF_X + XN(2 * warp) + (lm & 1) * 80 + XI(lr) + (lm >> 1) * 16;
            asm volatile("cp.async.wait_group 0;" ::: "memory");
            __syncwarp();
            ldsm_x4(a, xa); ldsm_x4(a + 4, xa + 32); ldsm_x2(a + 8, xa + 64);
            named_arrive(9, 640);
            float c1[4] = {0.f, 0.f, 0.f, 0.f}, c2[4] = {0.f, 0.f, 0.f, 0.f}, c3[4] = {0.f, 0.f, 0.f, 0.f};
#pragma unroll
            for (int j = 0; j < 2; j++) {
                mma_bf16(c1, a[4 * j], a[4 * j + 1], a[4 * j + 2], a[4 * j + 3], 0x3F803F80u, 0x3F803F80u);
                mma_bf16(c2, a[4 * j], a[4 * j + 1], a[4 * j + 2], a[4 * j + 3], a[4 * j], a[4 * j + 2]);
                mma_bf16(c3, a[4 * j], a[4 * j + 1], a[4 * j + 2], a[4 * j + 3], a[4 * j + 1], a[4 * j + 3]);
            }
            mma_k8(c1, a[8], a[9], 0x3F803F80u); mma_k8(c2, a[8], a[9], a[8]); mma_k8(c3, a[8], a[9], a[9]);
            float4* p = &S->acc1[256 * rk + 16 * warp + g];
            red4p(t == (g >> 1), p, c1[0], (g & 1) ? c2[1] : c2[0], 0.f);
            red4p(t == (g >> 1), p + 8, c1[2], (g & 1) ? c3[3] : c3[2], 0.f);
        }
    };
    {
        const int i = tid & 127;
        unsigned char* cp = sm + OFF_CH + wgi * CHS;
        const uint4 z = make_uint4(0, 0, 0, 0);
        *(uint4*)(cp + XO_TD + i * 16) = z;
        *(uint4*)(cp + XO_TF + i * 16) = z;
        *(uint4*)(cp + XO_U8 - 1024 + (i >> 6) * 4096 + (i & 63) * 16) = z;
        const int c = (i * 57) >> 9;
        if (i < 108) *(uint4*)(cp + (i < 72 ? c * ULBO + (i - 9 * c) * 16 : XO_TD + 2048 - 72 * 16 + i * 16)) = z;
    }
    if (tid < 224) {
        const int e = tid & 15, l = (tid >> 4) - 6 - (int)((0x3355544433666ull >> (4 * e)) & 15) + 8 * (int)((0x1021021010210ull >> (4 * e)) & 15);
        const unsigned wd = (0x1166688822444ull >> (4 * e)) & 15, one = e >= 11 ? 0xFFFFu : 0x3F80u;
        ((uint32_t*)M.box)[((e >> 2) * 14 + (tid >> 4)) * 4 + (e & 3)] = ((unsigned)l <= wd ? one : 0u) | ((unsigned)(l - 1) <= wd ? one << 16 : 0u);
    }
    const uint32_t scr = sb + warp * KSCR, ws = scr + lane * 4;
    {
        uint32_t zr;
        asm volatile("ld.volatile.shared.u32 %0, [%1];" : "=r"(zr) : "r"(cb + XO_TD + (tid & 127) * 16) : "memory");
        const float p_ldt = __uint_as_float(r_ldt * 65536u + zr), p_lar = __uint_as_float(r_lar * 65536u + zr), p_aim = __uint_as_float(r_aim * 65536u + zr);
        const float p_cr = __uint_as_float(r_cr * 65536u + zr), p_ci = __uint_as_float(r_ci * 65536u + zr);
        float acc[5][4];
        uint32_t afr[4][4], cz[4];
        const uint32_t ba = scr + lr * 144 + lm * 16;
        auto tile = [&](float* c, int rg) {
            __syncwarp();
            c[0] = c[1] = c[2] = c[3] = 0.f;
            uint32_t bb[2][4];
            ldsm_x4(bb[0], ba + rg * 1152);
            ldsm_x4(bb[1], ba + rg * 1152 + 64);
            mma_f16(c, afr[0], bb[0][0], bb[0][1]);
            mma_f16(c, afr[1], bb[0][2], bb[0][3]);
            mma_f16(c, afr[2], bb[1][0], bb[1][1]);
            mma_f16(c, afr[3], bb[1][2], bb[1][3]);
        };
#define CJ(z) packh((z).x, -(z).y)
#define CJP(z) packh((z).y, (z).x)
        const float dt = bfr(expf(p_ldt));
        const float al = -bfr(expf(p_lar)) * dt * 1.4426950408889634f;
        const float th = p_aim * dt;
        const float th_ = th * 0.15915494309189535f;
        const float tl_ = fmaf(th, 0.15915494309189535f, -th_) + th * 6.4206382e-9f;
        auto anchor = [&](float s) {
            float f = th_ * s;
            f -= rintf(f);
            f = fmaf(tl_, s, f) * 6.283185307179586f;
            const float e = fex2(al * s);
            return cplx{e * __cosf(f), e * __sinf(f)};
        };
        const float cx = p_cr * dt * 2.0f, cy = p_ci * dt * 2.0f;
        const uint32_t ex = __reduce_max_sync(0xffffffffu, __float_as_uint(fmaxf(fabsf(cx), fabsf(cy)))) >> 23;
        const float scl = __uint_as_float((254u - ex) << 23);
        const cplx C = cplx{cx * scl, cy * scl};
        const cplx z1 = anchor(1.f), z16 = anchor(16.f), z256 = anchor(256.f);
        {
            const cplx z32 = csq(z16), z48 = cmul(z32, z16), z64 = csq(z32), z128 = csq(z64), z192 = cmul(z128, z64);
            const uint32_t y[3] = {packh(z16.x, z16.y), packh(z32.x, z32.y), packh(z48.x, z48.y)};
            const uint32_t yp[3] = {packh(-z16.y, z16.x), packh(-z32.y, z32.x), packh(-z48.y, z48.x)};
            const uint32_t xx[3] = {packh(z64.x, z64.y), packh(z128.x, z128.y), packh(z192.x, z192.y)};
            sts32(ws, 0x00003C00u);
#pragma unroll
            for (int j = 0; j < 3; j++) sts32(ws + (1 + j) * 144, y[j]);
#pragma unroll
            for (int i = 0; i < 3; i++) {
                sts32(ws + (4 + 4 * i) * 144, xx[i]);
#pragma unroll
                for (int j = 0; j < 3; j++) sts32(ws + (5 + 4 * i + j) * 144, hcm(xx[i], y[j], yp[j]));
            }
        }
        ln1();
        const cplx z2 = csq(z1);
        {
            const cplx z3 = cmul(z2, z1), z4 = csq(z2), z8 = csq(z4);
            const cplx c4 = cmul(C, z4), c8 = cmul(C, z8), c12 = cmul(c8, z4);
            cz[0] = packh(C.x, -C.y); cz[1] = packh(c4.x, -c4.y); cz[2] = packh(c8.x, -c8.y); cz[3] = packh(c12.x, -c12.y);
            __syncwarp();
#pragma unroll
            for (int s = 0; s < 4; s++) ldsm_x4(afr[s], scr + (lr + 8 * (lm & 1)) * 144 + (2 * s + (lm >> 1)) * 16);
            const uint32_t y[3] = {CJ(z1), CJ(z2), CJ(z3)}, yp[3] = {CJP(z1), CJP(z2), CJP(z3)};
#pragma unroll
            for (int tt = 0; tt < 2; tt++) {
                const int rg = tt ? 0 : 2;
#pragma unroll
                for (int i = 0; i < 2; i++) {
                    sts32(ws + rg * 1152 + (4 * i) * 144, cz[2 * tt + i]);
#pragma unroll
                    for (int j = 0; j < 3; j++) sts32(ws + rg * 1152 + (4 * i + 1 + j) * 144, hcm(cz[2 * tt + i], y[j], yp[j]));
                }
                tile(acc[tt], rg);
            }
        }
        const cplx z258 = cmul(z256, z2), z512 = csq(z256), z768 = cmul(z512, z256);
        {
            const uint32_t a0 = CJ(z256), a0p = CJP(z256), a1 = CJ(z258), a1p = CJP(z258);
#pragma unroll
            for (int i = 0; i < 4; i++) { sts32(ws + 1152 + (2 * i) * 144, hcm(cz[i], a0, a0p)); sts32(ws + 1152 + (2 * i + 1) * 144, hcm(cz[i], a1, a1p)); }
            tile(acc[2], 1);
        }
        {
            const uint32_t a0 = CJ(z512), a0p = CJP(z512), a1 = CJ(z768), a1p = CJP(z768);
#pragma unroll
            for (int i = 0; i < 4; i++) { sts32(ws + 2304 + i * 144, hcm(cz[i], a0, a0p)); sts32(ws + 2304 + (4 + i) * 144, hcm(cz[i], a1, a1p)); }
            tile(acc[3], 2);
        }
        const cplx z1024 = csq(z512);
        {
            const cplx zk[4] = {z1024, cmul(z1024, z256), csq(z768), cmul(z1024, z768)};
#pragma unroll
            for (int h = 0; h < 4; h++) {
                const uint32_t a0 = CJ(zk[h]), a0p = CJP(zk[h]);
                sts32(ws + (2 * h) * 144, hcm(cz[0], a0, a0p));
                sts32(ws + (2 * h + 1) * 144, hcm(cz[2], a0, a0p));
            }
            tile(acc[4], 0);
        }
        const cplx z2048 = csq(z1024);
        float last = C.x * z2048.x - C.y * z2048.y;
#pragma unroll
        for (int o = 16; o; o >>= 1) last += __shfl_xor_sync(0xffffffffu, last, o);
        __syncwarp();
#pragma unroll
        for (int i = 0; i < 5; i++) *(float4*)(sm + (scr - sb) + i * 512 + lane * 16) = make_float4(acc[i][0], acc[i][1], acc[i][2], acc[i][3]);
        if (lane == 0) { const float inv = __uint_as_float(ex << 23); sts32(cb + XO_KINV + 4 * w, __float_as_uint(inv)); sts32(cb + XO_KLAST + 4 * w, __float_as_uint(last * inv)); }
        asm volatile("cp.async.wait_group 0;" ::: "memory");
        CL_WAIT();
        named_bar(1 + wgi, 128);
        const uint32_t td = cb + XO_TD + 64 * 4, tf = cb + XO_TF - 32 * 4;
        const float4 ki = *(const float4*)(sm + (cb - sb) + XO_KINV);
        auto fsum = [&](int off, uint32_t& r0, uint32_t& r1) {
            const unsigned char* p = sm + wgi * (4 * KSCR) + off;
            const float4 a = *(const float4*)p, b2 = *(const float4*)(p + KSCR), c = *(const float4*)(p + 2 * KSCR), d = *(const float4*)(p + 3 * KSCR);
            r0 = pack2(fmaf(a.y, ki.x, b2.y * ki.y) + fmaf(c.y, ki.z, d.y * ki.w), fmaf(a.x, ki.x, b2.x * ki.y) + fmaf(c.x, ki.z, d.x * ki.w));
            r1 = pack2(fmaf(a.w, ki.x, b2.w * ki.y) + fmaf(c.w, ki.z, d.w * ki.w), fmaf(a.z, ki.x, b2.z * ki.y) + fmaf(c.z, ki.z, d.z * ki.w));
        };
        uint32_t r[2], q[2];
        fsum(w * 512 + lane * 16, r[0], r[1]);
        fsum(2048 + w * 128 + lr * 16, q[0], q[1]);
        __syncwarp();
        if (lane == 0) mbar_arrive(MB(MB_KD));
        if (w < 2) {
            const uint32_t p = td + (16 * g + 8 * w + 2 * t) * 4;
#pragma unroll
            for (int h = 0; h < 2; h++) { sts16(p + h * 512, r[h] >> 16); sts32(p + h * 512 + 4, r[h]); sts16(p + h * 512 + 10, r[h]); }
        } else if (w == 2) {
            const uint32_t p = td + (256 + 16 * g + 4 * t) * 4;
#pragma unroll
            for (int h = 0; h < 2; h++) {
                const uint32_t k0 = r[h] >> 16;
                if (h || lane) { sts16(p + h * 512 - 4, k0); sts16(p + h * 512 + 2, k0); }
                sts16(p + h * 512, k0); sts32(p + h * 512 + 4, __byte_perm(r[h], 0, 0x3232)); sts32(p + h * 512 + 8, r[h]); sts16(p + h * 512 + 14, r[h]);
            }
        } else {
            const uint32_t p = tf + (64 + 32 * (t >> 1) + 2 * g + (t & 1)) * 4;
#pragma unroll
            for (int h = 0; h < 2; h++) {
                const uint32_t k0 = r[h] >> 16;
                sts16(p + h * 64 + 512, r[h]); sts16(p + h * 64 + 518, r[h]);
                if (h || lane) { sts16(p + h * 64 - 4, k0); sts16(p + h * 64 + 2, k0); }
            }
            if (lane == 0) {
                const uint32_t dd = __byte_perm(r[0], 0, 0x3232);
                sts16(td + 511 * 4, dd); sts32(td + 512 * 4, dd); sts32(td + 513 * 4, dd); sts32(td + 514 * 4, dd); sts16(td + 515 * 4 + 2, dd);
            }
        }
        if (lane < 8) {
            const uint32_t p = tf + 1024 + (64 + 16 * t + 2 * w + g) * 4;
#pragma unroll
            for (int h = 0; h < 2; h++) {
                const uint32_t k0 = q[h] >> 16;
                sts16(p + h * 32 + 512, q[h]); sts16(p + h * 32 + 518, q[h]);
                if (h || (tid & 127)) { sts16(p + h * 32 - 4, k0); sts16(p + h * 32 + 2, k0); }
            }
            if ((tid & 127) == 0) {
                const float4 kl4 = *(const float4*)(sm + (cb - sb) + XO_KLAST);
                const uint32_t kl = f2bits((kl4.x + kl4.y) + (kl4.z + kl4.w)), dd = __byte_perm(q[0], 0, 0x3232);
                sts16(tf + 127 * 4, dd); sts16(tf + 128 * 4 + 2, dd); sts32(cb + XO_K1024, dd);
                sts16(tf + 1024 + 127 * 4, kl); sts16(tf + 1024 + 128 * 4 + 2, kl);
            }
        }
        __syncwarp();
        mod2();
        asm volatile("setmaxnreg.inc.sync.aligned.u32 88;");
    }
    if (has_ch) {
        conv_channel(sm, rk);
    } else {
        mbar_wait(MB(MB_WG), 0);
        mbar_wait(MB(MB_C2), 0);
    }
    {
    const int tid = fresh_tid(), warp = __shfl_sync(0xffffffffu, tid >> 5, 0), lane = tid & 31;
    const int g = lane >> 2, t = lane & 3, lr = lane & 7, lm = lane >> 3;
    __syncwarp();
    if (lane == 0) mbar_arrive(MB(MB_KD));
    uint32_t x1[10];
    if (warp < 16) {
        uint32_t bw[5], v[10];
#pragma unroll
        for (int j = 0; j < 5; j++) bw[j] = (g & 1) ? M.c2[4 * j + t].w : 0x3F803F80u;
        const uint32_t xa = sb + OFF_X + XI(warp >> 1) + (2 * (warp & 1) + (lm & 1)) * XG + lr * 80 + (lm >> 1) * 16;
        const uint32_t va = sb + OFF_V + (8 * (lm >> 1) + lr) * VP + 32 * warp + 16 * (lm & 1);
        ldsm_x4(x1, xa); ldsm_x4(x1 + 4, xa + 32); ldsm_x2(x1 + 8, xa + 64);
        mbar_wait(MB(MB_CW), 0);
        mbar_wait(MB(MB_V), 0);
        ldsm_x4_t(v, va); ldsm_x4_t(v + 4, va + 16 * VP); ldsm_x2_t(v + 8, va + 32 * VP);
#pragma unroll
        for (int i = 0; i < 10; i++) x1[i] = add2(x1[i], (i >= 4 && cl == 14) ? 0u : v[i]);
        float c1[4] = {0.f, 0.f, 0.f, 0.f}, c2[4] = {0.f, 0.f, 0.f, 0.f}, c3[4] = {0.f, 0.f, 0.f, 0.f};
#pragma unroll
        for (int j = 0; j < 2; j++) {
            mma_bf16(c1, x1[4 * j], x1[4 * j + 1], x1[4 * j + 2], x1[4 * j + 3], bw[2 * j], bw[2 * j + 1]);
            mma_bf16(c2, x1[4 * j], x1[4 * j + 1], x1[4 * j + 2], x1[4 * j + 3], x1[4 * j], x1[4 * j + 2]);
            mma_bf16(c3, x1[4 * j], x1[4 * j + 1], x1[4 * j + 2], x1[4 * j + 3], x1[4 * j + 1], x1[4 * j + 3]);
        }
        mma_k8(c1, x1[8], x1[9], bw[4]); mma_k8(c2, x1[8], x1[9], x1[8]); mma_k8(c3, x1[8], x1[9], x1[9]);
        if (t == (g >> 1)) {
            float4* p = &S->acc2[256 * rk + 16 * warp + g];
            red4(p, c1[0], (g & 1) ? c2[1] : c2[0], c1[1]);
            red4(p + 8, c1[2], (g & 1) ? c3[3] : c3[2], c1[3]);
        }
        __syncwarp();
    }
    uint32_t wf[9][4], wd[2][3][4];
    const int fmt = warp >> 2, fsl = warp & 3;
    {
        mbar_wait(MB(MB_WG), 0);
        mbar_wait(MB(MB_WU), 0);
        const int half = lm & 1;
        const uint32_t base = (fmt == 4) ? ((half ? OFF_WU : OFF_WG) + 64) : ((fmt >> 1) * OFF_WU + ((2 * (fmt & 1) + half) << 4));
        const uint32_t wa = sb + base + (144 * fsl + lr + 8 * (lm >> 1)) * 80;
#pragma unroll
        for (int ks = 0; ks < 9; ks++) ldsm_x4_t(wf[ks], wa + ks * 1280);
    }
    if (warp < 16) {
        const float4* ap = &S->acc2[256 * rk + 16 * warp + g];
        float4 s[2];
        s[0] = ld_rlx4f(ap); s[1] = ld_rlx4f(ap + 8);
        uint4 kc[5];
#pragma unroll
        for (int j = 0; j < 5; j++) kc[j] = M.c2[4 * j + t];
        const float cw = M.cws[0], sbw = M.cws[1];
        uint32_t tk0 = (2047 - (((g & 6) << 8) + 256 * (warp & 1) + ((g & 1) << 6) + 8 * rk + (warp >> 1))) << 3;
        uint32_t ta = sb + OFF_H2T + (16 * warp + (lane & 15)) * 80 + (lane >> 4) * 16, ka = sb + OFF_MISC + (uint32_t)offsetof(Misc, key) + (16 * warp + g) * 4;
        asm volatile("" : "+r"(tk0), "+r"(ta), "+r"(ka));
        mbar_wait(MB(MB_KD), 1);
#pragma unroll 1
        for (int it = 0; it < SPIN_MAX && (s[0].w != (float)NCL || s[1].w != (float)NCL); it++) { s[0] = ld_rlx4f(ap); s[1] = ld_rlx4f(ap + 8); }
        __syncwarp();
        uint32_t st[2][3];
#pragma unroll
        for (int h = 0; h < 2; h++) {
            float meanb, rinv;
            ln_stats(s[h].x, s[h].y, meanb, rinv);
            const uint32_t rbits = __float_as_uint(fmaf(fmaf(-meanb, cw, s[h].z), rinv, sbw));
            const uint32_t key = ((rbits ^ (((int)rbits >> 31) | 0x80000000u)) & 0xFFFFC000u) | (tk0 - 1024 * h);
            if (t == 0) sts32(ka + 32 * h, key);
            const float rh = bfr(rinv);
            st[h][0] = pack2(meanb, meanb); st[h][1] = pack2(rh, rh); st[h][2] = pack2(rinv - rh, rinv - rh);
        }
        named_arrive(6, 768);
        uint32_t h2[10], o[10];
#pragma unroll
        for (int i = 0; i < 10; i++) h2[i] = add2(mul2(norm2(x1[i], st[i & 1][0], st[i & 1][1], st[i & 1][2]), kc[i >> 1].x), kc[i >> 1].y);
        stsm_x4(ta, h2[0], h2[1], h2[2], h2[3]); stsm_x4(ta + 32, h2[4], h2[5], h2[6], h2[7]); stsm_x2(ta + 64, h2[8], h2[9]);
        named_arrive(7, 640);
        asm volatile("" : "+r"(kc[0].z), "+r"(kc[1].z), "+r"(kc[2].z), "+r"(kc[3].z), "+r"(kc[4].z));
        if ((warp == cl || (warp == 15 && cl == 0)) && lane < 16) st_rlx4(&S->acc1[256 * rk + 16 * warp + lane], make_uint4(0, 0, 0, 0));
#pragma unroll
        for (int i = 0; i < 10; i++) o[i] = add2(x1[i], mul2(kc[i >> 1].z, h2[i]));
        stsm_x4(ta + (OFF_OUT - OFF_H2T), o[0], o[1], o[2], o[3]); stsm_x4(ta + (OFF_OUT - OFF_H2T) + 32, o[4], o[5], o[6], o[7]); stsm_x2(ta + (OFF_OUT - OFF_H2T) + 64, o[8], o[9]);
        PROXY_FENCE();
    } else named_arrive(6, 768);
    uint4 gv = make_uint4(1, 1, 1, 1);
    const uint4* gp = nullptr;
    uint32_t gdst = 0;
    const int gi = GW(warp) * 32 + lane, kk = (gi * 911) >> 16, seg = gi - 72 * kk;
    mbar_wait(MB(MB_KEY), 0);
    if (warp < 18) {
        const int kmax = ((GW(warp) * 32 + 31) * 911) >> 16;
        uint4 k = make_uint4(0, 0, 0, 0);
        if (lane < 16) k = *(const uint4*)&M.cand[4 * lane];
        uint32_t key = 0;
#pragma unroll
        for (int rnd = 0; rnd < 8; rnd++) {
            const uint32_t m = __reduce_max_sync(0xffffffffu, k.x);
            if (kk == rnd) key = m;
            if (rnd >= kmax) break;
            POP(k, m);
        }
        gp = &S->h2c[SLOT(key) * 72 + seg];
        gv = ld_rlx4(gp);
        if (__any_sync(0xffffffffu, lane < 16 && k.x == 0u)) {
            mbar_wait(MB(MB_KEY2), 0);
            k = *(const uint4*)&M.cand[4 * lane];
#pragma unroll 1
            for (int rnd = 0; rnd <= kmax; rnd++) {
                const uint32_t m = __reduce_max_sync(0xffffffffu, k.x);
                if (kk == rnd) key = m;
                POP(k, m);
            }
            gp = &S->h2c[SLOT(key) * 72 + seg];
            gv = ld_rlx4(gp);
        }
        gdst = sb + OFF_H2S + kk * (ROWP * 2) + seg * 16;
    }
    mbar_wait(MB(MB_WD), 0);
#pragma unroll
    for (int i = 0; i < 2; i++) {
        const int mt = warp + 20 * i;
        const uint32_t wa = sb + OFF_WD + (mt >> 2) * 5120 + lr * 128 + (((2 * (mt & 3) + (lm & 1)) ^ lr) << 4);
#pragma unroll
        for (int ks = 0; ks < 3; ks++)
            if (i == 0 || warp < 16) ldsm_x4_t(wd[i][ks], wa + ks * 2048 + ((ks < 2) ? (lm >> 1) * 1024 : 0));
    }
#pragma unroll 1
    for (int it = 0; it < SPIN_MAX && gv.x == 0u; it++) gv = ld_rlx4(gp);
    if (gdst) asm volatile("st.shared.v4.u32 [%0], {%1,%2,%3,%4};" ::"r"(gdst), "r"(~gv.x), "r"(~gv.y), "r"(~gv.z), "r"(~gv.w) : "memory");
    CBAR();
    if (warp == 19) named_arrive(8, 64);
    float* ffr = (float*)(sm + OFF_FFR);
    auto ffn1 = [&]() {
        float acc[2][4] = {{0.f, 0.f, 0.f, 0.f}, {0.f, 0.f, 0.f, 0.f}};
        const uint32_t ha = sb + OFF_H2S + lr * (ROWP * 2) + (144 * fsl) * 2 + lm * 16;
#pragma unroll
        for (int k2 = 0; k2 < 5; k2++) {
            uint32_t hb[4];
            ldsm_x4(hb, ha + k2 * 64 - ((k2 == 4) ? (lm >> 1) * 32 : 0));
            mma_bf16(acc[0], wf[2 * k2][0], wf[2 * k2][1], wf[2 * k2][2], wf[2 * k2][3], hb[0], hb[1]);
            if (k2 < 4) mma_bf16(acc[1], wf[2 * k2 + 1][0], wf[2 * k2 + 1][1], wf[2 * k2 + 1][2], wf[2 * k2 + 1][3], hb[2], hb[3]);
        }
        float* o = ffr + ((fsl * 80 + 16 * fmt + g) * 8 + 2 * t);
        *(float2*)o = make_float2(acc[0][0] + acc[1][0], acc[0][1] + acc[1][1]);
        *(float2*)(o + 64) = make_float2(acc[0][2] + acc[1][2], acc[0][3] + acc[1][3]);
    };
    ffn1();
    bf16(*act)[56] = (bf16(*)[56])(sm + OFF_ACT);
    auto gate = [&]() {
        if (tid < 384) {
            const int f = tid >> 3, a = tid & 7;
            float v = 0.f;
            if (f < 40) {
                const int rg = (f < 32) ? f : f + 32, ru = (f < 32) ? f + 32 : f + 40;
                const float* pg = ffr + rg * 8 + a;
                const float* pu = ffr + ru * 8 + a;
                float gg = bfr((pg[0] + pg[640]) + (pg[1280] + pg[1920]));
                gg = bfr(silu(gg));
                const float uu = bfr((pu[0] + pu[640]) + (pu[1280] + pu[1920]));
                v = gg * uu;
            }
            act[a][f] = __ushort_as_bfloat16((unsigned short)f2bits(v));
        }
    };
    CBAR();
    gate();
    named_bar(12, 672);
    const uint32_t redo = M.fin[8];
    uint32_t bq[3][2];
    auto ldact = [&]() {
#pragma unroll
        for (int ks = 0; ks < 3; ks++) {
            bq[ks][0] = *(const uint32_t*)&act[g][16 * ks + 2 * t];
            bq[ks][1] = *(const uint32_t*)&act[g][16 * ks + 2 * t + 8];
        }
    };
    ldact();
    if (redo) {
        if (warp < 18) {
            const int gi = fresh_tid(), kk = (gi * 911) >> 16, seg = gi - 72 * kk;
            gp = &S->h2c[SLOT(M.fin[kk]) * 72 + seg];
            gv.x = 0u;
#pragma unroll 1
            for (int it = 0; it < SPIN_MAX && gv.x == 0u; it++) gv = ld_rlx4(gp);
            *(uint4*)(sm + OFF_H2S + kk * (ROWP * 2) + seg * 16) = make_uint4(~gv.x, ~gv.y, ~gv.z, ~gv.w);
        }
        CBAR();
        ffn1();
        CBAR();
        gate();
        CBAR();
        ldact();
    }
    {
#pragma unroll
        for (int i = 0; i < 2; i++) {
            if (i == 0 || warp < 16) {
                float acc[4] = {0.f, 0.f, 0.f, 0.f};
#pragma unroll
                for (int ks = 0; ks < 3; ks++) mma_bf16(acc, wd[i][ks][0], wd[i][ks][1], wd[i][ks][2], wd[i][ks][3], bq[ks][0], bq[ks][1]);
                const int d = i ? 4 + (warp >> 2) : (warp * 13) >> 6, slot = i ? (warp & 3) : warp - 5 * d;
                const uint32_t rb = mapa(sb, d);
                sta2(rb + OFF_RS + ((rk * 5 + slot) * 32 + lane) * 8, movm(pack2(acc[0], acc[1])), movm(pack2(acc[2], acc[3])), rb + (MB(MB_RS) - sb));
            }
        }
    }
    if (warp >= 8) {
        const int s = (warp - 8) >> 1, h = warp & 1;
        if (s < (rk < 4 ? 5 : 4)) {
            mbar_wait(MB(MB_RS), 0);
            const uint32_t p = sb + OFF_RS + (s * 32 + lane) * 8 + 4 * h;
            uint32_t v[8];
#pragma unroll
            for (int i = 0; i < 8; i++) v[i] = lds32(p + i * 1280);
            const float s0 = ((lo2f(v[0]) + lo2f(v[1])) + (lo2f(v[2]) + lo2f(v[3]))) + ((lo2f(v[4]) + lo2f(v[5])) + (lo2f(v[6]) + lo2f(v[7])));
            const float s1 = ((hi2f(v[0]) + hi2f(v[1])) + (hi2f(v[2]) + hi2f(v[3]))) + ((hi2f(v[4]) + hi2f(v[5])) + (hi2f(v[6]) + hi2f(v[7])));
            st_rlx2(&S->part[((cl * 36 + (rk < 4 ? 5 * rk : 4 * rk + 4) + s) * 2 + h) * 32 + lane], ~__float_as_uint(s0), ~__float_as_uint(s1));
        }
    } else {
        const uint32_t key = M.fin[warp], tk = (~key >> 3) & 2047u;
        const int P = 20 * cl + lane;
        if (((tk >> 3) & 7u) == (uint32_t)rk && lane < 20 && P < D_ / 2) {
            const uint2* src = &S->part[(P >> 2) * 32 + 4 * warp + (P & 3)];
            uint2 a[NCL];
#pragma unroll
            for (int i = 0; i < NCL; i++) a[i] = ld_rlx2(src + i * 2304);
            const float rs = __fdividef(1.0f, 1.0f + __expf(-hi2f(key ^ (((int)~key >> 31) | 0x80000000u))));
            const uint32_t row = ROW(key);
            const unsigned short* vp = (const unsigned short*)(sm + OFF_V + 2 * lane * VP) + row;
            const uint32_t xv = add2(lds32(sb + OFF_X + XI(row >> 5) + ((row >> 3) & 3) * XG + (row & 7) * 80 + 4 * lane), (uint32_t)vp[0] | ((uint32_t)vp[VP / 2] << 16));
            const uint32_t hv = lds32(sb + OFF_H2T + row * 80 + 4 * lane), gb = M.c2[lane].z;
#pragma unroll 1
            for (int it = 0; it < SPIN_MAX; it++) {
                bool bad = false;
#pragma unroll
                for (int i = 0; i < NCL; i++) if (a[i].x == 0u) { a[i] = ld_rlx2(src + i * 2304); bad = true; }
                if (!bad) break;
            }
            float s0 = 0.f, s1 = 0.f;
#pragma unroll
            for (int i = 0; i < NCL; i++) { s0 += __uint_as_float(~a[i].x); s1 += __uint_as_float(~a[i].y); }
            const uint32_t ov = add2(xv, mul2(gb, add2(hv, mul2(pack2(s0, s1), pack2(rs, rs)))));
            mbar_wait(MB(MB_OUT), 0);
            *(uint32_t*)(out + tk * D_ + 2 * P) = ov;
        }
    }
    }
    }
}

typedef CUresult (*EncodeFn)(CUtensorMap*, CUtensorMapDataType, cuuint32_t, void*, const cuuint64_t*, const cuuint64_t*,
                             const cuuint32_t*, const cuuint32_t*, CUtensorMapInterleave, CUtensorMapSwizzle,
                             CUtensorMapL2promotion, CUtensorMapFloatOOBfill);

static void make_map(EncodeFn fn, CUtensorMap* m, const void* ptr, uint64_t cols, uint64_t rows, uint32_t bc, uint32_t br,
                     CUtensorMapSwizzle sw, int five) {
    cuuint64_t dims[5] = {cols, rows, 4, 4, 64};
    cuuint64_t strides[4] = {cols * 2 * (five ? 64 : 1), cols * 2 * 512, cols * 2 * 128, cols * 2};
    cuuint32_t box[5] = {bc, br, 4, 4, 8};
    cuuint32_t es[5] = {1, 1, 1, 1, 1};
    CUresult rc = fn(m, CU_TENSOR_MAP_DATA_TYPE_BFLOAT16, five ? 5 : 2, (void*)ptr, dims, strides, box, es, CU_TENSOR_MAP_INTERLEAVE_NONE,
                     sw, CU_TENSOR_MAP_L2_PROMOTION_NONE, CU_TENSOR_MAP_FLOAT_OOB_FILL_NONE);
    (void)rc;
}

static void launch(void* const* d_in, const int* in_sizes, int n_in, void* d_out, int out_size) {
    static EncodeFn enc = nullptr;
    static CUtensorMap tmm, tmg, tmu, tmd, tmo;
    static Scratch* sp = nullptr;
    static const void* cached[6] = {nullptr, nullptr, nullptr, nullptr, nullptr, nullptr};
    if (!enc) {
        cudaDriverEntryPointQueryResult qr;
        void* fn = nullptr;
        cudaGetDriverEntryPoint("cuTensorMapEncodeTiled", &fn, cudaEnableDefault, &qr);
        enc = (EncodeFn)fn;
        cudaFuncSetAttribute(clus_kernel, cudaFuncAttributeMaxDynamicSharedMemorySize, SMEM_TOTAL);
        cudaGetSymbolAddress((void**)&sp, g_s);
    }
    if (cached[0] != d_in[13] || cached[1] != d_in[9] || cached[2] != d_in[10] || cached[3] != d_in[11] || cached[4] != d_in[0] || cached[5] != d_out) {
        make_map(enc, &tmo, d_out, D_, 2, 40, 2, CU_TENSOR_MAP_SWIZZLE_NONE, 1);
        make_map(enc, &tmm, d_in[13], 6 * D_, D_, 40, 72, CU_TENSOR_MAP_SWIZZLE_NONE, 0);
        make_map(enc, &tmg, d_in[9], F_, D_, 40, 192, CU_TENSOR_MAP_SWIZZLE_NONE, 0);
        make_map(enc, &tmu, d_in[10], F_, D_, 40, 192, CU_TENSOR_MAP_SWIZZLE_NONE, 0);
        make_map(enc, &tmd, d_in[11], D_, F_, 64, 40, CU_TENSOR_MAP_SWIZZLE_128B, 0);
        cached[0] = d_in[13]; cached[1] = d_in[9]; cached[2] = d_in[10]; cached[3] = d_in[11]; cached[4] = d_in[0]; cached[5] = d_out;
    }
    clus_kernel<<<G_, NTHR, SMEM_TOTAL>>>((const bf16*)d_in[0], (const bf16*)d_in[1], (const bf16*)d_in[2], (const bf16*)d_in[3], (const bf16*)d_in[4],
                                          (const bf16*)d_in[5], (const bf16*)d_in[12], sp, (const bf16*)d_in[6], (const bf16*)d_in[8], (const bf16*)d_in[13],
                                          (bf16*)d_out, tmm, tmg, tmu, tmd, tmo);
}


static bool fits() {
    cudaFuncSetAttribute(clus_kernel, cudaFuncAttributeMaxDynamicSharedMemorySize, SMEM_TOTAL);
    cudaLaunchConfig_t cfg = {};
    cudaLaunchAttribute at;
    at.id = cudaLaunchAttributeClusterDimension;
    at.val.clusterDim.x = 8; at.val.clusterDim.y = 1; at.val.clusterDim.z = 1;
    cfg.gridDim = dim3(G_); cfg.blockDim = dim3(NTHR); cfg.dynamicSmemBytes = SMEM_TOTAL; cfg.attrs = &at; cfg.numAttrs = 1;
    int n = 0;
    const bool ok = cudaOccupancyMaxActiveClusters(&n, clus_kernel, &cfg) == cudaSuccess && n >= NCL;
    cudaGetLastError();
    return ok;
}
}
#undef L_
#undef D_
#undef N_
#undef F_
#undef G_
#undef NCL
#undef NTHR
#undef SPIN_MAX
#undef NRST
#undef OFF_WG
#undef OFF_WU
#undef KSCR
#undef OFF_WM0
#undef OFF_STG
#undef OFF_MG2
#undef OFF_CH
#undef CHS
#undef ULBO
#undef XO_U8
#undef XO_U16
#undef XO_ZA
#undef XO_ZB
#undef XO_ZC
#undef XO_ZD
#undef XO_TF
#undef XO_TD
#undef XO_K1024
#undef XO_DSK
#undef XO_KINV
#undef XO_KLAST
#undef XO_MBU
#undef OFF_X
#undef XG
#undef XI
#undef XN
#undef OFF_V
#undef VP
#undef OFF_EK
#undef OFF_WM2
#undef OFF_MG1
#undef OFF_SC
#undef OFF_C1
#undef OFF_MISC
#undef OFF_WD
#undef OFF_H2T
#undef OFF_OUT
#undef ROWP
#undef OFF_H2S
#undef OFF_FFR
#undef OFF_ACT
#undef OFF_RS
#undef SMEM_TOTAL
#undef CBAR
#undef PROXY_FENCE
#undef D4
#undef O4
#undef WG_FENCE
#undef WG_COMMIT
#undef WG_WAIT
#undef TQ
#undef MB
#undef DZ
#undef DS
#undef KST
#undef WMD
#undef PU
#undef PD
#undef LN1POS
#undef SLOT
#undef ROW
#undef CE
#undef POP
#undef GW
#undef CL_ARRIVE
#undef CL_WAIT
#undef RESET
#undef CJ
#undef CJP

namespace v4 {

#define L_ 2048
#define D_ 576
#define N_ 128
#define F_ 4608
#define G_ 128
#define NTHR 640
#define SPIN_MAX (1 << 18)
#define SENT 0u
#define HINT_N 182u

typedef __nv_bfloat16 bf16;

struct Scratch {
    uint4 xn[G_ * G_ * 10];
    uint4 v[G_ * D_ * 2];
    uint2 part[G_ * G_ * 9];
    uint4 h2w[L_ * 96];
    unsigned int rec[G_ * 8];
    unsigned int modw[6 * D_];
    unsigned int ticket[64];
    unsigned int cnt[64];
    unsigned int hint[64];
};
__device__ __align__(1024) Scratch g_s;

#define OFF_WG 0
#define OFF_WU 46080
#define OFF_CH 92160
#define CHS 20784
#define ULBO 656
#define XO_U8 6272
#define XO_U16 10368
#define XO_ZA 5248
#define XO_ZB 8448
#define XO_ZC 11648
#define XO_ZD 13824
#define XO_TD 16000
#define XO_TF 18624
#define XO_K1024 20672
#define KSCR 3456
#define OFF_TILE 196096
#define ROWP 584
#define OFF_MISC 214784
#define OFF_WD OFF_CH
#define OFF_H2T (OFF_CH + 3 * CHS)
#define OFF_H2S (OFF_H2T + 18688)
#define OFF_FFR (OFF_H2S + 9344)
#define OFF_FIN OFF_FFR
#define OFF_ACT (OFF_FFR + 10240)

struct Misc {
    __align__(16) uint4 sent[256];
    __align__(16) uint4 box[11 * 14];
    union {
        struct {
            __align__(16) float2 part[18][16];
            float rp[18][16];
        };
        struct {
            __align__(16) unsigned short st1[3][16];
            __align__(16) float p1[16][4], p2[16][4];
        };
    };
    __align__(16) bf16 cb1[D_], sb[D_], gb[D_];
    __align__(16) bf16 sc[D_];
    __align__(16) unsigned int cand[64], skey[16];
    __align__(16) float kinv[5][4], klast[5][4];
    unsigned int pk[4][8];
    __align__(16) uint4 st2[16];
    unsigned int wr[D_ / 2];
    float modx[32];
    unsigned int rank[16];
    volatile unsigned int flag;
    unsigned int e1cnt;
    unsigned long long mbar[5];
    unsigned int epoch;
};
#define SMEM_TOTAL (OFF_MISC + (int)sizeof(Misc))
static_assert(SMEM_TOTAL <= 232448, "smem");

__device__ __forceinline__ float lo2f(uint32_t w) { return __uint_as_float(w << 16); }
__device__ __forceinline__ float hi2f(uint32_t w) { return __uint_as_float(w & 0xFFFF0000u); }
__device__ __forceinline__ uint32_t pack2(float lo, float hi) { uint32_t r; asm("cvt.rn.bf16x2.f32 %0, %1, %2;" : "=r"(r) : "f"(hi), "f"(lo)); return r; }
__device__ __forceinline__ float bfr(float x) { return __uint_as_float(pack2(0.f, x)); }
__device__ __forceinline__ uint32_t f2bits(float x) { return pack2(x, 0.f); }
__device__ __forceinline__ uint32_t packh(float lo, float hi) { uint32_t r; asm("cvt.rn.f16x2.f32 %0, %1, %2;" : "=r"(r) : "f"(hi), "f"(lo)); return r; }
__device__ __forceinline__ float frcp(float x) { float r; asm("rcp.approx.ftz.f32 %0, %1;" : "=f"(r) : "f"(x)); return r; }
__device__ __forceinline__ float fsqrt(float x) { float r; asm("sqrt.approx.f32 %0, %1;" : "=f"(r) : "f"(x)); return r; }
__device__ __forceinline__ float fex2(float x) { float r; asm("ex2.approx.ftz.f32 %0, %1;" : "=f"(r) : "f"(x)); return r; }
__device__ __forceinline__ float silu(float x) { return __fdividef(x, 1.0f + __expf(-x)); }
__device__ __forceinline__ uint32_t add2(uint32_t a, uint32_t b) { uint32_t r; asm("add.rn.bf16x2 %0, %1, %2;" : "=r"(r) : "r"(a), "r"(b)); return r; }
__device__ __forceinline__ uint32_t sub2(uint32_t a, uint32_t b) { uint32_t r; asm("sub.rn.bf16x2 %0, %1, %2;" : "=r"(r) : "r"(a), "r"(b)); return r; }
__device__ __forceinline__ uint32_t mul2(uint32_t a, uint32_t b) { uint32_t r; asm("mul.rn.bf16x2 %0, %1, %2;" : "=r"(r) : "r"(a), "r"(b)); return r; }
__device__ __forceinline__ uint32_t fma2(uint32_t a, uint32_t b, uint32_t c) { uint32_t r; asm("fma.rn.bf16x2 %0, %1, %2, %3;" : "=r"(r) : "r"(a), "r"(b), "r"(c)); return r; }
__device__ __forceinline__ uint32_t norm2(uint32_t x, uint32_t m, uint32_t rh, uint32_t rl) { const uint32_t d = sub2(x, m); return fma2(d, rh, mul2(d, rl)); }

__device__ __forceinline__ void mma_bf16(float* c, uint32_t a0, uint32_t a1, uint32_t a2, uint32_t a3, uint32_t b0, uint32_t b1) {
    asm volatile("mma.sync.aligned.m16n8k16.row.col.f32.bf16.bf16.f32 {%0,%1,%2,%3}, {%4,%5,%6,%7}, {%8,%9}, {%0,%1,%2,%3};\n"
                 : "+f"(c[0]), "+f"(c[1]), "+f"(c[2]), "+f"(c[3]) : "r"(a0), "r"(a1), "r"(a2), "r"(a3), "r"(b0), "r"(b1));
}
__device__ __forceinline__ void mma_f16(float* c, const uint32_t* a, uint32_t b0, uint32_t b1) {
    asm volatile("mma.sync.aligned.m16n8k16.row.col.f32.f16.f16.f32 {%0,%1,%2,%3}, {%4,%5,%6,%7}, {%8,%9}, {%0,%1,%2,%3};\n"
                 : "+f"(c[0]), "+f"(c[1]), "+f"(c[2]), "+f"(c[3]) : "r"(a[0]), "r"(a[1]), "r"(a[2]), "r"(a[3]), "r"(b0), "r"(b1));
}
__device__ __forceinline__ void ldsm_x4(uint32_t* r, uint32_t addr) {
    asm volatile("ldmatrix.sync.aligned.m8n8.x4.shared.b16 {%0,%1,%2,%3}, [%4];" : "=r"(r[0]), "=r"(r[1]), "=r"(r[2]), "=r"(r[3]) : "r"(addr) : "memory");
}
__device__ __forceinline__ void ldsm_x4_t(uint32_t* r, uint32_t addr) {
    asm volatile("ldmatrix.sync.aligned.m8n8.x4.trans.shared.b16 {%0,%1,%2,%3}, [%4];" : "=r"(r[0]), "=r"(r[1]), "=r"(r[2]), "=r"(r[3]) : "r"(addr) : "memory");
}
__device__ __forceinline__ void stsm_x4(uint32_t addr, uint32_t r0, uint32_t r1, uint32_t r2, uint32_t r3) {
    asm volatile("stmatrix.sync.aligned.m8n8.x4.shared.b16 [%0], {%1,%2,%3,%4};" ::"r"(addr), "r"(r0), "r"(r1), "r"(r2), "r"(r3) : "memory");
}
__device__ __forceinline__ void stsm_x4_t(uint32_t addr, uint32_t r0, uint32_t r1, uint32_t r2, uint32_t r3) {
    asm volatile("stmatrix.sync.aligned.m8n8.x4.trans.shared.b16 [%0], {%1,%2,%3,%4};" ::"r"(addr), "r"(r0), "r"(r1), "r"(r2), "r"(r3) : "memory");
}
__device__ __forceinline__ uint32_t movm(uint32_t a) { uint32_t r; asm volatile("movmatrix.sync.aligned.m8n8.trans.b16 %0, %1;" : "=r"(r) : "r"(a)); return r; }
__device__ __forceinline__ uint32_t lds32(uint32_t a) { uint32_t v; asm volatile("ld.shared.u32 %0, [%1];" : "=r"(v) : "r"(a)); return v; }
__device__ __forceinline__ void sts32(uint32_t a, uint32_t v) { asm volatile("st.shared.u32 [%0], %1;" ::"r"(a), "r"(v) : "memory"); }
__device__ __forceinline__ void sts16(uint32_t a, uint32_t v) { asm volatile("st.shared.u16 [%0], %1;" ::"r"(a), "h"((unsigned short)v) : "memory"); }
__device__ __forceinline__ void named_bar(int id, int n) { asm volatile("bar.sync %0, %1;" ::"r"(id), "r"(n) : "memory"); }
__device__ __forceinline__ void named_arrive(int id, int n) { asm volatile("bar.arrive %0, %1;" ::"r"(id), "r"(n) : "memory"); }
#define CBAR() asm volatile("bar.sync 0, 640;" ::: "memory")
#define PROXY_FENCE() asm volatile("fence.proxy.async.shared::cta;" ::: "memory")

#define D4(d, o) "+f"(d[o]), "+f"(d[o + 1]), "+f"(d[o + 2]), "+f"(d[o + 3])
__device__ __forceinline__ void wg32(float* d, uint32_t a0, uint32_t a1, uint32_t a2, uint32_t a3, uint64_t desc) {
    asm volatile("wgmma.mma_async.sync.aligned.m64n32k16.f32.bf16.bf16 {%0,%1,%2,%3,%4,%5,%6,%7,%8,%9,%10,%11,%12,%13,%14,%15}, {%16,%17,%18,%19}, %20, 1, 1, 1, 0;"
                 : D4(d, 0), D4(d, 4), D4(d, 8), D4(d, 12) : "r"(a0), "r"(a1), "r"(a2), "r"(a3), "l"(desc));
}
__device__ __forceinline__ void wg48(float* d, uint32_t a0, uint32_t a1, uint32_t a2, uint32_t a3, uint64_t desc) {
    asm volatile("wgmma.mma_async.sync.aligned.m64n48k16.f32.bf16.bf16 {%0,%1,%2,%3,%4,%5,%6,%7,%8,%9,%10,%11,%12,%13,%14,%15,%16,%17,%18,%19,%20,%21,%22,%23}, {%24,%25,%26,%27}, %28, 1, 1, 1, 0;"
                 : D4(d, 0), D4(d, 4), D4(d, 8), D4(d, 12), D4(d, 16), D4(d, 20) : "r"(a0), "r"(a1), "r"(a2), "r"(a3), "l"(desc));
}
#define O4(d, o) "=f"(d[o]), "=f"(d[o + 1]), "=f"(d[o + 2]), "=f"(d[o + 3])
__device__ __forceinline__ void wg32z(float* d, uint32_t a0, uint32_t a1, uint32_t a2, uint32_t a3, uint64_t desc) {
    asm volatile("wgmma.mma_async.sync.aligned.m64n32k16.f32.bf16.bf16 {%0,%1,%2,%3,%4,%5,%6,%7,%8,%9,%10,%11,%12,%13,%14,%15}, {%16,%17,%18,%19}, %20, 0, 1, 1, 0;"
                 : O4(d, 0), O4(d, 4), O4(d, 8), O4(d, 12) : "r"(a0), "r"(a1), "r"(a2), "r"(a3), "l"(desc));
}
__device__ __forceinline__ void wg48z(float* d, uint32_t a0, uint32_t a1, uint32_t a2, uint32_t a3, uint64_t desc) {
    asm volatile("wgmma.mma_async.sync.aligned.m64n48k16.f32.bf16.bf16 {%0,%1,%2,%3,%4,%5,%6,%7,%8,%9,%10,%11,%12,%13,%14,%15,%16,%17,%18,%19,%20,%21,%22,%23}, {%24,%25,%26,%27}, %28, 0, 1, 1, 0;"
                 : O4(d, 0), O4(d, 4), O4(d, 8), O4(d, 12), O4(d, 16), O4(d, 20) : "r"(a0), "r"(a1), "r"(a2), "r"(a3), "l"(desc));
}
#define WG_FENCE() asm volatile("wgmma.fence.sync.aligned;" ::: "memory")
#define WG_COMMIT() asm volatile("wgmma.commit_group.sync.aligned;" ::: "memory")
#define WG_WAIT(n) asm volatile("wgmma.wait_group.sync.aligned " #n ";" ::: "memory")
#define TQ(p, k) p[2 * (k) + 1], p[2 * (k) + 2], p[2 * (k)], p[2 * (k) + 1]

__device__ __forceinline__ uint4 ld_nc4(const void* p) { uint4 v; asm volatile("ld.global.nc.v4.u32 {%0,%1,%2,%3}, [%4];" : "=r"(v.x), "=r"(v.y), "=r"(v.z), "=r"(v.w) : "l"(p)); return v; }
__device__ __forceinline__ unsigned short ld_nc16(const void* p) { unsigned short v; asm volatile("ld.global.nc.u16 %0, [%1];" : "=h"(v) : "l"(p)); return v; }
__device__ __forceinline__ uint32_t ld_nc(const void* p) { uint32_t v; asm volatile("ld.global.nc.u32 %0, [%1];" : "=r"(v) : "l"(p)); return v; }
__device__ __forceinline__ uint32_t ld_rlx(const unsigned int* p) { uint32_t v; asm volatile("ld.relaxed.gpu.global.u32 %0, [%1];" : "=r"(v) : "l"(p) : "memory"); return v; }
__device__ __forceinline__ uint2 ld_rlx2(const void* p) { uint2 v; asm volatile("ld.relaxed.gpu.global.v2.u32 {%0,%1}, [%2];" : "=r"(v.x), "=r"(v.y) : "l"(p) : "memory"); return v; }
__device__ __forceinline__ uint4 ld_rlx4(const void* p) { uint4 v; asm volatile("ld.relaxed.gpu.global.v4.u32 {%0,%1,%2,%3}, [%4];" : "=r"(v.x), "=r"(v.y), "=r"(v.z), "=r"(v.w) : "l"(p) : "memory"); return v; }
__device__ __forceinline__ void st_rlx(unsigned int* p, uint32_t v) { asm volatile("st.relaxed.gpu.global.u32 [%0], %1;" ::"l"(p), "r"(v) : "memory"); }
__device__ __forceinline__ void st_rlx2(void* p, uint32_t a, uint32_t b) { asm volatile("st.relaxed.gpu.global.v2.u32 [%0], {%1,%2};" ::"l"(p), "r"(a), "r"(b) : "memory"); }
__device__ __forceinline__ void st_rlx4(void* p, uint4 v) { asm volatile("st.relaxed.gpu.global.v4.u32 [%0], {%1,%2,%3,%4};" ::"l"(p), "r"(v.x), "r"(v.y), "r"(v.z), "r"(v.w) : "memory"); }
__device__ __forceinline__ void red_inc(unsigned int* p) { asm volatile("red.relaxed.gpu.global.add.u32 [%0], 1;" ::"l"(p) : "memory"); }

__device__ __forceinline__ void mbar_init(uint32_t a, int cnt) { asm volatile("mbarrier.init.shared::cta.b64 [%0], %1;" ::"r"(a), "r"(cnt) : "memory"); }
__device__ __forceinline__ void mbar_expect(uint32_t a, uint32_t bytes) { asm volatile("mbarrier.arrive.expect_tx.shared::cta.b64 _, [%0], %1;" ::"r"(a), "r"(bytes) : "memory"); }
__device__ __forceinline__ void mbar_wait(uint32_t a, uint32_t parity) {
    uint32_t ok = 0;
    int it = 0;
    do {
        asm volatile("{\n.reg .pred p;\nmbarrier.try_wait.parity.shared::cta.b64 p, [%1], %2;\nselp.u32 %0, 1, 0, p;\n}" : "=r"(ok) : "r"(a), "r"(parity) : "memory");
    } while (!ok && ++it < SPIN_MAX);
}
__device__ __forceinline__ void tma2d(uint32_t dst, const CUtensorMap* tm, int c0, int c1, uint32_t mbar) {
    asm volatile("cp.async.bulk.tensor.2d.shared::cluster.global.mbarrier::complete_tx::bytes [%0], [%1, {%3, %4}], [%2];"
                 ::"r"(dst), "l"(tm), "r"(mbar), "r"(c0), "r"(c1) : "memory");
}
__device__ __forceinline__ void bulk_s2g(void* dst, uint32_t src, uint32_t bytes) {
    asm volatile("cp.async.bulk.global.shared::cta.bulk_group [%0], [%1], %2;" ::"l"(dst), "r"(src), "r"(bytes) : "memory");
}
__device__ __forceinline__ uint32_t ld_acq(const unsigned int* p) { uint32_t v; asm volatile("ld.acquire.gpu.global.u32 %0, [%1];" : "=r"(v) : "l"(p) : "memory"); return v; }
__device__ __forceinline__ void bulk_pf(const void* src, uint32_t bytes) { asm volatile("cp.async.bulk.prefetch.L2.global [%0], %1;" ::"l"(src), "r"(bytes) : "memory"); }

__device__ __forceinline__ uint32_t wait_epoch(Misc& M) {
    uint32_t e = 0;
#pragma unroll 1
    for (int it = 0; it < (SPIN_MAX << 4) && e == 0; it++) e = *(volatile unsigned int*)&M.epoch;
    return e;
}
__device__ __forceinline__ void wait_reset(const unsigned int* ctr, uint32_t epoch) {
#pragma unroll 1
    for (int it = 0; it < SPIN_MAX; it++)
        if ((int)(ld_acq(ctr) - G_ * epoch) >= 0) break;
}
struct cplx { float x, y; };
__device__ __forceinline__ cplx cmul(cplx a, cplx b) { cplx r; r.x = a.x * b.x - a.y * b.y; r.y = a.x * b.y + a.y * b.x; return r; }
__device__ __forceinline__ cplx csq(cplx a) { cplx r; r.x = a.x * a.x - a.y * a.y; r.y = 2.0f * a.x * a.y; return r; }
__device__ __forceinline__ uint32_t hcm(uint32_t x, uint32_t y, uint32_t yp) {
    const __half2 X = *(const __half2*)&x, Y = *(const __half2*)&y, YP = *(const __half2*)&yp;
    const __half2 r = __hfma2(__high2half2(X), YP, __hmul2(__low2half2(X), Y));
    return *(const uint32_t*)&r;
}
__device__ __forceinline__ void ln_stats(float s1, float s2, float& meanb, float& rinv) {
    const float mean = s1 * (1.0f / D_);
    const float den = bfr(fsqrt(bfr(bfr(fmaxf(fmaf(-mean, mean, s2 * (1.0f / D_)), 0.f)) + 1e-5f)));
    meanb = bfr(mean);
    rinv = frcp(den);
}

__device__ __forceinline__ int fresh_tid() { int v; asm volatile("mov.u32 %0, %tid.x;" : "=r"(v)); return v; }
__device__ __forceinline__ void conv_channel(unsigned char* sm, Scratch* S, uint32_t gidx, uint32_t epoch, const void* pf_src,
                                             const CUtensorMap* tmu, int f0) {
    Misc& M = *(Misc*)(sm + OFF_MISC);
    const uint32_t sb = (uint32_t)__cvta_generic_to_shared(sm);
    const int tid = fresh_tid(), lane = tid & 31, g = lane >> 2, t = lane & 3, lr = lane & 7, lm = lane >> 3;
    const int warp_ = __shfl_sync(0xffffffffu, tid >> 5, 0), wgi = warp_ >> 2, w = warp_ & 3;
    const uint32_t cb = sb + OFF_CH + wgi * CHS, tag16 = (epoch % 65535u) + 1u;
    float D[16];
    uint32_t gaw, rcnt = 0;
    {
        {
            const uint32_t a8 = cb + lr * ULBO + (lm + 9) * 16 + w * 64, b8 = cb + XO_U8 + lm * 128 + lr * 16 + w * 512;
            const uint32_t a16 = cb + (((2 * lr) & 7) + (lm & 1)) * ULBO + (9 + (lr >> 2) + (lm & 2)) * 16 + w * 64;
            const uint32_t b16 = cb + XO_U16 + (lm & 1) * 512 + lr * 16 + (lm >> 1) * 128 + (w >> 1) * 1024 + (w & 1) * 256;
            uint32_t r[3][4];
            ldsm_x4_t(r[0], a8);
            ldsm_x4_t(r[1], a16);
            if (w < 2) ldsm_x4_t(r[2], a8 + 256);
            stsm_x4(b8, r[0][0], r[0][1], r[0][2], r[0][3]);
            stsm_x4(b16, r[1][0], r[1][1], r[1][2], r[1][3]);
            if (w < 2) stsm_x4(b8 + 2048, r[2][0], r[2][1], r[2][2], r[2][3]);
        }
        PROXY_FENCE();
        named_bar(1 + wgi, 128);
        {
            float Z8[24], Z16[16];
            const uint32_t pf = cb + XO_TF + (w >> 1) * 512 + (8 + 16 * (w & 1) + g - 2 * t) * 4;
            uint32_t p[13], q[9], z16[8];
#pragma unroll
            for (int s = 0; s < 9; s++) q[s] = lds32(pf + 1024 + s * 32);
            const uint32_t d8 = ((((cb + XO_U8) & 0x3FFFF) >> 4) | ((128 >> 4) << 16));
#define DZ(o) (((uint64_t)(512 >> 4) << 32) | (uint64_t)(d8 + (o)))
            WG_FENCE();
#pragma unroll
            for (int e = 0; e < 4; e++) {
                if (e == 0) wg32z(Z16, TQ(q, e), DZ(256 + 16));
                else wg32(Z16, TQ(q, e), DZ(256 - (e >> 1) * 64 + (1 - (e & 1)) * 16));
            }
            WG_COMMIT();
#pragma unroll
            for (int s = 0; s < 13; s++) p[s] = lds32(pf + s * 32);
            WG_WAIT(0);
#pragma unroll
            for (int i = 0; i < 8; i++) z16[i] = pack2(Z16[2 * i], Z16[2 * i + 1]);
            WG_FENCE();
#pragma unroll
            for (int e = 0; e < 6; e++) {
                if (e == 0) wg48z(Z8, TQ(p, e), DZ(16));
                else wg48(Z8, TQ(p, e), DZ(-(e >> 1) * 32 + (1 - (e & 1)) * 16));
            }
            WG_COMMIT();
            WG_WAIT(0);
            named_bar(1 + wgi, 128);
            const uint32_t za = cb + ((w >> 1) ? XO_ZB : XO_ZA) + lr * 400 + (1 + 2 * (w & 1) + (lm & 1) + 4 * (lm >> 1)) * 16;
#pragma unroll
            for (int i = 0; i < 3; i++)
                stsm_x4(za + i * 128, pack2(Z8[8 * i], Z8[8 * i + 1]), pack2(Z8[8 * i + 2], Z8[8 * i + 3]), pack2(Z8[8 * i + 4], Z8[8 * i + 5]), pack2(Z8[8 * i + 6], Z8[8 * i + 7]));
            const int Cz = 2 * (16 * (w & 1) + 8 * (lm & 1) + lr) + (lm >> 1);
            const uint32_t zc = cb + ((w >> 1) ? XO_ZD : XO_ZC) + (Cz & 7) * 272 + (1 + (Cz >> 3)) * 16;
#pragma unroll
            for (int ob = 0; ob < 2; ob++) stsm_x4(zc + ob * 128, z16[4 * ob], z16[4 * ob + 1], z16[4 * ob + 2], z16[4 * ob + 3]);
            if (lane < 8) *(uint4*)(sm + (cb - sb) + ((w < 2) ? (XO_ZA + w * 3200 + lane * 400) : (XO_ZC + (w - 2) * 2176 + lane * 272))) = make_uint4(0, 0, 0, 0);
        }
        gaw = ld_rlx(&S->modw[gidx]);
        if (tmu && wgi >= 2 && (tid & 127) == 96) {
            const uint32_t mbu = sb + OFF_MISC + (uint32_t)offsetof(Misc, mbar) + 24;
            if (wgi == 2) mbar_expect(mbu, 36864);
            tma2d(sb + OFF_WU + (wgi - 2) * 12288, tmu, f0, 192 * (wgi - 2), mbu);
        }
        __syncwarp();
        if ((tid & 127) == 64) rcnt = ld_rlx(S->cnt);
        {
#pragma unroll
            for (int i = 0; i < 16; i++) D[i] = 0.f;
            uint32_t pa = cb + XO_TD + (8 + 16 * w + g - 2 * t) * 4;
            uint32_t dlo = (((cb + 9 * 16) & 0x3FFFF) >> 4) | ((ULBO >> 4) << 16);
#define DS(o) (((uint64_t)(128 >> 4) << 32) | (uint64_t)(dlo + (o)))
#define KST (2 * (ULBO / 16))
            uint32_t pA[9], pB[9];
#pragma unroll
            for (int s = 0; s < 9; s++) pA[s] = lds32(pa + s * 32);
#pragma unroll 1
            for (int j = 0; j < 4; j++) {
                WG_FENCE();
#pragma unroll
                for (int q = 0; q < 4; q++) wg32(D, TQ(pA, q), DS((3 - q) * KST));
                WG_COMMIT();
                WG_WAIT(1);
#pragma unroll
                for (int s = 0; s < 9; s++) pB[s] = lds32(pa + 256 + s * 32);
                WG_FENCE();
#pragma unroll
                for (int q = 0; q < 4; q++) wg32(D, TQ(pB, q), DS((3 - q) * KST - 1));
                WG_COMMIT();
                WG_WAIT(1);
#pragma unroll
                for (int s = 0; s < 9; s++) pA[s] = lds32(pa + 512 + s * 32);
                dlo -= 2; pa += 512;
            }
            pB[1] = lds32(pa + 256 + 32); pB[2] = lds32(pa + 256 + 64);
            WG_FENCE();
#pragma unroll
            for (int q = 0; q < 4; q++) wg32(D, TQ(pA, q), DS((3 - q) * KST));
            wg32(D, pB[1], pB[2], pA[8], pB[1], DS(3 * KST - 1));
            WG_COMMIT();
        }
        if (tid == 128) bulk_pf(pf_src, 16 * D_ * 2);
        if ((tid & 127) == 64) {
#pragma unroll 1
            for (int it = 0; it < SPIN_MAX && (int)(rcnt - G_ * epoch) < 0; it++) rcnt = ld_rlx(S->cnt);
        }
    }
    {
        named_bar(1 + wgi, 128);
        {
            const uint4* pq = M.box + (6 + g - 2 * t);
#define QM(q) (q).x, (q).y, (q).z, (q).w
            uint32_t bA[2][6], bB[2][6], bC[3][4], bD[2][4], bU[2][4];
            const uint32_t k2 = lds32(cb + XO_K1024);
            uint32_t ofs[3];
#pragma unroll
            for (int d = 0; d < 3; d++) ofs[d] = cb + ((w - d) < 0 ? 0 : 16) + (lr + 8 * (lm >> 1)) * 16;
#define COL(d) (2 * ((w - (d)) & 3) + (lm & 1))
            WG_WAIT(0);
            uint4 m[4];
#pragma unroll
            for (int d = 0; d < 2; d++) {
                const uint32_t a = XO_ZA + COL(d) * 400 + ofs[d];
                ldsm_x4(bA[d], a); ldsm_x4(bB[d], a + 3200);
                uint32_t r[4];
                ldsm_x4(r, a + 256 + (lm >> 1) * (3200 - 128));
                bA[d][4] = r[0]; bA[d][5] = r[1]; bB[d][4] = r[2]; bB[d][5] = r[3];
            }
#pragma unroll
            for (int i = 0; i < 4; i++) m[i] = pq[14 * i];
#pragma unroll
            for (int d = 0; d < 2; d++)
#pragma unroll
                for (int c = 0; c < 3; c++) mma_bf16(D + 4 + 4 * c, QM(m[d]), bA[d][2 * c], bA[d][2 * c + 1]);
#pragma unroll
            for (int d = 0; d < 3; d++) ldsm_x4(bC[d], XO_ZC + COL(d) * 272 + ofs[d]);
#pragma unroll
            for (int d = 0; d < 2; d++)
#pragma unroll
                for (int c = 0; c < 3; c++) mma_bf16(D + 4 + 4 * c, QM(m[2 + d]), bB[d][2 * c], bB[d][2 * c + 1]);
#pragma unroll
            for (int i = 0; i < 3; i++) m[i] = pq[14 * (4 + i)];
#pragma unroll
            for (int d = 0; d < 2; d++) { ldsm_x4(bD[d], XO_ZD + COL(d) * 272 + ofs[d]); ldsm_x4(bU[d], COL(d) * ULBO + 128 + ofs[d]); }
#pragma unroll
            for (int d = 0; d < 3; d++)
#pragma unroll
                for (int c = 0; c < 2; c++) mma_bf16(D + 8 + 4 * c, QM(m[d]), bC[d][2 * c], bC[d][2 * c + 1]);
#pragma unroll
            for (int i = 0; i < 4; i++) m[i] = pq[14 * (7 + i)];
#pragma unroll
            for (int d = 0; d < 2; d++)
#pragma unroll
                for (int c = 0; c < 2; c++) mma_bf16(D + 8 + 4 * c, QM(m[d]), bD[d][2 * c], bD[d][2 * c + 1]);
#pragma unroll
            for (int d = 0; d < 2; d++) {
                m[2 + d].x &= k2; m[2 + d].y &= k2; m[2 + d].z &= k2; m[2 + d].w &= k2;
#pragma unroll
                for (int c = 0; c < 2; c++) mma_bf16(D + 8 + 4 * c, QM(m[2 + d]), bU[d][2 * c], bU[d][2 * c + 1]);
            }
        }
        {
#pragma unroll 1
            for (int it = 0; it < SPIN_MAX && (gaw >> 16) != tag16; it++) gaw = ld_rlx(&S->modw[gidx]);
            const uint32_t ga2 = __byte_perm(gaw, 0, 0x1010), dk2 = M.pk[3][wgi];
            const uint32_t ua = cb + (2 * w + (lm & 1)) * ULBO + (9 + lr + 8 * (lm >> 1)) * 16;
            const uint32_t ya = cb + XO_TD + w * 1024;
            const uint32_t sa = ya + (lr + 8 * (lm >> 1)) * 32 + (((lm & 1) ^ ((lane >> 2) & 1)) << 4);
#pragma unroll
            for (int cc = 0; cc < 2; cc++) {
                uint32_t u[4], v[4];
                ldsm_x4_t(u, ua + cc * 256);
#pragma unroll
                for (int m = 0; m < 4; m++) {
                    const int c = 2 * cc + (m >> 1), h = m & 1;
                    v[m] = ~mul2(ga2, add2(pack2(D[4 * c + 2 * h], D[4 * c + 2 * h + 1]), mul2(u[m], dk2)));
                }
                stsm_x4_t(sa + cc * 512, v[0], v[1], v[2], v[3]);
            }
            __syncwarp();
            const int sw = (lane >> 3) & 1;
            const uint32_t vo = (uint32_t)(((4 * (lane >> 1) + w) * D_ + gidx - 2 * D_) * 32 + (lane & 1) * 16);
            const unsigned char* yp = sm + (ya - sb) + (lane >> 1) * 32 + (lane & 1) * 8;
#pragma unroll
            for (int i = 0; i < 2; i++) {
                const uint2 A = *(const uint2*)(yp + i * 512 + (sw << 4)), B = *(const uint2*)(yp + i * 512 + ((sw ^ 1) << 4));
                st_rlx4((char*)S->v + vo + i * (64 * D_ * 32), make_uint4(A.x, B.x, A.y, B.y));
            }
        }
    }
}

__global__ void __launch_bounds__(NTHR, 1)
mega_kernel(const bf16* __restrict__ x, const bf16* __restrict__ logAr, const bf16* __restrict__ Aim,
            const bf16* __restrict__ Cr, const bf16* __restrict__ Ci, const bf16* __restrict__ logdt, const bf16* __restrict__ c_in,
            Scratch* __restrict__ S, const bf16* __restrict__ Dskip, const bf16* __restrict__ w_r, const bf16* __restrict__ w_down,
            bf16* __restrict__ out,
            const __grid_constant__ CUtensorMap tm_wm, const __grid_constant__ CUtensorMap tm_wg, const __grid_constant__ CUtensorMap tm_wu,
            const __grid_constant__ CUtensorMap tm_wd, const __grid_constant__ CUtensorMap tm_wd32,
            const __grid_constant__ CUtensorMap tm_wg32, const __grid_constant__ CUtensorMap tm_wu32) {
    extern __shared__ __align__(1024) unsigned char sm[];
    Misc& M = *(Misc*)(sm + OFF_MISC);
    const uint32_t sb = (uint32_t)__cvta_generic_to_shared(sm);
    const int tid = threadIdx.x, warp = __shfl_sync(0xffffffffu, tid >> 5, 0), lane = tid & 31;
    const int g = lane >> 2, t = lane & 3, lr = lane & 7, lm = lane >> 3;
    const int wgi = warp >> 2, w = warp & 3;
    const int b = blockIdx.x;
    const int nch = 5 - (b & 1), cs = 9 * (b >> 1) + 5 * (b & 1);
    const int f0 = 72 * (b >> 1) + 32 * (b & 1), nf = 32 + 8 * (b & 1);
    const bool has_ch = wgi < nch;
    const uint32_t mb0 = sb + OFF_MISC + offsetof(Misc, mbar), mb_wm = mb0, mb_wg = mb0 + 16, mb_wu = mb0 + 24, mb_wd = mb0 + 32;
    const uint32_t cb = sb + OFF_CH + wgi * CHS;

    if (wgi == 3) {
        M.sent[tid - 384] = make_uint4(SENT, SENT, SENT, SENT);
        M.sent[tid - 256] = make_uint4(SENT, SENT, SENT, SENT);
        if (tid == 384) {
            M.epoch = 0u; M.flag = 0u; M.e1cnt = 0u;
#pragma unroll
            for (int i = 0; i < 5; i++) mbar_init(mb0 + 8 * i, 1);
        }
        PROXY_FENCE();
        __syncwarp();
        if (warp == 12) { named_arrive(8, 160); if (b & 1) named_arrive(14, 64); }
        if (warp != 15) named_arrive(9, 128);
    }
    unsigned short r_ldt = 0, r_lar = 0, r_aim = 0, r_cr = 0, r_ci = 0;
    if (has_ch) {
        const int d = cs + wgi, n = d * N_ + (tid & 127);
        r_ldt = ld_nc16((const unsigned short*)logdt + d);
        r_lar = ld_nc16((const unsigned short*)logAr + n);
        r_aim = ld_nc16((const unsigned short*)Aim + n);
        r_cr = ld_nc16((const unsigned short*)Cr + n);
        r_ci = ld_nc16((const unsigned short*)Ci + n);
    } else {
        const unsigned short* cp = (const unsigned short*)c_in + (tid - 512);
        r_ldt = ld_nc16(cp); r_lar = ld_nc16(cp + 128); r_aim = ld_nc16(cp + 256); r_cr = ld_nc16(cp + 384);
        if (tid < 576) r_ci = ld_nc16(cp + 512);
    }
    uint4 xr[9];
    if (wgi == 4) {
        const uint4* p = (const uint4*)(x + (size_t)16 * b * D_) + (tid - 512);
#pragma unroll
        for (int i = 0; i < 9; i++) xr[i] = ld_nc4(p + 128 * i);
    }
    uint32_t wrv = 0;
    if (tid >= 128 && tid < 416) wrv = ld_nc((const uint32_t*)w_r + (tid - 128));
    if (warp == 2 && lane < nch) M.pk[3][lane] = (uint32_t)ld_nc16((const unsigned short*)Dskip + cs + lane) * 0x10001u;
    if (tid == 384) {
        const unsigned int tk = atomicAdd(S->ticket, 1u);
        *(volatile unsigned int*)&M.epoch = (tk >> 7) + 1u;
    }
    if (has_ch) {
        for (int i = tid & 127; i < 296; i += 128) *(uint4*)(sm + OFF_CH + wgi * CHS + XO_TD + i * 16) = make_uint4(0, 0, 0, 0);
    }
    if (tid < 154) {
        const int idx = (tid * 4682) >> 16, dl = tid - 14 * idx - 6;
        const int a = (0x44332221100ull >> (4 * idx)) & 7, d = (0x10102101010ull >> (4 * idx)) & 3;
        const int lo = (0x35c36 >> (4 * a)) & 15, wd = (0x16824 >> (4 * a)) & 15;
        const uint32_t one = (a == 4) ? 0xFFFFu : 0x3F80u;
        auto mk = [&](int l) { return (((unsigned)(l - lo) <= (unsigned)wd) ? one : 0u) | (((unsigned)(l - 1 - lo) <= (unsigned)wd) ? (one << 16) : 0u); };
        const int l0 = 16 * d + dl;
        M.box[tid] = make_uint4(mk(l0), mk(l0 + 8), mk(l0 - 8), mk(l0));
    }
    uint32_t xo[6];
#pragma unroll
    for (int i = 0; i < 6; i++) {
        const int ch = 16 * (warp + 16 * (i >> 1)) + 8 * (i & 1) + g;
        const int pr = (ch * 7282) >> 16, rm = ch - 9 * pr, hi = rm >= 5;
        xo[i] = (uint32_t)((((2 * pr + hi) * G_ + b) * 5 + rm - 5 * hi) * 32 + t * 8);
    }
    auto e1_store = [&]() {
        named_bar(11, 640);
        uint32_t mm[2], rhh[2], rll[2];
#pragma unroll
        for (int h = 0; h < 2; h++) {
            mm[h] = ((const uint32_t*)M.st1[0])[t + 4 * h]; rhh[h] = ((const uint32_t*)M.st1[1])[t + 4 * h]; rll[h] = ((const uint32_t*)M.st1[2])[t + 4 * h];
        }
        const uint32_t ta = sb + OFF_TILE + (lr + 8 * (lm & 1)) * (ROWP * 2) + (lm >> 1) * 16 + warp * 32;
#pragma unroll
        for (int i = 0; i < 3; i++) {
            if (i < 2 || warp < 4) {
                uint32_t r[4];
                ldsm_x4_t(r, ta + i * 512);
#pragma unroll
                for (int h = 0; h < 2; h++)
                    st_rlx2((char*)S->xn + xo[2 * i + h], ~norm2(r[2 * h], mm[0], rhh[0], rll[0]), ~norm2(r[2 * h + 1], mm[1], rhh[1], rll[1]));
            }
        }
        __syncwarp();
        if (lane == 0 && atomicAdd(&M.e1cnt, 1u) == 15u) red_inc(S->hint);
    };
    const float p_ldt = lo2f(r_ldt), p_lar = lo2f(r_lar), p_aim = lo2f(r_aim), p_cr = lo2f(r_cr), p_ci = lo2f(r_ci);
    cplx z1 = {0.f, 0.f}, z16 = z1, z256 = z1, C = z1;
    const uint32_t scr = cb + w * KSCR, ws = scr + lane * 4;
    float acc[5][4];
    uint32_t afr[4][4], cz[4];
    cplx z2 = {0.f, 0.f};
    const uint32_t ba = scr + lr * 144 + lm * 16;
    auto tile = [&](float* c, int rg) {
        __syncwarp();
        c[0] = c[1] = c[2] = c[3] = 0.f;
        uint32_t bb[2][4];
        ldsm_x4(bb[0], ba + rg * 1152);
        ldsm_x4(bb[1], ba + rg * 1152 + 64);
        mma_f16(c, afr[0], bb[0][0], bb[0][1]);
        mma_f16(c, afr[1], bb[0][2], bb[0][3]);
        mma_f16(c, afr[2], bb[1][0], bb[1][1]);
        mma_f16(c, afr[3], bb[1][2], bb[1][3]);
    };
#define CJ(z) packh((z).x, -(z).y)
#define CJP(z) packh((z).y, (z).x)
    uint32_t ex = 0;
    if (has_ch) {
        const float dt = bfr(expf(p_ldt));
        const float al = -bfr(expf(p_lar)) * dt * 1.4426950408889634f;
        const float th = p_aim * dt;
        const float th_ = th * 0.15915494309189535f;
        const float tl_ = fmaf(th, 0.15915494309189535f, -th_) + th * 6.4206382e-9f;
        auto anchor = [&](float s) {
            float f = th_ * s;
            f -= rintf(f);
            f = fmaf(tl_, s, f) * 6.283185307179586f;
            const float e = fex2(al * s);
            return cplx{e * __cosf(f), e * __sinf(f)};
        };
        const float cx = p_cr * dt * 2.0f, cy = p_ci * dt * 2.0f;
        ex = __reduce_max_sync(0xffffffffu, __float_as_uint(fmaxf(fabsf(cx), fabsf(cy)))) >> 23;
        const float scl = __uint_as_float((254u - ex) << 23);
        C = cplx{cx * scl, cy * scl};
        z1 = anchor(1.f); z16 = anchor(16.f); z256 = anchor(256.f);
            {
                const cplx z32 = csq(z16), z48 = cmul(z32, z16), z64 = csq(z32), z128 = csq(z64), z192 = cmul(z128, z64);
                const uint32_t y[3] = {packh(z16.x, z16.y), packh(z32.x, z32.y), packh(z48.x, z48.y)};
                const uint32_t yp[3] = {packh(-z16.y, z16.x), packh(-z32.y, z32.x), packh(-z48.y, z48.x)};
                const uint32_t xx[3] = {packh(z64.x, z64.y), packh(z128.x, z128.y), packh(z192.x, z192.y)};
                sts32(ws, 0x00003C00u);
#pragma unroll
                for (int j = 0; j < 3; j++) sts32(ws + (1 + j) * 144, y[j]);
#pragma unroll
                for (int i = 0; i < 3; i++) {
                    sts32(ws + (4 + 4 * i) * 144, xx[i]);
#pragma unroll
                    for (int j = 0; j < 3; j++) sts32(ws + (5 + 4 * i + j) * 144, hcm(xx[i], y[j], yp[j]));
                }
            }
    }
    if (wgi == 4) {
        if (!has_ch) {
            const int i = tid - 512;
            ((unsigned short*)M.sc)[i] = (unsigned short)f2bits(silu(lo2f(r_ldt)));
            ((unsigned short*)M.sc)[i + 128] = (unsigned short)f2bits(silu(lo2f(r_lar)));
            ((unsigned short*)M.sc)[i + 256] = (unsigned short)f2bits(silu(lo2f(r_aim)));
            ((unsigned short*)M.sc)[i + 384] = (unsigned short)f2bits(silu(lo2f(r_cr)));
            if (i < 64) ((unsigned short*)M.sc)[i + 512] = (unsigned short)f2bits(silu(lo2f(r_ci)));
            if (warp == 16) {
                named_bar(14, 64);
                if (lane == 0) {
                    mbar_expect(mb_wm, 36864);
#pragma unroll
                    for (int k = 0; k < 3; k++) tma2d(sb + OFF_WU + k * 12288, &tm_wm, 32 * (b >> 1), 192 * k, mb_wm);
                }
                __syncwarp();
            }
        }
#pragma unroll
        for (int i = 0; i < 9; i++) {
            const int c = tid - 512 + 128 * i, rr = (c * 911) >> 16;
            *(uint4*)(sm + OFF_TILE + rr * (ROWP * 2 - 1152) + c * 16) = xr[i];
        }
        named_bar(8, 160);
        {
            float c1[4] = {0.f, 0.f, 0.f, 0.f}, cl[4] = {0.f, 0.f, 0.f, 0.f}, chh[4] = {0.f, 0.f, 0.f, 0.f};
            const uint32_t a0 = sb + OFF_TILE + (lane & 15) * (ROWP * 2) + (lane >> 4) * 16 + w * 288;
            uint32_t a[9][4];
#pragma unroll
            for (int ks = 0; ks < 9; ks++) ldsm_x4(a[ks], a0 + ks * 32);
#pragma unroll
            for (int ks = 0; ks < 9; ks++) {
                mma_bf16(c1, a[ks][0], a[ks][1], a[ks][2], a[ks][3], 0x3F803F80u, 0x3F803F80u);
                mma_bf16(cl, a[ks][0], a[ks][1], a[ks][2], a[ks][3], a[ks][0], a[ks][2]);
                mma_bf16(chh, a[ks][0], a[ks][1], a[ks][2], a[ks][3], a[ks][1], a[ks][3]);
            }
            if (t == 0) { M.p1[g][w] = c1[0]; M.p1[g + 8][w] = c1[2]; }
            if (t == (g >> 1)) { M.p2[g][w] = (g & 1) ? cl[1] : cl[0]; M.p2[g + 8][w] = (g & 1) ? chh[3] : chh[2]; }
        }
        named_bar(5, 128);
        if (warp == 16) {
            const float4 q1 = *(const float4*)M.p1[lane & 15], q2 = *(const float4*)M.p2[lane & 15];
            float meanb, rinv;
            ln_stats((q1.x + q1.y) + (q1.z + q1.w), (q2.x + q2.y) + (q2.z + q2.w), meanb, rinv);
            const float rh = bfr(rinv);
            if (lane < 16) { M.st1[0][lane] = (unsigned short)f2bits(meanb); M.st1[1][lane] = (unsigned short)f2bits(rh); M.st1[2][lane] = (unsigned short)f2bits(rinv - rh); }
        }
        __syncwarp();
        named_arrive(11, 640);
    }
    auto publish_reset = [&]() {
        if (tid == 480) {
            asm volatile("cp.async.bulk.wait_group 0;" ::: "memory");
            asm volatile("fence.proxy.async;" ::: "memory");
            red_inc(S->cnt);
        }
    };
    uint32_t epoch = 0, tag16 = 0, pre = 0;
    auto mod_tile = [&](int rd) {
        const uint32_t* s2 = (const uint32_t*)M.sc + 144 * (w >> 1) + t;
        uint32_t bb[18][2];
#pragma unroll
        for (int ks = 0; ks < 18; ks++) { bb[ks][0] = (g == 0) ? s2[8 * ks] : 0u; bb[ks][1] = (g == 0) ? s2[8 * ks + 4] : 0u; }
        float acc[2][4] = {{0.f, 0.f, 0.f, 0.f}, {0.f, 0.f, 0.f, 0.f}};
        const int row = lr + 8 * (lm >> 1);
        const uint32_t wa = sb + OFF_WU + (288 * (w >> 1) + row) * 64 + ((((2 * (w & 1) + (lm & 1)) ^ (row >> 1)) & 3) << 4);
        mbar_wait(mb_wm + 8 * rd, 0);
        if (rd == 0)
#pragma unroll
        for (int kb = 0; kb < 2; kb++) {
            uint32_t a[9][4];
#pragma unroll
            for (int ks = 0; ks < 9; ks++) ldsm_x4_t(a[ks], wa + (9 * kb + ks) * 1024);
#pragma unroll
            for (int ks = 0; ks < 9; ks++) mma_bf16(acc[ks & 1], a[ks][0], a[ks][1], a[ks][2], a[ks][3], bb[9 * kb + ks][0], bb[9 * kb + ks][1]);
        }
        const float v0 = acc[0][0] + acc[1][0], v1 = acc[0][2] + acc[1][2];
        float* mx = M.modx + 16 * (w & 1) + g;
        if (w >= 2 && t == 0) { mx[0] = v0; mx[8] = v1; }
        named_bar(5, 128);
        if (w < 2 && t == 0) {
            unsigned int* mp = &S->modw[32 * ((b >> 1) + 64 * rd) + 16 * w + g];
            st_rlx(mp, f2bits(v0 + mx[0]) | (tag16 << 16));
            st_rlx(mp + 8, f2bits(v1 + mx[8]) | (tag16 << 16));
        }
        if (rd == 0 && w < 2 && b < 108) {
            named_bar(7, 64);
            if (tid == 512) red_inc(S->hint);
        }
    };
    if (has_ch) {
        {
            z2 = csq(z1);
            const cplx z3 = cmul(z2, z1), z4 = csq(z2), z8 = csq(z4);
            const cplx c4 = cmul(C, z4), c8 = cmul(C, z8), c12 = cmul(c8, z4);
            cz[0] = packh(C.x, -C.y); cz[1] = packh(c4.x, -c4.y); cz[2] = packh(c8.x, -c8.y); cz[3] = packh(c12.x, -c12.y);
            __syncwarp();
#pragma unroll
            for (int s = 0; s < 4; s++) ldsm_x4(afr[s], scr + (lr + 8 * (lm & 1)) * 144 + (2 * s + (lm >> 1)) * 16);
            {
                const uint32_t y[3] = {CJ(z1), CJ(z2), CJ(z3)}, yp[3] = {CJP(z1), CJP(z2), CJP(z3)};
#pragma unroll
                for (int tt = 0; tt < 2; tt++) {
                    const int rg = tt ? 0 : 2;
#pragma unroll
                    for (int i = 0; i < 2; i++) {
                        sts32(ws + rg * 1152 + (4 * i) * 144, cz[2 * tt + i]);
#pragma unroll
                        for (int j = 0; j < 3; j++) sts32(ws + rg * 1152 + (4 * i + 1 + j) * 144, hcm(cz[2 * tt + i], y[j], yp[j]));
                    }
                    tile(acc[tt], rg);
                }
            }
            if (tid >= 128 && tid < 416) M.wr[tid - 128] = wrv;
            if (wgi < 4) e1_store();
    if (warp == 15) {
        named_bar(9, 128);
        if (lane == 0) {
#pragma unroll 1
            for (int i = 0; i < 5; i++) {
                bulk_s2g((char*)&S->v[(size_t)b * 1152] + i * 4096, sb + OFF_MISC, i < 4 ? 4096 : 2048);
                if (i < 3) bulk_s2g((char*)&S->part[(size_t)b * 1152] + i * 4096, sb + OFF_MISC, i < 2 ? 4096 : 1024);
            }
            bulk_s2g(&S->rec[8 * b], sb + OFF_MISC, 32);
            asm volatile("cp.async.bulk.commit_group;" ::: "memory");
        }
        __syncwarp();
    }
            const cplx z258 = cmul(z256, z2), z512 = csq(z256), z768 = cmul(z512, z256);
            {
                const uint32_t a0 = CJ(z256), a0p = CJP(z256), a1 = CJ(z258), a1p = CJP(z258);
#pragma unroll
                for (int i = 0; i < 4; i++) { sts32(ws + 1152 + (2 * i) * 144, hcm(cz[i], a0, a0p)); sts32(ws + 1152 + (2 * i + 1) * 144, hcm(cz[i], a1, a1p)); }
                tile(acc[2], 1);
            }
            {
                const uint32_t a0 = CJ(z512), a0p = CJP(z512), a1 = CJ(z768), a1p = CJP(z768);
#pragma unroll
                for (int i = 0; i < 4; i++) { sts32(ws + 2304 + i * 144, hcm(cz[i], a0, a0p)); sts32(ws + 2304 + (4 + i) * 144, hcm(cz[i], a1, a1p)); }
                tile(acc[3], 2);
            }
            if (warp == 3) {
                if (lane == 15) pre = ld_rlx(S->hint);
            }
            const cplx z1024 = csq(z512);
            {
                const cplx zk[4] = {z1024, cmul(z1024, z256), csq(z768), cmul(z1024, z768)};
#pragma unroll
                for (int h = 0; h < 4; h++) {
                    const uint32_t a0 = CJ(zk[h]), a0p = CJP(zk[h]);
                    sts32(ws + (2 * h) * 144, hcm(cz[0], a0, a0p));
                    sts32(ws + (2 * h + 1) * 144, hcm(cz[2], a0, a0p));
                }
                tile(acc[4], 0);
            }
            const cplx z2048 = csq(z1024);
            float last = C.x * z2048.x - C.y * z2048.y;
#pragma unroll
            for (int o = 16; o; o >>= 1) last += __shfl_xor_sync(0xffffffffu, last, o);
            __syncwarp();
#pragma unroll
            for (int i = 0; i < 5; i++) *(float4*)(sm + (scr - sb) + i * 512 + lane * 16) = make_float4(acc[i][0], acc[i][1], acc[i][2], acc[i][3]);
            if (lane == 0) { const float inv = __uint_as_float(ex << 23); M.kinv[wgi][w] = inv; M.klast[wgi][w] = last * inv; }
        }
        if (tid == 111 && (int)(pre - HINT_N * wait_epoch(M)) >= 0) M.flag = 1u;
        named_bar(1 + wgi, 128);
        const uint32_t td = cb + XO_TD + 64 * 4, tf = cb + XO_TF - 32 * 4;
        if (tid == 111 && !M.flag) pre = ld_rlx(S->hint);
        const float4 ki = *(const float4*)M.kinv[wgi];
        auto fsum = [&](int off, uint32_t& r0, uint32_t& r1) {
            const unsigned char* p = sm + (cb - sb) + off;
            const float4 a = *(const float4*)p, b2 = *(const float4*)(p + KSCR), c = *(const float4*)(p + 2 * KSCR), d = *(const float4*)(p + 3 * KSCR);
            r0 = pack2(fmaf(a.y, ki.x, b2.y * ki.y) + fmaf(c.y, ki.z, d.y * ki.w), fmaf(a.x, ki.x, b2.x * ki.y) + fmaf(c.x, ki.z, d.x * ki.w));
            r1 = pack2(fmaf(a.w, ki.x, b2.w * ki.y) + fmaf(c.w, ki.z, d.w * ki.w), fmaf(a.z, ki.x, b2.z * ki.y) + fmaf(c.z, ki.z, d.z * ki.w));
        };
        uint32_t r[2], q[2];
        fsum(w * 512 + lane * 16, r[0], r[1]);
        fsum(2048 + w * 128 + lr * 16, q[0], q[1]);
        if (tid == 111) {
            if ((int)(pre - HINT_N * M.epoch) >= 0) M.flag = 1u;
            else pre = ld_rlx(S->hint);
        }
        __syncwarp();
        if (w < 2) {
            const uint32_t p = td + (16 * g + 8 * w + 2 * t) * 4;
#pragma unroll
            for (int h = 0; h < 2; h++) { sts16(p + h * 512, r[h] >> 16); sts32(p + h * 512 + 4, r[h]); sts16(p + h * 512 + 10, r[h]); }
        } else if (w == 2) {
            const uint32_t p = td + (256 + 16 * g + 4 * t) * 4;
#pragma unroll
            for (int h = 0; h < 2; h++) {
                const uint32_t k0 = r[h] >> 16;
                if (h || lane) { sts16(p + h * 512 - 4, k0); sts16(p + h * 512 + 2, k0); }
                sts16(p + h * 512, k0); sts32(p + h * 512 + 4, __byte_perm(r[h], 0, 0x3232)); sts32(p + h * 512 + 8, r[h]); sts16(p + h * 512 + 14, r[h]);
            }
        } else {
            const uint32_t p = tf + (64 + 32 * (t >> 1) + 2 * g + (t & 1)) * 4;
#pragma unroll
            for (int h = 0; h < 2; h++) {
                const uint32_t k0 = r[h] >> 16;
                sts16(p + h * 64 + 512, r[h]); sts16(p + h * 64 + 518, r[h]);
                if (h || lane) { sts16(p + h * 64 - 4, k0); sts16(p + h * 64 + 2, k0); }
            }
            if (lane == 0) {
                const uint32_t dd = __byte_perm(r[0], 0, 0x3232);
                sts16(td + 511 * 4, dd); sts32(td + 512 * 4, dd); sts32(td + 513 * 4, dd); sts32(td + 514 * 4, dd); sts16(td + 515 * 4 + 2, dd);
            }
        }
        if (lane < 8) {
            const uint32_t p = tf + 1024 + (64 + 16 * t + 2 * w + g) * 4;
#pragma unroll
            for (int h = 0; h < 2; h++) {
                const uint32_t k0 = q[h] >> 16;
                sts16(p + h * 32 + 512, q[h]); sts16(p + h * 32 + 518, q[h]);
                if (h || (tid & 127)) { sts16(p + h * 32 - 4, k0); sts16(p + h * 32 + 2, k0); }
            }
            if ((tid & 127) == 0) {
                const float4 kl4 = *(const float4*)M.klast[wgi];
                const uint32_t kl = f2bits((kl4.x + kl4.y) + (kl4.z + kl4.w)), dd = __byte_perm(q[0], 0, 0x3232);
                sts16(tf + 127 * 4, dd); sts16(tf + 128 * 4 + 2, dd); sts32(cb + XO_K1024, dd);
                sts16(tf + 1024 + 127 * 4, kl); sts16(tf + 1024 + 128 * 4 + 2, kl);
            }
        }
        __syncwarp();
    } else {
        const int i = tid - 512, idx = b >> 1;
        tag16 = (wait_epoch(M) % 65535u) + 1u;
        mod_tile(0);
        if (i == 0 && idx < 44) {
            PROXY_FENCE();
            mbar_expect(mb_wm + 8, 36864);
#pragma unroll
            for (int k = 0; k < 3; k++) tma2d(sb + OFF_WU + k * 12288, &tm_wm, 32 * (idx + 64), 192 * k, mb_wm + 8);
        }
        __syncwarp();
    }
    if (tid == 111) {
        epoch = wait_epoch(M);
#pragma unroll 1
        for (int it = 0; it < SPIN_MAX && (int)(pre - HINT_N * epoch) < 0; it++) pre = ld_rlx(S->hint);
        M.flag = 1u;
    }
    __syncwarp();
    const int ubp = (tid * 13108) >> 16, uloc = tid - 5 * ubp;
    const uint4* usrc = &S->xn[(size_t)b * 1280 + 2 * tid];
    uint4 ua = make_uint4(0, 0, 0, 0), uc = ua;
    uint32_t usa = 0, uca = 0;
    if (lane == 0) {
#pragma unroll 1
        for (int it = 0; it < (SPIN_MAX << 4) && !M.flag; it++) { }
    }
    __syncwarp();
    if (uloc < nch) {
 ua = ld_rlx4(usrc); uc = ld_rlx4(usrc + 1); usa = ld_rlx(&S->modw[cs + uloc]); uca = ld_rlx(&S->modw[D_ + cs + uloc]); }
    CBAR();
    epoch = M.epoch;
    tag16 = (epoch % 65535u) + 1u;
    {
        const int bp = ubp, loc = uloc;
        if (loc < nch) {
            const uint4* src = usrc;
            uint4 a = ua, c = uc;
#pragma unroll 1
            for (int it = 0; it < SPIN_MAX && (a.x == SENT || a.z == SENT || c.x == SENT || c.z == SENT || (usa >> 16) != tag16 || (uca >> 16) != tag16); it++) {
                a = ld_rlx4(src); c = ld_rlx4(src + 1); usa = ld_rlx(&S->modw[cs + loc]); uca = ld_rlx(&S->modw[D_ + cs + loc]);
            }
            const uint32_t sa = __byte_perm(usa, 0, 0x1010), ca = pack2(1.0f + lo2f(uca), 1.0f + lo2f(uca));
            unsigned char* up = sm + OFF_CH + loc * CHS + ((2 * bp) & 7) * ULBO + ((bp >> 2) + 9) * 16;
            *(uint4*)up = make_uint4(add2(mul2(~a.x, ca), sa), add2(mul2(~a.z, ca), sa), add2(mul2(~c.x, ca), sa), add2(mul2(~c.z, ca), sa));
            *(uint4*)(up + ULBO) = make_uint4(add2(mul2(~a.y, ca), sa), add2(mul2(~a.w, ca), sa), add2(mul2(~c.y, ca), sa), add2(mul2(~c.w, ca), sa));
        }
        publish_reset();
        const int i = tid & 127;
        unsigned char* cp = sm + OFF_CH + wgi * CHS;
        *(uint4*)(cp + XO_U8 - 1024 + (i >> 6) * 4096 + (i & 63) * 16) = make_uint4(0, 0, 0, 0);
        if (i < 72) { const int c = (i * 57) >> 9; *(uint4*)(cp + c * ULBO + (i - 9 * c) * 16) = make_uint4(0, 0, 0, 0); }
    }
    PROXY_FENCE();
    CBAR();
    if (w == 2 && lane == 0) {
        bulk_s2g((char*)&S->xn[(size_t)b * 1280] + wgi * 4096, sb + OFF_MISC, 4096);
        asm volatile("cp.async.bulk.commit_group;" ::: "memory");
    }
        if (tid == 416) {
            mbar_expect(mb_wg, nf * D_ * 2);
            tma2d(sb + OFF_WG, (b & 1) ? &tm_wg : &tm_wg32, f0, 0, mb_wg);
        }
    if (tid == 96 || tid == 224) tma2d(sb + OFF_WG + (1 + (tid >> 7)) * (nf * 384), (b & 1) ? &tm_wg : &tm_wg32, f0, 192 * (1 + (tid >> 7)), mb_wg);
    if (has_ch) {
        __syncwarp();
        conv_channel(sm, S, 2 * D_ + cs + wgi, epoch, w_down + (size_t)f0 * D_, (b & 1) ? nullptr : &tm_wu32, f0);
    } else {
        const int idx = b >> 1;
        if (idx < 44) mod_tile(1);
        if (tid == 512) {
            PROXY_FENCE();
            mbar_expect(mb_wu, 46080);
#pragma unroll 1
            for (int i = 0; i < 3; i++) {
                tma2d(sb + OFF_WU + i * 15360, &tm_wu, f0, 192 * i, mb_wu);
                const long long c0 = clock64();
                int it = 0;
                while (clock64() - c0 < 1200 && ++it < 4096) { }
            }
            wait_reset(S->cnt, epoch);
        }
        named_bar(5, 128);
    }
    {
    const int tid = fresh_tid(), warp = __shfl_sync(0xffffffffu, tid >> 5, 0), lane = tid & 31;
    const int g = lane >> 2, t = lane & 3, lr = lane & 7, lm = lane >> 3;
    uint32_t v3 = 0, v4 = 0, v5 = 0;
    auto load_consts = [&]() {
        if (tid < D_) { v3 = ld_rlx(&S->modw[3 * D_ + tid]); v4 = ld_rlx(&S->modw[4 * D_ + tid]); v5 = ld_rlx(&S->modw[5 * D_ + tid]); }
    };
    if (tid == 0) bulk_pf(w_down + (size_t)(f0 + 16) * D_, (nf - 16) * D_ * 2);
    uint32_t x1[2][4], wr2[2][2];
    if (warp < 18) {
        const char* vp = (const char*)S->v + ((size_t)b * D_ + 32 * warp + g) * 32 + t * 8;
        uint2 v[4];
#pragma unroll
        for (int i = 0; i < 4; i++) v[i] = ld_rlx2(vp + i * 256);
#pragma unroll
        for (int j = 0; j < 2; j++) {
            const uint32_t* wp = M.wr + 16 * warp + 8 * j + t;
            wr2[j][0] = (g == 0) ? wp[0] : 0u;
            wr2[j][1] = (g == 0) ? wp[4] : 0u;
            ldsm_x4(x1[j], sb + OFF_TILE + (lr + 8 * (lm & 1)) * (ROWP * 2) + (lm >> 1) * 16 + warp * 64 + j * 32);
        }
#pragma unroll 1
        for (int it = 0; it < SPIN_MAX && ((v3 >> 16) != tag16 || (v4 >> 16) != tag16 || (v5 >> 16) != tag16); it++) load_consts();
        ((unsigned short*)M.sb)[tid] = (unsigned short)v3;
        ((unsigned short*)M.cb1)[tid] = (unsigned short)f2bits(1.0f + lo2f(v4));
        ((unsigned short*)M.gb)[tid] = (unsigned short)v5;
#pragma unroll 1
        for (int it = 0; it < SPIN_MAX; it++) {
            bool bad = false;
#pragma unroll
            for (int i = 0; i < 4; i++) if (v[i].x == SENT) { v[i] = ld_rlx2(vp + i * 256); bad = true; }
            if (!bad) break;
        }
        __syncwarp();
        float c1[4] = {0.f, 0.f, 0.f, 0.f}, cl[4] = {0.f, 0.f, 0.f, 0.f}, chh[4] = {0.f, 0.f, 0.f, 0.f};
#pragma unroll
        for (int j = 0; j < 2; j++) {
            x1[j][0] = add2(x1[j][0], movm(~v[2 * j].x)); x1[j][1] = add2(x1[j][1], movm(~v[2 * j].y));
            x1[j][2] = add2(x1[j][2], movm(~v[2 * j + 1].x)); x1[j][3] = add2(x1[j][3], movm(~v[2 * j + 1].y));
            mma_bf16(c1, x1[j][0], x1[j][1], x1[j][2], x1[j][3], 0x3F803F80u, 0x3F803F80u);
            mma_bf16(cl, x1[j][0], x1[j][1], x1[j][2], x1[j][3], x1[j][0], x1[j][2]);
            mma_bf16(chh, x1[j][0], x1[j][1], x1[j][2], x1[j][3], x1[j][1], x1[j][3]);
        }
        float* pp = (float*)&M.part[warp][g];
        if (t == 0) { pp[0] = c1[0]; pp[16] = c1[2]; }
        if (t == (g >> 1)) { pp[1] = (g & 1) ? cl[1] : cl[0]; pp[17] = (g & 1) ? chh[3] : chh[2]; }
    }
    CBAR();
    if (warp < 18) {
        const int tok = lane & 15, hf = lane >> 4;
        uint32_t kc[2][2][2];
#pragma unroll
        for (int j = 0; j < 2; j++)
#pragma unroll
            for (int q = 0; q < 2; q++) { kc[j][q][0] = ((const uint32_t*)M.cb1)[16 * warp + 8 * j + 4 * q + t]; kc[j][q][1] = ((const uint32_t*)M.sb)[16 * warp + 8 * j + 4 * q + t]; }
        named_bar(13, 608);
        uint32_t st[2][3];
#pragma unroll
        for (int h = 0; h < 2; h++) { const uint4 q = M.st2[g + 8 * h]; st[h][0] = q.x; st[h][1] = q.y; st[h][2] = q.z; }
        float rc[4] = {0.f, 0.f, 0.f, 0.f};
        uint32_t h2[2][4];
#pragma unroll
        for (int j = 0; j < 2; j++) {
#pragma unroll
            for (int r = 0; r < 4; r++) {
                h2[j][r] = add2(mul2(norm2(x1[j][r], st[r & 1][0], st[r & 1][1], st[r & 1][2]), kc[j][r >> 1][0]), kc[j][r >> 1][1]);
            }
            mma_bf16(rc, h2[j][0], h2[j][1], h2[j][2], h2[j][3], wr2[j][0], wr2[j][1]);
        }
        if (t == 0) { M.rp[warp][g] = rc[0]; M.rp[warp][g + 8] = rc[2]; }
        if (warp == 0) {
            named_bar(12, 576);
            float r = M.rp[9 * hf][tok];
#pragma unroll
            for (int i = 1; i < 9; i++) r += M.rp[9 * hf + i][tok];
            r += __shfl_xor_sync(0xffffffffu, r, 16);
            const uint32_t rbits = f2bits(r);
            const uint32_t key = 0x80000000u | ((rbits ^ ((rbits & 0x8000u) ? 0xFFFFu : 0x8000u)) << 11) | (uint32_t)(2047 - (16 * b + tok));
            int rank = 0;
#pragma unroll
            for (int j = 1; j < 16; j++) rank += __shfl_xor_sync(0xffffffffu, key, j) > key;
            if (lane < 16) { M.skey[rank] = key; M.rank[rank] = tok; }
            __syncwarp();
            if (lane < 2) st_rlx4(&S->rec[8 * b + 4 * lane], *(const uint4*)&M.skey[4 * lane]);
        } else named_arrive(12, 576);
#pragma unroll
        for (int j = 0; j < 2; j++) {
            uint32_t o[4];
#pragma unroll
            for (int r = 0; r < 4; r++) o[r] = add2(x1[j][r], mul2(((const uint32_t*)M.gb)[16 * warp + 8 * j + 4 * (r >> 1) + t], h2[j][r]));
            const uint32_t to = (lr + 8 * (lm & 1)) * (ROWP * 2) + (lm >> 1) * 16 + warp * 64 + j * 32;
            stsm_x4(sb + OFF_H2T + to, h2[j][0], h2[j][1], h2[j][2], h2[j][3]);
            stsm_x4(sb + OFF_TILE + to, o[0], o[1], o[2], o[3]);
        }
    } else if (warp == 19) {
        const int tok = lane & 15, hf = lane >> 4;
        float2 s = M.part[9 * hf][tok];
#pragma unroll
        for (int i = 1; i < 9; i++) { const float2 q = M.part[9 * hf + i][tok]; s.x += q.x; s.y += q.y; }
        s.x += __shfl_xor_sync(0xffffffffu, s.x, 16); s.y += __shfl_xor_sync(0xffffffffu, s.y, 16);
        float meanb, rinv;
        ln_stats(s.x, s.y, meanb, rinv);
        const float rh = bfr(rinv);
        if (lane < 16) M.st2[tok] = make_uint4(pack2(meanb, meanb), pack2(rh, rh), pack2(rinv - rh, rinv - rh), 0u);
        __syncwarp();
        named_arrive(13, 608);
    } else if (lane < 9) {
        PROXY_FENCE();
        if (lane == 0) mbar_expect(mb_wd, nf * D_ * 2);
        tma2d(sb + OFF_WD + lane * 5120, (b & 1) ? &tm_wd : &tm_wd32, 64 * lane, f0, mb_wd);
    }
    CBAR();
    uint32_t wf[9][4], wd[2][3][4];
    const int fmt = warp >> 2, fsl = warp & 3;
    auto load_wf = [&]() {
        mbar_wait(mb_wg, 0);
        mbar_wait(mb_wu, 0);
        if (fmt < 4 || nf > 32) {
            const int half = lm & 1;
            const uint32_t base = (fmt == 4) ? ((half ? OFF_WU : OFF_WG) + 64)
                                             : ((fmt >> 1) * OFF_WU + (((2 * (fmt & 1) + half) ^ ((b & 1) ? 0 : (lr >> 1))) << 4));
            const uint32_t wa = sb + base + (144 * fsl + lr + 8 * (lm >> 1)) * (2 * nf);
#pragma unroll
            for (int ks = 0; ks < 9; ks++) ldsm_x4_t(wf[ks], wa + ks * (32 * nf));
        }
    mbar_wait(mb_wd, 0);
    {
#pragma unroll
        for (int i = 0; i < 2; i++) {
            const int mt = warp + 20 * i;
            const uint32_t wa = sb + OFF_WD + (mt >> 2) * 5120 + lr * 128 + (((2 * (mt & 3) + (lm & 1)) ^ lr) << 4);
#pragma unroll
            for (int ks = 0; ks < 3; ks++)
                if ((i == 0 || warp < 16) && (ks < 2 || nf > 32)) ldsm_x4_t(wd[i][ks], wa + ks * 2048 + ((ks < 2) ? (lm >> 1) * 1024 : 0));
        }
    }
    };
    if (warp >= 8) {
        if (warp < 16) {
            const int tk = M.rank[warp - 8];
            const uint32_t* hp = (const uint32_t*)(sm + OFF_H2T + tk * (ROWP * 2)) + lane;
            uint4* dst = &S->h2w[(size_t)(16 * b + tk) * 96 + lane];
#pragma unroll
            for (int j = 0; j < 3; j++) st_rlx4(dst + 32 * j, make_uint4(hp[96 * j], hp[96 * j + 32], hp[96 * j + 64], epoch));
        }
        load_wf();
    } else {
        const uint4* rp = (const uint4*)S->rec + tid;
        load_wf();
        uint4 rk = ld_rlx4(rp);
#pragma unroll 1
        for (int it = 0; it < SPIN_MAX && !rk.x; it++) rk = ld_rlx4(rp);
        __syncwarp();
        uint32_t mine = 0;
#pragma unroll
        for (int rnd = 0; rnd < 8; rnd++) {
            const uint32_t m = __reduce_max_sync(0xffffffffu, rk.x);
            if (rk.x == m) { rk.x = rk.y; rk.y = rk.z; rk.z = rk.w; rk.w = 0u; }
            if (lane == rnd) mine = m;
        }
        if (lane < 8) M.cand[8 * warp + lane] = mine;
    }
    CBAR();
    uint32_t selv = 0;
    if (warp < 12) {
        uint2 k = *(const uint2*)&M.cand[2 * lane];
#pragma unroll
        for (int rnd = 0; rnd < 8; rnd++) {
            const uint32_t m = __reduce_max_sync(0xffffffffu, k.x);
            if (k.x == m) { k.x = k.y; k.y = 0u; }
            if (lr == rnd) selv = m;
        }
        if (tid < 8) M.skey[tid] = selv;
    }
    const uint32_t seltok = 2047u - (selv & 2047u);
    const int fo = tid >> 3;
    const int fW = 9 * b + (fo >> 2), fcomp = fo & 3;
    const int fd = 16 * (fW >> 5) + ((fW >> 2) & 7) + 8 * (fcomp >> 1), fk = 2 * (fW & 3) + (fcomp & 1);
    const uint32_t fsel = __shfl_sync(0xffffffffu, selv, fk);
    uint32_t fx = 0, fv = 0;
    bf16(*h2s)[ROWP] = (bf16(*)[ROWP])(sm + OFF_H2S);
    if (warp < 12) {
        uint4 wv[2];
        const uint4* hp[2];
#pragma unroll
        for (int r = 0; r < 2; r++) {
            const int wi = warp + 12 * r, k = wi / 3, j = wi - 3 * k;
            hp[r] = &S->h2w[(size_t)__shfl_sync(0xffffffffu, seltok, k) * 96 + 32 * j + lane];
            wv[r] = ld_rlx4(hp[r]);
        }
        if (tid < 288 && (tid & 7) == 0) {
            const uint32_t ft = 2047u - (fsel & 2047u), pr = (ft & 15u) >> 1;
            fx = ((const unsigned short*)x)[(size_t)ft * D_ + fd];
            asm volatile("ld.relaxed.gpu.global.u16 %0, [%1];" : "=r"(fv)
                         : "l"((const unsigned short*)S->v + ((size_t)(ft >> 4) * D_ + fd) * 16 + ((pr & 3u) * 2 + (pr >> 2)) * 2 + (ft & 1u)) : "memory");
        }
#pragma unroll 1
        for (int it = 0; it < SPIN_MAX && (wv[0].w != epoch || wv[1].w != epoch); it++) { wv[0] = ld_rlx4(hp[0]); wv[1] = ld_rlx4(hp[1]); }
#pragma unroll
        for (int r = 0; r < 2; r++) {
            const int wi = warp + 12 * r, k = wi / 3, j = wi - 3 * k;
            uint32_t* dst = (uint32_t*)&h2s[k][0] + 96 * j + lane;
            dst[0] = wv[r].x; dst[32] = wv[r].y; dst[64] = wv[r].z;
        }
    }
    CBAR();
    float* ffr = (float*)(sm + OFF_FFR);
    if (fmt < 4 || nf > 32) {
        float acc[2][4] = {{0.f, 0.f, 0.f, 0.f}, {0.f, 0.f, 0.f, 0.f}};
        const uint32_t ha = sb + OFF_H2S + lr * (ROWP * 2) + (144 * fsl) * 2 + lm * 16;
#pragma unroll
        for (int k2 = 0; k2 < 5; k2++) {
            uint32_t hb[4];
            ldsm_x4(hb, ha + k2 * 64 - ((k2 == 4) ? (lm >> 1) * 32 : 0));
            mma_bf16(acc[0], wf[2 * k2][0], wf[2 * k2][1], wf[2 * k2][2], wf[2 * k2][3], hb[0], hb[1]);
            if (k2 < 4) mma_bf16(acc[1], wf[2 * k2 + 1][0], wf[2 * k2 + 1][1], wf[2 * k2 + 1][2], wf[2 * k2 + 1][3], hb[2], hb[3]);
        }
        float* o = ffr + ((fsl * 80 + 16 * fmt + g) * 8 + 2 * t);
        *(float2*)o = make_float2(acc[0][0] + acc[1][0], acc[0][1] + acc[1][1]);
        *(float2*)(o + 64) = make_float2(acc[0][2] + acc[1][2], acc[0][3] + acc[1][3]);
    }
    CBAR();
    bf16(*act)[56] = (bf16(*)[56])(sm + OFF_ACT);
    if (tid < 384) {
        const int f = tid >> 3, a = tid & 7;
        float v = 0.f;
        if (f < nf) {
            const int rg = (f < 32) ? f : f + 32, ru = (f < 32) ? f + 32 : f + 40;
            const float* pg = ffr + rg * 8 + a;
            const float* pu = ffr + ru * 8 + a;
            float gg = bfr((pg[0] + pg[640]) + (pg[1280] + pg[1920]));
            gg = bfr(silu(gg));
            const float uu = bfr((pu[0] + pu[640]) + (pu[1280] + pu[1920]));
            v = gg * uu;
        }
        act[a][f] = __ushort_as_bfloat16((unsigned short)f2bits(v));
    }
    CBAR();
    {
        uint32_t bq[3][2];
#pragma unroll
        for (int ks = 0; ks < 3; ks++) {
            bq[ks][0] = *(const uint32_t*)&act[g][16 * ks + 2 * t];
            bq[ks][1] = *(const uint32_t*)&act[g][16 * ks + 2 * t + 8];
        }
#pragma unroll
        for (int i = 0; i < 2; i++) {
            if (i == 0 || warp < 16) {
                float acc[4] = {0.f, 0.f, 0.f, 0.f};
#pragma unroll
                for (int ks = 0; ks < 3; ks++)
                    if (ks < 2 || nf > 32) mma_bf16(acc, wd[i][ks][0], wd[i][ks][1], wd[i][ks][2], wd[i][ks][3], bq[ks][0], bq[ks][1]);
                const int W = (warp + 20 * i) * 32 + lane, c = (W * 7282) >> 16;
                st_rlx2(&S->part[(c * G_ + b) * 9 + W - 9 * c], ~pack2(acc[0], acc[1]), ~pack2(acc[2], acc[3]));
            }
        }
    }
    if (warp >= 4) {
        const int tk = warp - 4;
        if (!__any_sync(0xffffffffu, 2047u - (M.skey[lr] & 2047u) == (uint32_t)(16 * b + tk))) {
            const uint4* src = (const uint4*)(sm + OFF_TILE + tk * (ROWP * 2));
            uint4* dst = (uint4*)(out + (size_t)(16 * b + tk) * D_);
            dst[lane] = src[lane]; dst[lane + 32] = src[lane + 32];
            if (lane < 8) dst[lane + 64] = src[lane + 64];
        }
    }
    float4* fin = (float4*)(sm + OFF_FIN);
    uint32_t rb = (fsel >> 11) & 0xFFFFu;
    rb ^= (rb & 0x8000u) ? 0x8000u : 0xFFFFu;
    const float rs = bfr(__fdividef(1.0f, 1.0f + __expf(-lo2f(rb))));
    const float fh2 = (tid < 288) ? __bfloat162float(h2s[fk][fd]) : 0.f, fgb = (tid < 288) ? __bfloat162float(M.gb[fd]) : 0.f;
    const float fx1 = bfr(lo2f(fx) + lo2f(~fv));
    if (tid < 576) {
        const uint2* src = &S->part[(size_t)b * 1152 + tid];
        uint2 a = ld_rlx2(src), c = ld_rlx2(src + 576);
#pragma unroll 1
        for (int it = 0; it < SPIN_MAX && (a.x == SENT || c.x == SENT); it++) {
            if (a.x == SENT) a = ld_rlx2(src);
            if (c.x == SENT) c = ld_rlx2(src + 576);
        }
        fin[tid] = make_float4(lo2f(~a.x) + lo2f(~c.x), hi2f(~a.x) + hi2f(~c.x), lo2f(~a.y) + lo2f(~c.y), hi2f(~a.y) + hi2f(~c.y));
    }
    CBAR();
    if (tid < 288) {
        const int part = tid & 7;
        const float* f = (const float*)fin + part * 36 + fo;
        float s = ((f[0] + f[288]) + (f[576] + f[864])) + ((f[1152] + f[1440]) + (f[1728] + f[2016]));
        s += __shfl_xor_sync(0xffffffffu, s, 1);
        s += __shfl_xor_sync(0xffffffffu, s, 2);
        s += __shfl_xor_sync(0xffffffffu, s, 4);
        const float upd = bfr(bfr(s) * rs);
        const float ov = fx1 + bfr(fgb * bfr(fh2 + upd));
        if (part == 0) out[(size_t)(2047u - (fsel & 2047u)) * D_ + fd] = __ushort_as_bfloat16((unsigned short)f2bits(ov));
    }
    if ((warp & 3) == 2 && lane == 0) asm volatile("cp.async.bulk.wait_group 0;" ::: "memory");
    }
}

typedef CUresult (*EncodeFn)(CUtensorMap*, CUtensorMapDataType, cuuint32_t, void*, const cuuint64_t*, const cuuint64_t*,
                             const cuuint32_t*, const cuuint32_t*, CUtensorMapInterleave, CUtensorMapSwizzle,
                             CUtensorMapL2promotion, CUtensorMapFloatOOBfill);

static void make_map(EncodeFn fn, CUtensorMap* m, const void* ptr, uint64_t cols, uint64_t rows, uint32_t bc, uint32_t br,
                     CUtensorMapSwizzle sw) {
    cuuint64_t dims[2] = {cols, rows};
    cuuint64_t strides[1] = {cols * 2};
    cuuint32_t box[2] = {bc, br};
    cuuint32_t es[2] = {1, 1};
    CUresult rc = fn(m, CU_TENSOR_MAP_DATA_TYPE_BFLOAT16, 2, (void*)ptr, dims, strides, box, es, CU_TENSOR_MAP_INTERLEAVE_NONE,
                     sw, CU_TENSOR_MAP_L2_PROMOTION_NONE, CU_TENSOR_MAP_FLOAT_OOB_FILL_NONE);
    (void)rc;
}

static void launch(void* const* d_in, const int* in_sizes, int n_in, void* d_out, int out_size) {
    static EncodeFn enc = nullptr;
    static CUtensorMap tmm, tmg, tmu, tmd, tmd32, tmg32, tmu32;
    static Scratch* sp = nullptr;
    static const void* cached[4] = {nullptr, nullptr, nullptr, nullptr};
    if (!enc) {
        cudaDriverEntryPointQueryResult qr;
        void* fn = nullptr;
        cudaGetDriverEntryPoint("cuTensorMapEncodeTiled", &fn, cudaEnableDefault, &qr);
        enc = (EncodeFn)fn;
        cudaFuncSetAttribute(mega_kernel, cudaFuncAttributeMaxDynamicSharedMemorySize, SMEM_TOTAL);
        cudaGetSymbolAddress((void**)&sp, g_s);
    }
    if (cached[0] != d_in[13] || cached[1] != d_in[9] || cached[2] != d_in[10] || cached[3] != d_in[11]) {
        make_map(enc, &tmm, d_in[13], 6 * D_, D_, 32, 192, CU_TENSOR_MAP_SWIZZLE_64B);
        make_map(enc, &tmg, d_in[9], F_, D_, 40, 192, CU_TENSOR_MAP_SWIZZLE_NONE);
        make_map(enc, &tmu, d_in[10], F_, D_, 40, 192, CU_TENSOR_MAP_SWIZZLE_NONE);
        make_map(enc, &tmg32, d_in[9], F_, D_, 32, 192, CU_TENSOR_MAP_SWIZZLE_64B);
        make_map(enc, &tmu32, d_in[10], F_, D_, 32, 192, CU_TENSOR_MAP_SWIZZLE_64B);
        make_map(enc, &tmd, d_in[11], D_, F_, 64, 40, CU_TENSOR_MAP_SWIZZLE_128B);
        make_map(enc, &tmd32, d_in[11], D_, F_, 64, 32, CU_TENSOR_MAP_SWIZZLE_128B);
        cached[3] = d_in[11];
        cached[0] = d_in[13]; cached[1] = d_in[9]; cached[2] = d_in[10];
    }
    mega_kernel<<<G_, NTHR, SMEM_TOTAL>>>((const bf16*)d_in[0], (const bf16*)d_in[1], (const bf16*)d_in[2], (const bf16*)d_in[3],
                                          (const bf16*)d_in[4], (const bf16*)d_in[5], (const bf16*)d_in[12], sp, (const bf16*)d_in[6],
                                          (const bf16*)d_in[8], (const bf16*)d_in[11], (bf16*)d_out, tmm, tmg, tmu, tmd, tmd32, tmg32, tmu32);
}

}

extern "C" void kernel_launch(void* const* d_in, const int* in_sizes, int n_in, void* d_out, int out_size) {
    static int mode = -1;
    if (mode < 0) mode = v5::fits() ? 1 : 0;
    if (mode) v5::launch(d_in, in_sizes, n_in, d_out, out_size);
    else v4::launch(d_in, in_sizes, n_in, d_out, out_size);
}
```

```cpp
#include <cuda_runtime.h>
#include <cuda.h>
#include <cuda_bf16.h>
#include <cuda_fp16.h>
#include <stdint.h>

namespace v5 {

#define L_ 2048
#define D_ 576
#define N_ 128
#define F_ 4608
#define G_ 120
#define NCL 15
#define NTHR 768
#define SPIN_MAX (1 << 18)

typedef __nv_bfloat16 bf16;

struct Scratch {
    float4 acc1[L_ + 8];
    float4 acc2[L_];
    uint4 h2c[128 * 72];
    uint2 part[NCL * 36 * 64];
    float4 rs[32 * 8];
};
#define NRST (L_ + 128 * 72 + NCL * 36 * 32 + 256)
static_assert(NRST == 240 * G_, "reset split");
__device__ __align__(1024) Scratch g_s;

#define OFF_WG 0
#define OFF_WU 46080
#define KSCR 3456
#define OFF_WM0 69120
#define OFF_STG OFF_WM0
#define OFF_MG2 86400
#define OFF_CH 92160
#define CHS 18688
#define ULBO 656
#define XO_U8 6272
#define XO_U16 10368
#define XO_ZA 5248
#define XO_ZB 8448
#define XO_ZC 11648
#define XO_ZD 13824
#define XO_TF 12416
#define XO_TD 16000
#define XO_K1024 18624
#define XO_DSK 18628
#define XO_KINV 18640
#define XO_KLAST 18656
#define XO_MBU 18672
#define OFF_X 185600
#define XG 672
#define XI(i) (((i) >> 1) * 5520 + ((i) & 1) * 2752)
#define XN(n) ((((n) >> 1) & 3) * XG + (2 * ((n) >> 3) + ((n) & 1)) * 80)
#define OFF_V 207616
#define VP 528
#define OFF_EK (OFF_V + 512)
#define OFF_WM2 OFF_V
#define OFF_MG1 (OFF_V + 17280)
#define OFF_SC (OFF_V + 19840)
#define OFF_C1 (OFF_V + 20640)
#define OFF_MISC 228736
#define OFF_WD OFF_CH
#define OFF_H2T (OFF_CH + 46080)
#define OFF_OUT (OFF_CH + 66560)
#define ROWP 584
#define OFF_H2S 0
#define OFF_FFR 9344
#define OFF_ACT 19584
#define OFF_RS 20480

enum { MB_WM2, MB_MG1, MB_MG2, MB_KEY, MB_V, MB_RS, MB_WG, MB_WU, MB_WD, MB_KEY2, MB_EK, MB_C2, MB_CW, MB_KD, MB_OUT, MB_C1, MB_N };

struct Misc {
    __align__(16) uint4 box[4 * 14];
    __align__(16) unsigned int key[256], cand[128];
    __align__(16) uint4 c2[20];
    __align__(16) unsigned int fin[12];
    unsigned int ga[8], wr[20];
    float cws[2];
    unsigned long long mbar[MB_N];
};
#define SMEM_TOTAL (OFF_MISC + (int)sizeof(Misc))
static_assert(SMEM_TOTAL <= 232448, "smem");

__device__ __forceinline__ float lo2f(uint32_t w) { return __uint_as_float(w << 16); }
__device__ __forceinline__ float hi2f(uint32_t w) { return __uint_as_float(w & 0xFFFF0000u); }
__device__ __forceinline__ uint32_t pack2(float lo, float hi) { uint32_t r; asm("cvt.rn.bf16x2.f32 %0, %1, %2;" : "=r"(r) : "f"(hi), "f"(lo)); return r; }
__device__ __forceinline__ float bfr(float x) { return __uint_as_float(pack2(0.f, x)); }
__device__ __forceinline__ uint32_t f2bits(float x) { return pack2(x, 0.f); }
__device__ __forceinline__ uint32_t packh(float lo, float hi) { uint32_t r; asm("cvt.rn.f16x2.f32 %0, %1, %2;" : "=r"(r) : "f"(hi), "f"(lo)); return r; }
__device__ __forceinline__ float frcp(float x) { float r; asm("rcp.approx.ftz.f32 %0, %1;" : "=f"(r) : "f"(x)); return r; }
__device__ __forceinline__ float fsqrt(float x) { float r; asm("sqrt.approx.f32 %0, %1;" : "=f"(r) : "f"(x)); return r; }
__device__ __forceinline__ float fex2(float x) { float r; asm("ex2.approx.ftz.f32 %0, %1;" : "=f"(r) : "f"(x)); return r; }
__device__ __forceinline__ float silu(float x) { return __fdividef(x, 1.0f + __expf(-x)); }
__device__ __forceinline__ uint32_t add2(uint32_t a, uint32_t b) { uint32_t r; asm("add.rn.bf16x2 %0, %1, %2;" : "=r"(r) : "r"(a), "r"(b)); return r; }
__device__ __forceinline__ uint32_t sub2(uint32_t a, uint32_t b) { uint32_t r; asm("sub.rn.bf16x2 %0, %1, %2;" : "=r"(r) : "r"(a), "r"(b)); return r; }
__device__ __forceinline__ uint32_t mul2(uint32_t a, uint32_t b) { uint32_t r; asm("mul.rn.bf16x2 %0, %1, %2;" : "=r"(r) : "r"(a), "r"(b)); return r; }
__device__ __forceinline__ uint32_t fma2(uint32_t a, uint32_t b, uint32_t c) { uint32_t r; asm("fma.rn.bf16x2 %0, %1, %2, %3;" : "=r"(r) : "r"(a), "r"(b), "r"(c)); return r; }
__device__ __forceinline__ uint32_t norm2(uint32_t x, uint32_t m, uint32_t rh, uint32_t rl) { const uint32_t d = sub2(x, m); return fma2(d, rh, mul2(d, rl)); }

__device__ __forceinline__ void mma_bf16(float* c, uint32_t a0, uint32_t a1, uint32_t a2, uint32_t a3, uint32_t b0, uint32_t b1) {
    asm volatile("mma.sync.aligned.m16n8k16.row.col.f32.bf16.bf16.f32 {%0,%1,%2,%3}, {%4,%5,%6,%7}, {%8,%9}, {%0,%1,%2,%3};\n"
                 : "+f"(c[0]), "+f"(c[1]), "+f"(c[2]), "+f"(c[3]) : "r"(a0), "r"(a1), "r"(a2), "r"(a3), "r"(b0), "r"(b1));
}
__device__ __forceinline__ void mma_f16(float* c, const uint32_t* a, uint32_t b0, uint32_t b1) {
    asm volatile("mma.sync.aligned.m16n8k16.row.col.f32.f16.f16.f32 {%0,%1,%2,%3}, {%4,%5,%6,%7}, {%8,%9}, {%0,%1,%2,%3};\n"
                 : "+f"(c[0]), "+f"(c[1]), "+f"(c[2]), "+f"(c[3]) : "r"(a[0]), "r"(a[1]), "r"(a[2]), "r"(a[3]), "r"(b0), "r"(b1));
}
__device__ __forceinline__ void ldsm_x4(uint32_t* r, uint32_t addr) {
    asm volatile("ldmatrix.sync.aligned.m8n8.x4.shared.b16 {%0,%1,%2,%3}, [%4];" : "=r"(r[0]), "=r"(r[1]), "=r"(r[2]), "=r"(r[3]) : "r"(addr) : "memory");
}
__device__ __forceinline__ void ldsm_x4_t(uint32_t* r, uint32_t addr) {
    asm volatile("ldmatrix.sync.aligned.m8n8.x4.trans.shared.b16 {%0,%1,%2,%3}, [%4];" : "=r"(r[0]), "=r"(r[1]), "=r"(r[2]), "=r"(r[3]) : "r"(addr) : "memory");
}
__device__ __forceinline__ void stsm_x4(uint32_t addr, uint32_t r0, uint32_t r1, uint32_t r2, uint32_t r3) {
    asm volatile("stmatrix.sync.aligned.m8n8.x4.shared.b16 [%0], {%1,%2,%3,%4};" ::"r"(addr), "r"(r0), "r"(r1), "r"(r2), "r"(r3) : "memory");
}
__device__ __forceinline__ void stsm_x4_t(uint32_t addr, uint32_t r0, uint32_t r1, uint32_t r2, uint32_t r3) {
    asm volatile("stmatrix.sync.aligned.m8n8.x4.trans.shared.b16 [%0], {%1,%2,%3,%4};" ::"r"(addr), "r"(r0), "r"(r1), "r"(r2), "r"(r3) : "memory");
}
__device__ __forceinline__ uint32_t movm(uint32_t a) { uint32_t r; asm volatile("movmatrix.sync.aligned.m8n8.trans.b16 %0, %1;" : "=r"(r) : "r"(a)); return r; }
__device__ __forceinline__ uint32_t lds32(uint32_t a) { uint32_t v; asm volatile("ld.shared.u32 %0, [%1];" : "=r"(v) : "r"(a)); return v; }
__device__ __forceinline__ void sts32(uint32_t a, uint32_t v) { asm volatile("st.shared.u32 [%0], %1;" ::"r"(a), "r"(v) : "memory"); }
__device__ __forceinline__ void sts16(uint32_t a, uint32_t v) { asm volatile("st.shared.u16 [%0], %1;" ::"r"(a), "h"((unsigned short)v) : "memory"); }
__device__ __forceinline__ void named_bar(int id, int n) { asm volatile("bar.sync %0, %1;" ::"r"(id), "r"(n) : "memory"); }
__device__ __forceinline__ void named_arrive(int id, int n) { asm volatile("bar.arrive %0, %1;" ::"r"(id), "r"(n) : "memory"); }
#define CBAR() asm volatile("bar.sync 0, 640;" ::: "memory")
#define PROXY_FENCE() asm volatile("fence.proxy.async.shared::cta;" ::: "memory")

#define D4(d, o) "+f"(d[o]), "+f"(d[o + 1]), "+f"(d[o + 2]), "+f"(d[o + 3])
__device__ __forceinline__ void wg32(float* d, uint32_t a0, uint32_t a1, uint32_t a2, uint32_t a3, uint64_t desc) {
    asm volatile("wgmma.mma_async.sync.aligned.m64n32k16.f32.bf16.bf16 {%0,%1,%2,%3,%4,%5,%6,%7,%8,%9,%10,%11,%12,%13,%14,%15}, {%16,%17,%18,%19}, %20, 1, 1, 1, 0;"
                 : D4(d, 0), D4(d, 4), D4(d, 8), D4(d, 12) : "r"(a0), "r"(a1), "r"(a2), "r"(a3), "l"(desc));
}
__device__ __forceinline__ void wg48(float* d, uint32_t a0, uint32_t a1, uint32_t a2, uint32_t a3, uint64_t desc) {
    asm volatile("wgmma.mma_async.sync.aligned.m64n48k16.f32.bf16.bf16 {%0,%1,%2,%3,%4,%5,%6,%7,%8,%9,%10,%11,%12,%13,%14,%15,%16,%17,%18,%19,%20,%21,%22,%23}, {%24,%25,%26,%27}, %28, 1, 1, 1, 0;"
                 : D4(d, 0), D4(d, 4), D4(d, 8), D4(d, 12), D4(d, 16), D4(d, 20) : "r"(a0), "r"(a1), "r"(a2), "r"(a3), "l"(desc));
}
#define O4(d, o) "=f"(d[o]), "=f"(d[o + 1]), "=f"(d[o + 2]), "=f"(d[o + 3])
__device__ __forceinline__ void wg32z(float* d, uint32_t a0, uint32_t a1, uint32_t a2, uint32_t a3, uint64_t desc) {
    asm volatile("wgmma.mma_async.sync.aligned.m64n32k16.f32.bf16.bf16 {%0,%1,%2,%3,%4,%5,%6,%7,%8,%9,%10,%11,%12,%13,%14,%15}, {%16,%17,%18,%19}, %20, 0, 1, 1, 0;"
                 : O4(d, 0), O4(d, 4), O4(d, 8), O4(d, 12) : "r"(a0), "r"(a1), "r"(a2), "r"(a3), "l"(desc));
}
__device__ __forceinline__ void wg48z(float* d, uint32_t a0, uint32_t a1, uint32_t a2, uint32_t a3, uint64_t desc) {
    asm volatile("wgmma.mma_async.sync.aligned.m64n48k16.f32.bf16.bf16 {%0,%1,%2,%3,%4,%5,%6,%7,%8,%9,%10,%11,%12,%13,%14,%15,%16,%17,%18,%19,%20,%21,%22,%23}, {%24,%25,%26,%27}, %28, 0, 1, 1, 0;"
                 : O4(d, 0), O4(d, 4), O4(d, 8), O4(d, 12), O4(d, 16), O4(d, 20) : "r"(a0), "r"(a1), "r"(a2), "r"(a3), "l"(desc));
}
#define WG_FENCE() asm volatile("wgmma.fence.sync.aligned;" ::: "memory")
#define WG_COMMIT() asm volatile("wgmma.commit_group.sync.aligned;" ::: "memory")
#define WG_WAIT(n) asm volatile("wgmma.wait_group.sync.aligned " #n ";" ::: "memory")
#define TQ(p, k) p[2 * (k) + 1], p[2 * (k) + 2], p[2 * (k)], p[2 * (k) + 1]

__device__ __forceinline__ uint4 ld_nc4(const void* p) { uint4 v; asm volatile("ld.global.nc.v4.u32 {%0,%1,%2,%3}, [%4];" : "=r"(v.x), "=r"(v.y), "=r"(v.z), "=r"(v.w) : "l"(p)); return v; }
__device__ __forceinline__ unsigned short ld_nc16(const void* p) { unsigned short v; asm volatile("ld.global.nc.u16 %0, [%1];" : "=h"(v) : "l"(p)); return v; }
__device__ __forceinline__ uint32_t ld_nc(const void* p) { uint32_t v; asm volatile("ld.global.nc.u32 %0, [%1];" : "=r"(v) : "l"(p)); return v; }
__device__ __forceinline__ uint32_t ld_rlx(const unsigned int* p) { uint32_t v; asm volatile("ld.relaxed.gpu.global.u32 %0, [%1];" : "=r"(v) : "l"(p) : "memory"); return v; }
__device__ __forceinline__ uint2 ld_rlx2(const void* p) { uint2 v; asm volatile("ld.relaxed.gpu.global.v2.u32 {%0,%1}, [%2];" : "=r"(v.x), "=r"(v.y) : "l"(p) : "memory"); return v; }
__device__ __forceinline__ uint4 ld_rlx4(const void* p) { uint4 v; asm volatile("ld.relaxed.gpu.global.v4.u32 {%0,%1,%2,%3}, [%4];" : "=r"(v.x), "=r"(v.y), "=r"(v.z), "=r"(v.w) : "l"(p) : "memory"); return v; }
__device__ __forceinline__ void st_rlx(unsigned int* p, uint32_t v) { asm volatile("st.relaxed.gpu.global.u32 [%0], %1;" ::"l"(p), "r"(v) : "memory"); }
__device__ __forceinline__ void st_rlx2(void* p, uint32_t a, uint32_t b) { asm volatile("st.relaxed.gpu.global.v2.u32 [%0], {%1,%2};" ::"l"(p), "r"(a), "r"(b) : "memory"); }
__device__ __forceinline__ void st_rlx4(void* p, uint4 v) { asm volatile("st.relaxed.gpu.global.v4.u32 [%0], {%1,%2,%3,%4};" ::"l"(p), "r"(v.x), "r"(v.y), "r"(v.z), "r"(v.w) : "memory"); }
__device__ __forceinline__ void red_inc(unsigned int* p) { asm volatile("red.relaxed.gpu.global.add.u32 [%0], 1;" ::"l"(p) : "memory"); }

__device__ __forceinline__ void mbar_init(uint32_t a, int cnt) { asm volatile("mbarrier.init.shared::cta.b64 [%0], %1;" ::"r"(a), "r"(cnt) : "memory"); }
__device__ __forceinline__ void mbar_expect(uint32_t a, uint32_t bytes) { asm volatile("mbarrier.arrive.expect_tx.shared::cta.b64 _, [%0], %1;" ::"r"(a), "r"(bytes) : "memory"); }
__device__ __forceinline__ void mbar_wait(uint32_t a, uint32_t parity) {
    uint32_t ok = 0;
    int it = 0;
    do {
        asm volatile("{\n.reg .pred p;\nmbarrier.try_wait.parity.shared::cta.b64 p, [%1], %2;\nselp.u32 %0, 1, 0, p;\n}" : "=r"(ok) : "r"(a), "r"(parity) : "memory");
    } while (!ok && ++it < SPIN_MAX);
}
__device__ __forceinline__ void tma2d(uint32_t dst, const CUtensorMap* tm, int c0, int c1, uint32_t mbar) {
    asm volatile("cp.async.bulk.tensor.2d.shared::cluster.global.mbarrier::complete_tx::bytes [%0], [%1, {%3, %4}], [%2];"
                 ::"r"(dst), "l"(tm), "r"(mbar), "r"(c0), "r"(c1) : "memory");
}
__device__ __forceinline__ void bulk_s2g(void* dst, uint32_t src, uint32_t bytes) {
    asm volatile("cp.async.bulk.global.shared::cta.bulk_group [%0], [%1], %2;" ::"l"(dst), "r"(src), "r"(bytes) : "memory");
}
__device__ __forceinline__ uint32_t ld_acq(const unsigned int* p) { uint32_t v; asm volatile("ld.acquire.gpu.global.u32 %0, [%1];" : "=r"(v) : "l"(p) : "memory"); return v; }
__device__ __forceinline__ void bulk_pf(const void* src, uint32_t bytes) { asm volatile("cp.async.bulk.prefetch.L2.global [%0], %1;" ::"l"(src), "r"(bytes) : "memory"); }

struct cplx { float x, y; };
__device__ __forceinline__ cplx cmul(cplx a, cplx b) { cplx r; r.x = a.x * b.x - a.y * b.y; r.y = a.x * b.y + a.y * b.x; return r; }
__device__ __forceinline__ cplx csq(cplx a) { cplx r; r.x = a.x * a.x - a.y * a.y; r.y = 2.0f * a.x * a.y; return r; }
__device__ __forceinline__ uint32_t hcm(uint32_t x, uint32_t y, uint32_t yp) {
    const __half2 X = *(const __half2*)&x, Y = *(const __half2*)&y, YP = *(const __half2*)&yp;
    const __half2 r = __hfma2(__high2half2(X), YP, __hmul2(__low2half2(X), Y));
    return *(const uint32_t*)&r;
}
__device__ __forceinline__ void ln_stats(float s1, float s2, float& meanb, float& rinv) {
    const float mean = s1 * (1.0f / D_);
    const float den = bfr(fsqrt(bfr(bfr(fmaxf(fmaf(-mean, mean, s2 * (1.0f / D_)), 0.f)) + 1e-5f)));
    meanb = bfr(mean);
    rinv = frcp(den);
}

__device__ __forceinline__ int fresh_tid() { int v; asm volatile("mov.u32 %0, %tid.x;" : "=r"(v)); return v - 128; }
__device__ __forceinline__ void mma_k8(float* c, uint32_t a0, uint32_t a1, uint32_t b0) {
    asm volatile("mma.sync.aligned.m16n8k8.row.col.f32.bf16.bf16.f32 {%0,%1,%2,%3}, {%4,%5}, {%6}, {%0,%1,%2,%3};\n"
                 : "+f"(c[0]), "+f"(c[1]), "+f"(c[2]), "+f"(c[3]) : "r"(a0), "r"(a1), "r"(b0));
}
__device__ __forceinline__ void ldsm_x2(uint32_t* r, uint32_t addr) {
    asm volatile("ldmatrix.sync.aligned.m8n8.x2.shared.b16 {%0,%1}, [%2];" : "=r"(r[0]), "=r"(r[1]) : "r"(addr) : "memory");
}
__device__ __forceinline__ void ldsm_x2_t(uint32_t* r, uint32_t addr) {
    asm volatile("ldmatrix.sync.aligned.m8n8.x2.trans.shared.b16 {%0,%1}, [%2];" : "=r"(r[0]), "=r"(r[1]) : "r"(addr) : "memory");
}
__device__ __forceinline__ void stsm_x2(uint32_t addr, uint32_t r0, uint32_t r1) {
    asm volatile("stmatrix.sync.aligned.m8n8.x2.shared.b16 [%0], {%1,%2};" ::"r"(addr), "r"(r0), "r"(r1) : "memory");
}
__device__ __forceinline__ uint4 lds128(uint32_t a) { uint4 v; asm volatile("ld.shared.v4.u32 {%0,%1,%2,%3}, [%4];" : "=r"(v.x), "=r"(v.y), "=r"(v.z), "=r"(v.w) : "r"(a) : "memory"); return v; }
__device__ __forceinline__ uint32_t mapa(uint32_t a, uint32_t r) { uint32_t o; asm("mapa.shared::cluster.u32 %0, %1, %2;" : "=r"(o) : "r"(a), "r"(r)); return o; }
__device__ __forceinline__ void sta4(uint32_t dst, uint4 v, uint32_t mb) {
    asm volatile("st.async.weak.shared::cluster.mbarrier::complete_tx::bytes.v4.b32 [%0], {%1,%2,%3,%4}, [%5];" ::"r"(dst), "r"(v.x), "r"(v.y), "r"(v.z), "r"(v.w), "r"(mb) : "memory");
}
__device__ __forceinline__ void sta2(uint32_t dst, uint32_t a, uint32_t b, uint32_t mb) {
    asm volatile("st.async.weak.shared::cluster.mbarrier::complete_tx::bytes.v2.b32 [%0], {%1,%2}, [%3];" ::"r"(dst), "r"(a), "r"(b), "r"(mb) : "memory");
}
__device__ __forceinline__ void mbar_arrive(uint32_t a) { asm volatile("mbarrier.arrive.shared::cta.b64 _, [%0];" ::"r"(a) : "memory"); }
__device__ __forceinline__ void red4(float4* p, float a, float b, float c) {
    asm volatile("red.relaxed.gpu.global.add.v4.f32 [%0], {%1,%2,%3,%4};" ::"l"(p), "f"(a), "f"(b), "f"(c), "f"(1.0f) : "memory");
}
__device__ __forceinline__ void red4p(bool on, float4* p, float a, float b, float c) {
    asm volatile("{\n.reg .pred q;\nsetp.ne.u32 q, %5, 0;\n@q red.relaxed.gpu.global.add.v4.f32 [%0], {%1,%2,%3,%4};\n}" ::"l"(p), "f"(a), "f"(b), "f"(c), "f"(1.0f), "r"((uint32_t)on) : "memory");
}
__device__ __forceinline__ float4 ld_rlx4f(const float4* p) { float4 v; asm volatile("ld.relaxed.gpu.global.v4.f32 {%0,%1,%2,%3}, [%4];" : "=f"(v.x), "=f"(v.y), "=f"(v.z), "=f"(v.w) : "l"(p) : "memory"); return v; }
__device__ __forceinline__ void tma5d_st(const CUtensorMap* tm, int c0, int c4, uint32_t src) {
    asm volatile("cp.async.bulk.tensor.5d.global.shared::cta.bulk_group [%0, {%2, %4, %4, %4, %3}], [%1];" ::"l"(tm), "r"(src), "r"(c0), "r"(c4), "r"(0) : "memory");
}
__device__ __forceinline__ void tma2d_pf(const CUtensorMap* tm, int c0, int c1) {
    asm volatile("cp.async.bulk.prefetch.tensor.2d.L2.global [%0, {%1, %2}];" ::"l"(tm), "r"(c0), "r"(c1) : "memory");
}
__device__ __forceinline__ void pace(int clk) {
    const long long c0 = clock64();
    int it = 0;
    while (clock64() - c0 < clk && ++it < 4096) { }
}
__device__ __forceinline__ uint32_t sign2(uint32_t a) { uint32_t r; asm("prmt.b32 %0, %1, 0, 0xBB99;" : "=r"(r) : "r"(a)); return r; }
#define MB(i) (sb + OFF_MISC + (uint32_t)offsetof(Misc, mbar) + 8 * (i))
#define PRE 1
__device__ __forceinline__ void conv_channel(unsigned char* sm, uint32_t rank) {
    Misc& M = *(Misc*)(sm + OFF_MISC);
    const uint32_t sb = (uint32_t)__cvta_generic_to_shared(sm);
    const int tid = fresh_tid(), lane = tid & 31, g = lane >> 2, t = lane & 3, lr = lane & 7, lm = lane >> 3;
    const int warp_ = __shfl_sync(0xffffffffu, tid >> 5, 0), wgi = warp_ >> 2, w = warp_ & 3;
    const uint32_t cb = sb + OFF_CH + wgi * CHS;
    float D[16];
    {
        const uint32_t pf = cb + XO_TF + (w >> 1) * 512 + (8 + 16 * (w & 1) + g - 2 * t) * 4;
        uint32_t p[13], q[9];
        named_bar(1 + wgi, 128);
#pragma unroll
        for (int s = 0; s < 13; s++) p[s] = lds32(pf + s * 32);
        {
            const uint32_t a8 = cb + lr * ULBO + (lm + 9) * 16 + w * 64, b8 = cb + XO_U8 + lm * 128 + lr * 16 + w * 512;
            const uint32_t a16 = cb + (((2 * lr) & 7) + (lm & 1)) * ULBO + (9 + (lr >> 2) + (lm & 2)) * 16 + w * 64;
            const uint32_t b16 = cb + XO_U16 + (lm & 1) * 512 + lr * 16 + (lm >> 1) * 128 + (w >> 1) * 1024 + (w & 1) * 256;
            uint32_t r[3][4];
            mbar_wait(cb + XO_MBU, 0);
            ldsm_x4_t(r[0], a8);
            ldsm_x4_t(r[1], a16);
            if (w < 2) ldsm_x4_t(r[2], a8 + 256);
            stsm_x4(b8, r[0][0], r[0][1], r[0][2], r[0][3]);
            stsm_x4(b16, r[1][0], r[1][1], r[1][2], r[1][3]);
            if (w < 2) stsm_x4(b8 + 2048, r[2][0], r[2][1], r[2][2], r[2][3]);
        }
        PROXY_FENCE();
        named_bar(1 + wgi, 128);
        {
            float Z8[24], Z16[16];
            uint32_t z8[12];
            const uint32_t d8 = ((((cb + XO_U8) & 0x3FFFF) >> 4) | ((128 >> 4) << 16));
#define DZ(o) (((uint64_t)(512 >> 4) << 32) | (uint64_t)(d8 + (o)))
            WG_FENCE();
#pragma unroll
            for (int e = 0; e < 6; e++) {
                if (e == 0) wg48z(Z8, TQ(p, e), DZ(16));
                else wg48(Z8, TQ(p, e), DZ(-(e >> 1) * 32 + (1 - (e & 1)) * 16));
            }
            WG_COMMIT();
            WG_WAIT(0);
            asm volatile("setmaxnreg.inc.sync.aligned.u32 88;");
#pragma unroll
            for (int s = 0; s < 9; s++) q[s] = lds32(pf + 1024 + s * 32);
#pragma unroll
            for (int i = 0; i < 12; i++) asm volatile("cvt.rn.bf16x2.f32 %0, %1, %2;" : "=r"(z8[i]) : "f"(Z8[2 * i + 1]), "f"(Z8[2 * i]));
            WG_FENCE();
#pragma unroll
            for (int e = 0; e < 4; e++) {
                if (e == 0) wg32z(Z16, TQ(q, e), DZ(256 + 16));
                else wg32(Z16, TQ(q, e), DZ(256 - (e >> 1) * 64 + (1 - (e & 1)) * 16));
            }
            WG_COMMIT();
            WG_WAIT(0);
            named_bar(1 + wgi, 128);
            const uint32_t za = cb + ((w >> 1) ? XO_ZB : XO_ZA) + lr * 400 + (1 + 2 * (w & 1) + (lm & 1) + 4 * (lm >> 1)) * 16;
#pragma unroll
            for (int i = 0; i < 3; i++) stsm_x4(za + i * 128, z8[4 * i], z8[4 * i + 1], z8[4 * i + 2], z8[4 * i + 3]);
            const int Cz = 2 * (16 * (w & 1) + 8 * (lm & 1) + lr) + (lm >> 1);
            const uint32_t zc = cb + ((w >> 1) ? XO_ZD : XO_ZC) + (Cz & 7) * 272 + (1 + (Cz >> 3)) * 16;
#pragma unroll
            for (int ob = 0; ob < 2; ob++) stsm_x4(zc + ob * 128, pack2(Z16[8 * ob], Z16[8 * ob + 1]), pack2(Z16[8 * ob + 2], Z16[8 * ob + 3]), pack2(Z16[8 * ob + 4], Z16[8 * ob + 5]), pack2(Z16[8 * ob + 6], Z16[8 * ob + 7]));
            if (lane < 8) *(uint4*)(sm + (cb - sb) + ((w < 2) ? (XO_ZA + w * 3200 + lane * 400) : (XO_ZC + (w - 2) * 2176 + lane * 272))) = make_uint4(0, 0, 0, 0);
        }
        {
#pragma unroll
            for (int i = 0; i < 16; i++) D[i] = 0.f;
            uint32_t pa = cb + XO_TD + (8 + 16 * w + g - 2 * t) * 4;
            uint32_t dlo = (((cb + 9 * 16) & 0x3FFFF) >> 4) | ((ULBO >> 4) << 16);
#define DS(o) (((uint64_t)(128 >> 4) << 32) | (uint64_t)(dlo + (o)))
#define KST (2 * (ULBO / 16))
            uint32_t pA[9], pB[9];
#pragma unroll
            for (int s = 0; s < 9; s++) pA[s] = lds32(pa + s * 32);
#pragma unroll 1
            for (int j = 0; j < 4; j++) {
                WG_FENCE();
#pragma unroll
                for (int q = 0; q < 4; q++) wg32(D, TQ(pA, q), DS((3 - q) * KST));
                WG_COMMIT();
                WG_WAIT(1);
#pragma unroll
                for (int s = 0; s < 9; s++) pB[s] = lds32(pa + 256 + s * 32);
                WG_FENCE();
#pragma unroll
                for (int q = 0; q < 4; q++) wg32(D, TQ(pB, q), DS((3 - q) * KST - 1));
                WG_COMMIT();
                WG_WAIT(1);
#pragma unroll
                for (int s = 0; s < 9; s++) pA[s] = lds32(pa + 512 + s * 32);
                dlo -= 2; pa += 512;
            }
            pB[1] = lds32(pa + 256 + 32); pB[2] = lds32(pa + 256 + 64);
            WG_FENCE();
#pragma unroll
            for (int q = 0; q < 4; q++) wg32(D, TQ(pA, q), DS((3 - q) * KST));
            wg32(D, pB[1], pB[2], pA[8], pB[1], DS(3 * KST - 1));
            WG_COMMIT();
        }
    }
    {
        named_bar(1 + wgi, 128);
        uint32_t u[2][4];
        {
            const uint4* pq = M.box + (6 + g - 2 * t);
            auto at = [&](int k, int pitch) { const int c = 2 * w + k; return cb + (c & 7) * pitch + (c < 0 ? 0 : 16) + lr * 16; };
            const int h1 = lm & 1;
            const uint32_t h2 = (lm >> 1) * 128;
            uint32_t bA[3][4], bB[2][4], bB3[2], bC[2][4], bD[2][4], bU[4], bU1[2];
            const uint32_t p0 = at(h1, 400) + XO_ZA;
            WG_WAIT(0);
            const uint4 m0 = pq[0], m1 = pq[14];
            ldsm_x4(bA[0], p0 + h2); ldsm_x4(bA[1], at(h1 - 2, 400) + XO_ZA + h2); ldsm_x4(bA[2], at(lm - 2, 400) + XO_ZA + 256);
            ldsm_x4(bB[0], p0 + 3200 + h2); ldsm_x2(bB3, p0 + 3200 + 256); ldsm_x4(bB[1], at(-1, 400) + XO_ZB + lm * 128);
            mma_bf16(D + 4, m0.x, m0.y, 0u, m0.x, bA[0][0], bA[0][1]);
            mma_bf16(D + 8, m0.x, m0.y, 0u, m0.x, bA[0][2], bA[0][3]);
            mma_bf16(D + 12, m0.x, m0.y, 0u, m0.x, bA[2][2], bA[2][3]);
            mma_bf16(D + 4, m0.z, 0u, m0.y, m0.z, bA[1][0], bA[1][1]);
            mma_bf16(D + 8, m0.z, 0u, m0.y, m0.z, bA[1][2], bA[1][3]);
            mma_bf16(D + 12, m0.z, 0u, m0.y, m0.z, bA[2][0], bA[2][1]);
            ldsm_x4(bC[0], at(h1 - 1, 272) + XO_ZC + h2); ldsm_x4(bC[1], at(h1 - 3, 272) + XO_ZC + h2);
            const uint4 m2 = pq[28];
            const uint32_t k2 = lds32(cb + XO_K1024), x0 = m2.w & k2, x8 = pq[42].x & k2;
            mma_bf16(D + 4, m0.w, m1.x, 0u, m0.w, bB[0][0], bB[0][1]);
            mma_bf16(D + 8, m0.w, m1.x, 0u, m0.w, bB[0][2], bB[0][3]);
            mma_bf16(D + 12, m0.w, m1.x, 0u, m0.w, bB3[0], bB3[1]);
            mma_k8(D + 4, m1.x, 0u, bB[1][0]);
            ldsm_x4(bD[0], at(h1, 272) + XO_ZD + h2); ldsm_x4(bD[1], at(h1 - 2, 272) + XO_ZD + h2);
            ldsm_x4(bU, at(h1, ULBO) + 128 + h2); ldsm_x2(bU1, at(-1, ULBO) + 128 + h1 * 128);
            ldsm_x4_t(u[0], cb + 2 * w * ULBO + 144 + lane * 16); ldsm_x4_t(u[1], cb + (2 * w + 1) * ULBO + 144 + lane * 16);
            const uint32_t dk2 = __byte_perm(lds32(cb + XO_DSK), 0, (rank & 1) ? 0x3232 : 0x1010);
#pragma unroll
            for (int c = 0; c < 2; c++) mma_bf16(D + 8 + 4 * c, m1.y, m1.z, 0u, m1.y, bC[0][2 * c], bC[0][2 * c + 1]);
#pragma unroll
            for (int c = 0; c < 2; c++) mma_bf16(D + 8 + 4 * c, m1.w, 0u, m1.z, m1.w, bC[1][2 * c], bC[1][2 * c + 1]);
#pragma unroll
            for (int c = 0; c < 2; c++) mma_bf16(D + 8 + 4 * c, m2.x, m2.y, 0u, m2.x, bD[0][2 * c], bD[0][2 * c + 1]);
#pragma unroll
            for (int i = 0; i < 8; i++) u[i >> 2][i & 3] = mul2(u[i >> 2][i & 3], dk2);
#pragma unroll
            for (int c = 0; c < 2; c++) mma_bf16(D + 8 + 4 * c, m2.z, 0u, m2.y, m2.z, bD[1][2 * c], bD[1][2 * c + 1]);
#pragma unroll
            for (int c = 0; c < 2; c++) mma_bf16(D + 8 + 4 * c, x0, x8, 0u, x0, bU[2 * c], bU[2 * c + 1]);
#pragma unroll
            for (int c = 0; c < 2; c++) mma_bf16(D + 8 + 4 * c, m1.x, 0u, x8, 0u, bB[1][1 + c], bU1[c]);
        }
        {
            mbar_wait(MB(MB_C2), 0);
            const uint32_t ga2 = M.ga[wgi];
#pragma unroll
            for (int h = 0; h < 2; h++) {
                const uint32_t rb = mapa(sb, 2 * w + h);
#pragma unroll
                for (int j = 0; j < 4; j++) u[h][j] = mul2(ga2, add2(pack2(D[4 * j + 2 * h], D[4 * j + 2 * h + 1]), u[h][j]));
                sta4(rb + OFF_V + (8 * wgi + rank) * VP + lane * 16, make_uint4(u[h][0], u[h][1], u[h][2], u[h][3]), rb + (MB(MB_V) - sb));
            }
        }
    }
}

#define WMD 400
#define PU 400
#define PD 100
#define PFG 2
#define CWP 200
#define CWD 5000
#define LN1POS 1
#define SLOT(key) (((~(key) >> 2) & 0x78u) | ((key) & 7u))
#define ROW(key) (((~(key) << 2) & 0xE0u) | ((~(key) >> 7) & 24u) | ((~(key) >> 11) & 6u) | ((~(key) >> 9) & 1u))
#define CE(a, b) { const uint32_t hi_ = max(a, b); b = min(a, b); a = hi_; }
#define POP(k, m) if (k.x == m) { k.x = k.y; k.y = k.z; k.z = k.w; k.w = 0u; }
#define GW(w) (17 - (w))
#define RESET() _Pragma("unroll") for (int i = 0; i < 8; i++) if (i < 7 || lane < 16) st_rlx4((uint4*)S->acc2 + 240 * b + 32 * i + lane, make_uint4(0, 0, 0, 0))
#define CL_ARRIVE() asm volatile("barrier.cluster.arrive.relaxed.aligned;" ::: "memory")
#define CL_WAIT() asm volatile("barrier.cluster.wait.aligned;" ::: "memory")
__global__ void __cluster_dims__(8, 1, 1) __launch_bounds__(NTHR, 1)
clus_kernel(const bf16* __restrict__ x, const bf16* __restrict__ logAr, const bf16* __restrict__ Aim, const bf16* __restrict__ Cr, const bf16* __restrict__ Ci,
            const bf16* __restrict__ logdt, const bf16* __restrict__ c_in, Scratch* __restrict__ S, const bf16* __restrict__ Dskip,
            const bf16* __restrict__ w_r, const bf16* __restrict__ w_mod, bf16* __restrict__ out,
            const __grid_constant__ CUtensorMap tm_wm, const __grid_constant__ CUtensorMap tm_wg,
            const __grid_constant__ CUtensorMap tm_wu, const __grid_constant__ CUtensorMap tm_wd, const __grid_constant__ CUtensorMap tm_out) {
    extern __shared__ __align__(1024) unsigned char sm[];
    Misc& M = *(Misc*)(sm + OFF_MISC);
    const uint32_t sb = (uint32_t)__cvta_generic_to_shared(sm);
    const int tid = threadIdx.x < 128 ? threadIdx.x + 640 : threadIdx.x - 128, warp = __shfl_sync(0xffffffffu, tid >> 5, 0), lane = tid & 31;
    const int g = lane >> 2, t = lane & 3, lr = lane & 7, lm = lane >> 3;
    const int wgi = warp >> 2, w = warp & 3;
    const int b = blockIdx.x, cl = b >> 3, rk = b & 7;
    auto mod_ld = [&](uint32_t (*a)[4], uint32_t s0, uint32_t s1, int i) {
        const uint32_t wa = sb + ((lm & 1) ? s1 : s0) + (lr + 8 * (lm >> 1)) * 80 + i * 16;
#pragma unroll
        for (int ks = 0; ks < 4; ks++) ldsm_x4_t(a[ks], wa + ks * 1280);
        ldsm_x2_t(a[4], wa + 5120);
    };
    auto mod_mma2 = [&](float* d, float* e, uint32_t (*a)[4], uint32_t (*c)[4], const uint32_t* bs) {
        mma_k8(d, a[4][0], a[4][1], bs[8]); mma_k8(e, c[4][0], c[4][1], bs[8]);
#pragma unroll
        for (int ks = 0; ks < 4; ks++) {
            mma_bf16(d, a[ks][0], a[ks][1], a[ks][2], a[ks][3], bs[2 * ks], bs[2 * ks + 1]);
            mma_bf16(e, c[ks][0], c[ks][1], c[ks][2], c[ks][3], bs[2 * ks], bs[2 * ks + 1]);
        }
    };
    auto mod_st = [&](const float* d, uint32_t dst, int mb) {
#pragma unroll
        for (int h = 0; h < 2; h++) {
            const uint32_t rb = mapa(sb, t + 4 * h);
            sta2(rb + dst + g * 8, __float_as_uint(d[0]), __float_as_uint(d[2]), rb + (MB(mb) - sb));
        }
    };
    if (wgi == 5) {
        CL_ARRIVE();
        const uint32_t c_a = ld_nc((const uint32_t*)c_in + 36 * rk + lane), c_b = ld_nc((const uint32_t*)c_in + 36 * rk + 32 + t);
        {
            pace(WMD);
            const char* wp = (const char*)(w_mod + (72 * rk + 18 * w) * (6 * D_) + 40 * cl);
#pragma unroll
            for (int i = 0; i < 3; i++) {
                const uint32_t c = lane + 32 * i, row = (c * 205) >> 10;
                const char* p = wp + (row * (12 * D_ - 80) + 16 * c);
                if (c < 90) {
                    asm volatile("cp.async.cg.shared.global [%0], [%1], 16;" ::"r"(sb + OFF_WM0 + 1440 * w + 16 * c), "l"(p) : "memory");
                    asm volatile("cp.async.cg.shared.global [%0], [%1], 16;" ::"r"(sb + OFF_WM0 + 5760 + 1440 * w + 16 * c), "l"(p + 2 * D_) : "memory");
                }
            }
            if (w == 3 && lane < 20)
                asm volatile("cp.async.ca.shared.global [%0], [%1], 4, %2;" ::"r"(sb + OFF_MISC + (uint32_t)offsetof(Misc, c2) + 12 + 16 * lane), "l"((const uint32_t*)w_r + min(20 * cl + lane, D_ / 2 - 1)),
                             "r"(20 * cl + lane < D_ / 2 ? 4 : 0) : "memory");
            asm volatile("cp.async.commit_group;" ::: "memory");
        }
        auto gsum = [&](uint32_t a, int pitch) {
            float4 s = make_float4(0.f, 0.f, 0.f, 0.f);
#pragma unroll
            for (int i = 0; i < 8; i++) { const float4 q = *(const float4*)(sm + a + i * pitch); s.x += q.x; s.y += q.y; s.z += q.z; s.w += q.w; }
            return make_uint2(pack2(s.x, s.z), pack2(s.y, s.w));
        };
        auto one_plus = [&](uint32_t v) { return pack2(1.0f + lo2f(v), 1.0f + hi2f(v)); };
        {
            uint32_t bs[9], a[5][4], c[5][4];
            float d[4] = {0.f, 0.f, 0.f, 0.f}, e[4] = {0.f, 0.f, 0.f, 0.f};
            const uint32_t sc = pack2(silu(lo2f(c_a)), silu(hi2f(c_a)));
            bs[8] = pack2(silu(lo2f(c_b)), silu(hi2f(c_b)));
            if (w == 2) { sts32(sb + OFF_SC + 4 * lane, sc); sts32(sb + OFF_SC + 128 + 4 * t, bs[8]); }
#pragma unroll
            for (int ks = 0; ks < 8; ks++) bs[ks] = __shfl_sync(0xffffffffu, sc, 4 * ks + t);
            CL_WAIT();
            asm volatile("cp.async.wait_group 0;" ::: "memory");
            named_bar(10, 128);
            mod_ld(a, OFF_WM0 + 5760, OFF_WM0, w);
            mod_ld(c, OFF_WM0 + 5760, OFF_WM0, 4);
            mod_mma2(d, e, a, c, bs);
            mod_st(d, OFF_MG1 + rk * 320 + 64 * w, MB_MG1);
            if (w == 1) mod_st(e, OFF_MG1 + rk * 320 + 256, MB_MG1);
        }
        {
            const int n0 = 8 * w + ((3 - rk) & 3), n1 = (n0 + 4 + t) & 31;
            const float4* ap = &S->acc1[256 * rk + 8 * (n0 + t) + g];
            const float4* aq = &S->acc1[256 * rk + 8 * n1 + g];
            named_bar(9, 640);
            if (w == 2 && lane == 0) {
#pragma unroll
                for (int i = 2; i < 6; i++) tma2d(sb + (i == 5 ? OFF_WM0 + 11520 : OFF_WM2 + (i - 2) * 5760), &tm_wm, i * D_ + 40 * cl, 72 * rk, MB(MB_WM2));
            }
            __syncwarp();
            if (w == 3) mbar_wait(MB(MB_MG1), 0);
            float4 pa = ld_rlx4f(ap), pb = ld_rlx4f(aq);
            if (w == 3) {
                const uint2 v = gsum(OFF_MG1 + 16 * min(lane, 19), 320);
                const uint32_t c1 = one_plus(v.x);
                if (lane < 20) *(uint4*)(sm + OFF_C1 + 16 * lane) = make_uint4(__byte_perm(c1, 0, 0x1010), __byte_perm(v.y, 0, 0x1010), __byte_perm(c1, 0, 0x3232), __byte_perm(v.y, 0, 0x3232));
                __syncwarp();
                named_arrive(10, 128);
            }
            uint32_t xq[2][5][4];
            uint2 cc[5];
            const uint32_t xa = sb + OFF_X + XI(2 * lm + (lr & 1)) + XN(n0 + (lr >> 1)), xb = sb + OFF_X + XI(2 * lm + (lr & 1)) + XN((n0 + 4 + (lr >> 1)) & 31);
            const uint32_t ua = mapa(sb, g) + OFF_CH;
#pragma unroll
            for (int j = 0; j < 5; j++) ldsm_x4_t(xq[0][j], xa + 16 * j);
#pragma unroll 1
            for (int it = 0; it < SPIN_MAX && (pa.w != (float)NCL || pb.w != (float)NCL); it++) { pa = ld_rlx4f(ap); pb = ld_rlx4f(aq); }
            __syncwarp();
            if (w == 2 && lane < PFG) tma2d_pf(&tm_wg, 40 * b, 192 * lane);
            __syncwarp();
            float m0, r0, m1, r1;
            ln_stats(pa.x, pa.y, m0, r0);
            ln_stats(pb.x, pb.y, m1, r1);
            const uint32_t rh = pack2(r0, r1), rl = pack2(r0 - lo2f(rh), r1 - hi2f(rh));
            const uint32_t stage = sb + OFF_STG + w * 512;
            stsm_x4_t(stage + lane * 16, pack2(m0, m1), rh, rl, rl);
            __syncwarp();
            if (w != 3) named_bar(10, 128);
            uint4 st[2][3];
#pragma unroll
            for (int q = 0; q < 2; q++)
#pragma unroll
                for (int i = 0; i < 3; i++) st[q][i] = lds128(stage + 128 * i + (2 * t + q) * 16);
#pragma unroll
            for (int j = 0; j < 5; j++) cc[j] = *(const uint2*)(sm + OFF_C1 + 64 * j + 8 * g);
            ldsm_x4_t(xq[1][0], xb);
            const uint32_t u0 = ua + rk * ULBO + (9 + n0 + t) * 16, u1 = ua + rk * ULBO + (9 + n1) * 16;
#pragma unroll
            for (int j = 0; j < 5; j++) {
                if (j >= 2 && cl == 14) break;
                if (j < 4) ldsm_x4_t(xq[1][j + 1], xb + 16 * (j + 1));
#pragma unroll
                for (int q = 0; q < 2; q++) {
                    const uint4 sm_ = st[q][0], sh = st[q][1], sl = st[q][2];
                    const uint32_t v0 = add2(mul2(norm2(xq[q][j][0], sm_.x, sh.x, sl.x), cc[j].x), cc[j].y), v1 = add2(mul2(norm2(xq[q][j][1], sm_.y, sh.y, sl.y), cc[j].x), cc[j].y);
                    const uint32_t v2 = add2(mul2(norm2(xq[q][j][2], sm_.z, sh.z, sl.z), cc[j].x), cc[j].y), v3 = add2(mul2(norm2(xq[q][j][3], sm_.w, sh.w, sl.w), cc[j].x), cc[j].y);
                    asm volatile("{\n.reg .pred p;\nsetp.ne.u32 p, %6, %7;\n"
                                 "@p st.async.weak.shared::cluster.mbarrier::complete_tx::bytes.v4.b32 [%0], {%1,%2,%3,%4}, [%5];\n"
                                 "@!p st.shared.v4.b32 [%0], {%1,%2,%3,%4};\n}"
                                 ::"r"((q ? u1 : u0) + j * CHS), "r"(v0), "r"(v1), "r"(v2), "r"(v3), "r"(ua + j * CHS + XO_MBU), "r"(g), "r"(rk) : "memory");
                }
                __syncwarp();
                if (lane == 0) mbar_arrive(sb + OFF_CH + XO_MBU + j * CHS);
            }
        }
        asm volatile("setmaxnreg.dec.sync.aligned.u32 40;");
        if (w) named_arrive(11, 128); else named_bar(11, 128);
        if (w == 0) {
            const int lane = fresh_tid() & 31;
            mbar_wait(MB(MB_KD), 0);
            PROXY_FENCE();
            if (lane == 0) {
#pragma unroll
                for (int i = 0; i < 3; i++) tma2d(sb + OFF_WG + i * 15360, &tm_wg, 40 * b, 192 * i, MB(MB_WG));
                mbar_wait(MB(MB_C2), 0);
                PROXY_FENCE();
#pragma unroll 1
                for (int i = 0; i < 3; i++) { pace(PU); tma2d(sb + OFF_WU + i * 15360, &tm_wu, 40 * b, 192 * i, MB(MB_WU)); }
                mbar_wait(MB(MB_WU), 0);
#pragma unroll 1
                for (int i = 0; i < 9; i++) { pace(PD); tma2d_pf(&tm_wd, 64 * i, 40 * b); }
            }
            __syncwarp();
            mbar_wait(MB(MB_KD), 1);
            PROXY_FENCE();
            if (lane < 9) tma2d(sb + OFF_WD + lane * 5120, &tm_wd, 64 * lane, 40 * b, MB(MB_WD));
            __syncwarp();
        } else if (w == 1) {
            const int lane = fresh_tid() & 31;
            RESET();
            uint32_t z = 0;
#pragma unroll
            for (int i = 0; i < 8; i++) z |= ld_rlx((const unsigned int*)((uint4*)S->acc2 + 240 * b + (i < 7 ? 32 * i + lane : 224 + (lane & 15))) + 3);
            z = __reduce_or_sync(0xffffffffu, z);
            if (lane == 0) asm volatile("red.relaxed.gpu.global.add.f32 [%0], %1;" ::"l"(&S->acc1[L_].z), "f"(__uint_as_float(z | 0x3F800000u)) : "memory");
        } else if (w == 2) {
            if ((fresh_tid() & 31) == 0) {
                float4 v;
                int it = 0;
                pace(CWD);
                for (;;) { v = ld_rlx4f(&S->acc1[L_]); if (++it >= SPIN_MAX || (v.z == (float)G_ && v.w == (float)NCL)) break; pace(CWP); }
                M.cws[0] = v.x; M.cws[1] = v.y;
                mbar_arrive(MB(MB_CW));
            }
        } else {
            const int lane = fresh_tid() & 31, l20 = min(lane, 19);
            mbar_wait(MB(MB_MG2), 0);
            const uint2 v = gsum(OFF_MG2 + 16 * l20, 640), u = gsum(OFF_MG2 + 320 + 16 * l20, 640);
            const uint32_t wr = lane < 20 ? M.c2[lane].w : 0u, cb1 = one_plus(v.x), cw = mul2(cb1, wr);
            if (lane < 20) {
                M.c2[lane] = make_uint4(cb1, v.y, u.x, cw);
                M.wr[lane] = wr;
                unsigned e;
                asm volatile("mov.u32 %0, %cluster_ctarank;" : "=r"(e));
                if ((lane & 3) == (e >> 1)) M.ga[lane >> 2] = __byte_perm(u.y, 0, (e & 1) ? 0x3232 : 0x1010);
            }
            __syncwarp();
            if (lane == 0) mbar_arrive(MB(MB_C2));
            if (rk == 0) {
                float a = lo2f(cw) + hi2f(cw), s = lo2f(v.y) * lo2f(wr) + hi2f(v.y) * hi2f(wr);
#pragma unroll
                for (int o = 16; o; o >>= 1) { a += __shfl_xor_sync(0xffffffffu, a, o); s += __shfl_xor_sync(0xffffffffu, s, o); }
                if (lane == 0) red4(&S->acc1[L_], a, s, 0.f);
            }
        }
        {
        const int lane = fresh_tid() & 31, g = lane >> 2, t = lane & 3, lr = lane & 7, lm = lane >> 3;
        uint32_t aw[5];
        __syncwarp();
        mbar_wait(MB(MB_C2), 0);
#pragma unroll
        for (int j = 0; j < 5; j++) aw[j] = M.wr[4 * j + t];
        const int ph = w >> 1, lst = 2 * rk + (w & 1);
        const uint32_t rb = mapa(sb, lr);
        uint4* dst = &S->h2c[(8 * lst + 4 * ph + t) * 72 + 5 * cl + g];
        named_bar(6, 768);
        uint4 k = *(const uint4*)&M.key[128 * (w & 1) + 4 * lane];
        CE(k.x, k.y); CE(k.z, k.w); CE(k.x, k.z); CE(k.y, k.w); CE(k.y, k.z);
        uint32_t m[4];
#pragma unroll 1
        for (int q = 0; q <= ph; q++) {
#pragma unroll
            for (int rnd = 0; rnd < 4; rnd++) {
                m[rnd] = __reduce_max_sync(0xffffffffu, k.x);
                POP(k, m[rnd]);
            }
        }
#pragma unroll
        for (int rnd = 0; rnd < 4; rnd++) m[rnd] |= 4 * ph + rnd;
        const uint32_t cd = rb + OFF_MISC + (uint32_t)offsetof(Misc, cand) + (16 * ph + lst) * 16;
        if (lane < 8) sta4(cd, make_uint4(m[0], m[1], m[2], m[3]), rb + ((ph ? MB(MB_KEY2) : MB(MB_KEY)) - sb));
        const uint32_t mine = (t & 2) ? ((t & 1) ? m[3] : m[2]) : ((t & 1) ? m[1] : m[0]);
        const uint32_t ra = sb + OFF_H2T + ROW(mine) * 80;
        uint32_t bq[6];
        float rr[4] = {0.f, 0.f, 0.f, 0.f};
        named_bar(7, 640);
        const uint4 a = lds128(ra + 16 * g);
        ldsm_x4(bq, ra + 16 * lm); ldsm_x2(bq + 4, ra + 64);
        if (g < (cl < 14 ? 5 : 2)) st_rlx4(dst, make_uint4(~a.x, ~a.y, ~a.z, ~a.w));
        mma_bf16(rr, aw[0], aw[0], aw[1], aw[1], bq[0], bq[1]); mma_bf16(rr, aw[2], aw[2], aw[3], aw[3], bq[2], bq[3]); mma_k8(rr, aw[4], aw[4], bq[4]);
        float4* p = &S->rs[8 * (16 * ph + lst)];
        if (lane < 2) red4(p + lane, rr[0], 1.0f, rr[1]);
        float4 e0 = ld_rlx4f(p), e1 = ld_rlx4f(p + 1);
        uint32_t col = 0, m8 = 0;
        if (w == 1) {
            mbar_wait(MB(MB_KEY), 0);
            mbar_wait(MB(MB_KEY2), 0);
            k = *(const uint4*)&M.cand[4 * lane];
            if (b == 0 && lane == 0) st_rlx4(&S->acc1[L_], make_uint4(0, 0, 0, 0));
#pragma unroll
            for (int rnd = 0; rnd < 8; rnd++) {
                m8 = __reduce_max_sync(0xffffffffu, k.x);
                POP(k, m8);
                if (lr == rnd) col = m8;
            }
        }
#pragma unroll 1
        for (int it = 0; it < SPIN_MAX && (e0.w != (float)NCL || e1.w != (float)NCL); it++) { e0 = ld_rlx4f(p); e1 = ld_rlx4f(p + 1); }
        {
            const uint32_t r0 = pack2(e0.x, e0.z), r1 = pack2(e1.x, e1.z);
            const uint32_t o0 = r0 ^ (sign2(r0) | 0x80008000u), o1 = r1 ^ (sign2(r1) | 0x80008000u);
            if (lane < 8) sta4(rb + OFF_EK + (16 * ph + lst) * VP, make_uint4((o0 << 16) | (m[0] & 0x3FFFu), (o0 & 0xFFFF0000u) | (m[1] & 0x3FFFu), (o1 << 16) | (m[2] & 0x3FFFu), (o1 & 0xFFFF0000u) | (m[3] & 0x3FFFu)),
                               rb + (MB(MB_EK) - sb));
        }
        if (w == 0) {
            named_bar(8, 64);
            if (lane == 0) {
                PROXY_FENCE();
                tma5d_st(&tm_out, 40 * cl, 8 * rk, sb + OFF_OUT);
                asm volatile("cp.async.bulk.commit_group;" ::: "memory");
                asm volatile("cp.async.bulk.wait_group 0;" ::: "memory");
                mbar_arrive(MB(MB_OUT));
            }
        } else if (w == 1) {
            const uint4 k0 = *(const uint4*)&M.cand[4 * lane];
            mbar_wait(MB(MB_EK), 0);
            k = lds128(sb + OFF_EK + lane * VP);
            col = lds32(sb + OFF_EK + (((col & 4u) << 2) | ((~col >> 5) & 15u)) * VP + (col & 3u) * 4);
            const uint32_t lo = min(min(k0.x >= m8 ? k.x : ~0u, k0.y >= m8 ? k.y : ~0u), min(k0.z >= m8 ? k.z : ~0u, k0.w >= m8 ? k.w : ~0u));
            const uint32_t hi = max(max(k0.x >= m8 ? 0u : k.x, k0.y >= m8 ? 0u : k.y), max(k0.z >= m8 ? 0u : k.z, k0.w >= m8 ? 0u : k.w));
            const bool redo = __reduce_max_sync(0xffffffffu, hi) > __reduce_min_sync(0xffffffffu, lo);
            if (redo) {
                CE(k.x, k.y); CE(k.z, k.w); CE(k.x, k.z); CE(k.y, k.w); CE(k.y, k.z);
#pragma unroll 1
                for (int rnd = 0; rnd < 8; rnd++) {
                    m8 = __reduce_max_sync(0xffffffffu, k.x);
                    POP(k, m8);
                    if (lr == rnd) col = m8;
                }
            }
            if (lane < 9) M.fin[lane] = lane < 8 ? col : redo;
            __syncwarp();
            named_arrive(12, 672);
        }
        }
    } else {
    if (warp != 19) CL_ARRIVE();
    const int chn = 40 * cl + 8 * wgi + rk;
    const bool has_ch = chn < D_;
    const uint32_t cb = sb + OFF_CH + wgi * CHS;
    unsigned short r_ldt = 0, r_lar = 0, r_aim = 0, r_cr = 0, r_ci = 0;
    {
        const int n = min(chn, D_ - 1) * N_ + (tid & 127);
        r_ldt = ld_nc16((const unsigned short*)logdt + min(chn, D_ - 1));
        r_lar = ld_nc16((const unsigned short*)logAr + n);
        r_aim = ld_nc16((const unsigned short*)Aim + n);
        r_cr = ld_nc16((const unsigned short*)Cr + n);
        r_ci = ld_nc16((const unsigned short*)Ci + n);
    }
    if (warp == 19) {
        if (lane == 0) asm volatile("prefetch.tensormap [%0];" ::"l"(&tm_wm) : "memory");
        const uint32_t lo = 90u | (10u << 8) | (20u << 16) | (1u << 24), hi = (cl == 14 ? 32u : 80u) | ((rk < 4 ? 40u : 32u) << 8) | (180u << 16) | (180u << 24);
        const uint32_t tx = lane < 8 ? (((lane & 4 ? hi : lo) >> (8 * (lane & 3))) & 255u) : lane == 8 ? 180u : lane < 11 ? lane - 8u : 14u;
        if (lane == 0) {
#pragma unroll
            for (int i = 0; i < MB_N; i++) mbar_init(MB(i), i == MB_KD ? 20 : 1);
#pragma unroll
            for (int i = 0; i < 5; i++) mbar_init(sb + OFF_CH + XO_MBU + i * CHS, 5);
        }
        __syncwarp();
        if (lane < 16) mbar_expect(lane < MB_C2 ? MB(lane) : sb + OFF_CH + XO_MBU + (lane - MB_C2) * CHS, tx << 8);
        asm volatile("fence.mbarrier_init.release.cluster;" ::: "memory");
        __syncwarp();
        CL_ARRIVE();
    }
    if (warp < 16) {
        const char* xp = (const char*)(x + (128 * warp + 8 * rk) * D_ + 40 * cl);
#pragma unroll
        for (int i = 0; i < 3; i++) {
            const uint32_t c = lane + 32 * i, row = (c * 205) >> 10, hi = c >= 40;
            if (c < 80) asm volatile("cp.async.cg.shared.global [%0], [%1], 16, %2;" ::"r"(sb + OFF_X + XN(2 * warp) + XI(row & 7) + 80 * (hi - row) + 16 * c), "l"(xp + (row * (2 * D_ - 80) + 16 * c + hi * (56 * 2 * D_))),
                                     "r"((cl < 14 || c - 5 * row < 2) ? 16 : 0) : "memory");
        }
    }
    if ((tid & 127) == 32) asm volatile("cp.async.ca.shared.global [%0], [%1], 4;" ::"r"(cb + XO_DSK), "l"((const uint32_t*)Dskip + (min(chn, D_ - 1) >> 1)) : "memory");
    asm volatile("cp.async.commit_group;" ::: "memory");
    auto mod2 = [&]() {
        if (wgi == 4) {
            uint32_t bs[9], a[5][4], c[5][4];
            float d[4] = {0.f, 0.f, 0.f, 0.f}, e[4] = {0.f, 0.f, 0.f, 0.f}, f[4] = {0.f, 0.f, 0.f, 0.f};
            mbar_wait(MB(MB_MG1), 0);
#pragma unroll
            for (int ks = 0; ks < 9; ks++) bs[ks] = lds32(sb + OFF_SC + 16 * ks + 4 * t);
            mbar_wait(MB(MB_WM2), 0);
            mod_ld(a, OFF_WM2 + 11520, OFF_WM2 + 5760, w);
            mod_ld(c, OFF_WM0 + 11520, OFF_WM2, w);
            mod_mma2(d, e, a, c, bs);
            mod_ld(a, (w & 1) ? OFF_WM0 + 11520 : OFF_WM2 + 11520, (w & 1) ? OFF_WM2 : OFF_WM2 + 5760, 4);
            mod_st(d, OFF_MG2 + rk * 640 + 64 * w, MB_MG2);
            mod_st(e, OFF_MG2 + rk * 640 + 320 + 64 * w, MB_MG2);
            d[0] = d[1] = d[2] = d[3] = 0.f;
            mma_k8(d, a[4][0], a[4][1], bs[8]);
#pragma unroll
            for (int ks = 0; ks < 4; ks++) mma_bf16((ks & 1) ? d : f, a[ks][0], a[ks][1], a[ks][2], a[ks][3], bs[2 * ks], bs[2 * ks + 1]);
            d[0] += f[0]; d[2] += f[2];
            if (w < 2) mod_st(d, OFF_MG2 + rk * 640 + 320 * w + 256, MB_MG2);
            __syncwarp();
        }
    };
    auto ln1 = [&]() {
        if (warp < 16) {
            uint32_t a[10];
            const uint32_t xa = sb + OFF_X + XN(2 * warp) + (lm & 1) * 80 + XI(lr) + (lm >> 1) * 16;
            asm volatile("cp.async.wait_group 0;" ::: "memory");
            __syncwarp();
            ldsm_x4(a, xa); ldsm_x4(a + 4, xa + 32); ldsm_x2(a + 8, xa + 64);
            named_arrive(9, 640);
            float c1[4] = {0.f, 0.f, 0.f, 0.f}, c2[4] = {0.f, 0.f, 0.f, 0.f}, c3[4] = {0.f, 0.f, 0.f, 0.f};
#pragma unroll
            for (int j = 0; j < 2; j++) {
                mma_bf16(c1, a[4 * j], a[4 * j + 1], a[4 * j + 2], a[4 * j + 3], 0x3F803F80u, 0x3F803F80u);
                mma_bf16(c2, a[4 * j], a[4 * j + 1], a[4 * j + 2], a[4 * j + 3], a[4 * j], a[4 * j + 2]);
                mma_bf16(c3, a[4 * j], a[4 * j + 1], a[4 * j + 2], a[4 * j + 3], a[4 * j + 1], a[4 * j + 3]);
            }
            mma_k8(c1, a[8], a[9], 0x3F803F80u); mma_k8(c2, a[8], a[9], a[8]); mma_k8(c3, a[8], a[9], a[9]);
            float4* p = &S->acc1[256 * rk + 16 * warp + g];
            red4p(t == (g >> 1), p, c1[0], (g & 1) ? c2[1] : c2[0], 0.f);
            red4p(t == (g >> 1), p + 8, c1[2], (g & 1) ? c3[3] : c3[2], 0.f);
        }
    };
    {
        const int i = tid & 127;
        unsigned char* cp = sm + OFF_CH + wgi * CHS;
        const uint4 z = make_uint4(0, 0, 0, 0);
        *(uint4*)(cp + XO_TD + i * 16) = z;
        *(uint4*)(cp + XO_TF + i * 16) = z;
        *(uint4*)(cp + XO_U8 - 1024 + (i >> 6) * 4096 + (i & 63) * 16) = z;
        const int c = (i * 57) >> 9;
        if (i < 108) *(uint4*)(cp + (i < 72 ? c * ULBO + (i - 9 * c) * 16 : XO_TD + 2048 - 72 * 16 + i * 16)) = z;
    }
    if (tid < 224) {
        const int e = tid & 15, l = (tid >> 4) - 6 - (int)((0x3355544433666ull >> (4 * e)) & 15) + 8 * (int)((0x1021021010210ull >> (4 * e)) & 15);
        const unsigned wd = (0x1166688822444ull >> (4 * e)) & 15, one = e >= 11 ? 0xFFFFu : 0x3F80u;
        ((uint32_t*)M.box)[((e >> 2) * 14 + (tid >> 4)) * 4 + (e & 3)] = ((unsigned)l <= wd ? one : 0u) | ((unsigned)(l - 1) <= wd ? one << 16 : 0u);
    }
    const uint32_t scr = sb + warp * KSCR, ws = scr + lane * 4;
    {
        uint32_t zr;
        asm volatile("ld.volatile.shared.u32 %0, [%1];" : "=r"(zr) : "r"(cb + XO_TD + (tid & 127) * 16) : "memory");
        const float p_ldt = __uint_as_float(r_ldt * 65536u + zr), p_lar = __uint_as_float(r_lar * 65536u + zr), p_aim = __uint_as_float(r_aim * 65536u + zr);
        const float p_cr = __uint_as_float(r_cr * 65536u + zr), p_ci = __uint_as_float(r_ci * 65536u + zr);
        float acc[5][4];
        uint32_t afr[4][4], cz[4];
        const uint32_t ba = scr + lr * 144 + lm * 16;
        auto tile = [&](float* c, int rg) {
            __syncwarp();
            c[0] = c[1] = c[2] = c[3] = 0.f;
            uint32_t bb[2][4];
            ldsm_x4(bb[0], ba + rg * 1152);
            ldsm_x4(bb[1], ba + rg * 1152 + 64);
            mma_f16(c, afr[0], bb[0][0], bb[0][1]);
            mma_f16(c, afr[1], bb[0][2], bb[0][3]);
            mma_f16(c, afr[2], bb[1][0], bb[1][1]);
            mma_f16(c, afr[3], bb[1][2], bb[1][3]);
        };
#define CJ(z) packh((z).x, -(z).y)
#define CJP(z) packh((z).y, (z).x)
        const float dt = bfr(expf(p_ldt));
        const float al = -bfr(expf(p_lar)) * dt * 1.4426950408889634f;
        const float th = p_aim * dt;
        const float th_ = th * 0.15915494309189535f;
        const float tl_ = fmaf(th, 0.15915494309189535f, -th_) + th * 6.4206382e-9f;
        auto anchor = [&](float s) {
            float f = th_ * s;
            f -= rintf(f);
            f = fmaf(tl_, s, f) * 6.283185307179586f;
            const float e = fex2(al * s);
            return cplx{e * __cosf(f), e * __sinf(f)};
        };
        const float cx = p_cr * dt * 2.0f, cy = p_ci * dt * 2.0f;
        const uint32_t ex = __reduce_max_sync(0xffffffffu, __float_as_uint(fmaxf(fabsf(cx), fabsf(cy)))) >> 23;
        const float scl = __uint_as_float((254u - ex) << 23);
        const cplx C = cplx{cx * scl, cy * scl};
        const cplx z1 = anchor(1.f), z16 = anchor(16.f), z256 = anchor(256.f);
        {
            const cplx z32 = csq(z16), z48 = cmul(z32, z16), z64 = csq(z32), z128 = csq(z64), z192 = cmul(z128, z64);
            const uint32_t y[3] = {packh(z16.x, z16.y), packh(z32.x, z32.y), packh(z48.x, z48.y)};
            const uint32_t yp[3] = {packh(-z16.y, z16.x), packh(-z32.y, z32.x), packh(-z48.y, z48.x)};
            const uint32_t xx[3] = {packh(z64.x, z64.y), packh(z128.x, z128.y), packh(z192.x, z192.y)};
            sts32(ws, 0x00003C00u);
#pragma unroll
            for (int j = 0; j < 3; j++) sts32(ws + (1 + j) * 144, y[j]);
#pragma unroll
            for (int i = 0; i < 3; i++) {
                sts32(ws + (4 + 4 * i) * 144, xx[i]);
#pragma unroll
                for (int j = 0; j < 3; j++) sts32(ws + (5 + 4 * i + j) * 144, hcm(xx[i], y[j], yp[j]));
            }
        }
        ln1();
        const cplx z2 = csq(z1);
        {
            const cplx z3 = cmul(z2, z1), z4 = csq(z2), z8 = csq(z4);
            const cplx c4 = cmul(C, z4), c8 = cmul(C, z8), c12 = cmul(c8, z4);
            cz[0] = packh(C.x, -C.y); cz[1] = packh(c4.x, -c4.y); cz[2] = packh(c8.x, -c8.y); cz[3] = packh(c12.x, -c12.y);
            __syncwarp();
#pragma unroll
            for (int s = 0; s < 4; s++) ldsm_x4(afr[s], scr + (lr + 8 * (lm & 1)) * 144 + (2 * s + (lm >> 1)) * 16);
            const uint32_t y[3] = {CJ(z1), CJ(z2), CJ(z3)}, yp[3] = {CJP(z1), CJP(z2), CJP(z3)};
#pragma unroll
            for (int tt = 0; tt < 2; tt++) {
                const int rg = tt ? 0 : 2;
#pragma unroll
                for (int i = 0; i < 2; i++) {
                    sts32(ws + rg * 1152 + (4 * i) * 144, cz[2 * tt + i]);
#pragma unroll
                    for (int j = 0; j < 3; j++) sts32(ws + rg * 1152 + (4 * i + 1 + j) * 144, hcm(cz[2 * tt + i], y[j], yp[j]));
                }
                tile(acc[tt], rg);
            }
        }
        const cplx z258 = cmul(z256, z2), z512 = csq(z256), z768 = cmul(z512, z256);
        {
            const uint32_t a0 = CJ(z256), a0p = CJP(z256), a1 = CJ(z258), a1p = CJP(z258);
#pragma unroll
            for (int i = 0; i < 4; i++) { sts32(ws + 1152 + (2 * i) * 144, hcm(cz[i], a0, a0p)); sts32(ws + 1152 + (2 * i + 1) * 144, hcm(cz[i], a1, a1p)); }
            tile(acc[2], 1);
        }
        {
            const uint32_t a0 = CJ(z512), a0p = CJP(z512), a1 = CJ(z768), a1p = CJP(z768);
#pragma unroll
            for (int i = 0; i < 4; i++) { sts32(ws + 2304 + i * 144, hcm(cz[i], a0, a0p)); sts32(ws + 2304 + (4 + i) * 144, hcm(cz[i], a1, a1p)); }
            tile(acc[3], 2);
        }
        const cplx z1024 = csq(z512);
        {
            const cplx zk[4] = {z1024, cmul(z1024, z256), csq(z768), cmul(z1024, z768)};
#pragma unroll
            for (int h = 0; h < 4; h++) {
                const uint32_t a0 = CJ(zk[h]), a0p = CJP(zk[h]);
                sts32(ws + (2 * h) * 144, hcm(cz[0], a0, a0p));
                sts32(ws + (2 * h + 1) * 144, hcm(cz[2], a0, a0p));
            }
            tile(acc[4], 0);
        }
        const cplx z2048 = csq(z1024);
        float last = C.x * z2048.x - C.y * z2048.y;
#pragma unroll
        for (int o = 16; o; o >>= 1) last += __shfl_xor_sync(0xffffffffu, last, o);
        __syncwarp();
#pragma unroll
        for (int i = 0; i < 5; i++) *(float4*)(sm + (scr - sb) + i * 512 + lane * 16) = make_float4(acc[i][0], acc[i][1], acc[i][2], acc[i][3]);
        if (lane == 0) { const float inv = __uint_as_float(ex << 23); sts32(cb + XO_KINV + 4 * w, __float_as_uint(inv)); sts32(cb + XO_KLAST + 4 * w, __float_as_uint(last * inv)); }
        asm volatile("cp.async.wait_group 0;" ::: "memory");
        CL_WAIT();
        named_bar(1 + wgi, 128);
        const uint32_t td = cb + XO_TD + 64 * 4, tf = cb + XO_TF - 32 * 4;
        const float4 ki = *(const float4*)(sm + (cb - sb) + XO_KINV);
        auto fsum = [&](int off, uint32_t& r0, uint32_t& r1) {
            const unsigned char* p = sm + wgi * (4 * KSCR) + off;
            const float4 a = *(const float4*)p, b2 = *(const float4*)(p + KSCR), c = *(const float4*)(p + 2 * KSCR), d = *(const float4*)(p + 3 * KSCR);
            r0 = pack2(fmaf(a.y, ki.x, b2.y * ki.y) + fmaf(c.y, ki.z, d.y * ki.w), fmaf(a.x, ki.x, b2.x * ki.y) + fmaf(c.x, ki.z, d.x * ki.w));
            r1 = pack2(fmaf(a.w, ki.x, b2.w * ki.y) + fmaf(c.w, ki.z, d.w * ki.w), fmaf(a.z, ki.x, b2.z * ki.y) + fmaf(c.z, ki.z, d.z * ki.w));
        };
        uint32_t r[2], q[2];
        fsum(w * 512 + lane * 16, r[0], r[1]);
        fsum(2048 + w * 128 + lr * 16, q[0], q[1]);
        __syncwarp();
        if (lane == 0) mbar_arrive(MB(MB_KD));
        if (w < 2) {
            const uint32_t p = td + (16 * g + 8 * w + 2 * t) * 4;
#pragma unroll
            for (int h = 0; h < 2; h++) { sts16(p + h * 512, r[h] >> 16); sts32(p + h * 512 + 4, r[h]); sts16(p + h * 512 + 10, r[h]); }
        } else if (w == 2) {
            const uint32_t p = td + (256 + 16 * g + 4 * t) * 4;
#pragma unroll
            for (int h = 0; h < 2; h++) {
                const uint32_t k0 = r[h] >> 16;
                if (h || lane) { sts16(p + h * 512 - 4, k0); sts16(p + h * 512 + 2, k0); }
                sts16(p + h * 512, k0); sts32(p + h * 512 + 4, __byte_perm(r[h], 0, 0x3232)); sts32(p + h * 512 + 8, r[h]); sts16(p + h * 512 + 14, r[h]);
            }
        } else {
            const uint32_t p = tf + (64 + 32 * (t >> 1) + 2 * g + (t & 1)) * 4;
#pragma unroll
            for (int h = 0; h < 2; h++) {
                const uint32_t k0 = r[h] >> 16;
                sts16(p + h * 64 + 512, r[h]); sts16(p + h * 64 + 518, r[h]);
                if (h || lane) { sts16(p + h * 64 - 4, k0); sts16(p + h * 64 + 2, k0); }
            }
            if (lane == 0) {
                const uint32_t dd = __byte_perm(r[0], 0, 0x3232);
                sts16(td + 511 * 4, dd); sts32(td + 512 * 4, dd); sts32(td + 513 * 4, dd); sts32(td + 514 * 4, dd); sts16(td + 515 * 4 + 2, dd);
            }
        }
        if (lane < 8) {
            const uint32_t p = tf + 1024 + (64 + 16 * t + 2 * w + g) * 4;
#pragma unroll
            for (int h = 0; h < 2; h++) {
                const uint32_t k0 = q[h] >> 16;
                sts16(p + h * 32 + 512, q[h]); sts16(p + h * 32 + 518, q[h]);
                if (h || (tid & 127)) { sts16(p + h * 32 - 4, k0); sts16(p + h * 32 + 2, k0); }
            }
            if ((tid & 127) == 0) {
                const float4 kl4 = *(const float4*)(sm + (cb - sb) + XO_KLAST);
                const uint32_t kl = f2bits((kl4.x + kl4.y) + (kl4.z + kl4.w)), dd = __byte_perm(q[0], 0, 0x3232);
                sts16(tf + 127 * 4, dd); sts16(tf + 128 * 4 + 2, dd); sts32(cb + XO_K1024, dd);
                sts16(tf + 1024 + 127 * 4, kl); sts16(tf + 1024 + 128 * 4 + 2, kl);
            }
        }
        __syncwarp();
        mod2();
    }
    if (has_ch) {
        conv_channel(sm, rk);
    } else {
        asm volatile("setmaxnreg.inc.sync.aligned.u32 88;");
        mbar_wait(MB(MB_WG), 0);
        mbar_wait(MB(MB_C2), 0);
    }
    {
    const int tid = fresh_tid(), warp = __shfl_sync(0xffffffffu, tid >> 5, 0), lane = tid & 31;
    const int g = lane >> 2, t = lane & 3, lr = lane & 7, lm = lane >> 3;
    __syncwarp();
    if (lane == 0) mbar_arrive(MB(MB_KD));
    uint32_t x1[10];
    if (warp < 16) {
        uint32_t bw[5], v[10];
#pragma unroll
        for (int j = 0; j < 5; j++) bw[j] = (g & 1) ? M.c2[4 * j + t].w : 0x3F803F80u;
        const uint32_t xa = sb + OFF_X + XI(warp >> 1) + (2 * (warp & 1) + (lm & 1)) * XG + lr * 80 + (lm >> 1) * 16;
        const uint32_t va = sb + OFF_V + (8 * (lm >> 1) + lr) * VP + 32 * warp + 16 * (lm & 1);
        ldsm_x4(x1, xa); ldsm_x4(x1 + 4, xa + 32); ldsm_x2(x1 + 8, xa + 64);
        mbar_wait(MB(MB_CW), 0);
        mbar_wait(MB(MB_V), 0);
        ldsm_x4_t(v, va); ldsm_x4_t(v + 4, va + 16 * VP); ldsm_x2_t(v + 8, va + 32 * VP);
#pragma unroll
        for (int i = 0; i < 10; i++) x1[i] = add2(x1[i], (i >= 4 && cl == 14) ? 0u : v[i]);
        float c1[4] = {0.f, 0.f, 0.f, 0.f}, c2[4] = {0.f, 0.f, 0.f, 0.f}, c3[4] = {0.f, 0.f, 0.f, 0.f};
#pragma unroll
        for (int j = 0; j < 2; j++) {
            mma_bf16(c1, x1[4 * j], x1[4 * j + 1], x1[4 * j + 2], x1[4 * j + 3], bw[2 * j], bw[2 * j + 1]);
            mma_bf16(c2, x1[4 * j], x1[4 * j + 1], x1[4 * j + 2], x1[4 * j + 3], x1[4 * j], x1[4 * j + 2]);
            mma_bf16(c3, x1[4 * j], x1[4 * j + 1], x1[4 * j + 2], x1[4 * j + 3], x1[4 * j + 1], x1[4 * j + 3]);
        }
        mma_k8(c1, x1[8], x1[9], bw[4]); mma_k8(c2, x1[8], x1[9], x1[8]); mma_k8(c3, x1[8], x1[9], x1[9]);
        if (t == (g >> 1)) {
            float4* p = &S->acc2[256 * rk + 16 * warp + g];
            red4(p, c1[0], (g & 1) ? c2[1] : c2[0], c1[1]);
            red4(p + 8, c1[2], (g & 1) ? c3[3] : c3[2], c1[3]);
        }
        __syncwarp();
    }
    uint32_t wf[9][4], wd[2][3][4];
    const int fmt = warp >> 2, fsl = warp & 3;
    auto ldwf = [&]() {
        const int half = lm & 1;
        const uint32_t base = (fmt == 4) ? ((half ? OFF_WU : OFF_WG) + 64) : ((fmt >> 1) * OFF_WU + ((2 * (fmt & 1) + half) << 4));
        const uint32_t wa = sb + base + (144 * fsl + lr + 8 * (lm >> 1)) * 80;
#pragma unroll
        for (int ks = 0; ks < 9; ks++) ldsm_x4_t(wf[ks], wa + ks * 1280);
    };
    mbar_wait(MB(MB_WG), 0);
    mbar_wait(MB(MB_WU), 0);
    ldwf();
    if (warp < 16) {
        const float4* ap = &S->acc2[256 * rk + 16 * warp + g];
        float4 s[2];
        s[0] = ld_rlx4f(ap); s[1] = ld_rlx4f(ap + 8);
        uint4 kc[5];
#pragma unroll
        for (int j = 0; j < 5; j++) kc[j] = M.c2[4 * j + t];
        const float cw = M.cws[0], sbw = M.cws[1];
        uint32_t tk0 = (2047 - (((g & 6) << 8) + 256 * (warp & 1) + ((g & 1) << 6) + 8 * rk + (warp >> 1))) << 3;
        uint32_t ta = sb + OFF_H2T + (16 * warp + (lane & 15)) * 80 + (lane >> 4) * 16, ka = sb + OFF_MISC + (uint32_t)offsetof(Misc, key) + (16 * warp + g) * 4;
        asm volatile("" : "+r"(tk0), "+r"(ta), "+r"(ka));
        mbar_wait(MB(MB_KD), 1);
#pragma unroll 1
        for (int it = 0; it < SPIN_MAX && (s[0].w != (float)NCL || s[1].w != (float)NCL); it++) { s[0] = ld_rlx4f(ap); s[1] = ld_rlx4f(ap + 8); }
        __syncwarp();
        uint32_t st[2][3];
#pragma unroll
        for (int h = 0; h < 2; h++) {
            float meanb, rinv;
            ln_stats(s[h].x, s[h].y, meanb, rinv);
            const uint32_t rbits = __float_as_uint(fmaf(fmaf(-meanb, cw, s[h].z), rinv, sbw));
            const uint32_t key = ((rbits ^ (((int)rbits >> 31) | 0x80000000u)) & 0xFFFFC000u) | (tk0 - 1024 * h);
            if (t == 0) sts32(ka + 32 * h, key);
            const float rh = bfr(rinv);
            st[h][0] = pack2(meanb, meanb); st[h][1] = pack2(rh, rh); st[h][2] = pack2(rinv - rh, rinv - rh);
        }
        named_arrive(6, 768);
        uint32_t h2[10], o[10];
#pragma unroll
        for (int i = 0; i < 10; i++) h2[i] = add2(mul2(norm2(x1[i], st[i & 1][0], st[i & 1][1], st[i & 1][2]), kc[i >> 1].x), kc[i >> 1].y);
        stsm_x4(ta, h2[0], h2[1], h2[2], h2[3]); stsm_x4(ta + 32, h2[4], h2[5], h2[6], h2[7]); stsm_x2(ta + 64, h2[8], h2[9]);
        named_arrive(7, 640);
        asm volatile("" : "+r"(kc[0].z), "+r"(kc[1].z), "+r"(kc[2].z), "+r"(kc[3].z), "+r"(kc[4].z));
        if ((warp == cl || (warp == 15 && cl == 0)) && lane < 16) st_rlx4(&S->acc1[256 * rk + 16 * warp + lane], make_uint4(0, 0, 0, 0));
#pragma unroll
        for (int i = 0; i < 10; i++) o[i] = add2(x1[i], mul2(kc[i >> 1].z, h2[i]));
        stsm_x4(ta + (OFF_OUT - OFF_H2T), o[0], o[1], o[2], o[3]); stsm_x4(ta + (OFF_OUT - OFF_H2T) + 32, o[4], o[5], o[6], o[7]); stsm_x2(ta + (OFF_OUT - OFF_H2T) + 64, o[8], o[9]);
        PROXY_FENCE();
    } else named_arrive(6, 768);
    uint4 gv = make_uint4(1, 1, 1, 1);
    const uint4* gp = nullptr;
    uint32_t gdst = 0;
    const int gi = GW(warp) * 32 + lane, kk = (gi * 911) >> 16, seg = gi - 72 * kk;
    mbar_wait(MB(MB_KEY), 0);
    if (warp < 18) {
        const int kmax = ((GW(warp) * 32 + 31) * 911) >> 16;
        uint4 k = make_uint4(0, 0, 0, 0);
        if (lane < 16) k = *(const uint4*)&M.cand[4 * lane];
        uint32_t key = 0;
#pragma unroll
        for (int rnd = 0; rnd < 8; rnd++) {
            const uint32_t m = __reduce_max_sync(0xffffffffu, k.x);
            if (kk == rnd) key = m;
            if (rnd >= kmax) break;
            POP(k, m);
        }
        gp = &S->h2c[SLOT(key) * 72 + seg];
        gv = ld_rlx4(gp);
        if (__any_sync(0xffffffffu, lane < 16 && k.x == 0u)) {
            mbar_wait(MB(MB_KEY2), 0);
            k = *(const uint4*)&M.cand[4 * lane];
#pragma unroll 1
            for (int rnd = 0; rnd <= kmax; rnd++) {
                const uint32_t m = __reduce_max_sync(0xffffffffu, k.x);
                if (kk == rnd) key = m;
                POP(k, m);
            }
            gp = &S->h2c[SLOT(key) * 72 + seg];
            gv = ld_rlx4(gp);
        }
        gdst = sb + OFF_H2S + kk * (ROWP * 2) + seg * 16;
    }
    mbar_wait(MB(MB_WD), 0);
#pragma unroll
    for (int i = 0; i < 2; i++) {
        const int mt = warp + 20 * i;
        const uint32_t wa = sb + OFF_WD + (mt >> 2) * 5120 + lr * 128 + (((2 * (mt & 3) + (lm & 1)) ^ lr) << 4);
#pragma unroll
        for (int ks = 0; ks < 3; ks++)
            if (i == 0 || warp < 16) ldsm_x4_t(wd[i][ks], wa + ks * 2048 + ((ks < 2) ? (lm >> 1) * 1024 : 0));
    }
#pragma unroll 1
    for (int it = 0; it < SPIN_MAX && gv.x == 0u; it++) gv = ld_rlx4(gp);
    if (gdst) asm volatile("st.shared.v4.u32 [%0], {%1,%2,%3,%4};" ::"r"(gdst), "r"(~gv.x), "r"(~gv.y), "r"(~gv.z), "r"(~gv.w) : "memory");
    CBAR();
    if (warp == 19) named_arrive(8, 64);
    float* ffr = (float*)(sm + OFF_FFR);
    auto ffn1 = [&]() {
        float acc[2][4] = {{0.f, 0.f, 0.f, 0.f}, {0.f, 0.f, 0.f, 0.f}};
        const uint32_t ha = sb + OFF_H2S + lr * (ROWP * 2) + (144 * fsl) * 2 + lm * 16;
#pragma unroll
        for (int k2 = 0; k2 < 5; k2++) {
            uint32_t hb[4];
            ldsm_x4(hb, ha + k2 * 64 - ((k2 == 4) ? (lm >> 1) * 32 : 0));
            mma_bf16(acc[0], wf[2 * k2][0], wf[2 * k2][1], wf[2 * k2][2], wf[2 * k2][3], hb[0], hb[1]);
            if (k2 < 4) mma_bf16(acc[1], wf[2 * k2 + 1][0], wf[2 * k2 + 1][1], wf[2 * k2 + 1][2], wf[2 * k2 + 1][3], hb[2], hb[3]);
        }
        float* o = ffr + ((fsl * 80 + 16 * fmt + g) * 8 + 2 * t);
        *(float2*)o = make_float2(acc[0][0] + acc[1][0], acc[0][1] + acc[1][1]);
        *(float2*)(o + 64) = make_float2(acc[0][2] + acc[1][2], acc[0][3] + acc[1][3]);
    };
    ffn1();
    bf16(*act)[56] = (bf16(*)[56])(sm + OFF_ACT);
    auto gate = [&]() {
        if (tid < 384) {
            const int f = tid >> 3, a = tid & 7;
            float v = 0.f;
            if (f < 40) {
                const int rg = (f < 32) ? f : f + 32, ru = (f < 32) ? f + 32 : f + 40;
                const float* pg = ffr + rg * 8 + a;
                const float* pu = ffr + ru * 8 + a;
                float gg = bfr((pg[0] + pg[640]) + (pg[1280] + pg[1920]));
                gg = bfr(silu(gg));
                const float uu = bfr((pu[0] + pu[640]) + (pu[1280] + pu[1920]));
                v = gg * uu;
            }
            act[a][f] = __ushort_as_bfloat16((unsigned short)f2bits(v));
        }
    };
    CBAR();
    gate();
    named_bar(12, 672);
    const uint32_t redo = M.fin[8];
    uint32_t bq[3][2];
    auto ldact = [&]() {
#pragma unroll
        for (int ks = 0; ks < 3; ks++) {
            bq[ks][0] = *(const uint32_t*)&act[g][16 * ks + 2 * t];
            bq[ks][1] = *(const uint32_t*)&act[g][16 * ks + 2 * t + 8];
        }
    };
    ldact();
    if (redo) {
        if (warp < 18) {
            const int gi = fresh_tid(), kk = (gi * 911) >> 16, seg = gi - 72 * kk;
            gp = &S->h2c[SLOT(M.fin[kk]) * 72 + seg];
            gv.x = 0u;
#pragma unroll 1
            for (int it = 0; it < SPIN_MAX && gv.x == 0u; it++) gv = ld_rlx4(gp);
            *(uint4*)(sm + OFF_H2S + kk * (ROWP * 2) + seg * 16) = make_uint4(~gv.x, ~gv.y, ~gv.z, ~gv.w);
        }
        CBAR();
        ffn1();
        CBAR();
        gate();
        CBAR();
        ldact();
    }
    {
#pragma unroll
        for (int i = 0; i < 2; i++) {
            if (i == 0 || warp < 16) {
                float acc[4] = {0.f, 0.f, 0.f, 0.f};
#pragma unroll
                for (int ks = 0; ks < 3; ks++) mma_bf16(acc, wd[i][ks][0], wd[i][ks][1], wd[i][ks][2], wd[i][ks][3], bq[ks][0], bq[ks][1]);
                const int d = i ? 4 + (warp >> 2) : (warp * 13) >> 6, slot = i ? (warp & 3) : warp - 5 * d;
                const uint32_t rb = mapa(sb, d);
                sta2(rb + OFF_RS + ((rk * 5 + slot) * 32 + lane) * 8, movm(pack2(acc[0], acc[1])), movm(pack2(acc[2], acc[3])), rb + (MB(MB_RS) - sb));
            }
        }
    }
    if (warp >= 8) {
        const int s = (warp - 8) >> 1, h = warp & 1;
        if (s < (rk < 4 ? 5 : 4)) {
            mbar_wait(MB(MB_RS), 0);
            const uint32_t p = sb + OFF_RS + (s * 32 + lane) * 8 + 4 * h;
            uint32_t v[8];
#pragma unroll
            for (int i = 0; i < 8; i++) v[i] = lds32(p + i * 1280);
            const float s0 = ((lo2f(v[0]) + lo2f(v[1])) + (lo2f(v[2]) + lo2f(v[3]))) + ((lo2f(v[4]) + lo2f(v[5])) + (lo2f(v[6]) + lo2f(v[7])));
            const float s1 = ((hi2f(v[0]) + hi2f(v[1])) + (hi2f(v[2]) + hi2f(v[3]))) + ((hi2f(v[4]) + hi2f(v[5])) + (hi2f(v[6]) + hi2f(v[7])));
            st_rlx2(&S->part[((cl * 36 + (rk < 4 ? 5 * rk : 4 * rk + 4) + s) * 2 + h) * 32 + lane], ~__float_as_uint(s0), ~__float_as_uint(s1));
        }
    } else {
        const uint32_t key = M.fin[warp], tk = (~key >> 3) & 2047u;
        const int P = 20 * cl + lane;
        if (((tk >> 3) & 7u) == (uint32_t)rk && lane < 20 && P < D_ / 2) {
            const uint2* src = &S->part[(P >> 2) * 32 + 4 * warp + (P & 3)];
            uint2 a[NCL];
#pragma unroll
            for (int i = 0; i < NCL; i++) a[i] = ld_rlx2(src + i * 2304);
            const float rs = __fdividef(1.0f, 1.0f + __expf(-hi2f(key ^ (((int)~key >> 31) | 0x80000000u))));
            const uint32_t row = ROW(key);
            const unsigned short* vp = (const unsigned short*)(sm + OFF_V + 2 * lane * VP) + row;
            const uint32_t xv = add2(lds32(sb + OFF_X + XI(row >> 5) + ((row >> 3) & 3) * XG + (row & 7) * 80 + 4 * lane), (uint32_t)vp[0] | ((uint32_t)vp[VP / 2] << 16));
            const uint32_t hv = lds32(sb + OFF_H2T + row * 80 + 4 * lane), gb = M.c2[lane].z;
#pragma unroll 1
            for (int it = 0; it < SPIN_MAX; it++) {
                bool bad = false;
#pragma unroll
                for (int i = 0; i < NCL; i++) if (a[i].x == 0u) { a[i] = ld_rlx2(src + i * 2304); bad = true; }
                if (!bad) break;
            }
            float s0 = 0.f, s1 = 0.f;
#pragma unroll
            for (int i = 0; i < NCL; i++) { s0 += __uint_as_float(~a[i].x); s1 += __uint_as_float(~a[i].y); }
            const uint32_t ov = add2(xv, mul2(gb, add2(hv, mul2(pack2(s0, s1), pack2(rs, rs)))));
            mbar_wait(MB(MB_OUT), 0);
            *(uint32_t*)(out + tk * D_ + 2 * P) = ov;
        }
    }
    }
    }
}

typedef CUresult (*EncodeFn)(CUtensorMap*, CUtensorMapDataType, cuuint32_t, void*, const cuuint64_t*, const cuuint64_t*,
                             const cuuint32_t*, const cuuint32_t*, CUtensorMapInterleave, CUtensorMapSwizzle,
                             CUtensorMapL2promotion, CUtensorMapFloatOOBfill);

static void make_map(EncodeFn fn, CUtensorMap* m, const void* ptr, uint64_t cols, uint64_t rows, uint32_t bc, uint32_t br,
                     CUtensorMapSwizzle sw, int five) {
    cuuint64_t dims[5] = {cols, rows, 4, 4, 64};
    cuuint64_t strides[4] = {cols * 2 * (five ? 64 : 1), cols * 2 * 512, cols * 2 * 128, cols * 2};
    cuuint32_t box[5] = {bc, br, 4, 4, 8};
    cuuint32_t es[5] = {1, 1, 1, 1, 1};
    CUresult rc = fn(m, CU_TENSOR_MAP_DATA_TYPE_BFLOAT16, five ? 5 : 2, (void*)ptr, dims, strides, box, es, CU_TENSOR_MAP_INTERLEAVE_NONE,
                     sw, CU_TENSOR_MAP_L2_PROMOTION_NONE, CU_TENSOR_MAP_FLOAT_OOB_FILL_NONE);
    (void)rc;
}

static void launch(void* const* d_in, const int* in_sizes, int n_in, void* d_out, int out_size) {
    static EncodeFn enc = nullptr;
    static CUtensorMap tmm, tmg, tmu, tmd, tmo;
    static Scratch* sp = nullptr;
    static const void* cached[6] = {nullptr, nullptr, nullptr, nullptr, nullptr, nullptr};
    if (!enc) {
        cudaDriverEntryPointQueryResult qr;
        void* fn = nullptr;
        cudaGetDriverEntryPoint("cuTensorMapEncodeTiled", &fn, cudaEnableDefault, &qr);
        enc = (EncodeFn)fn;
        cudaFuncSetAttribute(clus_kernel, cudaFuncAttributeMaxDynamicSharedMemorySize, SMEM_TOTAL);
        cudaGetSymbolAddress((void**)&sp, g_s);
    }
    if (cached[0] != d_in[13] || cached[1] != d_in[9] || cached[2] != d_in[10] || cached[3] != d_in[11] || cached[4] != d_in[0] || cached[5] != d_out) {
        make_map(enc, &tmo, d_out, D_, 2, 40, 2, CU_TENSOR_MAP_SWIZZLE_NONE, 1);
        make_map(enc, &tmm, d_in[13], 6 * D_, D_, 40, 72, CU_TENSOR_MAP_SWIZZLE_NONE, 0);
        make_map(enc, &tmg, d_in[9], F_, D_, 40, 192, CU_TENSOR_MAP_SWIZZLE_NONE, 0);
        make_map(enc, &tmu, d_in[10], F_, D_, 40, 192, CU_TENSOR_MAP_SWIZZLE_NONE, 0);
        make_map(enc, &tmd, d_in[11], D_, F_, 64, 40, CU_TENSOR_MAP_SWIZZLE_128B, 0);
        cached[0] = d_in[13]; cached[1] = d_in[9]; cached[2] = d_in[10]; cached[3] = d_in[11]; cached[4] = d_in[0]; cached[5] = d_out;
    }
    clus_kernel<<<G_, NTHR, SMEM_TOTAL>>>((const bf16*)d_in[0], (const bf16*)d_in[1], (const bf16*)d_in[2], (const bf16*)d_in[3], (const bf16*)d_in[4],
                                          (const bf16*)d_in[5], (const bf16*)d_in[12], sp, (const bf16*)d_in[6], (const bf16*)d_in[8], (const bf16*)d_in[13],
                                          (bf16*)d_out, tmm, tmg, tmu, tmd, tmo);
}

static bool fits() {
    cudaFuncSetAttribute(clus_kernel, cudaFuncAttributeMaxDynamicSharedMemorySize, SMEM_TOTAL);
    cudaLaunchConfig_t cfg = {};
    cudaLaunchAttribute at;
    at.id = cudaLaunchAttributeClusterDimension;
    at.val.clusterDim.x = 8; at.val.clusterDim.y = 1; at.val.clusterDim.z = 1;
    cfg.gridDim = dim3(G_); cfg.blockDim = dim3(NTHR); cfg.dynamicSmemBytes = SMEM_TOTAL; cfg.attrs = &at; cfg.numAttrs = 1;
    int n = 0;
    const bool ok = cudaOccupancyMaxActiveClusters(&n, clus_kernel, &cfg) == cudaSuccess && n >= NCL;
    cudaGetLastError();
    return ok;
}
}
#undef L_
#undef D_
#undef N_
#undef F_
#undef G_
#undef NCL
#undef NTHR
#undef SPIN_MAX
#undef NRST
#undef OFF_WG
#undef OFF_WU
#undef KSCR
#undef OFF_WM0
#undef OFF_STG
#undef OFF_MG2
#undef OFF_CH
#undef CHS
#undef ULBO
#undef XO_U8
#undef XO_U16
#undef XO_ZA
#undef XO_ZB
#undef XO_ZC
#undef XO_ZD
#undef XO_TF
#undef XO_TD
#undef XO_K1024
#undef XO_DSK
#undef XO_KINV
#undef XO_KLAST
#undef XO_MBU
#undef OFF_X
#undef XG
#undef XI
#undef XN
#undef OFF_V
#undef VP
#undef OFF_EK
#undef OFF_WM2
#undef OFF_MG1
#undef OFF_SC
#undef OFF_C1
#undef OFF_MISC
#undef OFF_WD
#undef OFF_H2T
#undef OFF_OUT
#undef ROWP
#undef OFF_H2S
#undef OFF_FFR
#undef OFF_ACT
#undef OFF_RS
#undef SMEM_TOTAL
#undef CBAR
#undef PROXY_FENCE
#undef D4
#undef O4
#undef WG_FENCE
#undef WG_COMMIT
#undef WG_WAIT
#undef TQ
#undef MB
#undef PRE
#undef DZ
#undef DS
#undef KST
#undef WMD
#undef PU
#undef PD
#undef PFG
#undef CWP
#undef CWD
#undef LN1POS
#undef SLOT
#undef ROW
#undef CE
#undef POP
#undef GW
#undef RESET
#undef CL_ARRIVE
#undef CL_WAIT
#undef CJ
#undef CJP

namespace v4 {

#define L_ 2048
#define D_ 576
#define N_ 128
#define F_ 4608
#define G_ 128
#define NTHR 640
#define SPIN_MAX (1 << 18)
#define SENT 0u
#define HINT_N 182u

typedef __nv_bfloat16 bf16;

struct Scratch {
    uint4 xn[G_ * G_ * 10];
    uint4 v[G_ * D_ * 2];
    uint2 part[G_ * G_ * 9];
    uint4 h2w[L_ * 96];
    unsigned int rec[G_ * 8];
    unsigned int modw[6 * D_];
    unsigned int ticket[64];
    unsigned int cnt[64];
    unsigned int hint[64];
};
__device__ __align__(1024) Scratch g_s;

#define OFF_WG 0
#define OFF_WU 46080
#define OFF_CH 92160
#define CHS 20784
#define ULBO 656
#define XO_U8 6272
#define XO_U16 10368
#define XO_ZA 5248
#define XO_ZB 8448
#define XO_ZC 11648
#define XO_ZD 13824
#define XO_TD 16000
#define XO_TF 18624
#define XO_K1024 20672
#define KSCR 3456
#define OFF_TILE 196096
#define ROWP 584
#define OFF_MISC 214784
#define OFF_WD OFF_CH
#define OFF_H2T (OFF_CH + 3 * CHS)
#define OFF_H2S (OFF_H2T + 18688)
#define OFF_FFR (OFF_H2S + 9344)
#define OFF_FIN OFF_FFR
#define OFF_ACT (OFF_FFR + 10240)

struct Misc {
    __align__(16) uint4 sent[256];
    __align__(16) uint4 box[11 * 14];
    union {
        struct {
            __align__(16) float2 part[18][16];
            float rp[18][16];
        };
        struct {
            __align__(16) unsigned short st1[3][16];
            __align__(16) float p1[16][4], p2[16][4];
        };
    };
    __align__(16) bf16 cb1[D_], sb[D_], gb[D_];
    __align__(16) bf16 sc[D_];
    __align__(16) unsigned int cand[64], skey[16];
    __align__(16) float kinv[5][4], klast[5][4];
    unsigned int pk[4][8];
    __align__(16) uint4 st2[16];
    unsigned int wr[D_ / 2];
    float modx[32];
    unsigned int rank[16];
    volatile unsigned int flag;
    unsigned int e1cnt;
    unsigned long long mbar[5];
    unsigned int epoch;
};
#define SMEM_TOTAL (OFF_MISC + (int)sizeof(Misc))
static_assert(SMEM_TOTAL <= 232448, "smem");

__device__ __forceinline__ float lo2f(uint32_t w) { return __uint_as_float(w << 16); }
__device__ __forceinline__ float hi2f(uint32_t w) { return __uint_as_float(w & 0xFFFF0000u); }
__device__ __forceinline__ uint32_t pack2(float lo, float hi) { uint32_t r; asm("cvt.rn.bf16x2.f32 %0, %1, %2;" : "=r"(r) : "f"(hi), "f"(lo)); return r; }
__device__ __forceinline__ float bfr(float x) { return __uint_as_float(pack2(0.f, x)); }
__device__ __forceinline__ uint32_t f2bits(float x) { return pack2(x, 0.f); }
__device__ __forceinline__ uint32_t packh(float lo, float hi) { uint32_t r; asm("cvt.rn.f16x2.f32 %0, %1, %2;" : "=r"(r) : "f"(hi), "f"(lo)); return r; }
__device__ __forceinline__ float frcp(float x) { float r; asm("rcp.approx.ftz.f32 %0, %1;" : "=f"(r) : "f"(x)); return r; }
__device__ __forceinline__ float fsqrt(float x) { float r; asm("sqrt.approx.f32 %0, %1;" : "=f"(r) : "f"(x)); return r; }
__device__ __forceinline__ float fex2(float x) { float r; asm("ex2.approx.ftz.f32 %0, %1;" : "=f"(r) : "f"(x)); return r; }
__device__ __forceinline__ float silu(float x) { return __fdividef(x, 1.0f + __expf(-x)); }
__device__ __forceinline__ uint32_t add2(uint32_t a, uint32_t b) { uint32_t r; asm("add.rn.bf16x2 %0, %1, %2;" : "=r"(r) : "r"(a), "r"(b)); return r; }
__device__ __forceinline__ uint32_t sub2(uint32_t a, uint32_t b) { uint32_t r; asm("sub.rn.bf16x2 %0, %1, %2;" : "=r"(r) : "r"(a), "r"(b)); return r; }
__device__ __forceinline__ uint32_t mul2(uint32_t a, uint32_t b) { uint32_t r; asm("mul.rn.bf16x2 %0, %1, %2;" : "=r"(r) : "r"(a), "r"(b)); return r; }
__device__ __forceinline__ uint32_t fma2(uint32_t a, uint32_t b, uint32_t c) { uint32_t r; asm("fma.rn.bf16x2 %0, %1, %2, %3;" : "=r"(r) : "r"(a), "r"(b), "r"(c)); return r; }
__device__ __forceinline__ uint32_t norm2(uint32_t x, uint32_t m, uint32_t rh, uint32_t rl) { const uint32_t d = sub2(x, m); return fma2(d, rh, mul2(d, rl)); }

__device__ __forceinline__ void mma_bf16(float* c, uint32_t a0, uint32_t a1, uint32_t a2, uint32_t a3, uint32_t b0, uint32_t b1) {
    asm volatile("mma.sync.aligned.m16n8k16.row.col.f32.bf16.bf16.f32 {%0,%1,%2,%3}, {%4,%5,%6,%7}, {%8,%9}, {%0,%1,%2,%3};\n"
                 : "+f"(c[0]), "+f"(c[1]), "+f"(c[2]), "+f"(c[3]) : "r"(a0), "r"(a1), "r"(a2), "r"(a3), "r"(b0), "r"(b1));
}
__device__ __forceinline__ void mma_f16(float* c, const uint32_t* a, uint32_t b0, uint32_t b1) {
    asm volatile("mma.sync.aligned.m16n8k16.row.col.f32.f16.f16.f32 {%0,%1,%2,%3}, {%4,%5,%6,%7}, {%8,%9}, {%0,%1,%2,%3};\n"
                 : "+f"(c[0]), "+f"(c[1]), "+f"(c[2]), "+f"(c[3]) : "r"(a[0]), "r"(a[1]), "r"(a[2]), "r"(a[3]), "r"(b0), "r"(b1));
}
__device__ __forceinline__ void ldsm_x4(uint32_t* r, uint32_t addr) {
    asm volatile("ldmatrix.sync.aligned.m8n8.x4.shared.b16 {%0,%1,%2,%3}, [%4];" : "=r"(r[0]), "=r"(r[1]), "=r"(r[2]), "=r"(r[3]) : "r"(addr) : "memory");
}
__device__ __forceinline__ void ldsm_x4_t(uint32_t* r, uint32_t addr) {
    asm volatile("ldmatrix.sync.aligned.m8n8.x4.trans.shared.b16 {%0,%1,%2,%3}, [%4];" : "=r"(r[0]), "=r"(r[1]), "=r"(r[2]), "=r"(r[3]) : "r"(addr) : "memory");
}
__device__ __forceinline__ void stsm_x4(uint32_t addr, uint32_t r0, uint32_t r1, uint32_t r2, uint32_t r3) {
    asm volatile("stmatrix.sync.aligned.m8n8.x4.shared.b16 [%0], {%1,%2,%3,%4};" ::"r"(addr), "r"(r0), "r"(r1), "r"(r2), "r"(r3) : "memory");
}
__device__ __forceinline__ void stsm_x4_t(uint32_t addr, uint32_t r0, uint32_t r1, uint32_t r2, uint32_t r3) {
    asm volatile("stmatrix.sync.aligned.m8n8.x4.trans.shared.b16 [%0], {%1,%2,%3,%4};" ::"r"(addr), "r"(r0), "r"(r1), "r"(r2), "r"(r3) : "memory");
}
__device__ __forceinline__ uint32_t movm(uint32_t a) { uint32_t r; asm volatile("movmatrix.sync.aligned.m8n8.trans.b16 %0, %1;" : "=r"(r) : "r"(a)); return r; }
__device__ __forceinline__ uint32_t lds32(uint32_t a) { uint32_t v; asm volatile("ld.shared.u32 %0, [%1];" : "=r"(v) : "r"(a)); return v; }
__device__ __forceinline__ void sts32(uint32_t a, uint32_t v) { asm volatile("st.shared.u32 [%0], %1;" ::"r"(a), "r"(v) : "memory"); }
__device__ __forceinline__ void sts16(uint32_t a, uint32_t v) { asm volatile("st.shared.u16 [%0], %1;" ::"r"(a), "h"((unsigned short)v) : "memory"); }
__device__ __forceinline__ void named_bar(int id, int n) { asm volatile("bar.sync %0, %1;" ::"r"(id), "r"(n) : "memory"); }
__device__ __forceinline__ void named_arrive(int id, int n) { asm volatile("bar.arrive %0, %1;" ::"r"(id), "r"(n) : "memory"); }
#define CBAR() asm volatile("bar.sync 0, 640;" ::: "memory")
#define PROXY_FENCE() asm volatile("fence.proxy.async.shared::cta;" ::: "memory")

#define D4(d, o) "+f"(d[o]), "+f"(d[o + 1]), "+f"(d[o + 2]), "+f"(d[o + 3])
__device__ __forceinline__ void wg32(float* d, uint32_t a0, uint32_t a1, uint32_t a2, uint32_t a3, uint64_t desc) {
    asm volatile("wgmma.mma_async.sync.aligned.m64n32k16.f32.bf16.bf16 {%0,%1,%2,%3,%4,%5,%6,%7,%8,%9,%10,%11,%12,%13,%14,%15}, {%16,%17,%18,%19}, %20, 1, 1, 1, 0;"
                 : D4(d, 0), D4(d, 4), D4(d, 8), D4(d, 12) : "r"(a0), "r"(a1), "r"(a2), "r"(a3), "l"(desc));
}
__device__ __forceinline__ void wg48(float* d, uint32_t a0, uint32_t a1, uint32_t a2, uint32_t a3, uint64_t desc) {
    asm volatile("wgmma.mma_async.sync.aligned.m64n48k16.f32.bf16.bf16 {%0,%1,%2,%3,%4,%5,%6,%7,%8,%9,%10,%11,%12,%13,%14,%15,%16,%17,%18,%19,%20,%21,%22,%23}, {%24,%25,%26,%27}, %28, 1, 1, 1, 0;"
                 : D4(d, 0), D4(d, 4), D4(d, 8), D4(d, 12), D4(d, 16), D4(d, 20) : "r"(a0), "r"(a1), "r"(a2), "r"(a3), "l"(desc));
}
#define O4(d, o) "=f"(d[o]), "=f"(d[o + 1]), "=f"(d[o + 2]), "=f"(d[o + 3])
__device__ __forceinline__ void wg32z(float* d, uint32_t a0, uint32_t a1, uint32_t a2, uint32_t a3, uint64_t desc) {
    asm volatile("wgmma.mma_async.sync.aligned.m64n32k16.f32.bf16.bf16 {%0,%1,%2,%3,%4,%5,%6,%7,%8,%9,%10,%11,%12,%13,%14,%15}, {%16,%17,%18,%19}, %20, 0, 1, 1, 0;"
                 : O4(d, 0), O4(d, 4), O4(d, 8), O4(d, 12) : "r"(a0), "r"(a1), "r"(a2), "r"(a3), "l"(desc));
}
__device__ __forceinline__ void wg48z(float* d, uint32_t a0, uint32_t a1, uint32_t a2, uint32_t a3, uint64_t desc) {
    asm volatile("wgmma.mma_async.sync.aligned.m64n48k16.f32.bf16.bf16 {%0,%1,%2,%3,%4,%5,%6,%7,%8,%9,%10,%11,%12,%13,%14,%15,%16,%17,%18,%19,%20,%21,%22,%23}, {%24,%25,%26,%27}, %28, 0, 1, 1, 0;"
                 : O4(d, 0), O4(d, 4), O4(d, 8), O4(d, 12), O4(d, 16), O4(d, 20) : "r"(a0), "r"(a1), "r"(a2), "r"(a3), "l"(desc));
}
#define WG_FENCE() asm volatile("wgmma.fence.sync.aligned;" ::: "memory")
#define WG_COMMIT() asm volatile("wgmma.commit_group.sync.aligned;" ::: "memory")
#define WG_WAIT(n) asm volatile("wgmma.wait_group.sync.aligned " #n ";" ::: "memory")
#define TQ(p, k) p[2 * (k) + 1], p[2 * (k) + 2], p[2 * (k)], p[2 * (k) + 1]

__device__ __forceinline__ uint4 ld_nc4(const void* p) { uint4 v; asm volatile("ld.global.nc.v4.u32 {%0,%1,%2,%3}, [%4];" : "=r"(v.x), "=r"(v.y), "=r"(v.z), "=r"(v.w) : "l"(p)); return v; }
__device__ __forceinline__ unsigned short ld_nc16(const void* p) { unsigned short v; asm volatile("ld.global.nc.u16 %0, [%1];" : "=h"(v) : "l"(p)); return v; }
__device__ __forceinline__ uint32_t ld_nc(const void* p) { uint32_t v; asm volatile("ld.global.nc.u32 %0, [%1];" : "=r"(v) : "l"(p)); return v; }
__device__ __forceinline__ uint32_t ld_rlx(const unsigned int* p) { uint32_t v; asm volatile("ld.relaxed.gpu.global.u32 %0, [%1];" : "=r"(v) : "l"(p) : "memory"); return v; }
__device__ __forceinline__ uint2 ld_rlx2(const void* p) { uint2 v; asm volatile("ld.relaxed.gpu.global.v2.u32 {%0,%1}, [%2];" : "=r"(v.x), "=r"(v.y) : "l"(p) : "memory"); return v; }
__device__ __forceinline__ uint4 ld_rlx4(const void* p) { uint4 v; asm volatile("ld.relaxed.gpu.global.v4.u32 {%0,%1,%2,%3}, [%4];" : "=r"(v.x), "=r"(v.y), "=r"(v.z), "=r"(v.w) : "l"(p) : "memory"); return v; }
__device__ __forceinline__ void st_rlx(unsigned int* p, uint32_t v) { asm volatile("st.relaxed.gpu.global.u32 [%0], %1;" ::"l"(p), "r"(v) : "memory"); }
__device__ __forceinline__ void st_rlx2(void* p, uint32_t a, uint32_t b) { asm volatile("st.relaxed.gpu.global.v2.u32 [%0], {%1,%2};" ::"l"(p), "r"(a), "r"(b) : "memory"); }
__device__ __forceinline__ void st_rlx4(void* p, uint4 v) { asm volatile("st.relaxed.gpu.global.v4.u32 [%0], {%1,%2,%3,%4};" ::"l"(p), "r"(v.x), "r"(v.y), "r"(v.z), "r"(v.w) : "memory"); }
__device__ __forceinline__ void red_inc(unsigned int* p) { asm volatile("red.relaxed.gpu.global.add.u32 [%0], 1;" ::"l"(p) : "memory"); }

__device__ __forceinline__ void mbar_init(uint32_t a, int cnt) { asm volatile("mbarrier.init.shared::cta.b64 [%0], %1;" ::"r"(a), "r"(cnt) : "memory"); }
__device__ __forceinline__ void mbar_expect(uint32_t a, uint32_t bytes) { asm volatile("mbarrier.arrive.expect_tx.shared::cta.b64 _, [%0], %1;" ::"r"(a), "r"(bytes) : "memory"); }
__device__ __forceinline__ void mbar_wait(uint32_t a, uint32_t parity) {
    uint32_t ok = 0;
    int it = 0;
    do {
        asm volatile("{\n.reg .pred p;\nmbarrier.try_wait.parity.shared::cta.b64 p, [%1], %2;\nselp.u32 %0, 1, 0, p;\n}" : "=r"(ok) : "r"(a), "r"(parity) : "memory");
    } while (!ok && ++it < SPIN_MAX);
}
__device__ __forceinline__ void tma2d(uint32_t dst, const CUtensorMap* tm, int c0, int c1, uint32_t mbar) {
    asm volatile("cp.async.bulk.tensor.2d.shared::cluster.global.mbarrier::complete_tx::bytes [%0], [%1, {%3, %4}], [%2];"
                 ::"r"(dst), "l"(tm), "r"(mbar), "r"(c0), "r"(c1) : "memory");
}
__device__ __forceinline__ void bulk_s2g(void* dst, uint32_t src, uint32_t bytes) {
    asm volatile("cp.async.bulk.global.shared::cta.bulk_group [%0], [%1], %2;" ::"l"(dst), "r"(src), "r"(bytes) : "memory");
}
__device__ __forceinline__ uint32_t ld_acq(const unsigned int* p) { uint32_t v; asm volatile("ld.acquire.gpu.global.u32 %0, [%1];" : "=r"(v) : "l"(p) : "memory"); return v; }
__device__ __forceinline__ void bulk_pf(const void* src, uint32_t bytes) { asm volatile("cp.async.bulk.prefetch.L2.global [%0], %1;" ::"l"(src), "r"(bytes) : "memory"); }

__device__ __forceinline__ uint32_t wait_epoch(Misc& M) {
    uint32_t e = 0;
#pragma unroll 1
    for (int it = 0; it < (SPIN_MAX << 4) && e == 0; it++) e = *(volatile unsigned int*)&M.epoch;
    return e;
}
__device__ __forceinline__ void wait_reset(const unsigned int* ctr, uint32_t epoch) {
#pragma unroll 1
    for (int it = 0; it < SPIN_MAX; it++)
        if ((int)(ld_acq(ctr) - G_ * epoch) >= 0) break;
}
struct cplx { float x, y; };
__device__ __forceinline__ cplx cmul(cplx a, cplx b) { cplx r; r.x = a.x * b.x - a.y * b.y; r.y = a.x * b.y + a.y * b.x; return r; }
__device__ __forceinline__ cplx csq(cplx a) { cplx r; r.x = a.x * a.x - a.y * a.y; r.y = 2.0f * a.x * a.y; return r; }
__device__ __forceinline__ uint32_t hcm(uint32_t x, uint32_t y, uint32_t yp) {
    const __half2 X = *(const __half2*)&x, Y = *(const __half2*)&y, YP = *(const __half2*)&yp;
    const __half2 r = __hfma2(__high2half2(X), YP, __hmul2(__low2half2(X), Y));
    return *(const uint32_t*)&r;
}
__device__ __forceinline__ void ln_stats(float s1, float s2, float& meanb, float& rinv) {
    const float mean = s1 * (1.0f / D_);
    const float den = bfr(fsqrt(bfr(bfr(fmaxf(fmaf(-mean, mean, s2 * (1.0f / D_)), 0.f)) + 1e-5f)));
    meanb = bfr(mean);
    rinv = frcp(den);
}

__device__ __forceinline__ int fresh_tid() { int v; asm volatile("mov.u32 %0, %tid.x;" : "=r"(v)); return v; }
__device__ __forceinline__ void conv_channel(unsigned char* sm, Scratch* S, uint32_t gidx, uint32_t epoch, const void* pf_src,
                                             const CUtensorMap* tmu, int f0) {
    Misc& M = *(Misc*)(sm + OFF_MISC);
    const uint32_t sb = (uint32_t)__cvta_generic_to_shared(sm);
    const int tid = fresh_tid(), lane = tid & 31, g = lane >> 2, t = lane & 3, lr = lane & 7, lm = lane >> 3;
    const int warp_ = __shfl_sync(0xffffffffu, tid >> 5, 0), wgi = warp_ >> 2, w = warp_ & 3;
    const uint32_t cb = sb + OFF_CH + wgi * CHS, tag16 = (epoch % 65535u) + 1u;
    float D[16];
    uint32_t gaw, rcnt = 0;
    {
        {
            const uint32_t a8 = cb + lr * ULBO + (lm + 9) * 16 + w * 64, b8 = cb + XO_U8 + lm * 128 + lr * 16 + w * 512;
            const uint32_t a16 = cb + (((2 * lr) & 7) + (lm & 1)) * ULBO + (9 + (lr >> 2) + (lm & 2)) * 16 + w * 64;
            const uint32_t b16 = cb + XO_U16 + (lm & 1) * 512 + lr * 16 + (lm >> 1) * 128 + (w >> 1) * 1024 + (w & 1) * 256;
            uint32_t r[3][4];
            ldsm_x4_t(r[0], a8);
            ldsm_x4_t(r[1], a16);
            if (w < 2) ldsm_x4_t(r[2], a8 + 256);
            stsm_x4(b8, r[0][0], r[0][1], r[0][2], r[0][3]);
            stsm_x4(b16, r[1][0], r[1][1], r[1][2], r[1][3]);
            if (w < 2) stsm_x4(b8 + 2048, r[2][0], r[2][1], r[2][2], r[2][3]);
        }
        PROXY_FENCE();
        named_bar(1 + wgi, 128);
        {
            float Z8[24], Z16[16];
            const uint32_t pf = cb + XO_TF + (w >> 1) * 512 + (8 + 16 * (w & 1) + g - 2 * t) * 4;
            uint32_t p[13], q[9], z16[8];
#pragma unroll
            for (int s = 0; s < 9; s++) q[s] = lds32(pf + 1024 + s * 32);
            const uint32_t d8 = ((((cb + XO_U8) & 0x3FFFF) >> 4) | ((128 >> 4) << 16));
#define DZ(o) (((uint64_t)(512 >> 4) << 32) | (uint64_t)(d8 + (o)))
            WG_FENCE();
#pragma unroll
            for (int e = 0; e < 4; e++) {
                if (e == 0) wg32z(Z16, TQ(q, e), DZ(256 + 16));
                else wg32(Z16, TQ(q, e), DZ(256 - (e >> 1) * 64 + (1 - (e & 1)) * 16));
            }
            WG_COMMIT();
#pragma unroll
            for (int s = 0; s < 13; s++) p[s] = lds32(pf + s * 32);
            WG_WAIT(0);
#pragma unroll
            for (int i = 0; i < 8; i++) z16[i] = pack2(Z16[2 * i], Z16[2 * i + 1]);
            WG_FENCE();
#pragma unroll
            for (int e = 0; e < 6; e++) {
                if (e == 0) wg48z(Z8, TQ(p, e), DZ(16));
                else wg48(Z8, TQ(p, e), DZ(-(e >> 1) * 32 + (1 - (e & 1)) * 16));
            }
            WG_COMMIT();
            WG_WAIT(0);
            named_bar(1 + wgi, 128);
            const uint32_t za = cb + ((w >> 1) ? XO_ZB : XO_ZA) + lr * 400 + (1 + 2 * (w & 1) + (lm & 1) + 4 * (lm >> 1)) * 16;
#pragma unroll
            for (int i = 0; i < 3; i++)
                stsm_x4(za + i * 128, pack2(Z8[8 * i], Z8[8 * i + 1]), pack2(Z8[8 * i + 2], Z8[8 * i + 3]), pack2(Z8[8 * i + 4], Z8[8 * i + 5]), pack2(Z8[8 * i + 6], Z8[8 * i + 7]));
            const int Cz = 2 * (16 * (w & 1) + 8 * (lm & 1) + lr) + (lm >> 1);
            const uint32_t zc = cb + ((w >> 1) ? XO_ZD : XO_ZC) + (Cz & 7) * 272 + (1 + (Cz >> 3)) * 16;
#pragma unroll
            for (int ob = 0; ob < 2; ob++) stsm_x4(zc + ob * 128, z16[4 * ob], z16[4 * ob + 1], z16[4 * ob + 2], z16[4 * ob + 3]);
            if (lane < 8) *(uint4*)(sm + (cb - sb) + ((w < 2) ? (XO_ZA + w * 3200 + lane * 400) : (XO_ZC + (w - 2) * 2176 + lane * 272))) = make_uint4(0, 0, 0, 0);
        }
        gaw = ld_rlx(&S->modw[gidx]);
        if (tmu && wgi >= 2 && (tid & 127) == 96) {
            const uint32_t mbu = sb + OFF_MISC + (uint32_t)offsetof(Misc, mbar) + 24;
            if (wgi == 2) mbar_expect(mbu, 36864);
            tma2d(sb + OFF_WU + (wgi - 2) * 12288, tmu, f0, 192 * (wgi - 2), mbu);
        }
        __syncwarp();
        if ((tid & 127) == 64) rcnt = ld_rlx(S->cnt);
        {
#pragma unroll
            for (int i = 0; i < 16; i++) D[i] = 0.f;
            uint32_t pa = cb + XO_TD + (8 + 16 * w + g - 2 * t) * 4;
            uint32_t dlo = (((cb + 9 * 16) & 0x3FFFF) >> 4) | ((ULBO >> 4) << 16);
#define DS(o) (((uint64_t)(128 >> 4) << 32) | (uint64_t)(dlo + (o)))
#define KST (2 * (ULBO / 16))
            uint32_t pA[9], pB[9];
#pragma unroll
            for (int s = 0; s < 9; s++) pA[s] = lds32(pa + s * 32);
#pragma unroll 1
            for (int j = 0; j < 4; j++) {
                WG_FENCE();
#pragma unroll
                for (int q = 0; q < 4; q++) wg32(D, TQ(pA, q), DS((3 - q) * KST));
                WG_COMMIT();
                WG_WAIT(1);
#pragma unroll
                for (int s = 0; s < 9; s++) pB[s] = lds32(pa + 256 + s * 32);
                WG_FENCE();
#pragma unroll
                for (int q = 0; q < 4; q++) wg32(D, TQ(pB, q), DS((3 - q) * KST - 1));
                WG_COMMIT();
                WG_WAIT(1);
#pragma unroll
                for (int s = 0; s < 9; s++) pA[s] = lds32(pa + 512 + s * 32);
                dlo -= 2; pa += 512;
            }
            pB[1] = lds32(pa + 256 + 32); pB[2] = lds32(pa + 256 + 64);
            WG_FENCE();
#pragma unroll
            for (int q = 0; q < 4; q++) wg32(D, TQ(pA, q), DS((3 - q) * KST));
            wg32(D, pB[1], pB[2], pA[8], pB[1], DS(3 * KST - 1));
            WG_COMMIT();
        }
        if (tid == 128) bulk_pf(pf_src, 16 * D_ * 2);
        if ((tid & 127) == 64) {
#pragma unroll 1
            for (int it = 0; it < SPIN_MAX && (int)(rcnt - G_ * epoch) < 0; it++) rcnt = ld_rlx(S->cnt);
        }
    }
    {
        named_bar(1 + wgi, 128);
        {
            const uint4* pq = M.box + (6 + g - 2 * t);
#define QM(q) (q).x, (q).y, (q).z, (q).w
            uint32_t bA[2][6], bB[2][6], bC[3][4], bD[2][4], bU[2][4];
            const uint32_t k2 = lds32(cb + XO_K1024);
            uint32_t ofs[3];
#pragma unroll
            for (int d = 0; d < 3; d++) ofs[d] = cb + ((w - d) < 0 ? 0 : 16) + (lr + 8 * (lm >> 1)) * 16;
#define COL(d) (2 * ((w - (d)) & 3) + (lm & 1))
            WG_WAIT(0);
            uint4 m[4];
#pragma unroll
            for (int d = 0; d < 2; d++) {
                const uint32_t a = XO_ZA + COL(d) * 400 + ofs[d];
                ldsm_x4(bA[d], a); ldsm_x4(bB[d], a + 3200);
                uint32_t r[4];
                ldsm_x4(r, a + 256 + (lm >> 1) * (3200 - 128));
                bA[d][4] = r[0]; bA[d][5] = r[1]; bB[d][4] = r[2]; bB[d][5] = r[3];
            }
#pragma unroll
            for (int i = 0; i < 4; i++) m[i] = pq[14 * i];
#pragma unroll
            for (int d = 0; d < 2; d++)
#pragma unroll
                for (int c = 0; c < 3; c++) mma_bf16(D + 4 + 4 * c, QM(m[d]), bA[d][2 * c], bA[d][2 * c + 1]);
#pragma unroll
            for (int d = 0; d < 3; d++) ldsm_x4(bC[d], XO_ZC + COL(d) * 272 + ofs[d]);
#pragma unroll
            for (int d = 0; d < 2; d++)
#pragma unroll
                for (int c = 0; c < 3; c++) mma_bf16(D + 4 + 4 * c, QM(m[2 + d]), bB[d][2 * c], bB[d][2 * c + 1]);
#pragma unroll
            for (int i = 0; i < 3; i++) m[i] = pq[14 * (4 + i)];
#pragma unroll
            for (int d = 0; d < 2; d++) { ldsm_x4(bD[d], XO_ZD + COL(d) * 272 + ofs[d]); ldsm_x4(bU[d], COL(d) * ULBO + 128 + ofs[d]); }
#pragma unroll
            for (int d = 0; d < 3; d++)
#pragma unroll
                for (int c = 0; c < 2; c++) mma_bf16(D + 8 + 4 * c, QM(m[d]), bC[d][2 * c], bC[d][2 * c + 1]);
#pragma unroll
            for (int i = 0; i < 4; i++) m[i] = pq[14 * (7 + i)];
#pragma unroll
            for (int d = 0; d < 2; d++)
#pragma unroll
                for (int c = 0; c < 2; c++) mma_bf16(D + 8 + 4 * c, QM(m[d]), bD[d][2 * c], bD[d][2 * c + 1]);
#pragma unroll
            for (int d = 0; d < 2; d++) {
                m[2 + d].x &= k2; m[2 + d].y &= k2; m[2 + d].z &= k2; m[2 + d].w &= k2;
#pragma unroll
                for (int c = 0; c < 2; c++) mma_bf16(D + 8 + 4 * c, QM(m[2 + d]), bU[d][2 * c], bU[d][2 * c + 1]);
            }
        }
        {
#pragma unroll 1
            for (int it = 0; it < SPIN_MAX && (gaw >> 16) != tag16; it++) gaw = ld_rlx(&S->modw[gidx]);
            const uint32_t ga2 = __byte_perm(gaw, 0, 0x1010), dk2 = M.pk[3][wgi];
            const uint32_t ua = cb + (2 * w + (lm & 1)) * ULBO + (9 + lr + 8 * (lm >> 1)) * 16;
            const uint32_t ya = cb + XO_TD + w * 1024;
            const uint32_t sa = ya + (lr + 8 * (lm >> 1)) * 32 + (((lm & 1) ^ ((lane >> 2) & 1)) << 4);
#pragma unroll
            for (int cc = 0; cc < 2; cc++) {
                uint32_t u[4], v[4];
                ldsm_x4_t(u, ua + cc * 256);
#pragma unroll
                for (int m = 0; m < 4; m++) {
                    const int c = 2 * cc + (m >> 1), h = m & 1;
                    v[m] = ~mul2(ga2, add2(pack2(D[4 * c + 2 * h], D[4 * c + 2 * h + 1]), mul2(u[m], dk2)));
                }
                stsm_x4_t(sa + cc * 512, v[0], v[1], v[2], v[3]);
            }
            __syncwarp();
            const int sw = (lane >> 3) & 1;
            const uint32_t vo = (uint32_t)(((4 * (lane >> 1) + w) * D_ + gidx - 2 * D_) * 32 + (lane & 1) * 16);
            const unsigned char* yp = sm + (ya - sb) + (lane >> 1) * 32 + (lane & 1) * 8;
#pragma unroll
            for (int i = 0; i < 2; i++) {
                const uint2 A = *(const uint2*)(yp + i * 512 + (sw << 4)), B = *(const uint2*)(yp + i * 512 + ((sw ^ 1) << 4));
                st_rlx4((char*)S->v + vo + i * (64 * D_ * 32), make_uint4(A.x, B.x, A.y, B.y));
            }
        }
    }
}

__global__ void __launch_bounds__(NTHR, 1)
mega_kernel(const bf16* __restrict__ x, const bf16* __restrict__ logAr, const bf16* __restrict__ Aim,
            const bf16* __restrict__ Cr, const bf16* __restrict__ Ci, const bf16* __restrict__ logdt, const bf16* __restrict__ c_in,
            Scratch* __restrict__ S, const bf16* __restrict__ Dskip, const bf16* __restrict__ w_r, const bf16* __restrict__ w_down,
            bf16* __restrict__ out,
            const __grid_constant__ CUtensorMap tm_wm, const __grid_constant__ CUtensorMap tm_wg, const __grid_constant__ CUtensorMap tm_wu,
            const __grid_constant__ CUtensorMap tm_wd, const __grid_constant__ CUtensorMap tm_wd32,
            const __grid_constant__ CUtensorMap tm_wg32, const __grid_constant__ CUtensorMap tm_wu32) {
    extern __shared__ __align__(1024) unsigned char sm[];
    Misc& M = *(Misc*)(sm + OFF_MISC);
    const uint32_t sb = (uint32_t)__cvta_generic_to_shared(sm);
    const int tid = threadIdx.x, warp = __shfl_sync(0xffffffffu, tid >> 5, 0), lane = tid & 31;
    const int g = lane >> 2, t = lane & 3, lr = lane & 7, lm = lane >> 3;
    const int wgi = warp >> 2, w = warp & 3;
    const int b = blockIdx.x;
    const int nch = 5 - (b & 1), cs = 9 * (b >> 1) + 5 * (b & 1);
    const int f0 = 72 * (b >> 1) + 32 * (b & 1), nf = 32 + 8 * (b & 1);
    const bool has_ch = wgi < nch;
    const uint32_t mb0 = sb + OFF_MISC + offsetof(Misc, mbar), mb_wm = mb0, mb_wg = mb0 + 16, mb_wu = mb0 + 24, mb_wd = mb0 + 32;
    const uint32_t cb = sb + OFF_CH + wgi * CHS;

    if (wgi == 3) {
        M.sent[tid - 384] = make_uint4(SENT, SENT, SENT, SENT);
        M.sent[tid - 256] = make_uint4(SENT, SENT, SENT, SENT);
        if (tid == 384) {
            M.epoch = 0u; M.flag = 0u; M.e1cnt = 0u;
#pragma unroll
            for (int i = 0; i < 5; i++) mbar_init(mb0 + 8 * i, 1);
        }
        PROXY_FENCE();
        __syncwarp();
        if (warp == 12) { named_arrive(8, 160); if (b & 1) named_arrive(14, 64); }
        if (warp != 15) named_arrive(9, 128);
    }
    unsigned short r_ldt = 0, r_lar = 0, r_aim = 0, r_cr = 0, r_ci = 0;
    if (has_ch) {
        const int d = cs + wgi, n = d * N_ + (tid & 127);
        r_ldt = ld_nc16((const unsigned short*)logdt + d);
        r_lar = ld_nc16((const unsigned short*)logAr + n);
        r_aim = ld_nc16((const unsigned short*)Aim + n);
        r_cr = ld_nc16((const unsigned short*)Cr + n);
        r_ci = ld_nc16((const unsigned short*)Ci + n);
    } else {
        const unsigned short* cp = (const unsigned short*)c_in + (tid - 512);
        r_ldt = ld_nc16(cp); r_lar = ld_nc16(cp + 128); r_aim = ld_nc16(cp + 256); r_cr = ld_nc16(cp + 384);
        if (tid < 576) r_ci = ld_nc16(cp + 512);
    }
    uint4 xr[9];
    if (wgi == 4) {
        const uint4* p = (const uint4*)(x + (size_t)16 * b * D_) + (tid - 512);
#pragma unroll
        for (int i = 0; i < 9; i++) xr[i] = ld_nc4(p + 128 * i);
    }
    uint32_t wrv = 0;
    if (tid >= 128 && tid < 416) wrv = ld_nc((const uint32_t*)w_r + (tid - 128));
    if (warp == 2 && lane < nch) M.pk[3][lane] = (uint32_t)ld_nc16((const unsigned short*)Dskip + cs + lane) * 0x10001u;
    if (tid == 384) {
        const unsigned int tk = atomicAdd(S->ticket, 1u);
        *(volatile unsigned int*)&M.epoch = (tk >> 7) + 1u;
    }
    if (has_ch) {
        for (int i = tid & 127; i < 296; i += 128) *(uint4*)(sm + OFF_CH + wgi * CHS + XO_TD + i * 16) = make_uint4(0, 0, 0, 0);
    }
    if (tid < 154) {
        const int idx = (tid * 4682) >> 16, dl = tid - 14 * idx - 6;
        const int a = (0x44332221100ull >> (4 * idx)) & 7, d = (0x10102101010ull >> (4 * idx)) & 3;
        const int lo = (0x35c36 >> (4 * a)) & 15, wd = (0x16824 >> (4 * a)) & 15;
        const uint32_t one = (a == 4) ? 0xFFFFu : 0x3F80u;
        auto mk = [&](int l) { return (((unsigned)(l - lo) <= (unsigned)wd) ? one : 0u) | (((unsigned)(l - 1 - lo) <= (unsigned)wd) ? (one << 16) : 0u); };
        const int l0 = 16 * d + dl;
        M.box[tid] = make_uint4(mk(l0), mk(l0 + 8), mk(l0 - 8), mk(l0));
    }
    uint32_t xo[6];
#pragma unroll
    for (int i = 0; i < 6; i++) {
        const int ch = 16 * (warp + 16 * (i >> 1)) + 8 * (i & 1) + g;
        const int pr = (ch * 7282) >> 16, rm = ch - 9 * pr, hi = rm >= 5;
        xo[i] = (uint32_t)((((2 * pr + hi) * G_ + b) * 5 + rm - 5 * hi) * 32 + t * 8);
    }
    auto e1_store = [&]() {
        named_bar(11, 640);
        uint32_t mm[2], rhh[2], rll[2];
#pragma unroll
        for (int h = 0; h < 2; h++) {
            mm[h] = ((const uint32_t*)M.st1[0])[t + 4 * h]; rhh[h] = ((const uint32_t*)M.st1[1])[t + 4 * h]; rll[h] = ((const uint32_t*)M.st1[2])[t + 4 * h];
        }
        const uint32_t ta = sb + OFF_TILE + (lr + 8 * (lm & 1)) * (ROWP * 2) + (lm >> 1) * 16 + warp * 32;
#pragma unroll
        for (int i = 0; i < 3; i++) {
            if (i < 2 || warp < 4) {
                uint32_t r[4];
                ldsm_x4_t(r, ta + i * 512);
#pragma unroll
                for (int h = 0; h < 2; h++)
                    st_rlx2((char*)S->xn + xo[2 * i + h], ~norm2(r[2 * h], mm[0], rhh[0], rll[0]), ~norm2(r[2 * h + 1], mm[1], rhh[1], rll[1]));
            }
        }
        __syncwarp();
        if (lane == 0 && atomicAdd(&M.e1cnt, 1u) == 15u) red_inc(S->hint);
    };
    const float p_ldt = lo2f(r_ldt), p_lar = lo2f(r_lar), p_aim = lo2f(r_aim), p_cr = lo2f(r_cr), p_ci = lo2f(r_ci);
    cplx z1 = {0.f, 0.f}, z16 = z1, z256 = z1, C = z1;
    const uint32_t scr = cb + w * KSCR, ws = scr + lane * 4;
    float acc[5][4];
    uint32_t afr[4][4], cz[4];
    cplx z2 = {0.f, 0.f};
    const uint32_t ba = scr + lr * 144 + lm * 16;
    auto tile = [&](float* c, int rg) {
        __syncwarp();
        c[0] = c[1] = c[2] = c[3] = 0.f;
        uint32_t bb[2][4];
        ldsm_x4(bb[0], ba + rg * 1152);
        ldsm_x4(bb[1], ba + rg * 1152 + 64);
        mma_f16(c, afr[0], bb[0][0], bb[0][1]);
        mma_f16(c, afr[1], bb[0][2], bb[0][3]);
        mma_f16(c, afr[2], bb[1][0], bb[1][1]);
        mma_f16(c, afr[3], bb[1][2], bb[1][3]);
    };
#define CJ(z) packh((z).x, -(z).y)
#define CJP(z) packh((z).y, (z).x)
    uint32_t ex = 0;
    if (has_ch) {
        const float dt = bfr(expf(p_ldt));
        const float al = -bfr(expf(p_lar)) * dt * 1.4426950408889634f;
        const float th = p_aim * dt;
        const float th_ = th * 0.15915494309189535f;
        const float tl_ = fmaf(th, 0.15915494309189535f, -th_) + th * 6.4206382e-9f;
        auto anchor = [&](float s) {
            float f = th_ * s;
            f -= rintf(f);
            f = fmaf(tl_, s, f) * 6.283185307179586f;
            const float e = fex2(al * s);
            return cplx{e * __cosf(f), e * __sinf(f)};
        };
        const float cx = p_cr * dt * 2.0f, cy = p_ci * dt * 2.0f;
        ex = __reduce_max_sync(0xffffffffu, __float_as_uint(fmaxf(fabsf(cx), fabsf(cy)))) >> 23;
        const float scl = __uint_as_float((254u - ex) << 23);
        C = cplx{cx * scl, cy * scl};
        z1 = anchor(1.f); z16 = anchor(16.f); z256 = anchor(256.f);
            {
                const cplx z32 = csq(z16), z48 = cmul(z32, z16), z64 = csq(z32), z128 = csq(z64), z192 = cmul(z128, z64);
                const uint32_t y[3] = {packh(z16.x, z16.y), packh(z32.x, z32.y), packh(z48.x, z48.y)};
                const uint32_t yp[3] = {packh(-z16.y, z16.x), packh(-z32.y, z32.x), packh(-z48.y, z48.x)};
                const uint32_t xx[3] = {packh(z64.x, z64.y), packh(z128.x, z128.y), packh(z192.x, z192.y)};
                sts32(ws, 0x00003C00u);
#pragma unroll
                for (int j = 0; j < 3; j++) sts32(ws + (1 + j) * 144, y[j]);
#pragma unroll
                for (int i = 0; i < 3; i++) {
                    sts32(ws + (4 + 4 * i) * 144, xx[i]);
#pragma unroll
                    for (int j = 0; j < 3; j++) sts32(ws + (5 + 4 * i + j) * 144, hcm(xx[i], y[j], yp[j]));
                }
            }
    }
    if (wgi == 4) {
        if (!has_ch) {
            const int i = tid - 512;
            ((unsigned short*)M.sc)[i] = (unsigned short)f2bits(silu(lo2f(r_ldt)));
            ((unsigned short*)M.sc)[i + 128] = (unsigned short)f2bits(silu(lo2f(r_lar)));
            ((unsigned short*)M.sc)[i + 256] = (unsigned short)f2bits(silu(lo2f(r_aim)));
            ((unsigned short*)M.sc)[i + 384] = (unsigned short)f2bits(silu(lo2f(r_cr)));
            if (i < 64) ((unsigned short*)M.sc)[i + 512] = (unsigned short)f2bits(silu(lo2f(r_ci)));
            if (warp == 16) {
                named_bar(14, 64);
                if (lane == 0) {
                    mbar_expect(mb_wm, 36864);
#pragma unroll
                    for (int k = 0; k < 3; k++) tma2d(sb + OFF_WU + k * 12288, &tm_wm, 32 * (b >> 1), 192 * k, mb_wm);
                }
                __syncwarp();
            }
        }
#pragma unroll
        for (int i = 0; i < 9; i++) {
            const int c = tid - 512 + 128 * i, rr = (c * 911) >> 16;
            *(uint4*)(sm + OFF_TILE + rr * (ROWP * 2 - 1152) + c * 16) = xr[i];
        }
        named_bar(8, 160);
        {
            float c1[4] = {0.f, 0.f, 0.f, 0.f}, cl[4] = {0.f, 0.f, 0.f, 0.f}, chh[4] = {0.f, 0.f, 0.f, 0.f};
            const uint32_t a0 = sb + OFF_TILE + (lane & 15) * (ROWP * 2) + (lane >> 4) * 16 + w * 288;
            uint32_t a[9][4];
#pragma unroll
            for (int ks = 0; ks < 9; ks++) ldsm_x4(a[ks], a0 + ks * 32);
#pragma unroll
            for (int ks = 0; ks < 9; ks++) {
                mma_bf16(c1, a[ks][0], a[ks][1], a[ks][2], a[ks][3], 0x3F803F80u, 0x3F803F80u);
                mma_bf16(cl, a[ks][0], a[ks][1], a[ks][2], a[ks][3], a[ks][0], a[ks][2]);
                mma_bf16(chh, a[ks][0], a[ks][1], a[ks][2], a[ks][3], a[ks][1], a[ks][3]);
            }
            if (t == 0) { M.p1[g][w] = c1[0]; M.p1[g + 8][w] = c1[2]; }
            if (t == (g >> 1)) { M.p2[g][w] = (g & 1) ? cl[1] : cl[0]; M.p2[g + 8][w] = (g & 1) ? chh[3] : chh[2]; }
        }
        named_bar(5, 128);
        if (warp == 16) {
            const float4 q1 = *(const float4*)M.p1[lane & 15], q2 = *(const float4*)M.p2[lane & 15];
            float meanb, rinv;
            ln_stats((q1.x + q1.y) + (q1.z + q1.w), (q2.x + q2.y) + (q2.z + q2.w), meanb, rinv);
            const float rh = bfr(rinv);
            if (lane < 16) { M.st1[0][lane] = (unsigned short)f2bits(meanb); M.st1[1][lane] = (unsigned short)f2bits(rh); M.st1[2][lane] = (unsigned short)f2bits(rinv - rh); }
        }
        __syncwarp();
        named_arrive(11, 640);
    }
    auto publish_reset = [&]() {
        if (tid == 480) {
            asm volatile("cp.async.bulk.wait_group 0;" ::: "memory");
            asm volatile("fence.proxy.async;" ::: "memory");
            red_inc(S->cnt);
        }
    };
    uint32_t epoch = 0, tag16 = 0, pre = 0;
    auto mod_tile = [&](int rd) {
        const uint32_t* s2 = (const uint32_t*)M.sc + 144 * (w >> 1) + t;
        uint32_t bb[18][2];
#pragma unroll
        for (int ks = 0; ks < 18; ks++) { bb[ks][0] = (g == 0) ? s2[8 * ks] : 0u; bb[ks][1] = (g == 0) ? s2[8 * ks + 4] : 0u; }
        float acc[2][4] = {{0.f, 0.f, 0.f, 0.f}, {0.f, 0.f, 0.f, 0.f}};
        const int row = lr + 8 * (lm >> 1);
        const uint32_t wa = sb + OFF_WU + (288 * (w >> 1) + row) * 64 + ((((2 * (w & 1) + (lm & 1)) ^ (row >> 1)) & 3) << 4);
        mbar_wait(mb_wm + 8 * rd, 0);
        if (rd == 0)
#pragma unroll
        for (int kb = 0; kb < 2; kb++) {
            uint32_t a[9][4];
#pragma unroll
            for (int ks = 0; ks < 9; ks++) ldsm_x4_t(a[ks], wa + (9 * kb + ks) * 1024);
#pragma unroll
            for (int ks = 0; ks < 9; ks++) mma_bf16(acc[ks & 1], a[ks][0], a[ks][1], a[ks][2], a[ks][3], bb[9 * kb + ks][0], bb[9 * kb + ks][1]);
        }
        const float v0 = acc[0][0] + acc[1][0], v1 = acc[0][2] + acc[1][2];
        float* mx = M.modx + 16 * (w & 1) + g;
        if (w >= 2 && t == 0) { mx[0] = v0; mx[8] = v1; }
        named_bar(5, 128);
        if (w < 2 && t == 0) {
            unsigned int* mp = &S->modw[32 * ((b >> 1) + 64 * rd) + 16 * w + g];
            st_rlx(mp, f2bits(v0 + mx[0]) | (tag16 << 16));
            st_rlx(mp + 8, f2bits(v1 + mx[8]) | (tag16 << 16));
        }
        if (rd == 0 && w < 2 && b < 108) {
            named_bar(7, 64);
            if (tid == 512) red_inc(S->hint);
        }
    };
    if (has_ch) {
        {
            z2 = csq(z1);
            const cplx z3 = cmul(z2, z1), z4 = csq(z2), z8 = csq(z4);
            const cplx c4 = cmul(C, z4), c8 = cmul(C, z8), c12 = cmul(c8, z4);
            cz[0] = packh(C.x, -C.y); cz[1] = packh(c4.x, -c4.y); cz[2] = packh(c8.x, -c8.y); cz[3] = packh(c12.x, -c12.y);
            __syncwarp();
#pragma unroll
            for (int s = 0; s < 4; s++) ldsm_x4(afr[s], scr + (lr + 8 * (lm & 1)) * 144 + (2 * s + (lm >> 1)) * 16);
            {
                const uint32_t y[3] = {CJ(z1), CJ(z2), CJ(z3)}, yp[3] = {CJP(z1), CJP(z2), CJP(z3)};
#pragma unroll
                for (int tt = 0; tt < 2; tt++) {
                    const int rg = tt ? 0 : 2;
#pragma unroll
                    for (int i = 0; i < 2; i++) {
                        sts32(ws + rg * 1152 + (4 * i) * 144, cz[2 * tt + i]);
#pragma unroll
                        for (int j = 0; j < 3; j++) sts32(ws + rg * 1152 + (4 * i + 1 + j) * 144, hcm(cz[2 * tt + i], y[j], yp[j]));
                    }
                    tile(acc[tt], rg);
                }
            }
            if (tid >= 128 && tid < 416) M.wr[tid - 128] = wrv;
            if (wgi < 4) e1_store();
    if (warp == 15) {
        named_bar(9, 128);
        if (lane == 0) {
#pragma unroll 1
            for (int i = 0; i < 5; i++) {
                bulk_s2g((char*)&S->v[(size_t)b * 1152] + i * 4096, sb + OFF_MISC, i < 4 ? 4096 : 2048);
                if (i < 3) bulk_s2g((char*)&S->part[(size_t)b * 1152] + i * 4096, sb + OFF_MISC, i < 2 ? 4096 : 1024);
            }
            bulk_s2g(&S->rec[8 * b], sb + OFF_MISC, 32);
            asm volatile("cp.async.bulk.commit_group;" ::: "memory");
        }
        __syncwarp();
    }
            const cplx z258 = cmul(z256, z2), z512 = csq(z256), z768 = cmul(z512, z256);
            {
                const uint32_t a0 = CJ(z256), a0p = CJP(z256), a1 = CJ(z258), a1p = CJP(z258);
#pragma unroll
                for (int i = 0; i < 4; i++) { sts32(ws + 1152 + (2 * i) * 144, hcm(cz[i], a0, a0p)); sts32(ws + 1152 + (2 * i + 1) * 144, hcm(cz[i], a1, a1p)); }
                tile(acc[2], 1);
            }
            {
                const uint32_t a0 = CJ(z512), a0p = CJP(z512), a1 = CJ(z768), a1p = CJP(z768);
#pragma unroll
                for (int i = 0; i < 4; i++) { sts32(ws + 2304 + i * 144, hcm(cz[i], a0, a0p)); sts32(ws + 2304 + (4 + i) * 144, hcm(cz[i], a1, a1p)); }
                tile(acc[3], 2);
            }
            if (warp == 3) {
                if (lane == 15) pre = ld_rlx(S->hint);
            }
            const cplx z1024 = csq(z512);
            {
                const cplx zk[4] = {z1024, cmul(z1024, z256), csq(z768), cmul(z1024, z768)};
#pragma unroll
                for (int h = 0; h < 4; h++) {
                    const uint32_t a0 = CJ(zk[h]), a0p = CJP(zk[h]);
                    sts32(ws + (2 * h) * 144, hcm(cz[0], a0, a0p));
                    sts32(ws + (2 * h + 1) * 144, hcm(cz[2], a0, a0p));
                }
                tile(acc[4], 0);
            }
            const cplx z2048 = csq(z1024);
            float last = C.x * z2048.x - C.y * z2048.y;
#pragma unroll
            for (int o = 16; o; o >>= 1) last += __shfl_xor_sync(0xffffffffu, last, o);
            __syncwarp();
#pragma unroll
            for (int i = 0; i < 5; i++) *(float4*)(sm + (scr - sb) + i * 512 + lane * 16) = make_float4(acc[i][0], acc[i][1], acc[i][2], acc[i][3]);
            if (lane == 0) { const float inv = __uint_as_float(ex << 23); M.kinv[wgi][w] = inv; M.klast[wgi][w] = last * inv; }
        }
        if (tid == 111 && (int)(pre - HINT_N * wait_epoch(M)) >= 0) M.flag = 1u;
        named_bar(1 + wgi, 128);
        const uint32_t td = cb + XO_TD + 64 * 4, tf = cb + XO_TF - 32 * 4;
        if (tid == 111 && !M.flag) pre = ld_rlx(S->hint);
        const float4 ki = *(const float4*)M.kinv[wgi];
        auto fsum = [&](int off, uint32_t& r0, uint32_t& r1) {
            const unsigned char* p = sm + (cb - sb) + off;
            const float4 a = *(const float4*)p, b2 = *(const float4*)(p + KSCR), c = *(const float4*)(p + 2 * KSCR), d = *(const float4*)(p + 3 * KSCR);
            r0 = pack2(fmaf(a.y, ki.x, b2.y * ki.y) + fmaf(c.y, ki.z, d.y * ki.w), fmaf(a.x, ki.x, b2.x * ki.y) + fmaf(c.x, ki.z, d.x * ki.w));
            r1 = pack2(fmaf(a.w, ki.x, b2.w * ki.y) + fmaf(c.w, ki.z, d.w * ki.w), fmaf(a.z, ki.x, b2.z * ki.y) + fmaf(c.z, ki.z, d.z * ki.w));
        };
        uint32_t r[2], q[2];
        fsum(w * 512 + lane * 16, r[0], r[1]);
        fsum(2048 + w * 128 + lr * 16, q[0], q[1]);
        if (tid == 111) {
            if ((int)(pre - HINT_N * M.epoch) >= 0) M.flag = 1u;
            else pre = ld_rlx(S->hint);
        }
        __syncwarp();
        if (w < 2) {
            const uint32_t p = td + (16 * g + 8 * w + 2 * t) * 4;
#pragma unroll
            for (int h = 0; h < 2; h++) { sts16(p + h * 512, r[h] >> 16); sts32(p + h * 512 + 4, r[h]); sts16(p + h * 512 + 10, r[h]); }
        } else if (w == 2) {
            const uint32_t p = td + (256 + 16 * g + 4 * t) * 4;
#pragma unroll
            for (int h = 0; h < 2; h++) {
                const uint32_t k0 = r[h] >> 16;
                if (h || lane) { sts16(p + h * 512 - 4, k0); sts16(p + h * 512 + 2, k0); }
                sts16(p + h * 512, k0); sts32(p + h * 512 + 4, __byte_perm(r[h], 0, 0x3232)); sts32(p + h * 512 + 8, r[h]); sts16(p + h * 512 + 14, r[h]);
            }
        } else {
            const uint32_t p = tf + (64 + 32 * (t >> 1) + 2 * g + (t & 1)) * 4;
#pragma unroll
            for (int h = 0; h < 2; h++) {
                const uint32_t k0 = r[h] >> 16;
                sts16(p + h * 64 + 512, r[h]); sts16(p + h * 64 + 518, r[h]);
                if (h || lane) { sts16(p + h * 64 - 4, k0); sts16(p + h * 64 + 2, k0); }
            }
            if (lane == 0) {
                const uint32_t dd = __byte_perm(r[0], 0, 0x3232);
                sts16(td + 511 * 4, dd); sts32(td + 512 * 4, dd); sts32(td + 513 * 4, dd); sts32(td + 514 * 4, dd); sts16(td + 515 * 4 + 2, dd);
            }
        }
        if (lane < 8) {
            const uint32_t p = tf + 1024 + (64 + 16 * t + 2 * w + g) * 4;
#pragma unroll
            for (int h = 0; h < 2; h++) {
                const uint32_t k0 = q[h] >> 16;
                sts16(p + h * 32 + 512, q[h]); sts16(p + h * 32 + 518, q[h]);
                if (h || (tid & 127)) { sts16(p + h * 32 - 4, k0); sts16(p + h * 32 + 2, k0); }
            }
            if ((tid & 127) == 0) {
                const float4 kl4 = *(const float4*)M.klast[wgi];
                const uint32_t kl = f2bits((kl4.x + kl4.y) + (kl4.z + kl4.w)), dd = __byte_perm(q[0], 0, 0x3232);
                sts16(tf + 127 * 4, dd); sts16(tf + 128 * 4 + 2, dd); sts32(cb + XO_K1024, dd);
                sts16(tf + 1024 + 127 * 4, kl); sts16(tf + 1024 + 128 * 4 + 2, kl);
            }
        }
        __syncwarp();
    } else {
        const int i = tid - 512, idx = b >> 1;
        tag16 = (wait_epoch(M) % 65535u) + 1u;
        mod_tile(0);
        if (i == 0 && idx < 44) {
            PROXY_FENCE();
            mbar_expect(mb_wm + 8, 36864);
#pragma unroll
            for (int k = 0; k < 3; k++) tma2d(sb + OFF_WU + k * 12288, &tm_wm, 32 * (idx + 64), 192 * k, mb_wm + 8);
        }
        __syncwarp();
    }
    if (tid == 111) {
        epoch = wait_epoch(M);
#pragma unroll 1
        for (int it = 0; it < SPIN_MAX && (int)(pre - HINT_N * epoch) < 0; it++) pre = ld_rlx(S->hint);
        M.flag = 1u;
    }
    __syncwarp();
    const int ubp = (tid * 13108) >> 16, uloc = tid - 5 * ubp;
    const uint4* usrc = &S->xn[(size_t)b * 1280 + 2 * tid];
    uint4 ua = make_uint4(0, 0, 0, 0), uc = ua;
    uint32_t usa = 0, uca = 0;
    if (lane == 0) {
#pragma unroll 1
        for (int it = 0; it < (SPIN_MAX << 4) && !M.flag; it++) { }
    }
    __syncwarp();
    if (uloc < nch) {
 ua = ld_rlx4(usrc); uc = ld_rlx4(usrc + 1); usa = ld_rlx(&S->modw[cs + uloc]); uca = ld_rlx(&S->modw[D_ + cs + uloc]); }
    CBAR();
    epoch = M.epoch;
    tag16 = (epoch % 65535u) + 1u;
    {
        const int bp = ubp, loc = uloc;
        if (loc < nch) {
            const uint4* src = usrc;
            uint4 a = ua, c = uc;
#pragma unroll 1
            for (int it = 0; it < SPIN_MAX && (a.x == SENT || a.z == SENT || c.x == SENT || c.z == SENT || (usa >> 16) != tag16 || (uca >> 16) != tag16); it++) {
                a = ld_rlx4(src); c = ld_rlx4(src + 1); usa = ld_rlx(&S->modw[cs + loc]); uca = ld_rlx(&S->modw[D_ + cs + loc]);
            }
            const uint32_t sa = __byte_perm(usa, 0, 0x1010), ca = pack2(1.0f + lo2f(uca), 1.0f + lo2f(uca));
            unsigned char* up = sm + OFF_CH + loc * CHS + ((2 * bp) & 7) * ULBO + ((bp >> 2) + 9) * 16;
            *(uint4*)up = make_uint4(add2(mul2(~a.x, ca), sa), add2(mul2(~a.z, ca), sa), add2(mul2(~c.x, ca), sa), add2(mul2(~c.z, ca), sa));
            *(uint4*)(up + ULBO) = make_uint4(add2(mul2(~a.y, ca), sa), add2(mul2(~a.w, ca), sa), add2(mul2(~c.y, ca), sa), add2(mul2(~c.w, ca), sa));
        }
        publish_reset();
        const int i = tid & 127;
        unsigned char* cp = sm + OFF_CH + wgi * CHS;
        *(uint4*)(cp + XO_U8 - 1024 + (i >> 6) * 4096 + (i & 63) * 16) = make_uint4(0, 0, 0, 0);
        if (i < 72) { const int c = (i * 57) >> 9; *(uint4*)(cp + c * ULBO + (i - 9 * c) * 16) = make_uint4(0, 0, 0, 0); }
    }
    PROXY_FENCE();
    CBAR();
    if (w == 2 && lane == 0) {
        bulk_s2g((char*)&S->xn[(size_t)b * 1280] + wgi * 4096, sb + OFF_MISC, 4096);
        asm volatile("cp.async.bulk.commit_group;" ::: "memory");
    }
        if (tid == 416) {
            mbar_expect(mb_wg, nf * D_ * 2);
            tma2d(sb + OFF_WG, (b & 1) ? &tm_wg : &tm_wg32, f0, 0, mb_wg);
        }
    if (tid == 96 || tid == 224) tma2d(sb + OFF_WG + (1 + (tid >> 7)) * (nf * 384), (b & 1) ? &tm_wg : &tm_wg32, f0, 192 * (1 + (tid >> 7)), mb_wg);
    if (has_ch) {
        __syncwarp();
        conv_channel(sm, S, 2 * D_ + cs + wgi, epoch, w_down + (size_t)f0 * D_, (b & 1) ? nullptr : &tm_wu32, f0);
    } else {
        const int idx = b >> 1;
        if (idx < 44) mod_tile(1);
        if (tid == 512) {
            PROXY_FENCE();
            mbar_expect(mb_wu, 46080);
#pragma unroll 1
            for (int i = 0; i < 3; i++) {
                tma2d(sb + OFF_WU + i * 15360, &tm_wu, f0, 192 * i, mb_wu);
                const long long c0 = clock64();
                int it = 0;
                while (clock64() - c0 < 1200 && ++it < 4096) { }
            }
            wait_reset(S->cnt, epoch);
        }
        named_bar(5, 128);
    }
    {
    const int tid = fresh_tid(), warp = __shfl_sync(0xffffffffu, tid >> 5, 0), lane = tid & 31;
    const int g = lane >> 2, t = lane & 3, lr = lane & 7, lm = lane >> 3;
    uint32_t v3 = 0, v4 = 0, v5 = 0;
    auto load_consts = [&]() {
        if (tid < D_) { v3 = ld_rlx(&S->modw[3 * D_ + tid]); v4 = ld_rlx(&S->modw[4 * D_ + tid]); v5 = ld_rlx(&S->modw[5 * D_ + tid]); }
    };
    if (tid == 0) bulk_pf(w_down + (size_t)(f0 + 16) * D_, (nf - 16) * D_ * 2);
    uint32_t x1[2][4], wr2[2][2];
    if (warp < 18) {
        const char* vp = (const char*)S->v + ((size_t)b * D_ + 32 * warp + g) * 32 + t * 8;
        uint2 v[4];
#pragma unroll
        for (int i = 0; i < 4; i++) v[i] = ld_rlx2(vp + i * 256);
#pragma unroll
        for (int j = 0; j < 2; j++) {
            const uint32_t* wp = M.wr + 16 * warp + 8 * j + t;
            wr2[j][0] = (g == 0) ? wp[0] : 0u;
            wr2[j][1] = (g == 0) ? wp[4] : 0u;
            ldsm_x4(x1[j], sb + OFF_TILE + (lr + 8 * (lm & 1)) * (ROWP * 2) + (lm >> 1) * 16 + warp * 64 + j * 32);
        }
#pragma unroll 1
        for (int it = 0; it < SPIN_MAX && ((v3 >> 16) != tag16 || (v4 >> 16) != tag16 || (v5 >> 16) != tag16); it++) load_consts();
        ((unsigned short*)M.sb)[tid] = (unsigned short)v3;
        ((unsigned short*)M.cb1)[tid] = (unsigned short)f2bits(1.0f + lo2f(v4));
        ((unsigned short*)M.gb)[tid] = (unsigned short)v5;
#pragma unroll 1
        for (int it = 0; it < SPIN_MAX; it++) {
            bool bad = false;
#pragma unroll
            for (int i = 0; i < 4; i++) if (v[i].x == SENT) { v[i] = ld_rlx2(vp + i * 256); bad = true; }
            if (!bad) break;
        }
        __syncwarp();
        float c1[4] = {0.f, 0.f, 0.f, 0.f}, cl[4] = {0.f, 0.f, 0.f, 0.f}, chh[4] = {0.f, 0.f, 0.f, 0.f};
#pragma unroll
        for (int j = 0; j < 2; j++) {
            x1[j][0] = add2(x1[j][0], movm(~v[2 * j].x)); x1[j][1] = add2(x1[j][1], movm(~v[2 * j].y));
            x1[j][2] = add2(x1[j][2], movm(~v[2 * j + 1].x)); x1[j][3] = add2(x1[j][3], movm(~v[2 * j + 1].y));
            mma_bf16(c1, x1[j][0], x1[j][1], x1[j][2], x1[j][3], 0x3F803F80u, 0x3F803F80u);
            mma_bf16(cl, x1[j][0], x1[j][1], x1[j][2], x1[j][3], x1[j][0], x1[j][2]);
            mma_bf16(chh, x1[j][0], x1[j][1], x1[j][2], x1[j][3], x1[j][1], x1[j][3]);
        }
        float* pp = (float*)&M.part[warp][g];
        if (t == 0) { pp[0] = c1[0]; pp[16] = c1[2]; }
        if (t == (g >> 1)) { pp[1] = (g & 1) ? cl[1] : cl[0]; pp[17] = (g & 1) ? chh[3] : chh[2]; }
    }
    CBAR();
    if (warp < 18) {
        const int tok = lane & 15, hf = lane >> 4;
        uint32_t kc[2][2][2];
#pragma unroll
        for (int j = 0; j < 2; j++)
#pragma unroll
            for (int q = 0; q < 2; q++) { kc[j][q][0] = ((const uint32_t*)M.cb1)[16 * warp + 8 * j + 4 * q + t]; kc[j][q][1] = ((const uint32_t*)M.sb)[16 * warp + 8 * j + 4 * q + t]; }
        named_bar(13, 608);
        uint32_t st[2][3];
#pragma unroll
        for (int h = 0; h < 2; h++) { const uint4 q = M.st2[g + 8 * h]; st[h][0] = q.x; st[h][1] = q.y; st[h][2] = q.z; }
        float rc[4] = {0.f, 0.f, 0.f, 0.f};
        uint32_t h2[2][4];
#pragma unroll
        for (int j = 0; j < 2; j++) {
#pragma unroll
            for (int r = 0; r < 4; r++) {
                h2[j][r] = add2(mul2(norm2(x1[j][r], st[r & 1][0], st[r & 1][1], st[r & 1][2]), kc[j][r >> 1][0]), kc[j][r >> 1][1]);
            }
            mma_bf16(rc, h2[j][0], h2[j][1], h2[j][2], h2[j][3], wr2[j][0], wr2[j][1]);
        }
        if (t == 0) { M.rp[warp][g] = rc[0]; M.rp[warp][g + 8] = rc[2]; }
        if (warp == 0) {
            named_bar(12, 576);
            float r = M.rp[9 * hf][tok];
#pragma unroll
            for (int i = 1; i < 9; i++) r += M.rp[9 * hf + i][tok];
            r += __shfl_xor_sync(0xffffffffu, r, 16);
            const uint32_t rbits = f2bits(r);
            const uint32_t key = 0x80000000u | ((rbits ^ ((rbits & 0x8000u) ? 0xFFFFu : 0x8000u)) << 11) | (uint32_t)(2047 - (16 * b + tok));
            int rank = 0;
#pragma unroll
            for (int j = 1; j < 16; j++) rank += __shfl_xor_sync(0xffffffffu, key, j) > key;
            if (lane < 16) { M.skey[rank] = key; M.rank[rank] = tok; }
            __syncwarp();
            if (lane < 2) st_rlx4(&S->rec[8 * b + 4 * lane], *(const uint4*)&M.skey[4 * lane]);
        } else named_arrive(12, 576);
#pragma unroll
        for (int j = 0; j < 2; j++) {
            uint32_t o[4];
#pragma unroll
            for (int r = 0; r < 4; r++) o[r] = add2(x1[j][r], mul2(((const uint32_t*)M.gb)[16 * warp + 8 * j + 4 * (r >> 1) + t], h2[j][r]));
            const uint32_t to = (lr + 8 * (lm & 1)) * (ROWP * 2) + (lm >> 1) * 16 + warp * 64 + j * 32;
            stsm_x4(sb + OFF_H2T + to, h2[j][0], h2[j][1], h2[j][2], h2[j][3]);
            stsm_x4(sb + OFF_TILE + to, o[0], o[1], o[2], o[3]);
        }
    } else if (warp == 19) {
        const int tok = lane & 15, hf = lane >> 4;
        float2 s = M.part[9 * hf][tok];
#pragma unroll
        for (int i = 1; i < 9; i++) { const float2 q = M.part[9 * hf + i][tok]; s.x += q.x; s.y += q.y; }
        s.x += __shfl_xor_sync(0xffffffffu, s.x, 16); s.y += __shfl_xor_sync(0xffffffffu, s.y, 16);
        float meanb, rinv;
        ln_stats(s.x, s.y, meanb, rinv);
        const float rh = bfr(rinv);
        if (lane < 16) M.st2[tok] = make_uint4(pack2(meanb, meanb), pack2(rh, rh), pack2(rinv - rh, rinv - rh), 0u);
        __syncwarp();
        named_arrive(13, 608);
    } else if (lane < 9) {
        PROXY_FENCE();
        if (lane == 0) mbar_expect(mb_wd, nf * D_ * 2);
        tma2d(sb + OFF_WD + lane * 5120, (b & 1) ? &tm_wd : &tm_wd32, 64 * lane, f0, mb_wd);
    }
    CBAR();
    uint32_t wf[9][4], wd[2][3][4];
    const int fmt = warp >> 2, fsl = warp & 3;
    auto load_wf = [&]() {
        mbar_wait(mb_wg, 0);
        mbar_wait(mb_wu, 0);
        if (fmt < 4 || nf > 32) {
            const int half = lm & 1;
            const uint32_t base = (fmt == 4) ? ((half ? OFF_WU : OFF_WG) + 64)
                                             : ((fmt >> 1) * OFF_WU + (((2 * (fmt & 1) + half) ^ ((b & 1) ? 0 : (lr >> 1))) << 4));
            const uint32_t wa = sb + base + (144 * fsl + lr + 8 * (lm >> 1)) * (2 * nf);
#pragma unroll
            for (int ks = 0; ks < 9; ks++) ldsm_x4_t(wf[ks], wa + ks * (32 * nf));
        }
    mbar_wait(mb_wd, 0);
    {
#pragma unroll
        for (int i = 0; i < 2; i++) {
            const int mt = warp + 20 * i;
            const uint32_t wa = sb + OFF_WD + (mt >> 2) * 5120 + lr * 128 + (((2 * (mt & 3) + (lm & 1)) ^ lr) << 4);
#pragma unroll
            for (int ks = 0; ks < 3; ks++)
                if ((i == 0 || warp < 16) && (ks < 2 || nf > 32)) ldsm_x4_t(wd[i][ks], wa + ks * 2048 + ((ks < 2) ? (lm >> 1) * 1024 : 0));
        }
    }
    };
    if (warp >= 8) {
        if (warp < 16) {
            const int tk = M.rank[warp - 8];
            const uint32_t* hp = (const uint32_t*)(sm + OFF_H2T + tk * (ROWP * 2)) + lane;
            uint4* dst = &S->h2w[(size_t)(16 * b + tk) * 96 + lane];
#pragma unroll
            for (int j = 0; j < 3; j++) st_rlx4(dst + 32 * j, make_uint4(hp[96 * j], hp[96 * j + 32], hp[96 * j + 64], epoch));
        }
        load_wf();
    } else {
        const uint4* rp = (const uint4*)S->rec + tid;
        load_wf();
        uint4 rk = ld_rlx4(rp);
#pragma unroll 1
        for (int it = 0; it < SPIN_MAX && !rk.x; it++) rk = ld_rlx4(rp);
        __syncwarp();
        uint32_t mine = 0;
#pragma unroll
        for (int rnd = 0; rnd < 8; rnd++) {
            const uint32_t m = __reduce_max_sync(0xffffffffu, rk.x);
            if (rk.x == m) { rk.x = rk.y; rk.y = rk.z; rk.z = rk.w; rk.w = 0u; }
            if (lane == rnd) mine = m;
        }
        if (lane < 8) M.cand[8 * warp + lane] = mine;
    }
    CBAR();
    uint32_t selv = 0;
    if (warp < 12) {
        uint2 k = *(const uint2*)&M.cand[2 * lane];
#pragma unroll
        for (int rnd = 0; rnd < 8; rnd++) {
            const uint32_t m = __reduce_max_sync(0xffffffffu, k.x);
            if (k.x == m) { k.x = k.y; k.y = 0u; }
            if (lr == rnd) selv = m;
        }
        if (tid < 8) M.skey[tid] = selv;
    }
    const uint32_t seltok = 2047u - (selv & 2047u);
    const int fo = tid >> 3;
    const int fW = 9 * b + (fo >> 2), fcomp = fo & 3;
    const int fd = 16 * (fW >> 5) + ((fW >> 2) & 7) + 8 * (fcomp >> 1), fk = 2 * (fW & 3) + (fcomp & 1);
    const uint32_t fsel = __shfl_sync(0xffffffffu, selv, fk);
    uint32_t fx = 0, fv = 0;
    bf16(*h2s)[ROWP] = (bf16(*)[ROWP])(sm + OFF_H2S);
    if (warp < 12) {
        uint4 wv[2];
        const uint4* hp[2];
#pragma unroll
        for (int r = 0; r < 2; r++) {
            const int wi = warp + 12 * r, k = wi / 3, j = wi - 3 * k;
            hp[r] = &S->h2w[(size_t)__shfl_sync(0xffffffffu, seltok, k) * 96 + 32 * j + lane];
            wv[r] = ld_rlx4(hp[r]);
        }
        if (tid < 288 && (tid & 7) == 0) {
            const uint32_t ft = 2047u - (fsel & 2047u), pr = (ft & 15u) >> 1;
            fx = ((const unsigned short*)x)[(size_t)ft * D_ + fd];
            asm volatile("ld.relaxed.gpu.global.u16 %0, [%1];" : "=r"(fv)
                         : "l"((const unsigned short*)S->v + ((size_t)(ft >> 4) * D_ + fd) * 16 + ((pr & 3u) * 2 + (pr >> 2)) * 2 + (ft & 1u)) : "memory");
        }
#pragma unroll 1
        for (int it = 0; it < SPIN_MAX && (wv[0].w != epoch || wv[1].w != epoch); it++) { wv[0] = ld_rlx4(hp[0]); wv[1] = ld_rlx4(hp[1]); }
#pragma unroll
        for (int r = 0; r < 2; r++) {
            const int wi = warp + 12 * r, k = wi / 3, j = wi - 3 * k;
            uint32_t* dst = (uint32_t*)&h2s[k][0] + 96 * j + lane;
            dst[0] = wv[r].x; dst[32] = wv[r].y; dst[64] = wv[r].z;
        }
    }
    CBAR();
    float* ffr = (float*)(sm + OFF_FFR);
    if (fmt < 4 || nf > 32) {
        float acc[2][4] = {{0.f, 0.f, 0.f, 0.f}, {0.f, 0.f, 0.f, 0.f}};
        const uint32_t ha = sb + OFF_H2S + lr * (ROWP * 2) + (144 * fsl) * 2 + lm * 16;
#pragma unroll
        for (int k2 = 0; k2 < 5; k2++) {
            uint32_t hb[4];
            ldsm_x4(hb, ha + k2 * 64 - ((k2 == 4) ? (lm >> 1) * 32 : 0));
            mma_bf16(acc[0], wf[2 * k2][0], wf[2 * k2][1], wf[2 * k2][2], wf[2 * k2][3], hb[0], hb[1]);
            if (k2 < 4) mma_bf16(acc[1], wf[2 * k2 + 1][0], wf[2 * k2 + 1][1], wf[2 * k2 + 1][2], wf[2 * k2 + 1][3], hb[2], hb[3]);
        }
        float* o = ffr + ((fsl * 80 + 16 * fmt + g) * 8 + 2 * t);
        *(float2*)o = make_float2(acc[0][0] + acc[1][0], acc[0][1] + acc[1][1]);
        *(float2*)(o + 64) = make_float2(acc[0][2] + acc[1][2], acc[0][3] + acc[1][3]);
    }
    CBAR();
    bf16(*act)[56] = (bf16(*)[56])(sm + OFF_ACT);
    if (tid < 384) {
        const int f = tid >> 3, a = tid & 7;
        float v = 0.f;
        if (f < nf) {
            const int rg = (f < 32) ? f : f + 32, ru = (f < 32) ? f + 32 : f + 40;
            const float* pg = ffr + rg * 8 + a;
            const float* pu = ffr + ru * 8 + a;
            float gg = bfr((pg[0] + pg[640]) + (pg[1280] + pg[1920]));
            gg = bfr(silu(gg));
            const float uu = bfr((pu[0] + pu[640]) + (pu[1280] + pu[1920]));
            v = gg * uu;
        }
        act[a][f] = __ushort_as_bfloat16((unsigned short)f2bits(v));
    }
    CBAR();
    {
        uint32_t bq[3][2];
#pragma unroll
        for (int ks = 0; ks < 3; ks++) {
            bq[ks][0] = *(const uint32_t*)&act[g][16 * ks + 2 * t];
            bq[ks][1] = *(const uint32_t*)&act[g][16 * ks + 2 * t + 8];
        }
#pragma unroll
        for (int i = 0; i < 2; i++) {
            if (i == 0 || warp < 16) {
                float acc[4] = {0.f, 0.f, 0.f, 0.f};
#pragma unroll
                for (int ks = 0; ks < 3; ks++)
                    if (ks < 2 || nf > 32) mma_bf16(acc, wd[i][ks][0], wd[i][ks][1], wd[i][ks][2], wd[i][ks][3], bq[ks][0], bq[ks][1]);
                const int W = (warp + 20 * i) * 32 + lane, c = (W * 7282) >> 16;
                st_rlx2(&S->part[(c * G_ + b) * 9 + W - 9 * c], ~pack2(acc[0], acc[1]), ~pack2(acc[2], acc[3]));
            }
        }
    }
    if (warp >= 4) {
        const int tk = warp - 4;
        if (!__any_sync(0xffffffffu, 2047u - (M.skey[lr] & 2047u) == (uint32_t)(16 * b + tk))) {
            const uint4* src = (const uint4*)(sm + OFF_TILE + tk * (ROWP * 2));
            uint4* dst = (uint4*)(out + (size_t)(16 * b + tk) * D_);
            dst[lane] = src[lane]; dst[lane + 32] = src[lane + 32];
            if (lane < 8) dst[lane + 64] = src[lane + 64];
        }
    }
    float4* fin = (float4*)(sm + OFF_FIN);
    uint32_t rb = (fsel >> 11) & 0xFFFFu;
    rb ^= (rb & 0x8000u) ? 0x8000u : 0xFFFFu;
    const float rs = bfr(__fdividef(1.0f, 1.0f + __expf(-lo2f(rb))));
    const float fh2 = (tid < 288) ? __bfloat162float(h2s[fk][fd]) : 0.f, fgb = (tid < 288) ? __bfloat162float(M.gb[fd]) : 0.f;
    const float fx1 = bfr(lo2f(fx) + lo2f(~fv));
    if (tid < 576) {
        const uint2* src = &S->part[(size_t)b * 1152 + tid];
        uint2 a = ld_rlx2(src), c = ld_rlx2(src + 576);
#pragma unroll 1
        for (int it = 0; it < SPIN_MAX && (a.x == SENT || c.x == SENT); it++) {
            if (a.x == SENT) a = ld_rlx2(src);
            if (c.x == SENT) c = ld_rlx2(src + 576);
        }
        fin[tid] = make_float4(lo2f(~a.x) + lo2f(~c.x), hi2f(~a.x) + hi2f(~c.x), lo2f(~a.y) + lo2f(~c.y), hi2f(~a.y) + hi2f(~c.y));
    }
    CBAR();
    if (tid < 288) {
        const int part = tid & 7;
        const float* f = (const float*)fin + part * 36 + fo;
        float s = ((f[0] + f[288]) + (f[576] + f[864])) + ((f[1152] + f[1440]) + (f[1728] + f[2016]));
        s += __shfl_xor_sync(0xffffffffu, s, 1);
        s += __shfl_xor_sync(0xffffffffu, s, 2);
        s += __shfl_xor_sync(0xffffffffu, s, 4);
        const float upd = bfr(bfr(s) * rs);
        const float ov = fx1 + bfr(fgb * bfr(fh2 + upd));
        if (part == 0) out[(size_t)(2047u - (fsel & 2047u)) * D_ + fd] = __ushort_as_bfloat16((unsigned short)f2bits(ov));
    }
    if ((warp & 3) == 2 && lane == 0) asm volatile("cp.async.bulk.wait_group 0;" ::: "memory");
    }
}

typedef CUresult (*EncodeFn)(CUtensorMap*, CUtensorMapDataType, cuuint32_t, void*, const cuuint64_t*, const cuuint64_t*,
                             const cuuint32_t*, const cuuint32_t*, CUtensorMapInterleave, CUtensorMapSwizzle,
                             CUtensorMapL2promotion, CUtensorMapFloatOOBfill);

static void make_map(EncodeFn fn, CUtensorMap* m, const void* ptr, uint64_t cols, uint64_t rows, uint32_t bc, uint32_t br,
                     CUtensorMapSwizzle sw) {
    cuuint64_t dims[2] = {cols, rows};
    cuuint64_t strides[1] = {cols * 2};
    cuuint32_t box[2] = {bc, br};
    cuuint32_t es[2] = {1, 1};
    CUresult rc = fn(m, CU_TENSOR_MAP_DATA_TYPE_BFLOAT16, 2, (void*)ptr, dims, strides, box, es, CU_TENSOR_MAP_INTERLEAVE_NONE,
                     sw, CU_TENSOR_MAP_L2_PROMOTION_NONE, CU_TENSOR_MAP_FLOAT_OOB_FILL_NONE);
    (void)rc;
}

static void launch(void* const* d_in, const int* in_sizes, int n_in, void* d_out, int out_size) {
    static EncodeFn enc = nullptr;
    static CUtensorMap tmm, tmg, tmu, tmd, tmd32, tmg32, tmu32;
    static Scratch* sp = nullptr;
    static const void* cached[4] = {nullptr, nullptr, nullptr, nullptr};
    if (!enc) {
        cudaDriverEntryPointQueryResult qr;
        void* fn = nullptr;
        cudaGetDriverEntryPoint("cuTensorMapEncodeTiled", &fn, cudaEnableDefault, &qr);
        enc = (EncodeFn)fn;
        cudaFuncSetAttribute(mega_kernel, cudaFuncAttributeMaxDynamicSharedMemorySize, SMEM_TOTAL);
        cudaGetSymbolAddress((void**)&sp, g_s);
    }
    if (cached[0] != d_in[13] || cached[1] != d_in[9] || cached[2] != d_in[10] || cached[3] != d_in[11]) {
        make_map(enc, &tmm, d_in[13], 6 * D_, D_, 32, 192, CU_TENSOR_MAP_SWIZZLE_64B);
        make_map(enc, &tmg, d_in[9], F_, D_, 40, 192, CU_TENSOR_MAP_SWIZZLE_NONE);
        make_map(enc, &tmu, d_in[10], F_, D_, 40, 192, CU_TENSOR_MAP_SWIZZLE_NONE);
        make_map(enc, &tmg32, d_in[9], F_, D_, 32, 192, CU_TENSOR_MAP_SWIZZLE_64B);
        make_map(enc, &tmu32, d_in[10], F_, D_, 32, 192, CU_TENSOR_MAP_SWIZZLE_64B);
        make_map(enc, &tmd, d_in[11], D_, F_, 64, 40, CU_TENSOR_MAP_SWIZZLE_128B);
        make_map(enc, &tmd32, d_in[11], D_, F_, 64, 32, CU_TENSOR_MAP_SWIZZLE_128B);
        cached[3] = d_in[11];
        cached[0] = d_in[13]; cached[1] = d_in[9]; cached[2] = d_in[10];
    }
    mega_kernel<<<G_, NTHR, SMEM_TOTAL>>>((const bf16*)d_in[0], (const bf16*)d_in[1], (const bf16*)d_in[2], (const bf16*)d_in[3],
                                          (const bf16*)d_in[4], (const bf16*)d_in[5], (const bf16*)d_in[12], sp, (const bf16*)d_in[6],
                                          (const bf16*)d_in[8], (const bf16*)d_in[11], (bf16*)d_out, tmm, tmg, tmu, tmd, tmd32, tmg32, tmu32);
}

}

extern "C" void kernel_launch(void* const* d_in, const int* in_sizes, int n_in, void* d_out, int out_size) {
    static int mode = -1;
    if (mode < 0) mode = v5::fits() ? 1 : 0;
    if (mode) v5::launch(d_in, in_sizes, n_in, d_out, out_size);
    else v4::launch(d_in, in_sizes, n_in, d_out, out_size);
}
```

```cpp
#include <cuda_runtime.h>
#include <cuda.h>
#include <cuda_bf16.h>
#include <cuda_fp16.h>
#include <stdint.h>

namespace v5 {

#define L_ 2048
#define D_ 576
#define N_ 128
#define F_ 4608
#define G_ 120
#define NCL 15
#define NTHR 768
#define SPIN_MAX (1 << 18)

typedef __nv_bfloat16 bf16;

struct Scratch {
    float4 acc1[L_ + 8];
    float4 acc2[L_];
    uint4 h2c[136 * 72];
    float4 acc3[72 * 32];
    float4 rs[32 * 8];
};
#define NRST (L_ + 136 * 72 + 72 * 32 + 256)
static_assert(NRST == 120 * G_, "reset split");
#define GBV(P) ((unsigned int*)S->rs + 32 * ((P) >> 4) + 16 + ((P) & 15))
__device__ __align__(1024) Scratch g_s;

#define OFF_WG 0
#define OFF_WU 46080
#define KSCR 3456
#define OFF_WM0 69120
#define OFF_STG OFF_WM0
#define OFF_MG2 86400
#define OFF_CH 92160
#define CHS 18688
#define ULBO 656
#define XO_U8 6272
#define XO_U16 10368
#define XO_ZA 5248
#define XO_ZB 8448
#define XO_ZC 11648
#define XO_ZD 13824
#define XO_TF 12416
#define XO_TD 16000
#define XO_K1024 18624
#define XO_DSK 18628
#define XO_KINV 18640
#define XO_KLAST 18656
#define XO_MBU 18672
#define OFF_X 185600
#define XG 672
#define XI(i) (((i) >> 1) * 5520 + ((i) & 1) * 2752)
#define XN(n) ((((n) >> 1) & 3) * XG + (2 * ((n) >> 3) + ((n) & 1)) * 80)
#define OFF_V 207616
#define VP 528
#define OFF_EK (OFF_V + 512)
#define OFF_WM2 OFF_V
#define OFF_MG1 (OFF_V + 17280)
#define OFF_SC (OFF_V + 19840)
#define OFF_C1 (OFF_V + 20640)
#define OFF_MISC 228736
#define OFF_WD OFF_CH
#define OFF_H2T (OFF_CH + 46080)
#define OFF_OUT (OFF_CH + 66560)
#define ROWP 584
#define OFF_H2S 0
#define OFF_FFR 9344
#define OFF_ACT 19584
#define OFF_RS 20480

enum { MB_WM2, MB_MG1, MB_MG2, MB_KEY, MB_V, MB_RS, MB_WG, MB_WU, MB_WD, MB_KEY2, MB_EK, MB_RS2, MB_C2, MB_CW, MB_KD, MB_OUT, MB_C1, MB_N };

struct Misc {
    union {
        __align__(16) uint4 box[4 * 14];
        unsigned int cand[128];
    };
    __align__(16) unsigned int key[256], cand2[128], sel[8];
    __align__(16) uint4 c2[20];
    __align__(16) unsigned int fin[12];
    unsigned int ga[8], wr[20];
    float cws[2];
    unsigned long long mbar[MB_N];
};
#define SMEM_TOTAL (OFF_MISC + (int)sizeof(Misc))
static_assert(SMEM_TOTAL <= 232448, "smem");

__device__ __forceinline__ float lo2f(uint32_t w) { return __uint_as_float(w << 16); }
__device__ __forceinline__ float hi2f(uint32_t w) { return __uint_as_float(w & 0xFFFF0000u); }
__device__ __forceinline__ uint32_t pack2(float lo, float hi) { uint32_t r; asm("cvt.rn.bf16x2.f32 %0, %1, %2;" : "=r"(r) : "f"(hi), "f"(lo)); return r; }
__device__ __forceinline__ float bfr(float x) { return __uint_as_float(pack2(0.f, x)); }
__device__ __forceinline__ uint32_t f2bits(float x) { return pack2(x, 0.f); }
__device__ __forceinline__ uint32_t packh(float lo, float hi) { uint32_t r; asm("cvt.rn.f16x2.f32 %0, %1, %2;" : "=r"(r) : "f"(hi), "f"(lo)); return r; }
__device__ __forceinline__ float frcp(float x) { float r; asm("rcp.approx.ftz.f32 %0, %1;" : "=f"(r) : "f"(x)); return r; }
__device__ __forceinline__ float fsqrt(float x) { float r; asm("sqrt.approx.f32 %0, %1;" : "=f"(r) : "f"(x)); return r; }
__device__ __forceinline__ float fex2(float x) { float r; asm("ex2.approx.ftz.f32 %0, %1;" : "=f"(r) : "f"(x)); return r; }
__device__ __forceinline__ float silu(float x) { return __fdividef(x, 1.0f + __expf(-x)); }
__device__ __forceinline__ uint32_t add2(uint32_t a, uint32_t b) { uint32_t r; asm("add.rn.bf16x2 %0, %1, %2;" : "=r"(r) : "r"(a), "r"(b)); return r; }
__device__ __forceinline__ uint32_t sub2(uint32_t a, uint32_t b) { uint32_t r; asm("sub.rn.bf16x2 %0, %1, %2;" : "=r"(r) : "r"(a), "r"(b)); return r; }
__device__ __forceinline__ uint32_t mul2(uint32_t a, uint32_t b) { uint32_t r; asm("mul.rn.bf16x2 %0, %1, %2;" : "=r"(r) : "r"(a), "r"(b)); return r; }
__device__ __forceinline__ uint32_t fma2(uint32_t a, uint32_t b, uint32_t c) { uint32_t r; asm("fma.rn.bf16x2 %0, %1, %2, %3;" : "=r"(r) : "r"(a), "r"(b), "r"(c)); return r; }
__device__ __forceinline__ uint32_t norm2(uint32_t x, uint32_t m, uint32_t rh, uint32_t rl) { const uint32_t d = sub2(x, m); return fma2(d, rh, mul2(d, rl)); }

__device__ __forceinline__ void mma_bf16(float* c, uint32_t a0, uint32_t a1, uint32_t a2, uint32_t a3, uint32_t b0, uint32_t b1) {
    asm volatile("mma.sync.aligned.m16n8k16.row.col.f32.bf16.bf16.f32 {%0,%1,%2,%3}, {%4,%5,%6,%7}, {%8,%9}, {%0,%1,%2,%3};\n"
                 : "+f"(c[0]), "+f"(c[1]), "+f"(c[2]), "+f"(c[3]) : "r"(a0), "r"(a1), "r"(a2), "r"(a3), "r"(b0), "r"(b1));
}
__device__ __forceinline__ void mma_f16(float* c, const uint32_t* a, uint32_t b0, uint32_t b1) {
    asm volatile("mma.sync.aligned.m16n8k16.row.col.f32.f16.f16.f32 {%0,%1,%2,%3}, {%4,%5,%6,%7}, {%8,%9}, {%0,%1,%2,%3};\n"
                 : "+f"(c[0]), "+f"(c[1]), "+f"(c[2]), "+f"(c[3]) : "r"(a[0]), "r"(a[1]), "r"(a[2]), "r"(a[3]), "r"(b0), "r"(b1));
}
__device__ __forceinline__ void ldsm_x4(uint32_t* r, uint32_t addr) {
    asm volatile("ldmatrix.sync.aligned.m8n8.x4.shared.b16 {%0,%1,%2,%3}, [%4];" : "=r"(r[0]), "=r"(r[1]), "=r"(r[2]), "=r"(r[3]) : "r"(addr) : "memory");
}
__device__ __forceinline__ void ldsm_x4_t(uint32_t* r, uint32_t addr) {
    asm volatile("ldmatrix.sync.aligned.m8n8.x4.trans.shared.b16 {%0,%1,%2,%3}, [%4];" : "=r"(r[0]), "=r"(r[1]), "=r"(r[2]), "=r"(r[3]) : "r"(addr) : "memory");
}
__device__ __forceinline__ void stsm_x4(uint32_t addr, uint32_t r0, uint32_t r1, uint32_t r2, uint32_t r3) {
    asm volatile("stmatrix.sync.aligned.m8n8.x4.shared.b16 [%0], {%1,%2,%3,%4};" ::"r"(addr), "r"(r0), "r"(r1), "r"(r2), "r"(r3) : "memory");
}
__device__ __forceinline__ void stsm_x4_t(uint32_t addr, uint32_t r0, uint32_t r1, uint32_t r2, uint32_t r3) {
    asm volatile("stmatrix.sync.aligned.m8n8.x4.trans.shared.b16 [%0], {%1,%2,%3,%4};" ::"r"(addr), "r"(r0), "r"(r1), "r"(r2), "r"(r3) : "memory");
}
__device__ __forceinline__ uint32_t movm(uint32_t a) { uint32_t r; asm volatile("movmatrix.sync.aligned.m8n8.trans.b16 %0, %1;" : "=r"(r) : "r"(a)); return r; }
__device__ __forceinline__ uint32_t lds32(uint32_t a) { uint32_t v; asm volatile("ld.shared.u32 %0, [%1];" : "=r"(v) : "r"(a)); return v; }
__device__ __forceinline__ void sts32(uint32_t a, uint32_t v) { asm volatile("st.shared.u32 [%0], %1;" ::"r"(a), "r"(v) : "memory"); }
__device__ __forceinline__ void sts16(uint32_t a, uint32_t v) { asm volatile("st.shared.u16 [%0], %1;" ::"r"(a), "h"((unsigned short)v) : "memory"); }
__device__ __forceinline__ void named_bar(int id, int n) { asm volatile("bar.sync %0, %1;" ::"r"(id), "r"(n) : "memory"); }
__device__ __forceinline__ void named_arrive(int id, int n) { asm volatile("bar.arrive %0, %1;" ::"r"(id), "r"(n) : "memory"); }
#define CBAR() asm volatile("bar.sync 0, 640;" ::: "memory")
#define PROXY_FENCE() asm volatile("fence.proxy.async.shared::cta;" ::: "memory")

#define D4(d, o) "+f"(d[o]), "+f"(d[o + 1]), "+f"(d[o + 2]), "+f"(d[o + 3])
__device__ __forceinline__ void wg32(float* d, uint32_t a0, uint32_t a1, uint32_t a2, uint32_t a3, uint64_t desc) {
    asm volatile("wgmma.mma_async.sync.aligned.m64n32k16.f32.bf16.bf16 {%0,%1,%2,%3,%4,%5,%6,%7,%8,%9,%10,%11,%12,%13,%14,%15}, {%16,%17,%18,%19}, %20, 1, 1, 1, 0;"
                 : D4(d, 0), D4(d, 4), D4(d, 8), D4(d, 12) : "r"(a0), "r"(a1), "r"(a2), "r"(a3), "l"(desc));
}
__device__ __forceinline__ void wg48(float* d, uint32_t a0, uint32_t a1, uint32_t a2, uint32_t a3, uint64_t desc) {
    asm volatile("wgmma.mma_async.sync.aligned.m64n48k16.f32.bf16.bf16 {%0,%1,%2,%3,%4,%5,%6,%7,%8,%9,%10,%11,%12,%13,%14,%15,%16,%17,%18,%19,%20,%21,%22,%23}, {%24,%25,%26,%27}, %28, 1, 1, 1, 0;"
                 : D4(d, 0), D4(d, 4), D4(d, 8), D4(d, 12), D4(d, 16), D4(d, 20) : "r"(a0), "r"(a1), "r"(a2), "r"(a3), "l"(desc));
}
#define O4(d, o) "=f"(d[o]), "=f"(d[o + 1]), "=f"(d[o + 2]), "=f"(d[o + 3])
__device__ __forceinline__ void wg32z(float* d, uint32_t a0, uint32_t a1, uint32_t a2, uint32_t a3, uint64_t desc) {
    asm volatile("wgmma.mma_async.sync.aligned.m64n32k16.f32.bf16.bf16 {%0,%1,%2,%3,%4,%5,%6,%7,%8,%9,%10,%11,%12,%13,%14,%15}, {%16,%17,%18,%19}, %20, 0, 1, 1, 0;"
                 : O4(d, 0), O4(d, 4), O4(d, 8), O4(d, 12) : "r"(a0), "r"(a1), "r"(a2), "r"(a3), "l"(desc));
}
__device__ __forceinline__ void wg48z(float* d, uint32_t a0, uint32_t a1, uint32_t a2, uint32_t a3, uint64_t desc) {
    asm volatile("wgmma.mma_async.sync.aligned.m64n48k16.f32.bf16.bf16 {%0,%1,%2,%3,%4,%5,%6,%7,%8,%9,%10,%11,%12,%13,%14,%15,%16,%17,%18,%19,%20,%21,%22,%23}, {%24,%25,%26,%27}, %28, 0, 1, 1, 0;"
                 : O4(d, 0), O4(d, 4), O4(d, 8), O4(d, 12), O4(d, 16), O4(d, 20) : "r"(a0), "r"(a1), "r"(a2), "r"(a3), "l"(desc));
}
#define WG_FENCE() asm volatile("wgmma.fence.sync.aligned;" ::: "memory")
#define WG_COMMIT() asm volatile("wgmma.commit_group.sync.aligned;" ::: "memory")
#define WG_WAIT(n) asm volatile("wgmma.wait_group.sync.aligned " #n ";" ::: "memory")
#define TQ(p, k) p[2 * (k) + 1], p[2 * (k) + 2], p[2 * (k)], p[2 * (k) + 1]

__device__ __forceinline__ uint4 ld_nc4(const void* p) { uint4 v; asm volatile("ld.global.nc.v4.u32 {%0,%1,%2,%3}, [%4];" : "=r"(v.x), "=r"(v.y), "=r"(v.z), "=r"(v.w) : "l"(p)); return v; }
__device__ __forceinline__ unsigned short ld_nc16(const void* p) { unsigned short v; asm volatile("ld.global.nc.u16 %0, [%1];" : "=h"(v) : "l"(p)); return v; }
__device__ __forceinline__ uint32_t ld_nc(const void* p) { uint32_t v; asm volatile("ld.global.nc.u32 %0, [%1];" : "=r"(v) : "l"(p)); return v; }
__device__ __forceinline__ uint32_t ld_rlx(const unsigned int* p) { uint32_t v; asm volatile("ld.relaxed.gpu.global.u32 %0, [%1];" : "=r"(v) : "l"(p) : "memory"); return v; }
__device__ __forceinline__ uint2 ld_rlx2(const void* p) { uint2 v; asm volatile("ld.relaxed.gpu.global.v2.u32 {%0,%1}, [%2];" : "=r"(v.x), "=r"(v.y) : "l"(p) : "memory"); return v; }
__device__ __forceinline__ uint4 ld_rlx4(const void* p) { uint4 v; asm volatile("ld.relaxed.gpu.global.v4.u32 {%0,%1,%2,%3}, [%4];" : "=r"(v.x), "=r"(v.y), "=r"(v.z), "=r"(v.w) : "l"(p) : "memory"); return v; }
__device__ __forceinline__ void st_rlx(unsigned int* p, uint32_t v) { asm volatile("st.relaxed.gpu.global.u32 [%0], %1;" ::"l"(p), "r"(v) : "memory"); }
__device__ __forceinline__ void st_rlx2(void* p, uint32_t a, uint32_t b) { asm volatile("st.relaxed.gpu.global.v2.u32 [%0], {%1,%2};" ::"l"(p), "r"(a), "r"(b) : "memory"); }
__device__ __forceinline__ void st_rlx4(void* p, uint4 v) { asm volatile("st.relaxed.gpu.global.v4.u32 [%0], {%1,%2,%3,%4};" ::"l"(p), "r"(v.x), "r"(v.y), "r"(v.z), "r"(v.w) : "memory"); }
__device__ __forceinline__ void red_inc(unsigned int* p) { asm volatile("red.relaxed.gpu.global.add.u32 [%0], 1;" ::"l"(p) : "memory"); }

__device__ __forceinline__ void mbar_init(uint32_t a, int cnt) { asm volatile("mbarrier.init.shared::cta.b64 [%0], %1;" ::"r"(a), "r"(cnt) : "memory"); }
__device__ __forceinline__ void mbar_expect(uint32_t a, uint32_t bytes) { asm volatile("mbarrier.arrive.expect_tx.shared::cta.b64 _, [%0], %1;" ::"r"(a), "r"(bytes) : "memory"); }
__device__ __forceinline__ void mbar_wait(uint32_t a, uint32_t parity) {
    uint32_t ok = 0;
    int it = 0;
    do {
        asm volatile("{\n.reg .pred p;\nmbarrier.try_wait.parity.shared::cta.b64 p, [%1], %2;\nselp.u32 %0, 1, 0, p;\n}" : "=r"(ok) : "r"(a), "r"(parity) : "memory");
    } while (!ok && ++it < SPIN_MAX);
}
__device__ __forceinline__ void tma2d(uint32_t dst, const CUtensorMap* tm, int c0, int c1, uint32_t mbar) {
    asm volatile("cp.async.bulk.tensor.2d.shared::cluster.global.mbarrier::complete_tx::bytes [%0], [%1, {%3, %4}], [%2];"
                 ::"r"(dst), "l"(tm), "r"(mbar), "r"(c0), "r"(c1) : "memory");
}
__device__ __forceinline__ void bulk_s2g(void* dst, uint32_t src, uint32_t bytes) {
    asm volatile("cp.async.bulk.global.shared::cta.bulk_group [%0], [%1], %2;" ::"l"(dst), "r"(src), "r"(bytes) : "memory");
}
__device__ __forceinline__ uint32_t ld_acq(const unsigned int* p) { uint32_t v; asm volatile("ld.acquire.gpu.global.u32 %0, [%1];" : "=r"(v) : "l"(p) : "memory"); return v; }
__device__ __forceinline__ void bulk_pf(const void* src, uint32_t bytes) { asm volatile("cp.async.bulk.prefetch.L2.global [%0], %1;" ::"l"(src), "r"(bytes) : "memory"); }

struct cplx { float x, y; };
__device__ __forceinline__ cplx cmul(cplx a, cplx b) { cplx r; r.x = a.x * b.x - a.y * b.y; r.y = a.x * b.y + a.y * b.x; return r; }
__device__ __forceinline__ cplx csq(cplx a) { cplx r; r.x = a.x * a.x - a.y * a.y; r.y = 2.0f * a.x * a.y; return r; }
__device__ __forceinline__ uint32_t hcm(uint32_t x, uint32_t y, uint32_t yp) {
    const __half2 X = *(const __half2*)&x, Y = *(const __half2*)&y, YP = *(const __half2*)&yp;
    const __half2 r = __hfma2(__high2half2(X), YP, __hmul2(__low2half2(X), Y));
    return *(const uint32_t*)&r;
}
__device__ __forceinline__ void ln_stats(float s1, float s2, float& meanb, float& rinv) {
    const float mean = s1 * (1.0f / D_);
    const float den = bfr(fsqrt(bfr(bfr(fmaxf(fmaf(-mean, mean, s2 * (1.0f / D_)), 0.f)) + 1e-5f)));
    meanb = bfr(mean);
    rinv = frcp(den);
}

__device__ __forceinline__ int fresh_tid() { int v; asm volatile("mov.u32 %0, %tid.x;" : "=r"(v)); return v - 128; }
__device__ __forceinline__ void mma_k8(float* c, uint32_t a0, uint32_t a1, uint32_t b0) {
    asm volatile("mma.sync.aligned.m16n8k8.row.col.f32.bf16.bf16.f32 {%0,%1,%2,%3}, {%4,%5}, {%6}, {%0,%1,%2,%3};\n"
                 : "+f"(c[0]), "+f"(c[1]), "+f"(c[2]), "+f"(c[3]) : "r"(a0), "r"(a1), "r"(b0));
}
__device__ __forceinline__ void ldsm_x2(uint32_t* r, uint32_t addr) {
    asm volatile("ldmatrix.sync.aligned.m8n8.x2.shared.b16 {%0,%1}, [%2];" : "=r"(r[0]), "=r"(r[1]) : "r"(addr) : "memory");
}
__device__ __forceinline__ void ldsm_x2_t(uint32_t* r, uint32_t addr) {
    asm volatile("ldmatrix.sync.aligned.m8n8.x2.trans.shared.b16 {%0,%1}, [%2];" : "=r"(r[0]), "=r"(r[1]) : "r"(addr) : "memory");
}
__device__ __forceinline__ void stsm_x2(uint32_t addr, uint32_t r0, uint32_t r1) {
    asm volatile("stmatrix.sync.aligned.m8n8.x2.shared.b16 [%0], {%1,%2};" ::"r"(addr), "r"(r0), "r"(r1) : "memory");
}
__device__ __forceinline__ uint4 lds128(uint32_t a) { uint4 v; asm volatile("ld.shared.v4.u32 {%0,%1,%2,%3}, [%4];" : "=r"(v.x), "=r"(v.y), "=r"(v.z), "=r"(v.w) : "r"(a) : "memory"); return v; }
__device__ __forceinline__ uint32_t mapa(uint32_t a, uint32_t r) { uint32_t o; asm("mapa.shared::cluster.u32 %0, %1, %2;" : "=r"(o) : "r"(a), "r"(r)); return o; }
__device__ __forceinline__ void sta4(uint32_t dst, uint4 v, uint32_t mb) {
    asm volatile("st.async.weak.shared::cluster.mbarrier::complete_tx::bytes.v4.b32 [%0], {%1,%2,%3,%4}, [%5];" ::"r"(dst), "r"(v.x), "r"(v.y), "r"(v.z), "r"(v.w), "r"(mb) : "memory");
}
__device__ __forceinline__ void sta2(uint32_t dst, uint32_t a, uint32_t b, uint32_t mb) {
    asm volatile("st.async.weak.shared::cluster.mbarrier::complete_tx::bytes.v2.b32 [%0], {%1,%2}, [%3];" ::"r"(dst), "r"(a), "r"(b), "r"(mb) : "memory");
}
__device__ __forceinline__ void mbar_arrive(uint32_t a) { asm volatile("mbarrier.arrive.shared::cta.b64 _, [%0];" ::"r"(a) : "memory"); }
__device__ __forceinline__ void red4(float4* p, float a, float b, float c) {
    asm volatile("red.relaxed.gpu.global.add.v4.f32 [%0], {%1,%2,%3,%4};" ::"l"(p), "f"(a), "f"(b), "f"(c), "f"(1.0f) : "memory");
}
__device__ __forceinline__ void red4p(bool on, float4* p, float a, float b, float c) {
    asm volatile("{\n.reg .pred q;\nsetp.ne.u32 q, %5, 0;\n@q red.relaxed.gpu.global.add.v4.f32 [%0], {%1,%2,%3,%4};\n}" ::"l"(p), "f"(a), "f"(b), "f"(c), "f"(1.0f), "r"((uint32_t)on) : "memory");
}
__device__ __forceinline__ float4 atom4(float4* p, float a, float b, float c, float d) {
    float4 v;
    asm volatile("atom.relaxed.gpu.global.add.v4.f32 {%0,%1,%2,%3}, [%4], {%5,%6,%7,%8};" : "=f"(v.x), "=f"(v.y), "=f"(v.z), "=f"(v.w) : "l"(p), "f"(a), "f"(b), "f"(c), "f"(d) : "memory");
    return v;
}
__device__ __forceinline__ uint2 lds64(uint32_t a) { uint2 v; asm volatile("ld.shared.v2.u32 {%0,%1}, [%2];" : "=r"(v.x), "=r"(v.y) : "r"(a) : "memory"); return v; }
__device__ __forceinline__ float4 ld_rlx4f(const float4* p) { float4 v; asm volatile("ld.relaxed.gpu.global.v4.f32 {%0,%1,%2,%3}, [%4];" : "=f"(v.x), "=f"(v.y), "=f"(v.z), "=f"(v.w) : "l"(p) : "memory"); return v; }
__device__ __forceinline__ void tma5d_st(const CUtensorMap* tm, int c0, int c4, uint32_t src) {
    asm volatile("cp.async.bulk.tensor.5d.global.shared::cta.bulk_group [%0, {%2, %4, %4, %4, %3}], [%1];" ::"l"(tm), "r"(src), "r"(c0), "r"(c4), "r"(0) : "memory");
}
__device__ __forceinline__ void tma2d_pf(const CUtensorMap* tm, int c0, int c1) {
    asm volatile("cp.async.bulk.prefetch.tensor.2d.L2.global [%0, {%1, %2}];" ::"l"(tm), "r"(c0), "r"(c1) : "memory");
}
__device__ __forceinline__ void pace(int clk) {
    const long long c0 = clock64();
    int it = 0;
    while (clock64() - c0 < clk && ++it < 4096) { }
}
__device__ __forceinline__ uint32_t sign2(uint32_t a) { uint32_t r; asm("prmt.b32 %0, %1, 0, 0xBB99;" : "=r"(r) : "r"(a)); return r; }
#define MB(i) (sb + OFF_MISC + (uint32_t)offsetof(Misc, mbar) + 8 * (i))
#define PRE 1
__device__ __forceinline__ void conv_channel(unsigned char* sm, uint32_t rank) {
    Misc& M = *(Misc*)(sm + OFF_MISC);
    const uint32_t sb = (uint32_t)__cvta_generic_to_shared(sm);
    const int tid = fresh_tid(), lane = tid & 31, g = lane >> 2, t = lane & 3, lr = lane & 7, lm = lane >> 3;
    const int warp_ = __shfl_sync(0xffffffffu, tid >> 5, 0), wgi = warp_ >> 2, w = warp_ & 3;
    const uint32_t cb = sb + OFF_CH + wgi * CHS;
    float D[16];
    {
        const uint32_t pf = cb + XO_TF + (w >> 1) * 512 + (8 + 16 * (w & 1) + g - 2 * t) * 4;
        uint32_t p[13], q[9];
        named_bar(1 + wgi, 128);
#pragma unroll
        for (int s = 0; s < 13; s++) p[s] = lds32(pf + s * 32);
        {
            const uint32_t a8 = cb + lr * ULBO + (lm + 9) * 16 + w * 64, b8 = cb + XO_U8 + lm * 128 + lr * 16 + w * 512;
            const uint32_t a16 = cb + (((2 * lr) & 7) + (lm & 1)) * ULBO + (9 + (lr >> 2) + (lm & 2)) * 16 + w * 64;
            const uint32_t b16 = cb + XO_U16 + (lm & 1) * 512 + lr * 16 + (lm >> 1) * 128 + (w >> 1) * 1024 + (w & 1) * 256;
            uint32_t r[3][4];
            mbar_wait(cb + XO_MBU, 0);
            ldsm_x4_t(r[0], a8);
            ldsm_x4_t(r[1], a16);
            if (w < 2) ldsm_x4_t(r[2], a8 + 256);
            stsm_x4(b8, r[0][0], r[0][1], r[0][2], r[0][3]);
            stsm_x4(b16, r[1][0], r[1][1], r[1][2], r[1][3]);
            if (w < 2) stsm_x4(b8 + 2048, r[2][0], r[2][1], r[2][2], r[2][3]);
        }
        PROXY_FENCE();
        named_bar(1 + wgi, 128);
        {
            float Z8[24], Z16[16];
            uint32_t z8[12];
            const uint32_t d8 = ((((cb + XO_U8) & 0x3FFFF) >> 4) | ((128 >> 4) << 16));
#define DZ(o) (((uint64_t)(512 >> 4) << 32) | (uint64_t)(d8 + (o)))
            WG_FENCE();
#pragma unroll
            for (int e = 0; e < 6; e++) {
                if (e == 0) wg48z(Z8, TQ(p, e), DZ(16));
                else wg48(Z8, TQ(p, e), DZ(-(e >> 1) * 32 + (1 - (e & 1)) * 16));
            }
            WG_COMMIT();
            WG_WAIT(0);
            asm volatile("setmaxnreg.inc.sync.aligned.u32 88;");
#pragma unroll
            for (int s = 0; s < 9; s++) q[s] = lds32(pf + 1024 + s * 32);
#pragma unroll
            for (int i = 0; i < 12; i++) asm volatile("cvt.rn.bf16x2.f32 %0, %1, %2;" : "=r"(z8[i]) : "f"(Z8[2 * i + 1]), "f"(Z8[2 * i]));
            WG_FENCE();
#pragma unroll
            for (int e = 0; e < 4; e++) {
                if (e == 0) wg32z(Z16, TQ(q, e), DZ(256 + 16));
                else wg32(Z16, TQ(q, e), DZ(256 - (e >> 1) * 64 + (1 - (e & 1)) * 16));
            }
            WG_COMMIT();
            WG_WAIT(0);
            named_bar(1 + wgi, 128);
            const uint32_t za = cb + ((w >> 1) ? XO_ZB : XO_ZA) + lr * 400 + (1 + 2 * (w & 1) + (lm & 1) + 4 * (lm >> 1)) * 16;
#pragma unroll
            for (int i = 0; i < 3; i++) stsm_x4(za + i * 128, z8[4 * i], z8[4 * i + 1], z8[4 * i + 2], z8[4 * i + 3]);
            const int Cz = 2 * (16 * (w & 1) + 8 * (lm & 1) + lr) + (lm >> 1);
            const uint32_t zc = cb + ((w >> 1) ? XO_ZD : XO_ZC) + (Cz & 7) * 272 + (1 + (Cz >> 3)) * 16;
#pragma unroll
            for (int ob = 0; ob < 2; ob++) stsm_x4(zc + ob * 128, pack2(Z16[8 * ob], Z16[8 * ob + 1]), pack2(Z16[8 * ob + 2], Z16[8 * ob + 3]), pack2(Z16[8 * ob + 4], Z16[8 * ob + 5]), pack2(Z16[8 * ob + 6], Z16[8 * ob + 7]));
            if (lane < 8) *(uint4*)(sm + (cb - sb) + ((w < 2) ? (XO_ZA + w * 3200 + lane * 400) : (XO_ZC + (w - 2) * 2176 + lane * 272))) = make_uint4(0, 0, 0, 0);
        }
        {
#pragma unroll
            for (int i = 0; i < 16; i++) D[i] = 0.f;
            uint32_t pa = cb + XO_TD + (8 + 16 * w + g - 2 * t) * 4;
            uint32_t dlo = (((cb + 9 * 16) & 0x3FFFF) >> 4) | ((ULBO >> 4) << 16);
#define DS(o) (((uint64_t)(128 >> 4) << 32) | (uint64_t)(dlo + (o)))
#define KST (2 * (ULBO / 16))
            uint32_t pA[9], pB[9];
#pragma unroll
            for (int s = 0; s < 9; s++) pA[s] = lds32(pa + s * 32);
#pragma unroll 1
            for (int j = 0; j < 4; j++) {
                WG_FENCE();
#pragma unroll
                for (int q = 0; q < 4; q++) wg32(D, TQ(pA, q), DS((3 - q) * KST));
                WG_COMMIT();
                WG_WAIT(1);
#pragma unroll
                for (int s = 0; s < 9; s++) pB[s] = lds32(pa + 256 + s * 32);
                WG_FENCE();
#pragma unroll
                for (int q = 0; q < 4; q++) wg32(D, TQ(pB, q), DS((3 - q) * KST - 1));
                WG_COMMIT();
                WG_WAIT(1);
#pragma unroll
                for (int s = 0; s < 9; s++) pA[s] = lds32(pa + 512 + s * 32);
                dlo -= 2; pa += 512;
            }
            pB[1] = lds32(pa + 256 + 32); pB[2] = lds32(pa + 256 + 64);
            WG_FENCE();
#pragma unroll
            for (int q = 0; q < 4; q++) wg32(D, TQ(pA, q), DS((3 - q) * KST));
            wg32(D, pB[1], pB[2], pA[8], pB[1], DS(3 * KST - 1));
            WG_COMMIT();
        }
    }
    {
        named_bar(1 + wgi, 128);
        uint32_t u[2][4];
        {
            const uint4* pq = M.box + (6 + g - 2 * t);
            auto at = [&](int k, int pitch) { const int c = 2 * w + k; return cb + (c & 7) * pitch + (c < 0 ? 0 : 16) + lr * 16; };
            const int h1 = lm & 1;
            const uint32_t h2 = (lm >> 1) * 128;
            uint32_t bA[3][4], bB[2][4], bB3[2], bC[2][4], bD[2][4], bU[4], bU1[2];
            const uint32_t p0 = at(h1, 400) + XO_ZA;
            WG_WAIT(0);
            const uint4 m0 = pq[0], m1 = pq[14];
            ldsm_x4(bA[0], p0 + h2); ldsm_x4(bA[1], at(h1 - 2, 400) + XO_ZA + h2); ldsm_x4(bA[2], at(lm - 2, 400) + XO_ZA + 256);
            ldsm_x4(bB[0], p0 + 3200 + h2); ldsm_x2(bB3, p0 + 3200 + 256); ldsm_x4(bB[1], at(-1, 400) + XO_ZB + lm * 128);
            mma_bf16(D + 4, m0.x, m0.y, 0u, m0.x, bA[0][0], bA[0][1]);
            mma_bf16(D + 8, m0.x, m0.y, 0u, m0.x, bA[0][2], bA[0][3]);
            mma_bf16(D + 12, m0.x, m0.y, 0u, m0.x, bA[2][2], bA[2][3]);
            mma_bf16(D + 4, m0.z, 0u, m0.y, m0.z, bA[1][0], bA[1][1]);
            mma_bf16(D + 8, m0.z, 0u, m0.y, m0.z, bA[1][2], bA[1][3]);
            mma_bf16(D + 12, m0.z, 0u, m0.y, m0.z, bA[2][0], bA[2][1]);
            ldsm_x4(bC[0], at(h1 - 1, 272) + XO_ZC + h2); ldsm_x4(bC[1], at(h1 - 3, 272) + XO_ZC + h2);
            const uint4 m2 = pq[28];
            const uint32_t k2 = lds32(cb + XO_K1024), x0 = m2.w & k2, x8 = pq[42].x & k2;
            mma_bf16(D + 4, m0.w, m1.x, 0u, m0.w, bB[0][0], bB[0][1]);
            mma_bf16(D + 8, m0.w, m1.x, 0u, m0.w, bB[0][2], bB[0][3]);
            mma_bf16(D + 12, m0.w, m1.x, 0u, m0.w, bB3[0], bB3[1]);
            mma_k8(D + 4, m1.x, 0u, bB[1][0]);
            ldsm_x4(bD[0], at(h1, 272) + XO_ZD + h2); ldsm_x4(bD[1], at(h1 - 2, 272) + XO_ZD + h2);
            ldsm_x4(bU, at(h1, ULBO) + 128 + h2); ldsm_x2(bU1, at(-1, ULBO) + 128 + h1 * 128);
            ldsm_x4_t(u[0], cb + 2 * w * ULBO + 144 + lane * 16); ldsm_x4_t(u[1], cb + (2 * w + 1) * ULBO + 144 + lane * 16);
            const uint32_t dk2 = __byte_perm(lds32(cb + XO_DSK), 0, (rank & 1) ? 0x3232 : 0x1010);
#pragma unroll
            for (int c = 0; c < 2; c++) mma_bf16(D + 8 + 4 * c, m1.y, m1.z, 0u, m1.y, bC[0][2 * c], bC[0][2 * c + 1]);
#pragma unroll
            for (int c = 0; c < 2; c++) mma_bf16(D + 8 + 4 * c, m1.w, 0u, m1.z, m1.w, bC[1][2 * c], bC[1][2 * c + 1]);
#pragma unroll
            for (int c = 0; c < 2; c++) mma_bf16(D + 8 + 4 * c, m2.x, m2.y, 0u, m2.x, bD[0][2 * c], bD[0][2 * c + 1]);
#pragma unroll
            for (int i = 0; i < 8; i++) u[i >> 2][i & 3] = mul2(u[i >> 2][i & 3], dk2);
#pragma unroll
            for (int c = 0; c < 2; c++) mma_bf16(D + 8 + 4 * c, m2.z, 0u, m2.y, m2.z, bD[1][2 * c], bD[1][2 * c + 1]);
#pragma unroll
            for (int c = 0; c < 2; c++) mma_bf16(D + 8 + 4 * c, x0, x8, 0u, x0, bU[2 * c], bU[2 * c + 1]);
#pragma unroll
            for (int c = 0; c < 2; c++) mma_bf16(D + 8 + 4 * c, m1.x, 0u, x8, 0u, bB[1][1 + c], bU1[c]);
        }
        {
            mbar_wait(MB(MB_C2), 0);
            const uint32_t ga2 = M.ga[wgi];
#pragma unroll
            for (int h = 0; h < 2; h++) {
                const uint32_t rb = mapa(sb, 2 * w + h);
#pragma unroll
                for (int j = 0; j < 4; j++) u[h][j] = mul2(ga2, add2(pack2(D[4 * j + 2 * h], D[4 * j + 2 * h + 1]), u[h][j]));
                sta4(rb + OFF_V + (8 * wgi + rank) * VP + lane * 16, make_uint4(u[h][0], u[h][1], u[h][2], u[h][3]), rb + (MB(MB_V) - sb));
            }
        }
    }
}

#define WMD 400
#define PU 400
#define PD 100
#define PFG 2
#define CWP 200
#define CWD 5000
#define LN1POS 1
#define SLOT(key) (((~(key) >> 2) & 0x78u) | ((key) & 7u))
#define ROW(key) (((~(key) << 2) & 0xE0u) | ((~(key) >> 7) & 24u) | ((~(key) >> 11) & 6u) | ((~(key) >> 9) & 1u))
#define CE(a, b) { const uint32_t hi_ = max(a, b); b = min(a, b); a = hi_; }
#define POP(k, m) if (k.x == m) { k.x = k.y; k.y = k.z; k.z = k.w; k.w = 0u; }
#define CGT(c, a, b, n) asm volatile("{\n.reg .pred p;\nsetp.gt.u32 p, %1, %2;\n@p add.u32 %0, %0, " #n ";\n}" : "+r"(c) : "r"(a), "r"(b))
#define RESET() _Pragma("unroll") for (int i = 0; i < 4; i++) if (i < 3 || lane < 24) st_rlx4((uint4*)S->acc2 + 120 * b + 32 * i + lane, make_uint4(0, 0, 0, 0))
#define CL_ARRIVE() asm volatile("barrier.cluster.arrive.relaxed.aligned;" ::: "memory")
#define CL_WAIT() asm volatile("barrier.cluster.wait.aligned;" ::: "memory")
__global__ void __cluster_dims__(8, 1, 1) __launch_bounds__(NTHR, 1)
clus_kernel(const bf16* __restrict__ x, const bf16* __restrict__ logAr, const bf16* __restrict__ Aim, const bf16* __restrict__ Cr, const bf16* __restrict__ Ci,
            const bf16* __restrict__ logdt, const bf16* __restrict__ c_in, Scratch* __restrict__ S, const bf16* __restrict__ Dskip,
            const bf16* __restrict__ w_r, const bf16* __restrict__ w_mod, bf16* __restrict__ out,
            const __grid_constant__ CUtensorMap tm_wm, const __grid_constant__ CUtensorMap tm_wg,
            const __grid_constant__ CUtensorMap tm_wu, const __grid_constant__ CUtensorMap tm_wd, const __grid_constant__ CUtensorMap tm_out) {
    extern __shared__ __align__(1024) unsigned char sm[];
    Misc& M = *(Misc*)(sm + OFF_MISC);
    const uint32_t sb = (uint32_t)__cvta_generic_to_shared(sm);
    const int tid = threadIdx.x < 128 ? threadIdx.x + 640 : threadIdx.x - 128, warp = __shfl_sync(0xffffffffu, tid >> 5, 0), lane = tid & 31;
    const int g = lane >> 2, t = lane & 3, lr = lane & 7, lm = lane >> 3;
    const int wgi = warp >> 2, w = warp & 3;
    const int b = blockIdx.x, cl = b >> 3, rk = b & 7;
    auto mod_ld = [&](uint32_t (*a)[4], uint32_t s0, uint32_t s1, int i) {
        const uint32_t wa = sb + ((lm & 1) ? s1 : s0) + (lr + 8 * (lm >> 1)) * 80 + i * 16;
#pragma unroll
        for (int ks = 0; ks < 4; ks++) ldsm_x4_t(a[ks], wa + ks * 1280);
        ldsm_x2_t(a[4], wa + 5120);
    };
    auto mod_mma2 = [&](float* d, float* e, uint32_t (*a)[4], uint32_t (*c)[4], const uint32_t* bs) {
        mma_k8(d, a[4][0], a[4][1], bs[8]); mma_k8(e, c[4][0], c[4][1], bs[8]);
#pragma unroll
        for (int ks = 0; ks < 4; ks++) {
            mma_bf16(d, a[ks][0], a[ks][1], a[ks][2], a[ks][3], bs[2 * ks], bs[2 * ks + 1]);
            mma_bf16(e, c[ks][0], c[ks][1], c[ks][2], c[ks][3], bs[2 * ks], bs[2 * ks + 1]);
        }
    };
    auto mod_st = [&](const float* d, uint32_t dst, int mb) {
#pragma unroll
        for (int h = 0; h < 2; h++) {
            const uint32_t rb = mapa(sb, t + 4 * h);
            sta2(rb + dst + g * 8, __float_as_uint(d[0]), __float_as_uint(d[2]), rb + (MB(mb) - sb));
        }
    };
    if (wgi == 5) {
        CL_ARRIVE();
        const uint32_t c_a = ld_nc((const uint32_t*)c_in + 36 * rk + lane), c_b = ld_nc((const uint32_t*)c_in + 36 * rk + 32 + t);
        {
            pace(WMD);
            const char* wp = (const char*)(w_mod + (72 * rk + 18 * w) * (6 * D_) + 40 * cl);
#pragma unroll
            for (int i = 0; i < 3; i++) {
                const uint32_t c = lane + 32 * i, row = (c * 205) >> 10;
                const char* p = wp + (row * (12 * D_ - 80) + 16 * c);
                if (c < 90) {
                    asm volatile("cp.async.cg.shared.global [%0], [%1], 16;" ::"r"(sb + OFF_WM0 + 1440 * w + 16 * c), "l"(p) : "memory");
                    asm volatile("cp.async.cg.shared.global [%0], [%1], 16;" ::"r"(sb + OFF_WM0 + 5760 + 1440 * w + 16 * c), "l"(p + 2 * D_) : "memory");
                }
            }
            if (w == 3 && lane < 20)
                asm volatile("cp.async.ca.shared.global [%0], [%1], 4, %2;" ::"r"(sb + OFF_MISC + (uint32_t)offsetof(Misc, c2) + 12 + 16 * lane), "l"((const uint32_t*)w_r + min(20 * cl + lane, D_ / 2 - 1)),
                             "r"(20 * cl + lane < D_ / 2 ? 4 : 0) : "memory");
            asm volatile("cp.async.commit_group;" ::: "memory");
        }
        auto gsum = [&](uint32_t a, int pitch) {
            float4 s = make_float4(0.f, 0.f, 0.f, 0.f);
#pragma unroll
            for (int i = 0; i < 8; i++) { const float4 q = *(const float4*)(sm + a + i * pitch); s.x += q.x; s.y += q.y; s.z += q.z; s.w += q.w; }
            return make_uint2(pack2(s.x, s.z), pack2(s.y, s.w));
        };
        auto one_plus = [&](uint32_t v) { return pack2(1.0f + lo2f(v), 1.0f + hi2f(v)); };
        {
            uint32_t bs[9], a[5][4], c[5][4];
            float d[4] = {0.f, 0.f, 0.f, 0.f}, e[4] = {0.f, 0.f, 0.f, 0.f};
            const uint32_t sc = pack2(silu(lo2f(c_a)), silu(hi2f(c_a)));
            bs[8] = pack2(silu(lo2f(c_b)), silu(hi2f(c_b)));
            if (w == 2) { sts32(sb + OFF_SC + 4 * lane, sc); sts32(sb + OFF_SC + 128 + 4 * t, bs[8]); }
#pragma unroll
            for (int ks = 0; ks < 8; ks++) bs[ks] = __shfl_sync(0xffffffffu, sc, 4 * ks + t);
            CL_WAIT();
            asm volatile("cp.async.wait_group 0;" ::: "memory");
            named_bar(10, 128);
            mod_ld(a, OFF_WM0 + 5760, OFF_WM0, w);
            mod_ld(c, OFF_WM0 + 5760, OFF_WM0, 4);
            mod_mma2(d, e, a, c, bs);
            mod_st(d, OFF_MG1 + rk * 320 + 64 * w, MB_MG1);
            if (w == 1) mod_st(e, OFF_MG1 + rk * 320 + 256, MB_MG1);
        }
        {
            const int n0 = 8 * w + ((3 - rk) & 3), n1 = (n0 + 4 + t) & 31;
            const float4* ap = &S->acc1[256 * rk + 8 * (n0 + t) + g];
            const float4* aq = &S->acc1[256 * rk + 8 * n1 + g];
            named_bar(9, 640);
            if (w == 2 && lane == 0) {
#pragma unroll
                for (int i = 2; i < 6; i++) tma2d(sb + (i == 5 ? OFF_WM0 + 11520 : OFF_WM2 + (i - 2) * 5760), &tm_wm, i * D_ + 40 * cl, 72 * rk, MB(MB_WM2));
            }
            __syncwarp();
            if (w == 3) mbar_wait(MB(MB_MG1), 0);
            float4 pa = ld_rlx4f(ap), pb = ld_rlx4f(aq);
            if (w == 3) {
                const uint2 v = gsum(OFF_MG1 + 16 * min(lane, 19), 320);
                const uint32_t c1 = one_plus(v.x);
                if (lane < 20) *(uint4*)(sm + OFF_C1 + 16 * lane) = make_uint4(__byte_perm(c1, 0, 0x1010), __byte_perm(v.y, 0, 0x1010), __byte_perm(c1, 0, 0x3232), __byte_perm(v.y, 0, 0x3232));
                __syncwarp();
                named_arrive(10, 128);
            }
            uint32_t xq[2][5][4];
            uint2 cc[5];
            const uint32_t xa = sb + OFF_X + XI(2 * lm + (lr & 1)) + XN(n0 + (lr >> 1)), xb = sb + OFF_X + XI(2 * lm + (lr & 1)) + XN((n0 + 4 + (lr >> 1)) & 31);
            const uint32_t ua = mapa(sb, g) + OFF_CH;
#pragma unroll
            for (int j = 0; j < 5; j++) ldsm_x4_t(xq[0][j], xa + 16 * j);
#pragma unroll 1
            for (int it = 0; it < SPIN_MAX && (pa.w != (float)NCL || pb.w != (float)NCL); it++) { pa = ld_rlx4f(ap); pb = ld_rlx4f(aq); }
            __syncwarp();
            if (w == 2 && lane < PFG) tma2d_pf(&tm_wg, 40 * b, 192 * lane);
            __syncwarp();
            float m0, r0, m1, r1;
            ln_stats(pa.x, pa.y, m0, r0);
            ln_stats(pb.x, pb.y, m1, r1);
            const uint32_t rh = pack2(r0, r1), rl = pack2(r0 - lo2f(rh), r1 - hi2f(rh));
            const uint32_t stage = sb + OFF_STG + w * 512;
            stsm_x4_t(stage + lane * 16, pack2(m0, m1), rh, rl, rl);
            __syncwarp();
            if (w != 3) named_bar(10, 128);
            uint4 st[2][3];
#pragma unroll
            for (int q = 0; q < 2; q++)
#pragma unroll
                for (int i = 0; i < 3; i++) st[q][i] = lds128(stage + 128 * i + (2 * t + q) * 16);
#pragma unroll
            for (int j = 0; j < 5; j++) cc[j] = *(const uint2*)(sm + OFF_C1 + 64 * j + 8 * g);
            ldsm_x4_t(xq[1][0], xb);
            const uint32_t u0 = ua + rk * ULBO + (9 + n0 + t) * 16, u1 = ua + rk * ULBO + (9 + n1) * 16;
#pragma unroll
            for (int j = 0; j < 5; j++) {
                if (j >= 2 && cl == 14) break;
                if (j < 4) ldsm_x4_t(xq[1][j + 1], xb + 16 * (j + 1));
#pragma unroll
                for (int q = 0; q < 2; q++) {
                    const uint4 sm_ = st[q][0], sh = st[q][1], sl = st[q][2];
                    const uint32_t v0 = add2(mul2(norm2(xq[q][j][0], sm_.x, sh.x, sl.x), cc[j].x), cc[j].y), v1 = add2(mul2(norm2(xq[q][j][1], sm_.y, sh.y, sl.y), cc[j].x), cc[j].y);
                    const uint32_t v2 = add2(mul2(norm2(xq[q][j][2], sm_.z, sh.z, sl.z), cc[j].x), cc[j].y), v3 = add2(mul2(norm2(xq[q][j][3], sm_.w, sh.w, sl.w), cc[j].x), cc[j].y);
                    asm volatile("{\n.reg .pred p;\nsetp.ne.u32 p, %6, %7;\n"
                                 "@p st.async.weak.shared::cluster.mbarrier::complete_tx::bytes.v4.b32 [%0], {%1,%2,%3,%4}, [%5];\n"
                                 "@!p st.shared.v4.b32 [%0], {%1,%2,%3,%4};\n}"
                                 ::"r"((q ? u1 : u0) + j * CHS), "r"(v0), "r"(v1), "r"(v2), "r"(v3), "r"(ua + j * CHS + XO_MBU), "r"(g), "r"(rk) : "memory");
                }
                __syncwarp();
                if (lane == 0) mbar_arrive(sb + OFF_CH + XO_MBU + j * CHS);
            }
        }
        asm volatile("setmaxnreg.dec.sync.aligned.u32 40;");
        {
        int cl;
        asm volatile("mov.u32 %0, %clusterid.x;" : "=r"(cl));
        const int w = __shfl_sync(0xffffffffu, (fresh_tid() >> 5) & 3, 0);
        if (w) named_arrive(11, 128); else named_bar(11, 128);
        if (w == 0) {
            const int lane = fresh_tid() & 31;
            mbar_wait(MB(MB_KD), 0);
            PROXY_FENCE();
            if (lane == 0) {
#pragma unroll
                for (int i = 0; i < 3; i++) tma2d(sb + OFF_WG + i * 15360, &tm_wg, 40 * b, 192 * i, MB(MB_WG));
                mbar_wait(MB(MB_C2), 0);
                PROXY_FENCE();
#pragma unroll 1
                for (int i = 0; i < 3; i++) { pace(PU); tma2d(sb + OFF_WU + i * 15360, &tm_wu, 40 * b, 192 * i, MB(MB_WU)); }
                mbar_wait(MB(MB_WU), 0);
#pragma unroll 1
                for (int i = 0; i < 9; i++) { pace(PD); tma2d_pf(&tm_wd, 64 * i, 40 * b); }
            }
            __syncwarp();
            mbar_wait(MB(MB_KD), 1);
            PROXY_FENCE();
            if (lane < 9) tma2d(sb + OFF_WD + lane * 5120, &tm_wd, 64 * lane, 40 * b, MB(MB_WD));
            __syncwarp();
        } else if (w == 1) {
            const int lane = fresh_tid() & 31;
            {
                RESET();
                uint32_t z = 0;
#pragma unroll
                for (int i = 0; i < 4; i++) z |= ld_rlx((const unsigned int*)((uint4*)S->acc2 + 120 * b + (i < 3 ? 32 * i + lane : 96 + min(lane, 23))) + 3);
                z = __reduce_or_sync(0xffffffffu, z);
                if (lane == 0) asm volatile("red.relaxed.gpu.global.add.f32 [%0], %1;" ::"l"(&S->acc1[L_].z), "f"(__uint_as_float(z | 0x3F800000u)) : "memory");
            }
        } else if (w == 2) {
            if ((fresh_tid() & 31) == 0) {
                float4 v;
                int it = 0;
                pace(CWD);
                for (;;) { v = ld_rlx4f(&S->acc1[L_]); if (++it >= SPIN_MAX || (v.z == (float)G_ && v.w == (float)NCL)) break; pace(CWP); }
                M.cws[0] = v.x; M.cws[1] = v.y;
                mbar_arrive(MB(MB_CW));
            }
        } else {
            const int lane = fresh_tid() & 31, l20 = min(lane, 19);
            mbar_wait(MB(MB_MG2), 0);
            const uint2 v = gsum(OFF_MG2 + 16 * l20, 640), u = gsum(OFF_MG2 + 320 + 16 * l20, 640);
            const uint32_t wr = lane < 20 ? M.c2[lane].w : 0u, cb1 = one_plus(v.x), cw = mul2(cb1, wr);
            if (lane < 20) {
                M.c2[lane] = make_uint4(cb1, v.y, u.x, cw);
                M.wr[lane] = wr;
                unsigned e;
                asm volatile("mov.u32 %0, %cluster_ctarank;" : "=r"(e));
                if ((lane & 3) == (e >> 1)) M.ga[lane >> 2] = __byte_perm(u.y, 0, (e & 1) ? 0x3232 : 0x1010);
            }
            __syncwarp();
            if (lane == 0) mbar_arrive(MB(MB_C2));
            if (rk == 0) {
                float a = lo2f(cw) + hi2f(cw), s = lo2f(v.y) * lo2f(wr) + hi2f(v.y) * hi2f(wr);
#pragma unroll
                for (int o = 16; o; o >>= 1) { a += __shfl_xor_sync(0xffffffffu, a, o); s += __shfl_xor_sync(0xffffffffu, s, o); }
                if (lane == 0) red4(&S->acc1[L_], a, s, 0.f);
                mbar_wait(MB(MB_CW), 0);
                const int P = 20 * cl + lane;
                if (lane < 20 && P < D_ / 2) st_rlx(GBV(P), ~u.x);
            }
        }
        {
        const int lane = fresh_tid() & 31, t = lane & 3, lr = lane & 7, lm = lane >> 3;
        uint32_t aw[5];
        __syncwarp();
        mbar_wait(MB(MB_C2), 0);
#pragma unroll
        for (int j = 0; j < 5; j++) aw[j] = M.wr[4 * j + t];
        const int ph = w >> 1, lst = 16 * ph + 2 * rk + (w & 1);
        const uint32_t rb = mapa(sb, lr);
        named_bar(6, 640);
        uint4 k = *(const uint4*)&M.key[128 * (w & 1) + 4 * lane];
        CE(k.x, k.y); CE(k.z, k.w); CE(k.x, k.z); CE(k.y, k.w); CE(k.y, k.z);
        uint32_t m[4];
#pragma unroll 1
        for (int q = 0; q <= ph; q++) {
#pragma unroll
            for (int rnd = 0; rnd < 4; rnd++) {
                m[rnd] = __reduce_max_sync(0xffffffffu, k.x);
                POP(k, m[rnd]);
            }
        }
        if (lane < 8) sta4(rb + OFF_MISC + (uint32_t)offsetof(Misc, cand) + lst * 16, make_uint4(m[0], m[1], m[2], m[3]), rb + (MB(MB_KEY2) - sb));
        const uint32_t mine = (t & 2) ? ((t & 1) ? m[3] : m[2]) : ((t & 1) ? m[1] : m[0]);
        const uint32_t ra = sb + OFF_H2T + ROW(mine) * 80;
        uint32_t bq[6];
        float rr[4] = {0.f, 0.f, 0.f, 0.f};
        ldsm_x4(bq, ra + 16 * lm); ldsm_x2(bq + 4, ra + 64);
        mma_bf16(rr, aw[0], aw[0], aw[1], aw[1], bq[0], bq[1]); mma_bf16(rr, aw[2], aw[2], aw[3], aw[3], bq[2], bq[3]); mma_k8(rr, aw[4], aw[4], bq[4]);
        float4* p = &S->rs[8 * lst];
        if (lane < 2) red4(p + lane, rr[0], 1.0f, rr[1]);
        float4 e0 = ld_rlx4f(p), e1 = ld_rlx4f(p + 1);
        uint32_t sl = 0;
        if (w == 1) {
            mbar_wait(MB(MB_KEY2), 0);
            k = *(const uint4*)&M.cand[4 * lane];
            if (b == 0 && lane == 0) st_rlx4(&S->acc1[L_], make_uint4(0, 0, 0, 0));
            named_bar(14, 64);
#pragma unroll
            for (int s = 0; s < 8; s++) {
                const uint32_t v = M.sel[s] & ~1u;
                if (k.x == v) sl |= 8 + s;
                if (k.y == v) sl |= (8 + s) << 8;
                if (k.z == v) sl |= (8 + s) << 16;
                if (k.w == v) sl |= (8 + s) << 24;
            }
        }
        if (w == 0) {
            named_bar(8, 64);
            if (lane == 0) {
                PROXY_FENCE();
                tma5d_st(&tm_out, 40 * cl, 8 * rk, sb + OFF_OUT);
                asm volatile("cp.async.bulk.commit_group;" ::: "memory");
            }
            __syncwarp();
        }
#pragma unroll 1
        for (int it = 0; it < SPIN_MAX && (e0.w != (float)NCL || e1.w != (float)NCL); it++) { e0 = ld_rlx4f(p); e1 = ld_rlx4f(p + 1); }
        {
            const uint32_t r0 = pack2(e0.x, e0.z), r1 = pack2(e1.x, e1.z);
            const uint32_t o0 = r0 ^ (sign2(r0) | 0x80008000u), o1 = r1 ^ (sign2(r1) | 0x80008000u);
            if (lane < 8) sta4(rb + OFF_EK + lst * VP, make_uint4((o0 << 16) | (m[0] & 0x3FFFu), (o0 & 0xFFFF0000u) | (m[1] & 0x3FFFu), (o1 << 16) | (m[2] & 0x3FFFu), (o1 & 0xFFFF0000u) | (m[3] & 0x3FFFu)),
                               rb + (MB(MB_EK) - sb));
        }
        if (w == 0) {
            if (lane == 0) {
                asm volatile("cp.async.bulk.wait_group 0;" ::: "memory");
                asm volatile("fence.acq_rel.gpu;" ::: "memory");
                mbar_arrive(MB(MB_OUT));
            }
        } else if (w == 1) {
            const uint32_t found = __reduce_add_sync(0xffffffffu, __popc(sl & 0x08080808u));
            mbar_wait(MB(MB_EK), 0);
            k = lds128(sb + OFF_EK + lane * VP);
            const bool s0 = sl & 8u, s1 = sl & 0x800u, s2 = sl & 0x80000u, s3 = sl & 0x8000000u;
            if (s0) M.fin[sl & 7u] = k.x;
            if (s1) M.fin[(sl >> 8) & 7u] = k.y;
            if (s2) M.fin[(sl >> 16) & 7u] = k.z;
            if (s3) M.fin[(sl >> 24) & 7u] = k.w;
            const uint32_t lo = min(min(s0 ? k.x : ~0u, s1 ? k.y : ~0u), min(s2 ? k.z : ~0u, s3 ? k.w : ~0u));
            const uint32_t hi = max(max(s0 ? 0u : k.x, s1 ? 0u : k.y), max(s2 ? 0u : k.z, s3 ? 0u : k.w));
            const bool redo = __reduce_max_sync(0xffffffffu, hi) > __reduce_min_sync(0xffffffffu, lo) || found != 8u;
            if (redo) {
                CE(k.x, k.y); CE(k.z, k.w); CE(k.x, k.z); CE(k.y, k.w); CE(k.y, k.z);
                __syncwarp();
#pragma unroll 1
                for (int rnd = 0; rnd < 8; rnd++) {
                    const uint32_t m8 = __reduce_max_sync(0xffffffffu, k.x);
                    POP(k, m8);
                    if (lane == 0) M.fin[rnd] = m8;
                }
            }
            if (lane == 0) M.fin[8] = redo;
            __syncwarp();
            named_arrive(12, 672);
        }
        }
        }
    } else {
    if (warp != 19) CL_ARRIVE();
    const int chn = 40 * cl + 8 * wgi + rk;
    const bool has_ch = chn < D_;
    const uint32_t cb = sb + OFF_CH + wgi * CHS;
    unsigned short r_ldt = 0, r_lar = 0, r_aim = 0, r_cr = 0, r_ci = 0;
    {
        const int n = min(chn, D_ - 1) * N_ + (tid & 127);
        r_ldt = ld_nc16((const unsigned short*)logdt + min(chn, D_ - 1));
        r_lar = ld_nc16((const unsigned short*)logAr + n);
        r_aim = ld_nc16((const unsigned short*)Aim + n);
        r_cr = ld_nc16((const unsigned short*)Cr + n);
        r_ci = ld_nc16((const unsigned short*)Ci + n);
    }
    if (warp == 19) {
        if (lane == 0) asm volatile("prefetch.tensormap [%0];" ::"l"(&tm_wm) : "memory");
        const uint32_t lo = 90u | (10u << 8) | (20u << 16) | (2u << 24), hi = (cl == 14 ? 32u : 80u) | ((rk < 4 ? 40u : 32u) << 8) | (180u << 16) | (180u << 24);
        const uint32_t tx = lane < 8 ? (((lane & 4 ? hi : lo) >> (8 * (lane & 3))) & 255u) : lane == 8 ? 180u : lane < 11 ? 2u : lane == 11 ? (hi >> 8) & 255u : 14u;
        if (lane == 0) {
#pragma unroll
            for (int i = 0; i < MB_N; i++) mbar_init(MB(i), i == MB_KD ? 20 : 1);
#pragma unroll
            for (int i = 0; i < 5; i++) mbar_init(sb + OFF_CH + XO_MBU + i * CHS, 5);
        }
        __syncwarp();
        if (lane < 17) mbar_expect(lane < MB_C2 ? MB(lane) : sb + OFF_CH + XO_MBU + (lane - MB_C2) * CHS, tx << 8);
        asm volatile("fence.mbarrier_init.release.cluster;" ::: "memory");
        __syncwarp();
        CL_ARRIVE();
    }
    if (warp < 16) {
        const char* xp = (const char*)(x + (128 * warp + 8 * rk) * D_ + 40 * cl);
#pragma unroll
        for (int i = 0; i < 3; i++) {
            const uint32_t c = lane + 32 * i, row = (c * 205) >> 10, hi = c >= 40;
            if (c < 80) asm volatile("cp.async.cg.shared.global [%0], [%1], 16, %2;" ::"r"(sb + OFF_X + XN(2 * warp) + XI(row & 7) + 80 * (hi - row) + 16 * c), "l"(xp + (row * (2 * D_ - 80) + 16 * c + hi * (56 * 2 * D_))),
                                     "r"((cl < 14 || c - 5 * row < 2) ? 16 : 0) : "memory");
        }
    }
    if ((tid & 127) == 32) asm volatile("cp.async.ca.shared.global [%0], [%1], 4;" ::"r"(cb + XO_DSK), "l"((const uint32_t*)Dskip + (min(chn, D_ - 1) >> 1)) : "memory");
    asm volatile("cp.async.commit_group;" ::: "memory");
    auto mod2 = [&]() {
        if (wgi == 4) {
            uint32_t bs[9], a[5][4], c[5][4];
            float d[4] = {0.f, 0.f, 0.f, 0.f}, e[4] = {0.f, 0.f, 0.f, 0.f}, f[4] = {0.f, 0.f, 0.f, 0.f};
            mbar_wait(MB(MB_MG1), 0);
#pragma unroll
            for (int ks = 0; ks < 9; ks++) bs[ks] = lds32(sb + OFF_SC + 16 * ks + 4 * t);
            mbar_wait(MB(MB_WM2), 0);
            mod_ld(a, OFF_WM2 + 11520, OFF_WM2 + 5760, w);
            mod_ld(c, OFF_WM0 + 11520, OFF_WM2, w);
            mod_mma2(d, e, a, c, bs);
            mod_ld(a, (w & 1) ? OFF_WM0 + 11520 : OFF_WM2 + 11520, (w & 1) ? OFF_WM2 : OFF_WM2 + 5760, 4);
            mod_st(d, OFF_MG2 + rk * 640 + 64 * w, MB_MG2);
            mod_st(e, OFF_MG2 + rk * 640 + 320 + 64 * w, MB_MG2);
            d[0] = d[1] = d[2] = d[3] = 0.f;
            mma_k8(d, a[4][0], a[4][1], bs[8]);
#pragma unroll
            for (int ks = 0; ks < 4; ks++) mma_bf16((ks & 1) ? d : f, a[ks][0], a[ks][1], a[ks][2], a[ks][3], bs[2 * ks], bs[2 * ks + 1]);
            d[0] += f[0]; d[2] += f[2];
            if (w < 2) mod_st(d, OFF_MG2 + rk * 640 + 320 * w + 256, MB_MG2);
            __syncwarp();
        }
    };
    auto ln1 = [&]() {
        if (warp < 16) {
            uint32_t a[10];
            const uint32_t xa = sb + OFF_X + XN(2 * warp) + (lm & 1) * 80 + XI(lr) + (lm >> 1) * 16;
            asm volatile("cp.async.wait_group 0;" ::: "memory");
            __syncwarp();
            ldsm_x4(a, xa); ldsm_x4(a + 4, xa + 32); ldsm_x2(a + 8, xa + 64);
            named_arrive(9, 640);
            float c1[4] = {0.f, 0.f, 0.f, 0.f}, c2[4] = {0.f, 0.f, 0.f, 0.f}, c3[4] = {0.f, 0.f, 0.f, 0.f};
#pragma unroll
            for (int j = 0; j < 2; j++) {
                mma_bf16(c1, a[4 * j], a[4 * j + 1], a[4 * j + 2], a[4 * j + 3], 0x3F803F80u, 0x3F803F80u);
                mma_bf16(c2, a[4 * j], a[4 * j + 1], a[4 * j + 2], a[4 * j + 3], a[4 * j], a[4 * j + 2]);
                mma_bf16(c3, a[4 * j], a[4 * j + 1], a[4 * j + 2], a[4 * j + 3], a[4 * j + 1], a[4 * j + 3]);
            }
            mma_k8(c1, a[8], a[9], 0x3F803F80u); mma_k8(c2, a[8], a[9], a[8]); mma_k8(c3, a[8], a[9], a[9]);
            float4* p = &S->acc1[256 * rk + 16 * warp + g];
            red4p(t == (g >> 1), p, c1[0], (g & 1) ? c2[1] : c2[0], 0.f);
            red4p(t == (g >> 1), p + 8, c1[2], (g & 1) ? c3[3] : c3[2], 0.f);
        }
    };
    {
        const int i = tid & 127;
        unsigned char* cp = sm + OFF_CH + wgi * CHS;
        const uint4 z = make_uint4(0, 0, 0, 0);
        *(uint4*)(cp + XO_TD + i * 16) = z;
        *(uint4*)(cp + XO_TF + i * 16) = z;
        *(uint4*)(cp + XO_U8 - 1024 + (i >> 6) * 4096 + (i & 63) * 16) = z;
        const int c = (i * 57) >> 9;
        if (i < 108) *(uint4*)(cp + (i < 72 ? c * ULBO + (i - 9 * c) * 16 : XO_TD + 2048 - 72 * 16 + i * 16)) = z;
    }
    if (tid < 224) {
        const int e = tid & 15, l = (tid >> 4) - 6 - (int)((0x3355544433666ull >> (4 * e)) & 15) + 8 * (int)((0x1021021010210ull >> (4 * e)) & 15);
        const unsigned wd = (0x1166688822444ull >> (4 * e)) & 15, one = e >= 11 ? 0xFFFFu : 0x3F80u;
        ((uint32_t*)M.box)[((e >> 2) * 14 + (tid >> 4)) * 4 + (e & 3)] = ((unsigned)l <= wd ? one : 0u) | ((unsigned)(l - 1) <= wd ? one << 16 : 0u);
    }
    const uint32_t scr = sb + warp * KSCR, ws = scr + lane * 4;
    {
        uint32_t zr;
        asm volatile("ld.volatile.shared.u32 %0, [%1];" : "=r"(zr) : "r"(cb + XO_TD + (tid & 127) * 16) : "memory");
        const float p_ldt = __uint_as_float(r_ldt * 65536u + zr), p_lar = __uint_as_float(r_lar * 65536u + zr), p_aim = __uint_as_float(r_aim * 65536u + zr);
        const float p_cr = __uint_as_float(r_cr * 65536u + zr), p_ci = __uint_as_float(r_ci * 65536u + zr);
        float acc[5][4];
        uint32_t afr[4][4], cz[4];
        const uint32_t ba = scr + lr * 144 + lm * 16;
        auto tile = [&](float* c, int rg) {
            __syncwarp();
            c[0] = c[1] = c[2] = c[3] = 0.f;
            uint32_t bb[2][4];
            ldsm_x4(bb[0], ba + rg * 1152);
            ldsm_x4(bb[1], ba + rg * 1152 + 64);
            mma_f16(c, afr[0], bb[0][0], bb[0][1]);
            mma_f16(c, afr[1], bb[0][2], bb[0][3]);
            mma_f16(c, afr[2], bb[1][0], bb[1][1]);
            mma_f16(c, afr[3], bb[1][2], bb[1][3]);
        };
#define CJ(z) packh((z).x, -(z).y)
#define CJP(z) packh((z).y, (z).x)
        const float dt = bfr(expf(p_ldt));
        const float al = -bfr(expf(p_lar)) * dt * 1.4426950408889634f;
        const float th = p_aim * dt;
        const float th_ = th * 0.15915494309189535f;
        const float tl_ = fmaf(th, 0.15915494309189535f, -th_) + th * 6.4206382e-9f;
        auto anchor = [&](float s) {
            float f = th_ * s;
            f -= rintf(f);
            f = fmaf(tl_, s, f) * 6.283185307179586f;
            const float e = fex2(al * s);
            return cplx{e * __cosf(f), e * __sinf(f)};
        };
        const float cx = p_cr * dt * 2.0f, cy = p_ci * dt * 2.0f;
        const uint32_t ex = __reduce_max_sync(0xffffffffu, __float_as_uint(fmaxf(fabsf(cx), fabsf(cy)))) >> 23;
        const float scl = __uint_as_float((254u - ex) << 23);
        const cplx C = cplx{cx * scl, cy * scl};
        const cplx z1 = anchor(1.f), z16 = anchor(16.f), z256 = anchor(256.f);
        {
            const cplx z32 = csq(z16), z48 = cmul(z32, z16), z64 = csq(z32), z128 = csq(z64), z192 = cmul(z128, z64);
            const uint32_t y[3] = {packh(z16.x, z16.y), packh(z32.x, z32.y), packh(z48.x, z48.y)};
            const uint32_t yp[3] = {packh(-z16.y, z16.x), packh(-z32.y, z32.x), packh(-z48.y, z48.x)};
            const uint32_t xx[3] = {packh(z64.x, z64.y), packh(z128.x, z128.y), packh(z192.x, z192.y)};
            sts32(ws, 0x00003C00u);
#pragma unroll
            for (int j = 0; j < 3; j++) sts32(ws + (1 + j) * 144, y[j]);
#pragma unroll
            for (int i = 0; i < 3; i++) {
                sts32(ws + (4 + 4 * i) * 144, xx[i]);
#pragma unroll
                for (int j = 0; j < 3; j++) sts32(ws + (5 + 4 * i + j) * 144, hcm(xx[i], y[j], yp[j]));
            }
        }
        ln1();
        const cplx z2 = csq(z1);
        {
            const cplx z3 = cmul(z2, z1), z4 = csq(z2), z8 = csq(z4);
            const cplx c4 = cmul(C, z4), c8 = cmul(C, z8), c12 = cmul(c8, z4);
            cz[0] = packh(C.x, -C.y); cz[1] = packh(c4.x, -c4.y); cz[2] = packh(c8.x, -c8.y); cz[3] = packh(c12.x, -c12.y);
            __syncwarp();
#pragma unroll
            for (int s = 0; s < 4; s++) ldsm_x4(afr[s], scr + (lr + 8 * (lm & 1)) * 144 + (2 * s + (lm >> 1)) * 16);
            const uint32_t y[3] = {CJ(z1), CJ(z2), CJ(z3)}, yp[3] = {CJP(z1), CJP(z2), CJP(z3)};
#pragma unroll
            for (int tt = 0; tt < 2; tt++) {
                const int rg = tt ? 0 : 2;
#pragma unroll
                for (int i = 0; i < 2; i++) {
                    sts32(ws + rg * 1152 + (4 * i) * 144, cz[2 * tt + i]);
#pragma unroll
                    for (int j = 0; j < 3; j++) sts32(ws + rg * 1152 + (4 * i + 1 + j) * 144, hcm(cz[2 * tt + i], y[j], yp[j]));
                }
                tile(acc[tt], rg);
            }
        }
        const cplx z258 = cmul(z256, z2), z512 = csq(z256), z768 = cmul(z512, z256);
        {
            const uint32_t a0 = CJ(z256), a0p = CJP(z256), a1 = CJ(z258), a1p = CJP(z258);
#pragma unroll
            for (int i = 0; i < 4; i++) { sts32(ws + 1152 + (2 * i) * 144, hcm(cz[i], a0, a0p)); sts32(ws + 1152 + (2 * i + 1) * 144, hcm(cz[i], a1, a1p)); }
            tile(acc[2], 1);
        }
        {
            const uint32_t a0 = CJ(z512), a0p = CJP(z512), a1 = CJ(z768), a1p = CJP(z768);
#pragma unroll
            for (int i = 0; i < 4; i++) { sts32(ws + 2304 + i * 144, hcm(cz[i], a0, a0p)); sts32(ws + 2304 + (4 + i) * 144, hcm(cz[i], a1, a1p)); }
            tile(acc[3], 2);
        }
        const cplx z1024 = csq(z512);
        {
            const cplx zk[4] = {z1024, cmul(z1024, z256), csq(z768), cmul(z1024, z768)};
#pragma unroll
            for (int h = 0; h < 4; h++) {
                const uint32_t a0 = CJ(zk[h]), a0p = CJP(zk[h]);
                sts32(ws + (2 * h) * 144, hcm(cz[0], a0, a0p));
                sts32(ws + (2 * h + 1) * 144, hcm(cz[2], a0, a0p));
            }
            tile(acc[4], 0);
        }
        const cplx z2048 = csq(z1024);
        float last = C.x * z2048.x - C.y * z2048.y;
#pragma unroll
        for (int o = 16; o; o >>= 1) last += __shfl_xor_sync(0xffffffffu, last, o);
        __syncwarp();
#pragma unroll
        for (int i = 0; i < 5; i++) *(float4*)(sm + (scr - sb) + i * 512 + lane * 16) = make_float4(acc[i][0], acc[i][1], acc[i][2], acc[i][3]);
        if (lane == 0) { const float inv = __uint_as_float(ex << 23); sts32(cb + XO_KINV + 4 * w, __float_as_uint(inv)); sts32(cb + XO_KLAST + 4 * w, __float_as_uint(last * inv)); }
        asm volatile("cp.async.wait_group 0;" ::: "memory");
        CL_WAIT();
        named_bar(1 + wgi, 128);
        const uint32_t td = cb + XO_TD + 64 * 4, tf = cb + XO_TF - 32 * 4;
        const float4 ki = *(const float4*)(sm + (cb - sb) + XO_KINV);
        auto fsum = [&](int off, uint32_t& r0, uint32_t& r1) {
            const unsigned char* p = sm + wgi * (4 * KSCR) + off;
            const float4 a = *(const float4*)p, b2 = *(const float4*)(p + KSCR), c = *(const float4*)(p + 2 * KSCR), d = *(const float4*)(p + 3 * KSCR);
            r0 = pack2(fmaf(a.y, ki.x, b2.y * ki.y) + fmaf(c.y, ki.z, d.y * ki.w), fmaf(a.x, ki.x, b2.x * ki.y) + fmaf(c.x, ki.z, d.x * ki.w));
            r1 = pack2(fmaf(a.w, ki.x, b2.w * ki.y) + fmaf(c.w, ki.z, d.w * ki.w), fmaf(a.z, ki.x, b2.z * ki.y) + fmaf(c.z, ki.z, d.z * ki.w));
        };
        uint32_t r[2], q[2];
        fsum(w * 512 + lane * 16, r[0], r[1]);
        fsum(2048 + w * 128 + lr * 16, q[0], q[1]);
        __syncwarp();
        if (lane == 0) mbar_arrive(MB(MB_KD));
        if (w < 2) {
            const uint32_t p = td + (16 * g + 8 * w + 2 * t) * 4;
#pragma unroll
            for (int h = 0; h < 2; h++) { sts16(p + h * 512, r[h] >> 16); sts32(p + h * 512 + 4, r[h]); sts16(p + h * 512 + 10, r[h]); }
        } else if (w == 2) {
            const uint32_t p = td + (256 + 16 * g + 4 * t) * 4;
#pragma unroll
            for (int h = 0; h < 2; h++) {
                const uint32_t k0 = r[h] >> 16;
                if (h || lane) { sts16(p + h * 512 - 4, k0); sts16(p + h * 512 + 2, k0); }
                sts16(p + h * 512, k0); sts32(p + h * 512 + 4, __byte_perm(r[h], 0, 0x3232)); sts32(p + h * 512 + 8, r[h]); sts16(p + h * 512 + 14, r[h]);
            }
        } else {
            const uint32_t p = tf + (64 + 32 * (t >> 1) + 2 * g + (t & 1)) * 4;
#pragma unroll
            for (int h = 0; h < 2; h++) {
                const uint32_t k0 = r[h] >> 16;
                sts16(p + h * 64 + 512, r[h]); sts16(p + h * 64 + 518, r[h]);
                if (h || lane) { sts16(p + h * 64 - 4, k0); sts16(p + h * 64 + 2, k0); }
            }
            if (lane == 0) {
                const uint32_t dd = __byte_perm(r[0], 0, 0x3232);
                sts16(td + 511 * 4, dd); sts32(td + 512 * 4, dd); sts32(td + 513 * 4, dd); sts32(td + 514 * 4, dd); sts16(td + 515 * 4 + 2, dd);
            }
        }
        if (lane < 8) {
            const uint32_t p = tf + 1024 + (64 + 16 * t + 2 * w + g) * 4;
#pragma unroll
            for (int h = 0; h < 2; h++) {
                const uint32_t k0 = q[h] >> 16;
                sts16(p + h * 32 + 512, q[h]); sts16(p + h * 32 + 518, q[h]);
                if (h || (tid & 127)) { sts16(p + h * 32 - 4, k0); sts16(p + h * 32 + 2, k0); }
            }
            if ((tid & 127) == 0) {
                const float4 kl4 = *(const float4*)(sm + (cb - sb) + XO_KLAST);
                const uint32_t kl = f2bits((kl4.x + kl4.y) + (kl4.z + kl4.w)), dd = __byte_perm(q[0], 0, 0x3232);
                sts16(tf + 127 * 4, dd); sts16(tf + 128 * 4 + 2, dd); sts32(cb + XO_K1024, dd);
                sts16(tf + 1024 + 127 * 4, kl); sts16(tf + 1024 + 128 * 4 + 2, kl);
            }
        }
        __syncwarp();
        mod2();
    }
    if (has_ch) {
        conv_channel(sm, rk);
    } else {
        asm volatile("setmaxnreg.inc.sync.aligned.u32 88;");
        mbar_wait(MB(MB_WG), 0);
        mbar_wait(MB(MB_C2), 0);
    }
    {
    const int tid = fresh_tid(), warp = __shfl_sync(0xffffffffu, tid >> 5, 0), lane = tid & 31;
    const int g = lane >> 2, t = lane & 3, lr = lane & 7, lm = lane >> 3;
    __syncwarp();
    if (lane == 0) mbar_arrive(MB(MB_KD));
    uint32_t x1[10];
    if (warp < 16) {
        uint32_t bw[5], v[10];
#pragma unroll
        for (int j = 0; j < 5; j++) bw[j] = (g & 1) ? M.c2[4 * j + t].w : 0x3F803F80u;
        const uint32_t xa = sb + OFF_X + XI(warp >> 1) + (2 * (warp & 1) + (lm & 1)) * XG + lr * 80 + (lm >> 1) * 16;
        const uint32_t va = sb + OFF_V + (8 * (lm >> 1) + lr) * VP + 32 * warp + 16 * (lm & 1);
        ldsm_x4(x1, xa); ldsm_x4(x1 + 4, xa + 32); ldsm_x2(x1 + 8, xa + 64);
        mbar_wait(MB(MB_CW), 0);
        mbar_wait(MB(MB_V), 0);
        ldsm_x4_t(v, va); ldsm_x4_t(v + 4, va + 16 * VP); ldsm_x2_t(v + 8, va + 32 * VP);
#pragma unroll
        for (int i = 0; i < 10; i++) x1[i] = add2(x1[i], (i >= 4 && cl == 14) ? 0u : v[i]);
        float c1[4] = {0.f, 0.f, 0.f, 0.f}, c2[4] = {0.f, 0.f, 0.f, 0.f}, c3[4] = {0.f, 0.f, 0.f, 0.f};
#pragma unroll
        for (int j = 0; j < 2; j++) {
            mma_bf16(c1, x1[4 * j], x1[4 * j + 1], x1[4 * j + 2], x1[4 * j + 3], bw[2 * j], bw[2 * j + 1]);
            mma_bf16(c2, x1[4 * j], x1[4 * j + 1], x1[4 * j + 2], x1[4 * j + 3], x1[4 * j], x1[4 * j + 2]);
            mma_bf16(c3, x1[4 * j], x1[4 * j + 1], x1[4 * j + 2], x1[4 * j + 3], x1[4 * j + 1], x1[4 * j + 3]);
        }
        mma_k8(c1, x1[8], x1[9], bw[4]); mma_k8(c2, x1[8], x1[9], x1[8]); mma_k8(c3, x1[8], x1[9], x1[9]);
        if (t == (g >> 1)) {
            float4* p = &S->acc2[256 * rk + 16 * warp + g];
            red4(p, c1[0], (g & 1) ? c2[1] : c2[0], c1[1]);
            red4(p + 8, c1[2], (g & 1) ? c3[3] : c3[2], c1[3]);
        }
        __syncwarp();
    }
    uint32_t wf[9][4], wd[2][3][4];
    const int fmt = warp >> 2, fsl = warp & 3;
    auto ldwf = [&]() {
        const int half = lm & 1;
        const uint32_t base = (fmt == 4) ? ((half ? OFF_WU : OFF_WG) + 64) : ((fmt >> 1) * OFF_WU + ((2 * (fmt & 1) + half) << 4));
        const uint32_t wa = sb + base + (144 * fsl + lr + 8 * (lm >> 1)) * 80;
#pragma unroll
        for (int ks = 0; ks < 9; ks++) ldsm_x4_t(wf[ks], wa + ks * 1280);
    };
    mbar_wait(MB(MB_WG), 0);
    mbar_wait(MB(MB_WU), 0);
    ldwf();
    uint32_t h2[10];
    uint32_t ta = sb + OFF_H2T + (16 * warp + (lane & 15)) * 80 + (lane >> 4) * 16;
    if (warp < 16) {
        const float4* ap = &S->acc2[256 * rk + 32 * (warp >> 1) + lane];
        float4 s = ld_rlx4f(ap);
        uint2 kc[5];
#pragma unroll
        for (int j = 0; j < 5; j++) kc[j] = *(const uint2*)&M.c2[4 * j + t];
        const float cw = M.cws[0], sbw = M.cws[1];
        uint32_t tk0 = (2047 - (((lane & 6) << 8) + ((lane & 24) << 4) + ((lane & 1) << 6) + 8 * rk + (warp >> 1))) << 3;
        uint32_t ka = sb + OFF_MISC + (uint32_t)offsetof(Misc, key) + (32 * (warp >> 1) + lane) * 4;
        uint32_t rb = mapa(sb, 4 * (warp & 1) + t), cd = rb + OFF_MISC + (uint32_t)offsetof(Misc, cand2) + (8 * rk + (warp >> 1)) * 8;
        const int pj = lane >= 5, pc = lane - 5 * pj;
        uint4* dst = &S->h2c[(2 * (8 * rk + (warp >> 1)) + pj) * 72 + 5 * cl + pc];
        uint32_t pa = sb + OFF_H2T + 32 * (warp >> 1) * 80 + 16 * pc;
        asm volatile("" : "+r"(tk0), "+r"(ta), "+r"(ka), "+r"(rb), "+r"(cd), "+r"(pa), "+l"(dst));
        mbar_wait(MB(MB_KD), 1);
#pragma unroll 1
        for (int it = 0; it < SPIN_MAX && s.w != (float)NCL; it++) s = ld_rlx4f(ap);
        __syncwarp();
        float meanb, rinv;
        ln_stats(s.x, s.y, meanb, rinv);
        const uint32_t rbits = __float_as_uint(fmaf(fmaf(-meanb, cw, s.z), rinv, sbw));
        const uint32_t key = ((rbits ^ (((int)rbits >> 31) | 0x80000000u)) & 0xFFFFC000u) | tk0;
        const uint32_t m0 = __reduce_max_sync(0xffffffffu, key);
        const uint32_t mr = pack2(meanb, rinv), rl = f2bits(rinv - hi2f(mr));
        const uint32_t m1 = __reduce_max_sync(0xffffffffu, key == m0 ? 0u : key);
        uint32_t st[2][2];
#pragma unroll
        for (int h = 0; h < 2; h++) { st[h][0] = __shfl_sync(0xffffffffu, mr, 16 * (warp & 1) + 8 * h + g); st[h][1] = __shfl_sync(0xffffffffu, rl, 16 * (warp & 1) + 8 * h + g); }
        if (lane < 4) sta2(cd, m0, m1 | 1u, rb + (MB(MB_KEY) - sb));
        sts32(ka, key);
        const int pr = __ffs(__ballot_sync(0xffffffffu, key == m0) | 0x80000000u) - 1, pr1 = __ffs(__ballot_sync(0xffffffffu, key == m1) | 0x80000000u) - 1;
#pragma unroll
        for (int i = 0; i < 10; i++)
            h2[i] = add2(mul2(norm2(x1[i], __byte_perm(st[i & 1][0], 0, 0x1010), __byte_perm(st[i & 1][0], 0, 0x3232), __byte_perm(st[i & 1][1], 0, 0x1010)), kc[i >> 1].x), kc[i >> 1].y);
        stsm_x4(ta, h2[0], h2[1], h2[2], h2[3]); stsm_x4(ta + 32, h2[4], h2[5], h2[6], h2[7]); stsm_x2(ta + 64, h2[8], h2[9]);
        __syncwarp();
        const int row = pj ? pr1 : pr;
        if (lane < 10 && (row >> 4) == (warp & 1) && pc < (cl < 14 ? 5 : 2)) {
            const uint4 a = lds128(pa + 80 * row);
            st_rlx4(dst, make_uint4(~a.x, ~a.y, ~a.z, ~a.w));
        }
        __syncwarp();
        named_arrive(6, 640);
    }
    auto outt = [&]() {
        if (warp < 16) {
            uint32_t o[10];
            if ((warp == cl || (warp == 15 && cl == 0)) && lane < 16) st_rlx4(&S->acc1[256 * rk + 16 * warp + lane], make_uint4(0, 0, 0, 0));
#pragma unroll
            for (int i = 0; i < 10; i++) o[i] = add2(x1[i], mul2(M.c2[4 * (i >> 1) + t].z, h2[i]));
            stsm_x4(ta + (OFF_OUT - OFF_H2T), o[0], o[1], o[2], o[3]); stsm_x4(ta + (OFF_OUT - OFF_H2T) + 32, o[4], o[5], o[6], o[7]); stsm_x2(ta + (OFF_OUT - OFF_H2T) + 64, o[8], o[9]);
        }
    };
    outt();
    uint4 gv = make_uint4(1, 1, 1, 1);
    const uint4* gp;
    uint32_t gdst;
    {
        const int gi = 32 * warp + lane, kk = (gi * 911) >> 16, seg = gi - 72 * kk;
        uint32_t ca = sb + OFF_MISC + (uint32_t)offsetof(Misc, cand2), sa = ca + 512 + 4 * (kk & 7);
        gp = &S->h2c[seg];
        gdst = sb + OFF_H2S + kk * (ROWP * 2) + seg * 16;
        asm volatile("" : "+r"(sa), "+r"(gdst), "+l"(gp));
        mbar_wait(MB(MB_KEY), 0);
        if (warp < 16) {
            const uint4 o = lds128(ca + 16 * lane), a = lds128(ca + 32 * warp), c = lds128(ca + 32 * warp + 16);
            const uint32_t mx = max(o.x, o.z), hd[4] = {a.x, a.z, c.x, c.z}, sc[4] = {a.y, a.w, c.y, c.w};
            uint32_t n[4];
#pragma unroll
            for (int q = 0; q < 4; q++) n[q] = __popc(__ballot_sync(0xffffffffu, mx > hd[q]));
            auto rank = [&](uint32_t k) {
                return (__popc(__ballot_sync(0xffffffffu, o.x > k)) + __popc(__ballot_sync(0xffffffffu, o.y > k))) + (__popc(__ballot_sync(0xffffffffu, o.z > k)) + __popc(__ballot_sync(0xffffffffu, o.w > k)));
            };
#pragma unroll
            for (int q = 0; q < 4; q++) {
                if (n[q] < 8) {
                    const uint32_t r0 = rank(hd[q]), r1 = rank(sc[q]);
                    if (r0 < 8) sts32(ca + 512 + 4 * r0, hd[q]);
                    if (r1 < 8) sts32(ca + 512 + 4 * r1, sc[q]);
                }
            }
        }
        named_bar(13, 640);
        if (warp < 18) {
            const uint32_t key = lds32(sa);
            gp += (((~key >> 2) & 0x7Eu) | (key & 1u)) * 72;
            gv = ld_rlx4(gp);
        } else if (warp == 18) named_arrive(14, 64);
        else named_arrive(8, 64);
    }
    uint32_t wda = sb + OFF_WD + fmt * 5120 + lr * 128 + (((2 * fsl + (lm & 1)) ^ lr) << 4), wda2 = wda + (lm >> 1) * 1024;
    uint32_t ha = sb + OFF_H2S + lr * (ROWP * 2) + (144 * fsl) * 2 + lm * 16, fo = sb + OFF_FFR + ((fsl * 80 + 16 * fmt + g) * 8 + 2 * t) * 4;
    asm volatile("" : "+r"(ha), "+r"(fo));
    mbar_wait(MB(MB_WD), 0);
#pragma unroll
    for (int i = 0; i < 2; i++)
#pragma unroll
        for (int ks = 0; ks < 3; ks++)
            if (i == 0 || warp < 16) ldsm_x4_t(wd[i][ks], ((ks < 2) ? wda2 : wda) + ks * 2048 + i * 5 * 5120);
#pragma unroll 1
    for (int it = 0; it < SPIN_MAX && gv.x == 0u; it++) gv = ld_rlx4(gp);
    if (warp < 18) asm volatile("st.shared.v4.u32 [%0], {%1,%2,%3,%4};" ::"r"(gdst), "r"(~gv.x), "r"(~gv.y), "r"(~gv.z), "r"(~gv.w) : "memory");
    CBAR();
    float* ffr = (float*)(sm + OFF_FFR);
    auto ffn1 = [&]() {
        float acc[2][4] = {{0.f, 0.f, 0.f, 0.f}, {0.f, 0.f, 0.f, 0.f}};
#pragma unroll
        for (int k2 = 0; k2 < 5; k2++) {
            uint32_t hb[4];
            if (k2 < 4) ldsm_x4(hb, ha + k2 * 64); else ldsm_x2(hb, ha + 256);
            mma_bf16(acc[0], wf[2 * k2][0], wf[2 * k2][1], wf[2 * k2][2], wf[2 * k2][3], hb[0], hb[1]);
            if (k2 < 4) mma_bf16(acc[1], wf[2 * k2 + 1][0], wf[2 * k2 + 1][1], wf[2 * k2 + 1][2], wf[2 * k2 + 1][3], hb[2], hb[3]);
        }
        asm volatile("st.shared.v2.f32 [%0], {%1,%2};" ::"r"(fo), "f"(acc[0][0] + acc[1][0]), "f"(acc[0][1] + acc[1][1]) : "memory");
        asm volatile("st.shared.v2.f32 [%0+256], {%1,%2};" ::"r"(fo), "f"(acc[0][2] + acc[1][2]), "f"(acc[0][3] + acc[1][3]) : "memory");
    };
    ffn1();
    bf16(*act)[56] = (bf16(*)[56])(sm + OFF_ACT);
    auto gate = [&]() {
        if (warp < 12) {
            const int f = 4 * warp + lm, a = lr;
            float v = 0.f;
            if (warp < 10) {
                const float* pg = ffr + 32 * warp + (warp < 8 ? 0 : 256) + lane;
                const float* pu = pg + (warp < 8 ? 256 : 64);
                float gg = bfr((pg[0] + pg[640]) + (pg[1280] + pg[1920]));
                gg = bfr(silu(gg));
                const float uu = bfr((pu[0] + pu[640]) + (pu[1280] + pu[1920]));
                v = gg * uu;
            }
            act[a][f] = __ushort_as_bfloat16((unsigned short)f2bits(v));
        }
    };
    CBAR();
    gate();
    CBAR();
    auto ffn2 = [&](uint32_t buf, int mb) {
        uint32_t bq[3][2];
#pragma unroll
        for (int ks = 0; ks < 3; ks++) {
            bq[ks][0] = *(const uint32_t*)&act[g][16 * ks + 2 * t];
            bq[ks][1] = *(const uint32_t*)&act[g][16 * ks + 2 * t + 8];
        }
#pragma unroll
        for (int i = 0; i < 2; i++) {
            if (i == 0 || warp < 16) {
                float acc[4] = {0.f, 0.f, 0.f, 0.f};
#pragma unroll
                for (int ks = 0; ks < 3; ks++) mma_bf16(acc, wd[i][ks][0], wd[i][ks][1], wd[i][ks][2], wd[i][ks][3], bq[ks][0], bq[ks][1]);
                const int d = i ? 4 + (warp >> 2) : (warp * 13) >> 6, slot = i ? (warp & 3) : warp - 5 * d;
                const uint32_t rb = mapa(sb, d);
                sta2(rb + buf + ((rk * 5 + slot) * 32 + lane) * 8, movm(pack2(acc[0], acc[1])), movm(pack2(acc[2], acc[3])), rb + (MB(mb) - sb));
            }
        }
    };
    ffn2(OFF_RS, MB_RS);
    named_bar(12, 672);
    const uint32_t redo = M.fin[8];
    if (redo) {
        const int gi = fresh_tid(), kk = (gi * 911) >> 16, seg = gi - 72 * kk;
        if (warp < 8) {
            const uint32_t key = M.fin[warp];
            if (((~key >> 6) & 7u) == (uint32_t)rk && lane < (cl < 14 ? 5 : 2)) {
                const uint4 a = lds128(sb + OFF_H2T + ROW(key) * 80 + 16 * lane);
                st_rlx4(&S->h2c[(128 + warp) * 72 + 5 * cl + lane], make_uint4(~a.x, ~a.y, ~a.z, ~a.w));
            }
            __syncwarp();
        }
        if (warp < 18) {
            uint4 gv = make_uint4(0, 0, 0, 0);
#pragma unroll 1
            for (int it = 0; it < SPIN_MAX && gv.x == 0u; it++) gv = ld_rlx4(&S->h2c[128 * 72 + gi]);
            *(uint4*)(sm + OFF_H2S + kk * (ROWP * 2) + seg * 16) = make_uint4(~gv.x, ~gv.y, ~gv.z, ~gv.w);
        }
        CBAR();
        ffn1();
        CBAR();
        gate();
        CBAR();
        ffn2(OFF_RS + 10240, MB_RS2);
        mbar_wait(MB(MB_RS2), 0);
    }
    {
        const int lane = fresh_tid() & 31;
        const int fP = min(warp < 8 ? 20 * cl + lane : 8 * (rk < 4 ? 5 * rk : 4 * rk + 4) + 4 * (warp - 8) + (lane & 3), D_ / 2);
        uint32_t fgb = ld_rlx(GBV(fP));
        const int ftok = warp < 8 ? warp : lane >> 2;
        const uint32_t fkey = M.fin[ftok];
        const bool fon = warp < 8 ? (((~fkey >> 6) & 7u) == (uint32_t)rk && lane < 20 && fP < D_ / 2) : warp < (rk < 4 ? 18 : 16);
        const float rs = __fdividef(1.0f, 1.0f + __expf(-hi2f(fkey ^ (((int)~fkey >> 31) | 0x80000000u))));
        const uint32_t hv = lds32(sb + OFF_H2S + ftok * (ROWP * 2) + 4 * fP);
        float s0 = 0.f, s1 = 0.f, s2 = 1.0f, s3 = 0.f;
        if (warp >= 8) {
            if (fon) {
                mbar_wait(MB(MB_RS), 0);
                const uint32_t p = sb + OFF_RS + redo * 10240 + (((warp - 8) >> 1) * 32 + lane) * 8 + 4 * (warp & 1);
                uint32_t v[8];
#pragma unroll
                for (int i = 0; i < 8; i++) v[i] = lds32(p + i * 1280);
                s0 = ((lo2f(v[0]) + lo2f(v[1])) + (lo2f(v[2]) + lo2f(v[3]))) + ((lo2f(v[4]) + lo2f(v[5])) + (lo2f(v[6]) + lo2f(v[7])));
                s1 = ((hi2f(v[0]) + hi2f(v[1])) + (hi2f(v[2]) + hi2f(v[3]))) + ((hi2f(v[4]) + hi2f(v[5])) + (hi2f(v[6]) + hi2f(v[7])));
            }
        } else if (fon) {
            const uint32_t row = ROW(fkey);
            const unsigned short* vp = (const unsigned short*)(sm + OFF_V + 2 * lane * VP) + row;
            const uint32_t xv = add2(lds32(sb + OFF_X + XI(row >> 5) + ((row >> 3) & 3) * XG + (row & 7) * 80 + 4 * lane), (uint32_t)vp[0] | ((uint32_t)vp[VP / 2] << 16));
            s2 = (float)(((xv & 0xFFFFu) << 5) | 1u); s3 = (float)(xv >> 16);
            mbar_wait(MB(MB_OUT), 0);
        }
        if (fon) {
            const float4 o = atom4(&S->acc3[(fP >> 2) * 32 + 4 * ftok + (fP & 3)], s0, s1, s2, s3);
            const uint32_t z = __float_as_uint((o.z + s2) + 8388608.f), zh = __float_as_uint((o.w + s3) + 8388608.f);
            if (z & 16u) {
#pragma unroll 1
                for (int it = 0; it < SPIN_MAX && fgb == 0u; it++) fgb = ld_rlx(GBV(fP));
                const uint32_t xv = __byte_perm(z >> 5, zh, 0x5410);
                *(uint32_t*)(out + ((~fkey >> 3) & 2047u) * D_ + 2 * fP) = add2(xv, mul2(~fgb, add2(hv, mul2(pack2(o.x + s0, o.y + s1), pack2(rs, rs)))));
            }
        }
    }
    }
    }
}

typedef CUresult (*EncodeFn)(CUtensorMap*, CUtensorMapDataType, cuuint32_t, void*, const cuuint64_t*, const cuuint64_t*,
                             const cuuint32_t*, const cuuint32_t*, CUtensorMapInterleave, CUtensorMapSwizzle,
                             CUtensorMapL2promotion, CUtensorMapFloatOOBfill);

static void make_map(EncodeFn fn, CUtensorMap* m, const void* ptr, uint64_t cols, uint64_t rows, uint32_t bc, uint32_t br,
                     CUtensorMapSwizzle sw, int five) {
    cuuint64_t dims[5] = {cols, rows, 4, 4, 64};
    cuuint64_t strides[4] = {cols * 2 * (five ? 64 : 1), cols * 2 * 512, cols * 2 * 128, cols * 2};
    cuuint32_t box[5] = {bc, br, 4, 4, 8};
    cuuint32_t es[5] = {1, 1, 1, 1, 1};
    CUresult rc = fn(m, CU_TENSOR_MAP_DATA_TYPE_BFLOAT16, five ? 5 : 2, (void*)ptr, dims, strides, box, es, CU_TENSOR_MAP_INTERLEAVE_NONE,
                     sw, CU_TENSOR_MAP_L2_PROMOTION_NONE, CU_TENSOR_MAP_FLOAT_OOB_FILL_NONE);
    (void)rc;
}

static void launch(void* const* d_in, const int* in_sizes, int n_in, void* d_out, int out_size) {
    static EncodeFn enc = nullptr;
    static CUtensorMap tmm, tmg, tmu, tmd, tmo;
    static Scratch* sp = nullptr;
    static const void* cached[6] = {nullptr, nullptr, nullptr, nullptr, nullptr, nullptr};
    if (!enc) {
        cudaDriverEntryPointQueryResult qr;
        void* fn = nullptr;
        cudaGetDriverEntryPoint("cuTensorMapEncodeTiled", &fn, cudaEnableDefault, &qr);
        enc = (EncodeFn)fn;
        cudaFuncSetAttribute(clus_kernel, cudaFuncAttributeMaxDynamicSharedMemorySize, SMEM_TOTAL);
        cudaGetSymbolAddress((void**)&sp, g_s);
    }
    if (cached[0] != d_in[13] || cached[1] != d_in[9] || cached[2] != d_in[10] || cached[3] != d_in[11] || cached[4] != d_in[0] || cached[5] != d_out) {
        make_map(enc, &tmo, d_out, D_, 2, 40, 2, CU_TENSOR_MAP_SWIZZLE_NONE, 1);
        make_map(enc, &tmm, d_in[13], 6 * D_, D_, 40, 72, CU_TENSOR_MAP_SWIZZLE_NONE, 0);
        make_map(enc, &tmg, d_in[9], F_, D_, 40, 192, CU_TENSOR_MAP_SWIZZLE_NONE, 0);
        make_map(enc, &tmu, d_in[10], F_, D_, 40, 192, CU_TENSOR_MAP_SWIZZLE_NONE, 0);
        make_map(enc, &tmd, d_in[11], D_, F_, 64, 40, CU_TENSOR_MAP_SWIZZLE_128B, 0);
        cached[0] = d_in[13]; cached[1] = d_in[9]; cached[2] = d_in[10]; cached[3] = d_in[11]; cached[4] = d_in[0]; cached[5] = d_out;
    }
    clus_kernel<<<G_, NTHR, SMEM_TOTAL>>>((const bf16*)d_in[0], (const bf16*)d_in[1], (const bf16*)d_in[2], (const bf16*)d_in[3], (const bf16*)d_in[4],
                                          (const bf16*)d_in[5], (const bf16*)d_in[12], sp, (const bf16*)d_in[6], (const bf16*)d_in[8], (const bf16*)d_in[13],
                                          (bf16*)d_out, tmm, tmg, tmu, tmd, tmo);
}

static bool fits() {
    cudaFuncSetAttribute(clus_kernel, cudaFuncAttributeMaxDynamicSharedMemorySize, SMEM_TOTAL);
    cudaLaunchConfig_t cfg = {};
    cudaLaunchAttribute at;
    at.id = cudaLaunchAttributeClusterDimension;
    at.val.clusterDim.x = 8; at.val.clusterDim.y = 1; at.val.clusterDim.z = 1;
    cfg.gridDim = dim3(G_); cfg.blockDim = dim3(NTHR); cfg.dynamicSmemBytes = SMEM_TOTAL; cfg.attrs = &at; cfg.numAttrs = 1;
    int n = 0;
    const bool ok = cudaOccupancyMaxActiveClusters(&n, clus_kernel, &cfg) == cudaSuccess && n >= NCL;
    cudaGetLastError();
    return ok;
}
}
#undef L_
#undef D_
#undef N_
#undef F_
#undef G_
#undef NCL
#undef NTHR
#undef SPIN_MAX
#undef NRST
#undef GBV
#undef OFF_WG
#undef OFF_WU
#undef KSCR
#undef OFF_WM0
#undef OFF_STG
#undef OFF_MG2
#undef OFF_CH
#undef CHS
#undef ULBO
#undef XO_U8
#undef XO_U16
#undef XO_ZA
#undef XO_ZB
#undef XO_ZC
#undef XO_ZD
#undef XO_TF
#undef XO_TD
#undef XO_K1024
#undef XO_DSK
#undef XO_KINV
#undef XO_KLAST
#undef XO_MBU
#undef OFF_X
#undef XG
#undef XI
#undef XN
#undef OFF_V
#undef VP
#undef OFF_EK
#undef OFF_WM2
#undef OFF_MG1
#undef OFF_SC
#undef OFF_C1
#undef OFF_MISC
#undef OFF_WD
#undef OFF_H2T
#undef OFF_OUT
#undef ROWP
#undef OFF_H2S
#undef OFF_FFR
#undef OFF_ACT
#undef OFF_RS
#undef SMEM_TOTAL
#undef CBAR
#undef PROXY_FENCE
#undef D4
#undef O4
#undef WG_FENCE
#undef WG_COMMIT
#undef WG_WAIT
#undef TQ
#undef MB
#undef PRE
#undef DZ
#undef DS
#undef KST
#undef WMD
#undef PU
#undef PD
#undef PFG
#undef CWP
#undef CWD
#undef LN1POS
#undef SLOT
#undef ROW
#undef CE
#undef POP
#undef CGT
#undef RESET
#undef CL_ARRIVE
#undef CL_WAIT
#undef CJ
#undef CJP

namespace v4 {

#define L_ 2048
#define D_ 576
#define N_ 128
#define F_ 4608
#define G_ 128
#define NTHR 640
#define SPIN_MAX (1 << 18)
#define SENT 0u
#define HINT_N 182u

typedef __nv_bfloat16 bf16;

struct Scratch {
    uint4 xn[G_ * G_ * 10];
    uint4 v[G_ * D_ * 2];
    uint2 part[G_ * G_ * 9];
    uint4 h2w[L_ * 96];
    unsigned int rec[G_ * 8];
    unsigned int modw[6 * D_];
    unsigned int ticket[64];
    unsigned int cnt[64];
    unsigned int hint[64];
};
__device__ __align__(1024) Scratch g_s;

#define OFF_WG 0
#define OFF_WU 46080
#define OFF_CH 92160
#define CHS 20784
#define ULBO 656
#define XO_U8 6272
#define XO_U16 10368
#define XO_ZA 5248
#define XO_ZB 8448
#define XO_ZC 11648
#define XO_ZD 13824
#define XO_TD 16000
#define XO_TF 18624
#define XO_K1024 20672
#define KSCR 3456
#define OFF_TILE 196096
#define ROWP 584
#define OFF_MISC 214784
#define OFF_WD OFF_CH
#define OFF_H2T (OFF_CH + 3 * CHS)
#define OFF_H2S (OFF_H2T + 18688)
#define OFF_FFR (OFF_H2S + 9344)
#define OFF_FIN OFF_FFR
#define OFF_ACT (OFF_FFR + 10240)

struct Misc {
    __align__(16) uint4 sent[256];
    __align__(16) uint4 box[11 * 14];
    union {
        struct {
            __align__(16) float2 part[18][16];
            float rp[18][16];
        };
        struct {
            __align__(16) unsigned short st1[3][16];
            __align__(16) float p1[16][4], p2[16][4];
        };
    };
    __align__(16) bf16 cb1[D_], sb[D_], gb[D_];
    __align__(16) bf16 sc[D_];
    __align__(16) unsigned int cand[64], skey[16];
    __align__(16) float kinv[5][4], klast[5][4];
    unsigned int pk[4][8];
    __align__(16) uint4 st2[16];
    unsigned int wr[D_ / 2];
    float modx[32];
    unsigned int rank[16];
    volatile unsigned int flag;
    unsigned int e1cnt;
    unsigned long long mbar[5];
    unsigned int epoch;
};
#define SMEM_TOTAL (OFF_MISC + (int)sizeof(Misc))
static_assert(SMEM_TOTAL <= 232448, "smem");

__device__ __forceinline__ float lo2f(uint32_t w) { return __uint_as_float(w << 16); }
__device__ __forceinline__ float hi2f(uint32_t w) { return __uint_as_float(w & 0xFFFF0000u); }
__device__ __forceinline__ uint32_t pack2(float lo, float hi) { uint32_t r; asm("cvt.rn.bf16x2.f32 %0, %1, %2;" : "=r"(r) : "f"(hi), "f"(lo)); return r; }
__device__ __forceinline__ float bfr(float x) { return __uint_as_float(pack2(0.f, x)); }
__device__ __forceinline__ uint32_t f2bits(float x) { return pack2(x, 0.f); }
__device__ __forceinline__ uint32_t packh(float lo, float hi) { uint32_t r; asm("cvt.rn.f16x2.f32 %0, %1, %2;" : "=r"(r) : "f"(hi), "f"(lo)); return r; }
__device__ __forceinline__ float frcp(float x) { float r; asm("rcp.approx.ftz.f32 %0, %1;" : "=f"(r) : "f"(x)); return r; }
__device__ __forceinline__ float fsqrt(float x) { float r; asm("sqrt.approx.f32 %0, %1;" : "=f"(r) : "f"(x)); return r; }
__device__ __forceinline__ float fex2(float x) { float r; asm("ex2.approx.ftz.f32 %0, %1;" : "=f"(r) : "f"(x)); return r; }
__device__ __forceinline__ float silu(float x) { return __fdividef(x, 1.0f + __expf(-x)); }
__device__ __forceinline__ uint32_t add2(uint32_t a, uint32_t b) { uint32_t r; asm("add.rn.bf16x2 %0, %1, %2;" : "=r"(r) : "r"(a), "r"(b)); return r; }
__device__ __forceinline__ uint32_t sub2(uint32_t a, uint32_t b) { uint32_t r; asm("sub.rn.bf16x2 %0, %1, %2;" : "=r"(r) : "r"(a), "r"(b)); return r; }
__device__ __forceinline__ uint32_t mul2(uint32_t a, uint32_t b) { uint32_t r; asm("mul.rn.bf16x2 %0, %1, %2;" : "=r"(r) : "r"(a), "r"(b)); return r; }
__device__ __forceinline__ uint32_t fma2(uint32_t a, uint32_t b, uint32_t c) { uint32_t r; asm("fma.rn.bf16x2 %0, %1, %2, %3;" : "=r"(r) : "r"(a), "r"(b), "r"(c)); return r; }
__device__ __forceinline__ uint32_t norm2(uint32_t x, uint32_t m, uint32_t rh, uint32_t rl) { const uint32_t d = sub2(x, m); return fma2(d, rh, mul2(d, rl)); }

__device__ __forceinline__ void mma_bf16(float* c, uint32_t a0, uint32_t a1, uint32_t a2, uint32_t a3, uint32_t b0, uint32_t b1) {
    asm volatile("mma.sync.aligned.m16n8k16.row.col.f32.bf16.bf16.f32 {%0,%1,%2,%3}, {%4,%5,%6,%7}, {%8,%9}, {%0,%1,%2,%3};\n"
                 : "+f"(c[0]), "+f"(c[1]), "+f"(c[2]), "+f"(c[3]) : "r"(a0), "r"(a1), "r"(a2), "r"(a3), "r"(b0), "r"(b1));
}
__device__ __forceinline__ void mma_f16(float* c, const uint32_t* a, uint32_t b0, uint32_t b1) {
    asm volatile("mma.sync.aligned.m16n8k16.row.col.f32.f16.f16.f32 {%0,%1,%2,%3}, {%4,%5,%6,%7}, {%8,%9}, {%0,%1,%2,%3};\n"
                 : "+f"(c[0]), "+f"(c[1]), "+f"(c[2]), "+f"(c[3]) : "r"(a[0]), "r"(a[1]), "r"(a[2]), "r"(a[3]), "r"(b0), "r"(b1));
}
__device__ __forceinline__ void ldsm_x4(uint32_t* r, uint32_t addr) {
    asm volatile("ldmatrix.sync.aligned.m8n8.x4.shared.b16 {%0,%1,%2,%3}, [%4];" : "=r"(r[0]), "=r"(r[1]), "=r"(r[2]), "=r"(r[3]) : "r"(addr) : "memory");
}
__device__ __forceinline__ void ldsm_x4_t(uint32_t* r, uint32_t addr) {
    asm volatile("ldmatrix.sync.aligned.m8n8.x4.trans.shared.b16 {%0,%1,%2,%3}, [%4];" : "=r"(r[0]), "=r"(r[1]), "=r"(r[2]), "=r"(r[3]) : "r"(addr) : "memory");
}
__device__ __forceinline__ void stsm_x4(uint32_t addr, uint32_t r0, uint32_t r1, uint32_t r2, uint32_t r3) {
    asm volatile("stmatrix.sync.aligned.m8n8.x4.shared.b16 [%0], {%1,%2,%3,%4};" ::"r"(addr), "r"(r0), "r"(r1), "r"(r2), "r"(r3) : "memory");
}
__device__ __forceinline__ void stsm_x4_t(uint32_t addr, uint32_t r0, uint32_t r1, uint32_t r2, uint32_t r3) {
    asm volatile("stmatrix.sync.aligned.m8n8.x4.trans.shared.b16 [%0], {%1,%2,%3,%4};" ::"r"(addr), "r"(r0), "r"(r1), "r"(r2), "r"(r3) : "memory");
}
__device__ __forceinline__ uint32_t movm(uint32_t a) { uint32_t r; asm volatile("movmatrix.sync.aligned.m8n8.trans.b16 %0, %1;" : "=r"(r) : "r"(a)); return r; }
__device__ __forceinline__ uint32_t lds32(uint32_t a) { uint32_t v; asm volatile("ld.shared.u32 %0, [%1];" : "=r"(v) : "r"(a)); return v; }
__device__ __forceinline__ void sts32(uint32_t a, uint32_t v) { asm volatile("st.shared.u32 [%0], %1;" ::"r"(a), "r"(v) : "memory"); }
__device__ __forceinline__ void sts16(uint32_t a, uint32_t v) { asm volatile("st.shared.u16 [%0], %1;" ::"r"(a), "h"((unsigned short)v) : "memory"); }
__device__ __forceinline__ void named_bar(int id, int n) { asm volatile("bar.sync %0, %1;" ::"r"(id), "r"(n) : "memory"); }
__device__ __forceinline__ void named_arrive(int id, int n) { asm volatile("bar.arrive %0, %1;" ::"r"(id), "r"(n) : "memory"); }
#define CBAR() asm volatile("bar.sync 0, 640;" ::: "memory")
#define PROXY_FENCE() asm volatile("fence.proxy.async.shared::cta;" ::: "memory")

#define D4(d, o) "+f"(d[o]), "+f"(d[o + 1]), "+f"(d[o + 2]), "+f"(d[o + 3])
__device__ __forceinline__ void wg32(float* d, uint32_t a0, uint32_t a1, uint32_t a2, uint32_t a3, uint64_t desc) {
    asm volatile("wgmma.mma_async.sync.aligned.m64n32k16.f32.bf16.bf16 {%0,%1,%2,%3,%4,%5,%6,%7,%8,%9,%10,%11,%12,%13,%14,%15}, {%16,%17,%18,%19}, %20, 1, 1, 1, 0;"
                 : D4(d, 0), D4(d, 4), D4(d, 8), D4(d, 12) : "r"(a0), "r"(a1), "r"(a2), "r"(a3), "l"(desc));
}
__device__ __forceinline__ void wg48(float* d, uint32_t a0, uint32_t a1, uint32_t a2, uint32_t a3, uint64_t desc) {
    asm volatile("wgmma.mma_async.sync.aligned.m64n48k16.f32.bf16.bf16 {%0,%1,%2,%3,%4,%5,%6,%7,%8,%9,%10,%11,%12,%13,%14,%15,%16,%17,%18,%19,%20,%21,%22,%23}, {%24,%25,%26,%27}, %28, 1, 1, 1, 0;"
                 : D4(d, 0), D4(d, 4), D4(d, 8), D4(d, 12), D4(d, 16), D4(d, 20) : "r"(a0), "r"(a1), "r"(a2), "r"(a3), "l"(desc));
}
#define O4(d, o) "=f"(d[o]), "=f"(d[o + 1]), "=f"(d[o + 2]), "=f"(d[o + 3])
__device__ __forceinline__ void wg32z(float* d, uint32_t a0, uint32_t a1, uint32_t a2, uint32_t a3, uint64_t desc) {
    asm volatile("wgmma.mma_async.sync.aligned.m64n32k16.f32.bf16.bf16 {%0,%1,%2,%3,%4,%5,%6,%7,%8,%9,%10,%11,%12,%13,%14,%15}, {%16,%17,%18,%19}, %20, 0, 1, 1, 0;"
                 : O4(d, 0), O4(d, 4), O4(d, 8), O4(d, 12) : "r"(a0), "r"(a1), "r"(a2), "r"(a3), "l"(desc));
}
__device__ __forceinline__ void wg48z(float* d, uint32_t a0, uint32_t a1, uint32_t a2, uint32_t a3, uint64_t desc) {
    asm volatile("wgmma.mma_async.sync.aligned.m64n48k16.f32.bf16.bf16 {%0,%1,%2,%3,%4,%5,%6,%7,%8,%9,%10,%11,%12,%13,%14,%15,%16,%17,%18,%19,%20,%21,%22,%23}, {%24,%25,%26,%27}, %28, 0, 1, 1, 0;"
                 : O4(d, 0), O4(d, 4), O4(d, 8), O4(d, 12), O4(d, 16), O4(d, 20) : "r"(a0), "r"(a1), "r"(a2), "r"(a3), "l"(desc));
}
#define WG_FENCE() asm volatile("wgmma.fence.sync.aligned;" ::: "memory")
#define WG_COMMIT() asm volatile("wgmma.commit_group.sync.aligned;" ::: "memory")
#define WG_WAIT(n) asm volatile("wgmma.wait_group.sync.aligned " #n ";" ::: "memory")
#define TQ(p, k) p[2 * (k) + 1], p[2 * (k) + 2], p[2 * (k)], p[2 * (k) + 1]

__device__ __forceinline__ uint4 ld_nc4(const void* p) { uint4 v; asm volatile("ld.global.nc.v4.u32 {%0,%1,%2,%3}, [%4];" : "=r"(v.x), "=r"(v.y), "=r"(v.z), "=r"(v.w) : "l"(p)); return v; }
__device__ __forceinline__ unsigned short ld_nc16(const void* p) { unsigned short v; asm volatile("ld.global.nc.u16 %0, [%1];" : "=h"(v) : "l"(p)); return v; }
__device__ __forceinline__ uint32_t ld_nc(const void* p) { uint32_t v; asm volatile("ld.global.nc.u32 %0, [%1];" : "=r"(v) : "l"(p)); return v; }
__device__ __forceinline__ uint32_t ld_rlx(const unsigned int* p) { uint32_t v; asm volatile("ld.relaxed.gpu.global.u32 %0, [%1];" : "=r"(v) : "l"(p) : "memory"); return v; }
__device__ __forceinline__ uint2 ld_rlx2(const void* p) { uint2 v; asm volatile("ld.relaxed.gpu.global.v2.u32 {%0,%1}, [%2];" : "=r"(v.x), "=r"(v.y) : "l"(p) : "memory"); return v; }
__device__ __forceinline__ uint4 ld_rlx4(const void* p) { uint4 v; asm volatile("ld.relaxed.gpu.global.v4.u32 {%0,%1,%2,%3}, [%4];" : "=r"(v.x), "=r"(v.y), "=r"(v.z), "=r"(v.w) : "l"(p) : "memory"); return v; }
__device__ __forceinline__ void st_rlx(unsigned int* p, uint32_t v) { asm volatile("st.relaxed.gpu.global.u32 [%0], %1;" ::"l"(p), "r"(v) : "memory"); }
__device__ __forceinline__ void st_rlx2(void* p, uint32_t a, uint32_t b) { asm volatile("st.relaxed.gpu.global.v2.u32 [%0], {%1,%2};" ::"l"(p), "r"(a), "r"(b) : "memory"); }
__device__ __forceinline__ void st_rlx4(void* p, uint4 v) { asm volatile("st.relaxed.gpu.global.v4.u32 [%0], {%1,%2,%3,%4};" ::"l"(p), "r"(v.x), "r"(v.y), "r"(v.z), "r"(v.w) : "memory"); }
__device__ __forceinline__ void red_inc(unsigned int* p) { asm volatile("red.relaxed.gpu.global.add.u32 [%0], 1;" ::"l"(p) : "memory"); }

__device__ __forceinline__ void mbar_init(uint32_t a, int cnt) { asm volatile("mbarrier.init.shared::cta.b64 [%0], %1;" ::"r"(a), "r"(cnt) : "memory"); }
__device__ __forceinline__ void mbar_expect(uint32_t a, uint32_t bytes) { asm volatile("mbarrier.arrive.expect_tx.shared::cta.b64 _, [%0], %1;" ::"r"(a), "r"(bytes) : "memory"); }
__device__ __forceinline__ void mbar_wait(uint32_t a, uint32_t parity) {
    uint32_t ok = 0;
    int it = 0;
    do {
        asm volatile("{\n.reg .pred p;\nmbarrier.try_wait.parity.shared::cta.b64 p, [%1], %2;\nselp.u32 %0, 1, 0, p;\n}" : "=r"(ok) : "r"(a), "r"(parity) : "memory");
    } while (!ok && ++it < SPIN_MAX);
}
__device__ __forceinline__ void tma2d(uint32_t dst, const CUtensorMap* tm, int c0, int c1, uint32_t mbar) {
    asm volatile("cp.async.bulk.tensor.2d.shared::cluster.global.mbarrier::complete_tx::bytes [%0], [%1, {%3, %4}], [%2];"
                 ::"r"(dst), "l"(tm), "r"(mbar), "r"(c0), "r"(c1) : "memory");
}
__device__ __forceinline__ void bulk_s2g(void* dst, uint32_t src, uint32_t bytes) {
    asm volatile("cp.async.bulk.global.shared::cta.bulk_group [%0], [%1], %2;" ::"l"(dst), "r"(src), "r"(bytes) : "memory");
}
__device__ __forceinline__ uint32_t ld_acq(const unsigned int* p) { uint32_t v; asm volatile("ld.acquire.gpu.global.u32 %0, [%1];" : "=r"(v) : "l"(p) : "memory"); return v; }
__device__ __forceinline__ void bulk_pf(const void* src, uint32_t bytes) { asm volatile("cp.async.bulk.prefetch.L2.global [%0], %1;" ::"l"(src), "r"(bytes) : "memory"); }

__device__ __forceinline__ uint32_t wait_epoch(Misc& M) {
    uint32_t e = 0;
#pragma unroll 1
    for (int it = 0; it < (SPIN_MAX << 4) && e == 0; it++) e = *(volatile unsigned int*)&M.epoch;
    return e;
}
__device__ __forceinline__ void wait_reset(const unsigned int* ctr, uint32_t epoch) {
#pragma unroll 1
    for (int it = 0; it < SPIN_MAX; it++)
        if ((int)(ld_acq(ctr) - G_ * epoch) >= 0) break;
}
struct cplx { float x, y; };
__device__ __forceinline__ cplx cmul(cplx a, cplx b) { cplx r; r.x = a.x * b.x - a.y * b.y; r.y = a.x * b.y + a.y * b.x; return r; }
__device__ __forceinline__ cplx csq(cplx a) { cplx r; r.x = a.x * a.x - a.y * a.y; r.y = 2.0f * a.x * a.y; return r; }
__device__ __forceinline__ uint32_t hcm(uint32_t x, uint32_t y, uint32_t yp) {
    const __half2 X = *(const __half2*)&x, Y = *(const __half2*)&y, YP = *(const __half2*)&yp;
    const __half2 r = __hfma2(__high2half2(X), YP, __hmul2(__low2half2(X), Y));
    return *(const uint32_t*)&r;
}
__device__ __forceinline__ void ln_stats(float s1, float s2, float& meanb, float& rinv) {
    const float mean = s1 * (1.0f / D_);
    const float den = bfr(fsqrt(bfr(bfr(fmaxf(fmaf(-mean, mean, s2 * (1.0f / D_)), 0.f)) + 1e-5f)));
    meanb = bfr(mean);
    rinv = frcp(den);
}

__device__ __forceinline__ int fresh_tid() { int v; asm volatile("mov.u32 %0, %tid.x;" : "=r"(v)); return v; }
__device__ __forceinline__ void conv_channel(unsigned char* sm, Scratch* S, uint32_t gidx, uint32_t epoch, const void* pf_src,
                                             const CUtensorMap* tmu, int f0) {
    Misc& M = *(Misc*)(sm + OFF_MISC);
    const uint32_t sb = (uint32_t)__cvta_generic_to_shared(sm);
    const int tid = fresh_tid(), lane = tid & 31, g = lane >> 2, t = lane & 3, lr = lane & 7, lm = lane >> 3;
    const int warp_ = __shfl_sync(0xffffffffu, tid >> 5, 0), wgi = warp_ >> 2, w = warp_ & 3;
    const uint32_t cb = sb + OFF_CH + wgi * CHS, tag16 = (epoch % 65535u) + 1u;
    float D[16];
    uint32_t gaw, rcnt = 0;
    {
        {
            const uint32_t a8 = cb + lr * ULBO + (lm + 9) * 16 + w * 64, b8 = cb + XO_U8 + lm * 128 + lr * 16 + w * 512;
            const uint32_t a16 = cb + (((2 * lr) & 7) + (lm & 1)) * ULBO + (9 + (lr >> 2) + (lm & 2)) * 16 + w * 64;
            const uint32_t b16 = cb + XO_U16 + (lm & 1) * 512 + lr * 16 + (lm >> 1) * 128 + (w >> 1) * 1024 + (w & 1) * 256;
            uint32_t r[3][4];
            ldsm_x4_t(r[0], a8);
            ldsm_x4_t(r[1], a16);
            if (w < 2) ldsm_x4_t(r[2], a8 + 256);
            stsm_x4(b8, r[0][0], r[0][1], r[0][2], r[0][3]);
            stsm_x4(b16, r[1][0], r[1][1], r[1][2], r[1][3]);
            if (w < 2) stsm_x4(b8 + 2048, r[2][0], r[2][1], r[2][2], r[2][3]);
        }
        PROXY_FENCE();
        named_bar(1 + wgi, 128);
        {
            float Z8[24], Z16[16];
            const uint32_t pf = cb + XO_TF + (w >> 1) * 512 + (8 + 16 * (w & 1) + g - 2 * t) * 4;
            uint32_t p[13], q[9], z16[8];
#pragma unroll
            for (int s = 0; s < 9; s++) q[s] = lds32(pf + 1024 + s * 32);
            const uint32_t d8 = ((((cb + XO_U8) & 0x3FFFF) >> 4) | ((128 >> 4) << 16));
#define DZ(o) (((uint64_t)(512 >> 4) << 32) | (uint64_t)(d8 + (o)))
            WG_FENCE();
#pragma unroll
            for (int e = 0; e < 4; e++) {
                if (e == 0) wg32z(Z16, TQ(q, e), DZ(256 + 16));
                else wg32(Z16, TQ(q, e), DZ(256 - (e >> 1) * 64 + (1 - (e & 1)) * 16));
            }
            WG_COMMIT();
#pragma unroll
            for (int s = 0; s < 13; s++) p[s] = lds32(pf + s * 32);
            WG_WAIT(0);
#pragma unroll
            for (int i = 0; i < 8; i++) z16[i] = pack2(Z16[2 * i], Z16[2 * i + 1]);
            WG_FENCE();
#pragma unroll
            for (int e = 0; e < 6; e++) {
                if (e == 0) wg48z(Z8, TQ(p, e), DZ(16));
                else wg48(Z8, TQ(p, e), DZ(-(e >> 1) * 32 + (1 - (e & 1)) * 16));
            }
            WG_COMMIT();
            WG_WAIT(0);
            named_bar(1 + wgi, 128);
            const uint32_t za = cb + ((w >> 1) ? XO_ZB : XO_ZA) + lr * 400 + (1 + 2 * (w & 1) + (lm & 1) + 4 * (lm >> 1)) * 16;
#pragma unroll
            for (int i = 0; i < 3; i++)
                stsm_x4(za + i * 128, pack2(Z8[8 * i], Z8[8 * i + 1]), pack2(Z8[8 * i + 2], Z8[8 * i + 3]), pack2(Z8[8 * i + 4], Z8[8 * i + 5]), pack2(Z8[8 * i + 6], Z8[8 * i + 7]));
            const int Cz = 2 * (16 * (w & 1) + 8 * (lm & 1) + lr) + (lm >> 1);
            const uint32_t zc = cb + ((w >> 1) ? XO_ZD : XO_ZC) + (Cz & 7) * 272 + (1 + (Cz >> 3)) * 16;
#pragma unroll
            for (int ob = 0; ob < 2; ob++) stsm_x4(zc + ob * 128, z16[4 * ob], z16[4 * ob + 1], z16[4 * ob + 2], z16[4 * ob + 3]);
            if (lane < 8) *(uint4*)(sm + (cb - sb) + ((w < 2) ? (XO_ZA + w * 3200 + lane * 400) : (XO_ZC + (w - 2) * 2176 + lane * 272))) = make_uint4(0, 0, 0, 0);
        }
        gaw = ld_rlx(&S->modw[gidx]);
        if (tmu && wgi >= 2 && (tid & 127) == 96) {
            const uint32_t mbu = sb + OFF_MISC + (uint32_t)offsetof(Misc, mbar) + 24;
            if (wgi == 2) mbar_expect(mbu, 36864);
            tma2d(sb + OFF_WU + (wgi - 2) * 12288, tmu, f0, 192 * (wgi - 2), mbu);
        }
        __syncwarp();
        if ((tid & 127) == 64) rcnt = ld_rlx(S->cnt);
        {
#pragma unroll
            for (int i = 0; i < 16; i++) D[i] = 0.f;
            uint32_t pa = cb + XO_TD + (8 + 16 * w + g - 2 * t) * 4;
            uint32_t dlo = (((cb + 9 * 16) & 0x3FFFF) >> 4) | ((ULBO >> 4) << 16);
#define DS(o) (((uint64_t)(128 >> 4) << 32) | (uint64_t)(dlo + (o)))
#define KST (2 * (ULBO / 16))
            uint32_t pA[9], pB[9];
#pragma unroll
            for (int s = 0; s < 9; s++) pA[s] = lds32(pa + s * 32);
#pragma unroll 1
            for (int j = 0; j < 4; j++) {
                WG_FENCE();
#pragma unroll
                for (int q = 0; q < 4; q++) wg32(D, TQ(pA, q), DS((3 - q) * KST));
                WG_COMMIT();
                WG_WAIT(1);
#pragma unroll
                for (int s = 0; s < 9; s++) pB[s] = lds32(pa + 256 + s * 32);
                WG_FENCE();
#pragma unroll
                for (int q = 0; q < 4; q++) wg32(D, TQ(pB, q), DS((3 - q) * KST - 1));
                WG_COMMIT();
                WG_WAIT(1);
#pragma unroll
                for (int s = 0; s < 9; s++) pA[s] = lds32(pa + 512 + s * 32);
                dlo -= 2; pa += 512;
            }
            pB[1] = lds32(pa + 256 + 32); pB[2] = lds32(pa + 256 + 64);
            WG_FENCE();
#pragma unroll
            for (int q = 0; q < 4; q++) wg32(D, TQ(pA, q), DS((3 - q) * KST));
            wg32(D, pB[1], pB[2], pA[8], pB[1], DS(3 * KST - 1));
            WG_COMMIT();
        }
        if (tid == 128) bulk_pf(pf_src, 16 * D_ * 2);
        if ((tid & 127) == 64) {
#pragma unroll 1
            for (int it = 0; it < SPIN_MAX && (int)(rcnt - G_ * epoch) < 0; it++) rcnt = ld_rlx(S->cnt);
        }
    }
    {
        named_bar(1 + wgi, 128);
        {
            const uint4* pq = M.box + (6 + g - 2 * t);
#define QM(q) (q).x, (q).y, (q).z, (q).w
            uint32_t bA[2][6], bB[2][6], bC[3][4], bD[2][4], bU[2][4];
            const uint32_t k2 = lds32(cb + XO_K1024);
            uint32_t ofs[3];
#pragma unroll
            for (int d = 0; d < 3; d++) ofs[d] = cb + ((w - d) < 0 ? 0 : 16) + (lr + 8 * (lm >> 1)) * 16;
#define COL(d) (2 * ((w - (d)) & 3) + (lm & 1))
            WG_WAIT(0);
            uint4 m[4];
#pragma unroll
            for (int d = 0; d < 2; d++) {
                const uint32_t a = XO_ZA + COL(d) * 400 + ofs[d];
                ldsm_x4(bA[d], a); ldsm_x4(bB[d], a + 3200);
                uint32_t r[4];
                ldsm_x4(r, a + 256 + (lm >> 1) * (3200 - 128));
                bA[d][4] = r[0]; bA[d][5] = r[1]; bB[d][4] = r[2]; bB[d][5] = r[3];
            }
#pragma unroll
            for (int i = 0; i < 4; i++) m[i] = pq[14 * i];
#pragma unroll
            for (int d = 0; d < 2; d++)
#pragma unroll
                for (int c = 0; c < 3; c++) mma_bf16(D + 4 + 4 * c, QM(m[d]), bA[d][2 * c], bA[d][2 * c + 1]);
#pragma unroll
            for (int d = 0; d < 3; d++) ldsm_x4(bC[d], XO_ZC + COL(d) * 272 + ofs[d]);
#pragma unroll
            for (int d = 0; d < 2; d++)
#pragma unroll
                for (int c = 0; c < 3; c++) mma_bf16(D + 4 + 4 * c, QM(m[2 + d]), bB[d][2 * c], bB[d][2 * c + 1]);
#pragma unroll
            for (int i = 0; i < 3; i++) m[i] = pq[14 * (4 + i)];
#pragma unroll
            for (int d = 0; d < 2; d++) { ldsm_x4(bD[d], XO_ZD + COL(d) * 272 + ofs[d]); ldsm_x4(bU[d], COL(d) * ULBO + 128 + ofs[d]); }
#pragma unroll
            for (int d = 0; d < 3; d++)
#pragma unroll
                for (int c = 0; c < 2; c++) mma_bf16(D + 8 + 4 * c, QM(m[d]), bC[d][2 * c], bC[d][2 * c + 1]);
#pragma unroll
            for (int i = 0; i < 4; i++) m[i] = pq[14 * (7 + i)];
#pragma unroll
            for (int d = 0; d < 2; d++)
#pragma unroll
                for (int c = 0; c < 2; c++) mma_bf16(D + 8 + 4 * c, QM(m[d]), bD[d][2 * c], bD[d][2 * c + 1]);
#pragma unroll
            for (int d = 0; d < 2; d++) {
                m[2 + d].x &= k2; m[2 + d].y &= k2; m[2 + d].z &= k2; m[2 + d].w &= k2;
#pragma unroll
                for (int c = 0; c < 2; c++) mma_bf16(D + 8 + 4 * c, QM(m[2 + d]), bU[d][2 * c], bU[d][2 * c + 1]);
            }
        }
        {
#pragma unroll 1
            for (int it = 0; it < SPIN_MAX && (gaw >> 16) != tag16; it++) gaw = ld_rlx(&S->modw[gidx]);
            const uint32_t ga2 = __byte_perm(gaw, 0, 0x1010), dk2 = M.pk[3][wgi];
            const uint32_t ua = cb + (2 * w + (lm & 1)) * ULBO + (9 + lr + 8 * (lm >> 1)) * 16;
            const uint32_t ya = cb + XO_TD + w * 1024;
            const uint32_t sa = ya + (lr + 8 * (lm >> 1)) * 32 + (((lm & 1) ^ ((lane >> 2) & 1)) << 4);
#pragma unroll
            for (int cc = 0; cc < 2; cc++) {
                uint32_t u[4], v[4];
                ldsm_x4_t(u, ua + cc * 256);
#pragma unroll
                for (int m = 0; m < 4; m++) {
                    const int c = 2 * cc + (m >> 1), h = m & 1;
                    v[m] = ~mul2(ga2, add2(pack2(D[4 * c + 2 * h], D[4 * c + 2 * h + 1]), mul2(u[m], dk2)));
                }
                stsm_x4_t(sa + cc * 512, v[0], v[1], v[2], v[3]);
            }
            __syncwarp();
            const int sw = (lane >> 3) & 1;
            const uint32_t vo = (uint32_t)(((4 * (lane >> 1) + w) * D_ + gidx - 2 * D_) * 32 + (lane & 1) * 16);
            const unsigned char* yp = sm + (ya - sb) + (lane >> 1) * 32 + (lane & 1) * 8;
#pragma unroll
            for (int i = 0; i < 2; i++) {
                const uint2 A = *(const uint2*)(yp + i * 512 + (sw << 4)), B = *(const uint2*)(yp + i * 512 + ((sw ^ 1) << 4));
                st_rlx4((char*)S->v + vo + i * (64 * D_ * 32), make_uint4(A.x, B.x, A.y, B.y));
            }
        }
    }
}

__global__ void __launch_bounds__(NTHR, 1)
mega_kernel(const bf16* __restrict__ x, const bf16* __restrict__ logAr, const bf16* __restrict__ Aim,
            const bf16* __restrict__ Cr, const bf16* __restrict__ Ci, const bf16* __restrict__ logdt, const bf16* __restrict__ c_in,
            Scratch* __restrict__ S, const bf16* __restrict__ Dskip, const bf16* __restrict__ w_r, const bf16* __restrict__ w_down,
            bf16* __restrict__ out,
            const __grid_constant__ CUtensorMap tm_wm, const __grid_constant__ CUtensorMap tm_wg, const __grid_constant__ CUtensorMap tm_wu,
            const __grid_constant__ CUtensorMap tm_wd, const __grid_constant__ CUtensorMap tm_wd32,
            const __grid_constant__ CUtensorMap tm_wg32, const __grid_constant__ CUtensorMap tm_wu32) {
    extern __shared__ __align__(1024) unsigned char sm[];
    Misc& M = *(Misc*)(sm + OFF_MISC);
    const uint32_t sb = (uint32_t)__cvta_generic_to_shared(sm);
    const int tid = threadIdx.x, warp = __shfl_sync(0xffffffffu, tid >> 5, 0), lane = tid & 31;
    const int g = lane >> 2, t = lane & 3, lr = lane & 7, lm = lane >> 3;
    const int wgi = warp >> 2, w = warp & 3;
    const int b = blockIdx.x;
    const int nch = 5 - (b & 1), cs = 9 * (b >> 1) + 5 * (b & 1);
    const int f0 = 72 * (b >> 1) + 32 * (b & 1), nf = 32 + 8 * (b & 1);
    const bool has_ch = wgi < nch;
    const uint32_t mb0 = sb + OFF_MISC + offsetof(Misc, mbar), mb_wm = mb0, mb_wg = mb0 + 16, mb_wu = mb0 + 24, mb_wd = mb0 + 32;
    const uint32_t cb = sb + OFF_CH + wgi * CHS;

    if (wgi == 3) {
        M.sent[tid - 384] = make_uint4(SENT, SENT, SENT, SENT);
        M.sent[tid - 256] = make_uint4(SENT, SENT, SENT, SENT);
        if (tid == 384) {
            M.epoch = 0u; M.flag = 0u; M.e1cnt = 0u;
#pragma unroll
            for (int i = 0; i < 5; i++) mbar_init(mb0 + 8 * i, 1);
        }
        PROXY_FENCE();
        __syncwarp();
        if (warp == 12) { named_arrive(8, 160); if (b & 1) named_arrive(14, 64); }
        if (warp != 15) named_arrive(9, 128);
    }
    unsigned short r_ldt = 0, r_lar = 0, r_aim = 0, r_cr = 0, r_ci = 0;
    if (has_ch) {
        const int d = cs + wgi, n = d * N_ + (tid & 127);
        r_ldt = ld_nc16((const unsigned short*)logdt + d);
        r_lar = ld_nc16((const unsigned short*)logAr + n);
        r_aim = ld_nc16((const unsigned short*)Aim + n);
        r_cr = ld_nc16((const unsigned short*)Cr + n);
        r_ci = ld_nc16((const unsigned short*)Ci + n);
    } else {
        const unsigned short* cp = (const unsigned short*)c_in + (tid - 512);
        r_ldt = ld_nc16(cp); r_lar = ld_nc16(cp + 128); r_aim = ld_nc16(cp + 256); r_cr = ld_nc16(cp + 384);
        if (tid < 576) r_ci = ld_nc16(cp + 512);
    }
    uint4 xr[9];
    if (wgi == 4) {
        const uint4* p = (const uint4*)(x + (size_t)16 * b * D_) + (tid - 512);
#pragma unroll
        for (int i = 0; i < 9; i++) xr[i] = ld_nc4(p + 128 * i);
    }
    uint32_t wrv = 0;
    if (tid >= 128 && tid < 416) wrv = ld_nc((const uint32_t*)w_r + (tid - 128));
    if (warp == 2 && lane < nch) M.pk[3][lane] = (uint32_t)ld_nc16((const unsigned short*)Dskip + cs + lane) * 0x10001u;
    if (tid == 384) {
        const unsigned int tk = atomicAdd(S->ticket, 1u);
        *(volatile unsigned int*)&M.epoch = (tk >> 7) + 1u;
    }
    if (has_ch) {
        for (int i = tid & 127; i < 296; i += 128) *(uint4*)(sm + OFF_CH + wgi * CHS + XO_TD + i * 16) = make_uint4(0, 0, 0, 0);
    }
    if (tid < 154) {
        const int idx = (tid * 4682) >> 16, dl = tid - 14 * idx - 6;
        const int a = (0x44332221100ull >> (4 * idx)) & 7, d = (0x10102101010ull >> (4 * idx)) & 3;
        const int lo = (0x35c36 >> (4 * a)) & 15, wd = (0x16824 >> (4 * a)) & 15;
        const uint32_t one = (a == 4) ? 0xFFFFu : 0x3F80u;
        auto mk = [&](int l) { return (((unsigned)(l - lo) <= (unsigned)wd) ? one : 0u) | (((unsigned)(l - 1 - lo) <= (unsigned)wd) ? (one << 16) : 0u); };
        const int l0 = 16 * d + dl;
        M.box[tid] = make_uint4(mk(l0), mk(l0 + 8), mk(l0 - 8), mk(l0));
    }
    uint32_t xo[6];
#pragma unroll
    for (int i = 0; i < 6; i++) {
        const int ch = 16 * (warp + 16 * (i >> 1)) + 8 * (i & 1) + g;
        const int pr = (ch * 7282) >> 16, rm = ch - 9 * pr, hi = rm >= 5;
        xo[i] = (uint32_t)((((2 * pr + hi) * G_ + b) * 5 + rm - 5 * hi) * 32 + t * 8);
    }
    auto e1_store = [&]() {
        named_bar(11, 640);
        uint32_t mm[2], rhh[2], rll[2];
#pragma unroll
        for (int h = 0; h < 2; h++) {
            mm[h] = ((const uint32_t*)M.st1[0])[t + 4 * h]; rhh[h] = ((const uint32_t*)M.st1[1])[t + 4 * h]; rll[h] = ((const uint32_t*)M.st1[2])[t + 4 * h];
        }
        const uint32_t ta = sb + OFF_TILE + (lr + 8 * (lm & 1)) * (ROWP * 2) + (lm >> 1) * 16 + warp * 32;
#pragma unroll
        for (int i = 0; i < 3; i++) {
            if (i < 2 || warp < 4) {
                uint32_t r[4];
                ldsm_x4_t(r, ta + i * 512);
#pragma unroll
                for (int h = 0; h < 2; h++)
                    st_rlx2((char*)S->xn + xo[2 * i + h], ~norm2(r[2 * h], mm[0], rhh[0], rll[0]), ~norm2(r[2 * h + 1], mm[1], rhh[1], rll[1]));
            }
        }
        __syncwarp();
        if (lane == 0 && atomicAdd(&M.e1cnt, 1u) == 15u) red_inc(S->hint);
    };
    const float p_ldt = lo2f(r_ldt), p_lar = lo2f(r_lar), p_aim = lo2f(r_aim), p_cr = lo2f(r_cr), p_ci = lo2f(r_ci);
    cplx z1 = {0.f, 0.f}, z16 = z1, z256 = z1, C = z1;
    const uint32_t scr = cb + w * KSCR, ws = scr + lane * 4;
    float acc[5][4];
    uint32_t afr[4][4], cz[4];
    cplx z2 = {0.f, 0.f};
    const uint32_t ba = scr + lr * 144 + lm * 16;
    auto tile = [&](float* c, int rg) {
        __syncwarp();
        c[0] = c[1] = c[2] = c[3] = 0.f;
        uint32_t bb[2][4];
        ldsm_x4(bb[0], ba + rg * 1152);
        ldsm_x4(bb[1], ba + rg * 1152 + 64);
        mma_f16(c, afr[0], bb[0][0], bb[0][1]);
        mma_f16(c, afr[1], bb[0][2], bb[0][3]);
        mma_f16(c, afr[2], bb[1][0], bb[1][1]);
        mma_f16(c, afr[3], bb[1][2], bb[1][3]);
    };
#define CJ(z) packh((z).x, -(z).y)
#define CJP(z) packh((z).y, (z).x)
    uint32_t ex = 0;
    if (has_ch) {
        const float dt = bfr(expf(p_ldt));
        const float al = -bfr(expf(p_lar)) * dt * 1.4426950408889634f;
        const float th = p_aim * dt;
        const float th_ = th * 0.15915494309189535f;
        const float tl_ = fmaf(th, 0.15915494309189535f, -th_) + th * 6.4206382e-9f;
        auto anchor = [&](float s) {
            float f = th_ * s;
            f -= rintf(f);
            f = fmaf(tl_, s, f) * 6.283185307179586f;
            const float e = fex2(al * s);
            return cplx{e * __cosf(f), e * __sinf(f)};
        };
        const float cx = p_cr * dt * 2.0f, cy = p_ci * dt * 2.0f;
        ex = __reduce_max_sync(0xffffffffu, __float_as_uint(fmaxf(fabsf(cx), fabsf(cy)))) >> 23;
        const float scl = __uint_as_float((254u - ex) << 23);
        C = cplx{cx * scl, cy * scl};
        z1 = anchor(1.f); z16 = anchor(16.f); z256 = anchor(256.f);
            {
                const cplx z32 = csq(z16), z48 = cmul(z32, z16), z64 = csq(z32), z128 = csq(z64), z192 = cmul(z128, z64);
                const uint32_t y[3] = {packh(z16.x, z16.y), packh(z32.x, z32.y), packh(z48.x, z48.y)};
                const uint32_t yp[3] = {packh(-z16.y, z16.x), packh(-z32.y, z32.x), packh(-z48.y, z48.x)};
                const uint32_t xx[3] = {packh(z64.x, z64.y), packh(z128.x, z128.y), packh(z192.x, z192.y)};
                sts32(ws, 0x00003C00u);
#pragma unroll
                for (int j = 0; j < 3; j++) sts32(ws + (1 + j) * 144, y[j]);
#pragma unroll
                for (int i = 0; i < 3; i++) {
                    sts32(ws + (4 + 4 * i) * 144, xx[i]);
#pragma unroll
                    for (int j = 0; j < 3; j++) sts32(ws + (5 + 4 * i + j) * 144, hcm(xx[i], y[j], yp[j]));
                }
            }
    }
    if (wgi == 4) {
        if (!has_ch) {
            const int i = tid - 512;
            ((unsigned short*)M.sc)[i] = (unsigned short)f2bits(silu(lo2f(r_ldt)));
            ((unsigned short*)M.sc)[i + 128] = (unsigned short)f2bits(silu(lo2f(r_lar)));
            ((unsigned short*)M.sc)[i + 256] = (unsigned short)f2bits(silu(lo2f(r_aim)));
            ((unsigned short*)M.sc)[i + 384] = (unsigned short)f2bits(silu(lo2f(r_cr)));
            if (i < 64) ((unsigned short*)M.sc)[i + 512] = (unsigned short)f2bits(silu(lo2f(r_ci)));
            if (warp == 16) {
                named_bar(14, 64);
                if (lane == 0) {
                    mbar_expect(mb_wm, 36864);
#pragma unroll
                    for (int k = 0; k < 3; k++) tma2d(sb + OFF_WU + k * 12288, &tm_wm, 32 * (b >> 1), 192 * k, mb_wm);
                }
                __syncwarp();
            }
        }
#pragma unroll
        for (int i = 0; i < 9; i++) {
            const int c = tid - 512 + 128 * i, rr = (c * 911) >> 16;
            *(uint4*)(sm + OFF_TILE + rr * (ROWP * 2 - 1152) + c * 16) = xr[i];
        }
        named_bar(8, 160);
        {
            float c1[4] = {0.f, 0.f, 0.f, 0.f}, cl[4] = {0.f, 0.f, 0.f, 0.f}, chh[4] = {0.f, 0.f, 0.f, 0.f};
            const uint32_t a0 = sb + OFF_TILE + (lane & 15) * (ROWP * 2) + (lane >> 4) * 16 + w * 288;
            uint32_t a[9][4];
#pragma unroll
            for (int ks = 0; ks < 9; ks++) ldsm_x4(a[ks], a0 + ks * 32);
#pragma unroll
            for (int ks = 0; ks < 9; ks++) {
                mma_bf16(c1, a[ks][0], a[ks][1], a[ks][2], a[ks][3], 0x3F803F80u, 0x3F803F80u);
                mma_bf16(cl, a[ks][0], a[ks][1], a[ks][2], a[ks][3], a[ks][0], a[ks][2]);
                mma_bf16(chh, a[ks][0], a[ks][1], a[ks][2], a[ks][3], a[ks][1], a[ks][3]);
            }
            if (t == 0) { M.p1[g][w] = c1[0]; M.p1[g + 8][w] = c1[2]; }
            if (t == (g >> 1)) { M.p2[g][w] = (g & 1) ? cl[1] : cl[0]; M.p2[g + 8][w] = (g & 1) ? chh[3] : chh[2]; }
        }
        named_bar(5, 128);
        if (warp == 16) {
            const float4 q1 = *(const float4*)M.p1[lane & 15], q2 = *(const float4*)M.p2[lane & 15];
            float meanb, rinv;
            ln_stats((q1.x + q1.y) + (q1.z + q1.w), (q2.x + q2.y) + (q2.z + q2.w), meanb, rinv);
            const float rh = bfr(rinv);
            if (lane < 16) { M.st1[0][lane] = (unsigned short)f2bits(meanb); M.st1[1][lane] = (unsigned short)f2bits(rh); M.st1[2][lane] = (unsigned short)f2bits(rinv - rh); }
        }
        __syncwarp();
        named_arrive(11, 640);
    }
    auto publish_reset = [&]() {
        if (tid == 480) {
            asm volatile("cp.async.bulk.wait_group 0;" ::: "memory");
            asm volatile("fence.proxy.async;" ::: "memory");
            red_inc(S->cnt);
        }
    };
    uint32_t epoch = 0, tag16 = 0, pre = 0;
    auto mod_tile = [&](int rd) {
        const uint32_t* s2 = (const uint32_t*)M.sc + 144 * (w >> 1) + t;
        uint32_t bb[18][2];
#pragma unroll
        for (int ks = 0; ks < 18; ks++) { bb[ks][0] = (g == 0) ? s2[8 * ks] : 0u; bb[ks][1] = (g == 0) ? s2[8 * ks + 4] : 0u; }
        float acc[2][4] = {{0.f, 0.f, 0.f, 0.f}, {0.f, 0.f, 0.f, 0.f}};
        const int row = lr + 8 * (lm >> 1);
        const uint32_t wa = sb + OFF_WU + (288 * (w >> 1) + row) * 64 + ((((2 * (w & 1) + (lm & 1)) ^ (row >> 1)) & 3) << 4);
        mbar_wait(mb_wm + 8 * rd, 0);
        if (rd == 0)
#pragma unroll
        for (int kb = 0; kb < 2; kb++) {
            uint32_t a[9][4];
#pragma unroll
            for (int ks = 0; ks < 9; ks++) ldsm_x4_t(a[ks], wa + (9 * kb + ks) * 1024);
#pragma unroll
            for (int ks = 0; ks < 9; ks++) mma_bf16(acc[ks & 1], a[ks][0], a[ks][1], a[ks][2], a[ks][3], bb[9 * kb + ks][0], bb[9 * kb + ks][1]);
        }
        const float v0 = acc[0][0] + acc[1][0], v1 = acc[0][2] + acc[1][2];
        float* mx = M.modx + 16 * (w & 1) + g;
        if (w >= 2 && t == 0) { mx[0] = v0; mx[8] = v1; }
        named_bar(5, 128);
        if (w < 2 && t == 0) {
            unsigned int* mp = &S->modw[32 * ((b >> 1) + 64 * rd) + 16 * w + g];
            st_rlx(mp, f2bits(v0 + mx[0]) | (tag16 << 16));
            st_rlx(mp + 8, f2bits(v1 + mx[8]) | (tag16 << 16));
        }
        if (rd == 0 && w < 2 && b < 108) {
            named_bar(7, 64);
            if (tid == 512) red_inc(S->hint);
        }
    };
    if (has_ch) {
        {
            z2 = csq(z1);
            const cplx z3 = cmul(z2, z1), z4 = csq(z2), z8 = csq(z4);
            const cplx c4 = cmul(C, z4), c8 = cmul(C, z8), c12 = cmul(c8, z4);
            cz[0] = packh(C.x, -C.y); cz[1] = packh(c4.x, -c4.y); cz[2] = packh(c8.x, -c8.y); cz[3] = packh(c12.x, -c12.y);
            __syncwarp();
#pragma unroll
            for (int s = 0; s < 4; s++) ldsm_x4(afr[s], scr + (lr + 8 * (lm & 1)) * 144 + (2 * s + (lm >> 1)) * 16);
            {
                const uint32_t y[3] = {CJ(z1), CJ(z2), CJ(z3)}, yp[3] = {CJP(z1), CJP(z2), CJP(z3)};
#pragma unroll
                for (int tt = 0; tt < 2; tt++) {
                    const int rg = tt ? 0 : 2;
#pragma unroll
                    for (int i = 0; i < 2; i++) {
                        sts32(ws + rg * 1152 + (4 * i) * 144, cz[2 * tt + i]);
#pragma unroll
                        for (int j = 0; j < 3; j++) sts32(ws + rg * 1152 + (4 * i + 1 + j) * 144, hcm(cz[2 * tt + i], y[j], yp[j]));
                    }
                    tile(acc[tt], rg);
                }
            }
            if (tid >= 128 && tid < 416) M.wr[tid - 128] = wrv;
            if (wgi < 4) e1_store();
    if (warp == 15) {
        named_bar(9, 128);
        if (lane == 0) {
#pragma unroll 1
            for (int i = 0; i < 5; i++) {
                bulk_s2g((char*)&S->v[(size_t)b * 1152] + i * 4096, sb + OFF_MISC, i < 4 ? 4096 : 2048);
                if (i < 3) bulk_s2g((char*)&S->part[(size_t)b * 1152] + i * 4096, sb + OFF_MISC, i < 2 ? 4096 : 1024);
            }
            bulk_s2g(&S->rec[8 * b], sb + OFF_MISC, 32);
            asm volatile("cp.async.bulk.commit_group;" ::: "memory");
        }
        __syncwarp();
    }
            const cplx z258 = cmul(z256, z2), z512 = csq(z256), z768 = cmul(z512, z256);
            {
                const uint32_t a0 = CJ(z256), a0p = CJP(z256), a1 = CJ(z258), a1p = CJP(z258);
#pragma unroll
                for (int i = 0; i < 4; i++) { sts32(ws + 1152 + (2 * i) * 144, hcm(cz[i], a0, a0p)); sts32(ws + 1152 + (2 * i + 1) * 144, hcm(cz[i], a1, a1p)); }
                tile(acc[2], 1);
            }
            {
                const uint32_t a0 = CJ(z512), a0p = CJP(z512), a1 = CJ(z768), a1p = CJP(z768);
#pragma unroll
                for (int i = 0; i < 4; i++) { sts32(ws + 2304 + i * 144, hcm(cz[i], a0, a0p)); sts32(ws + 2304 + (4 + i) * 144, hcm(cz[i], a1, a1p)); }
                tile(acc[3], 2);
            }
            if (warp == 3) {
                if (lane == 15) pre = ld_rlx(S->hint);
            }
            const cplx z1024 = csq(z512);
            {
                const cplx zk[4] = {z1024, cmul(z1024, z256), csq(z768), cmul(z1024, z768)};
#pragma unroll
                for (int h = 0; h < 4; h++) {
                    const uint32_t a0 = CJ(zk[h]), a0p = CJP(zk[h]);
                    sts32(ws + (2 * h) * 144, hcm(cz[0], a0, a0p));
                    sts32(ws + (2 * h + 1) * 144, hcm(cz[2], a0, a0p));
                }
                tile(acc[4], 0);
            }
            const cplx z2048 = csq(z1024);
            float last = C.x * z2048.x - C.y * z2048.y;
#pragma unroll
            for (int o = 16; o; o >>= 1) last += __shfl_xor_sync(0xffffffffu, last, o);
            __syncwarp();
#pragma unroll
            for (int i = 0; i < 5; i++) *(float4*)(sm + (scr - sb) + i * 512 + lane * 16) = make_float4(acc[i][0], acc[i][1], acc[i][2], acc[i][3]);
            if (lane == 0) { const float inv = __uint_as_float(ex << 23); M.kinv[wgi][w] = inv; M.klast[wgi][w] = last * inv; }
        }
        if (tid == 111 && (int)(pre - HINT_N * wait_epoch(M)) >= 0) M.flag = 1u;
        named_bar(1 + wgi, 128);
        const uint32_t td = cb + XO_TD + 64 * 4, tf = cb + XO_TF - 32 * 4;
        if (tid == 111 && !M.flag) pre = ld_rlx(S->hint);
        const float4 ki = *(const float4*)M.kinv[wgi];
        auto fsum = [&](int off, uint32_t& r0, uint32_t& r1) {
            const unsigned char* p = sm + (cb - sb) + off;
            const float4 a = *(const float4*)p, b2 = *(const float4*)(p + KSCR), c = *(const float4*)(p + 2 * KSCR), d = *(const float4*)(p + 3 * KSCR);
            r0 = pack2(fmaf(a.y, ki.x, b2.y * ki.y) + fmaf(c.y, ki.z, d.y * ki.w), fmaf(a.x, ki.x, b2.x * ki.y) + fmaf(c.x, ki.z, d.x * ki.w));
            r1 = pack2(fmaf(a.w, ki.x, b2.w * ki.y) + fmaf(c.w, ki.z, d.w * ki.w), fmaf(a.z, ki.x, b2.z * ki.y) + fmaf(c.z, ki.z, d.z * ki.w));
        };
        uint32_t r[2], q[2];
        fsum(w * 512 + lane * 16, r[0], r[1]);
        fsum(2048 + w * 128 + lr * 16, q[0], q[1]);
        if (tid == 111) {
            if ((int)(pre - HINT_N * M.epoch) >= 0) M.flag = 1u;
            else pre = ld_rlx(S->hint);
        }
        __syncwarp();
        if (w < 2) {
            const uint32_t p = td + (16 * g + 8 * w + 2 * t) * 4;
#pragma unroll
            for (int h = 0; h < 2; h++) { sts16(p + h * 512, r[h] >> 16); sts32(p + h * 512 + 4, r[h]); sts16(p + h * 512 + 10, r[h]); }
        } else if (w == 2) {
            const uint32_t p = td + (256 + 16 * g + 4 * t) * 4;
#pragma unroll
            for (int h = 0; h < 2; h++) {
                const uint32_t k0 = r[h] >> 16;
                if (h || lane) { sts16(p + h * 512 - 4, k0); sts16(p + h * 512 + 2, k0); }
                sts16(p + h * 512, k0); sts32(p + h * 512 + 4, __byte_perm(r[h], 0, 0x3232)); sts32(p + h * 512 + 8, r[h]); sts16(p + h * 512 + 14, r[h]);
            }
        } else {
            const uint32_t p = tf + (64 + 32 * (t >> 1) + 2 * g + (t & 1)) * 4;
#pragma unroll
            for (int h = 0; h < 2; h++) {
                const uint32_t k0 = r[h] >> 16;
                sts16(p + h * 64 + 512, r[h]); sts16(p + h * 64 + 518, r[h]);
                if (h || lane) { sts16(p + h * 64 - 4, k0); sts16(p + h * 64 + 2, k0); }
            }
            if (lane == 0) {
                const uint32_t dd = __byte_perm(r[0], 0, 0x3232);
                sts16(td + 511 * 4, dd); sts32(td + 512 * 4, dd); sts32(td + 513 * 4, dd); sts32(td + 514 * 4, dd); sts16(td + 515 * 4 + 2, dd);
            }
        }
        if (lane < 8) {
            const uint32_t p = tf + 1024 + (64 + 16 * t + 2 * w + g) * 4;
#pragma unroll
            for (int h = 0; h < 2; h++) {
                const uint32_t k0 = q[h] >> 16;
                sts16(p + h * 32 + 512, q[h]); sts16(p + h * 32 + 518, q[h]);
                if (h || (tid & 127)) { sts16(p + h * 32 - 4, k0); sts16(p + h * 32 + 2, k0); }
            }
            if ((tid & 127) == 0) {
                const float4 kl4 = *(const float4*)M.klast[wgi];
                const uint32_t kl = f2bits((kl4.x + kl4.y) + (kl4.z + kl4.w)), dd = __byte_perm(q[0], 0, 0x3232);
                sts16(tf + 127 * 4, dd); sts16(tf + 128 * 4 + 2, dd); sts32(cb + XO_K1024, dd);
                sts16(tf + 1024 + 127 * 4, kl); sts16(tf + 1024 + 128 * 4 + 2, kl);
            }
        }
        __syncwarp();
    } else {
        const int i = tid - 512, idx = b >> 1;
        tag16 = (wait_epoch(M) % 65535u) + 1u;
        mod_tile(0);
        if (i == 0 && idx < 44) {
            PROXY_FENCE();
            mbar_expect(mb_wm + 8, 36864);
#pragma unroll
            for (int k = 0; k < 3; k++) tma2d(sb + OFF_WU + k * 12288, &tm_wm, 32 * (idx + 64), 192 * k, mb_wm + 8);
        }
        __syncwarp();
    }
    if (tid == 111) {
        epoch = wait_epoch(M);
#pragma unroll 1
        for (int it = 0; it < SPIN_MAX && (int)(pre - HINT_N * epoch) < 0; it++) pre = ld_rlx(S->hint);
        M.flag = 1u;
    }
    __syncwarp();
    const int ubp = (tid * 13108) >> 16, uloc = tid - 5 * ubp;
    const uint4* usrc = &S->xn[(size_t)b * 1280 + 2 * tid];
    uint4 ua = make_uint4(0, 0, 0, 0), uc = ua;
    uint32_t usa = 0, uca = 0;
    if (lane == 0) {
#pragma unroll 1
        for (int it = 0; it < (SPIN_MAX << 4) && !M.flag; it++) { }
    }
    __syncwarp();
    if (uloc < nch) {
 ua = ld_rlx4(usrc); uc = ld_rlx4(usrc + 1); usa = ld_rlx(&S->modw[cs + uloc]); uca = ld_rlx(&S->modw[D_ + cs + uloc]); }
    CBAR();
    epoch = M.epoch;
    tag16 = (epoch % 65535u) + 1u;
    {
        const int bp = ubp, loc = uloc;
        if (loc < nch) {
            const uint4* src = usrc;
            uint4 a = ua, c = uc;
#pragma unroll 1
            for (int it = 0; it < SPIN_MAX && (a.x == SENT || a.z == SENT || c.x == SENT || c.z == SENT || (usa >> 16) != tag16 || (uca >> 16) != tag16); it++) {
                a = ld_rlx4(src); c = ld_rlx4(src + 1); usa = ld_rlx(&S->modw[cs + loc]); uca = ld_rlx(&S->modw[D_ + cs + loc]);
            }
            const uint32_t sa = __byte_perm(usa, 0, 0x1010), ca = pack2(1.0f + lo2f(uca), 1.0f + lo2f(uca));
            unsigned char* up = sm + OFF_CH + loc * CHS + ((2 * bp) & 7) * ULBO + ((bp >> 2) + 9) * 16;
            *(uint4*)up = make_uint4(add2(mul2(~a.x, ca), sa), add2(mul2(~a.z, ca), sa), add2(mul2(~c.x, ca), sa), add2(mul2(~c.z, ca), sa));
            *(uint4*)(up + ULBO) = make_uint4(add2(mul2(~a.y, ca), sa), add2(mul2(~a.w, ca), sa), add2(mul2(~c.y, ca), sa), add2(mul2(~c.w, ca), sa));
        }
        publish_reset();
        const int i = tid & 127;
        unsigned char* cp = sm + OFF_CH + wgi * CHS;
        *(uint4*)(cp + XO_U8 - 1024 + (i >> 6) * 4096 + (i & 63) * 16) = make_uint4(0, 0, 0, 0);
        if (i < 72) { const int c = (i * 57) >> 9; *(uint4*)(cp + c * ULBO + (i - 9 * c) * 16) = make_uint4(0, 0, 0, 0); }
    }
    PROXY_FENCE();
    CBAR();
    if (w == 2 && lane == 0) {
        bulk_s2g((char*)&S->xn[(size_t)b * 1280] + wgi * 4096, sb + OFF_MISC, 4096);
        asm volatile("cp.async.bulk.commit_group;" ::: "memory");
    }
        if (tid == 416) {
            mbar_expect(mb_wg, nf * D_ * 2);
            tma2d(sb + OFF_WG, (b & 1) ? &tm_wg : &tm_wg32, f0, 0, mb_wg);
        }
    if (tid == 96 || tid == 224) tma2d(sb + OFF_WG + (1 + (tid >> 7)) * (nf * 384), (b & 1) ? &tm_wg : &tm_wg32, f0, 192 * (1 + (tid >> 7)), mb_wg);
    if (has_ch) {
        __syncwarp();
        conv_channel(sm, S, 2 * D_ + cs + wgi, epoch, w_down + (size_t)f0 * D_, (b & 1) ? nullptr : &tm_wu32, f0);
    } else {
        const int idx = b >> 1;
        if (idx < 44) mod_tile(1);
        if (tid == 512) {
            PROXY_FENCE();
            mbar_expect(mb_wu, 46080);
#pragma unroll 1
            for (int i = 0; i < 3; i++) {
                tma2d(sb + OFF_WU + i * 15360, &tm_wu, f0, 192 * i, mb_wu);
                const long long c0 = clock64();
                int it = 0;
                while (clock64() - c0 < 1200 && ++it < 4096) { }
            }
            wait_reset(S->cnt, epoch);
        }
        named_bar(5, 128);
    }
    {
    const int tid = fresh_tid(), warp = __shfl_sync(0xffffffffu, tid >> 5, 0), lane = tid & 31;
    const int g = lane >> 2, t = lane & 3, lr = lane & 7, lm = lane >> 3;
    uint32_t v3 = 0, v4 = 0, v5 = 0;
    auto load_consts = [&]() {
        if (tid < D_) { v3 = ld_rlx(&S->modw[3 * D_ + tid]); v4 = ld_rlx(&S->modw[4 * D_ + tid]); v5 = ld_rlx(&S->modw[5 * D_ + tid]); }
    };
    if (tid == 0) bulk_pf(w_down + (size_t)(f0 + 16) * D_, (nf - 16) * D_ * 2);
    uint32_t x1[2][4], wr2[2][2];
    if (warp < 18) {
        const char* vp = (const char*)S->v + ((size_t)b * D_ + 32 * warp + g) * 32 + t * 8;
        uint2 v[4];
#pragma unroll
        for (int i = 0; i < 4; i++) v[i] = ld_rlx2(vp + i * 256);
#pragma unroll
        for (int j = 0; j < 2; j++) {
            const uint32_t* wp = M.wr + 16 * warp + 8 * j + t;
            wr2[j][0] = (g == 0) ? wp[0] : 0u;
            wr2[j][1] = (g == 0) ? wp[4] : 0u;
            ldsm_x4(x1[j], sb + OFF_TILE + (lr + 8 * (lm & 1)) * (ROWP * 2) + (lm >> 1) * 16 + warp * 64 + j * 32);
        }
#pragma unroll 1
        for (int it = 0; it < SPIN_MAX && ((v3 >> 16) != tag16 || (v4 >> 16) != tag16 || (v5 >> 16) != tag16); it++) load_consts();
        ((unsigned short*)M.sb)[tid] = (unsigned short)v3;
        ((unsigned short*)M.cb1)[tid] = (unsigned short)f2bits(1.0f + lo2f(v4));
        ((unsigned short*)M.gb)[tid] = (unsigned short)v5;
#pragma unroll 1
        for (int it = 0; it < SPIN_MAX; it++) {
            bool bad = false;
#pragma unroll
            for (int i = 0; i < 4; i++) if (v[i].x == SENT) { v[i] = ld_rlx2(vp + i * 256); bad = true; }
            if (!bad) break;
        }
        __syncwarp();
        float c1[4] = {0.f, 0.f, 0.f, 0.f}, cl[4] = {0.f, 0.f, 0.f, 0.f}, chh[4] = {0.f, 0.f, 0.f, 0.f};
#pragma unroll
        for (int j = 0; j < 2; j++) {
            x1[j][0] = add2(x1[j][0], movm(~v[2 * j].x)); x1[j][1] = add2(x1[j][1], movm(~v[2 * j].y));
            x1[j][2] = add2(x1[j][2], movm(~v[2 * j + 1].x)); x1[j][3] = add2(x1[j][3], movm(~v[2 * j + 1].y));
            mma_bf16(c1, x1[j][0], x1[j][1], x1[j][2], x1[j][3], 0x3F803F80u, 0x3F803F80u);
            mma_bf16(cl, x1[j][0], x1[j][1], x1[j][2], x1[j][3], x1[j][0], x1[j][2]);
            mma_bf16(chh, x1[j][0], x1[j][1], x1[j][2], x1[j][3], x1[j][1], x1[j][3]);
        }
        float* pp = (float*)&M.part[warp][g];
        if (t == 0) { pp[0] = c1[0]; pp[16] = c1[2]; }
        if (t == (g >> 1)) { pp[1] = (g & 1) ? cl[1] : cl[0]; pp[17] = (g & 1) ? chh[3] : chh[2]; }
    }
    CBAR();
    if (warp < 18) {
        const int tok = lane & 15, hf = lane >> 4;
        uint32_t kc[2][2][2];
#pragma unroll
        for (int j = 0; j < 2; j++)
#pragma unroll
            for (int q = 0; q < 2; q++) { kc[j][q][0] = ((const uint32_t*)M.cb1)[16 * warp + 8 * j + 4 * q + t]; kc[j][q][1] = ((const uint32_t*)M.sb)[16 * warp + 8 * j + 4 * q + t]; }
        named_bar(13, 608);
        uint32_t st[2][3];
#pragma unroll
        for (int h = 0; h < 2; h++) { const uint4 q = M.st2[g + 8 * h]; st[h][0] = q.x; st[h][1] = q.y; st[h][2] = q.z; }
        float rc[4] = {0.f, 0.f, 0.f, 0.f};
        uint32_t h2[2][4];
#pragma unroll
        for (int j = 0; j < 2; j++) {
#pragma unroll
            for (int r = 0; r < 4; r++) {
                h2[j][r] = add2(mul2(norm2(x1[j][r], st[r & 1][0], st[r & 1][1], st[r & 1][2]), kc[j][r >> 1][0]), kc[j][r >> 1][1]);
            }
            mma_bf16(rc, h2[j][0], h2[j][1], h2[j][2], h2[j][3], wr2[j][0], wr2[j][1]);
        }
        if (t == 0) { M.rp[warp][g] = rc[0]; M.rp[warp][g + 8] = rc[2]; }
        if (warp == 0) {
            named_bar(12, 576);
            float r = M.rp[9 * hf][tok];
#pragma unroll
            for (int i = 1; i < 9; i++) r += M.rp[9 * hf + i][tok];
            r += __shfl_xor_sync(0xffffffffu, r, 16);
            const uint32_t rbits = f2bits(r);
            const uint32_t key = 0x80000000u | ((rbits ^ ((rbits & 0x8000u) ? 0xFFFFu : 0x8000u)) << 11) | (uint32_t)(2047 - (16 * b + tok));
            int rank = 0;
#pragma unroll
            for (int j = 1; j < 16; j++) rank += __shfl_xor_sync(0xffffffffu, key, j) > key;
            if (lane < 16) { M.skey[rank] = key; M.rank[rank] = tok; }
            __syncwarp();
            if (lane < 2) st_rlx4(&S->rec[8 * b + 4 * lane], *(const uint4*)&M.skey[4 * lane]);
        } else named_arrive(12, 576);
#pragma unroll
        for (int j = 0; j < 2; j++) {
            uint32_t o[4];
#pragma unroll
            for (int r = 0; r < 4; r++) o[r] = add2(x1[j][r], mul2(((const uint32_t*)M.gb)[16 * warp + 8 * j + 4 * (r >> 1) + t], h2[j][r]));
            const uint32_t to = (lr + 8 * (lm & 1)) * (ROWP * 2) + (lm >> 1) * 16 + warp * 64 + j * 32;
            stsm_x4(sb + OFF_H2T + to, h2[j][0], h2[j][1], h2[j][2], h2[j][3]);
            stsm_x4(sb + OFF_TILE + to, o[0], o[1], o[2], o[3]);
        }
    } else if (warp == 19) {
        const int tok = lane & 15, hf = lane >> 4;
        float2 s = M.part[9 * hf][tok];
#pragma unroll
        for (int i = 1; i < 9; i++) { const float2 q = M.part[9 * hf + i][tok]; s.x += q.x; s.y += q.y; }
        s.x += __shfl_xor_sync(0xffffffffu, s.x, 16); s.y += __shfl_xor_sync(0xffffffffu, s.y, 16);
        float meanb, rinv;
        ln_stats(s.x, s.y, meanb, rinv);
        const float rh = bfr(rinv);
        if (lane < 16) M.st2[tok] = make_uint4(pack2(meanb, meanb), pack2(rh, rh), pack2(rinv - rh, rinv - rh), 0u);
        __syncwarp();
        named_arrive(13, 608);
    } else if (lane < 9) {
        PROXY_FENCE();
        if (lane == 0) mbar_expect(mb_wd, nf * D_ * 2);
        tma2d(sb + OFF_WD + lane * 5120, (b & 1) ? &tm_wd : &tm_wd32, 64 * lane, f0, mb_wd);
    }
    CBAR();
    uint32_t wf[9][4], wd[2][3][4];
    const int fmt = warp >> 2, fsl = warp & 3;
    auto load_wf = [&]() {
        mbar_wait(mb_wg, 0);
        mbar_wait(mb_wu, 0);
        if (fmt < 4 || nf > 32) {
            const int half = lm & 1;
            const uint32_t base = (fmt == 4) ? ((half ? OFF_WU : OFF_WG) + 64)
                                             : ((fmt >> 1) * OFF_WU + (((2 * (fmt & 1) + half) ^ ((b & 1) ? 0 : (lr >> 1))) << 4));
            const uint32_t wa = sb + base + (144 * fsl + lr + 8 * (lm >> 1)) * (2 * nf);
#pragma unroll
            for (int ks = 0; ks < 9; ks++) ldsm_x4_t(wf[ks], wa + ks * (32 * nf));
        }
    mbar_wait(mb_wd, 0);
    {
#pragma unroll
        for (int i = 0; i < 2; i++) {
            const int mt = warp + 20 * i;
            const uint32_t wa = sb + OFF_WD + (mt >> 2) * 5120 + lr * 128 + (((2 * (mt & 3) + (lm & 1)) ^ lr) << 4);
#pragma unroll
            for (int ks = 0; ks < 3; ks++)
                if ((i == 0 || warp < 16) && (ks < 2 || nf > 32)) ldsm_x4_t(wd[i][ks], wa + ks * 2048 + ((ks < 2) ? (lm >> 1) * 1024 : 0));
        }
    }
    };
    if (warp >= 8) {
        if (warp < 16) {
            const int tk = M.rank[warp - 8];
            const uint32_t* hp = (const uint32_t*)(sm + OFF_H2T + tk * (ROWP * 2)) + lane;
            uint4* dst = &S->h2w[(size_t)(16 * b + tk) * 96 + lane];
#pragma unroll
            for (int j = 0; j < 3; j++) st_rlx4(dst + 32 * j, make_uint4(hp[96 * j], hp[96 * j + 32], hp[96 * j + 64], epoch));
        }
        load_wf();
    } else {
        const uint4* rp = (const uint4*)S->rec + tid;
        load_wf();
        uint4 rk = ld_rlx4(rp);
#pragma unroll 1
        for (int it = 0; it < SPIN_MAX && !rk.x; it++) rk = ld_rlx4(rp);
        __syncwarp();
        uint32_t mine = 0;
#pragma unroll
        for (int rnd = 0; rnd < 8; rnd++) {
            const uint32_t m = __reduce_max_sync(0xffffffffu, rk.x);
            if (rk.x == m) { rk.x = rk.y; rk.y = rk.z; rk.z = rk.w; rk.w = 0u; }
            if (lane == rnd) mine = m;
        }
        if (lane < 8) M.cand[8 * warp + lane] = mine;
    }
    CBAR();
    uint32_t selv = 0;
    if (warp < 12) {
        uint2 k = *(const uint2*)&M.cand[2 * lane];
#pragma unroll
        for (int rnd = 0; rnd < 8; rnd++) {
            const uint32_t m = __reduce_max_sync(0xffffffffu, k.x);
            if (k.x == m) { k.x = k.y; k.y = 0u; }
            if (lr == rnd) selv = m;
        }
        if (tid < 8) M.skey[tid] = selv;
    }
    const uint32_t seltok = 2047u - (selv & 2047u);
    const int fo = tid >> 3;
    const int fW = 9 * b + (fo >> 2), fcomp = fo & 3;
    const int fd = 16 * (fW >> 5) + ((fW >> 2) & 7) + 8 * (fcomp >> 1), fk = 2 * (fW & 3) + (fcomp & 1);
    const uint32_t fsel = __shfl_sync(0xffffffffu, selv, fk);
    uint32_t fx = 0, fv = 0;
    bf16(*h2s)[ROWP] = (bf16(*)[ROWP])(sm + OFF_H2S);
    if (warp < 12) {
        uint4 wv[2];
        const uint4* hp[2];
#pragma unroll
        for (int r = 0; r < 2; r++) {
            const int wi = warp + 12 * r, k = wi / 3, j = wi - 3 * k;
            hp[r] = &S->h2w[(size_t)__shfl_sync(0xffffffffu, seltok, k) * 96 + 32 * j + lane];
            wv[r] = ld_rlx4(hp[r]);
        }
        if (tid < 288 && (tid & 7) == 0) {
            const uint32_t ft = 2047u - (fsel & 2047u), pr = (ft & 15u) >> 1;
            fx = ((const unsigned short*)x)[(size_t)ft * D_ + fd];
            asm volatile("ld.relaxed.gpu.global.u16 %0, [%1];" : "=r"(fv)
                         : "l"((const unsigned short*)S->v + ((size_t)(ft >> 4) * D_ + fd) * 16 + ((pr & 3u) * 2 + (pr >> 2)) * 2 + (ft & 1u)) : "memory");
        }
#pragma unroll 1
        for (int it = 0; it < SPIN_MAX && (wv[0].w != epoch || wv[1].w != epoch); it++) { wv[0] = ld_rlx4(hp[0]); wv[1] = ld_rlx4(hp[1]); }
#pragma unroll
        for (int r = 0; r < 2; r++) {
            const int wi = warp + 12 * r, k = wi / 3, j = wi - 3 * k;
            uint32_t* dst = (uint32_t*)&h2s[k][0] + 96 * j + lane;
            dst[0] = wv[r].x; dst[32] = wv[r].y; dst[64] = wv[r].z;
        }
    }
    CBAR();
    float* ffr = (float*)(sm + OFF_FFR);
    if (fmt < 4 || nf > 32) {
        float acc[2][4] = {{0.f, 0.f, 0.f, 0.f}, {0.f, 0.f, 0.f, 0.f}};
        const uint32_t ha = sb + OFF_H2S + lr * (ROWP * 2) + (144 * fsl) * 2 + lm * 16;
#pragma unroll
        for (int k2 = 0; k2 < 5; k2++) {
            uint32_t hb[4];
            ldsm_x4(hb, ha + k2 * 64 - ((k2 == 4) ? (lm >> 1) * 32 : 0));
            mma_bf16(acc[0], wf[2 * k2][0], wf[2 * k2][1], wf[2 * k2][2], wf[2 * k2][3], hb[0], hb[1]);
            if (k2 < 4) mma_bf16(acc[1], wf[2 * k2 + 1][0], wf[2 * k2 + 1][1], wf[2 * k2 + 1][2], wf[2 * k2 + 1][3], hb[2], hb[3]);
        }
        float* o = ffr + ((fsl * 80 + 16 * fmt + g) * 8 + 2 * t);
        *(float2*)o = make_float2(acc[0][0] + acc[1][0], acc[0][1] + acc[1][1]);
        *(float2*)(o + 64) = make_float2(acc[0][2] + acc[1][2], acc[0][3] + acc[1][3]);
    }
    CBAR();
    bf16(*act)[56] = (bf16(*)[56])(sm + OFF_ACT);
    if (tid < 384) {
        const int f = tid >> 3, a = tid & 7;
        float v = 0.f;
        if (f < nf) {
            const int rg = (f < 32) ? f : f + 32, ru = (f < 32) ? f + 32 : f + 40;
            const float* pg = ffr + rg * 8 + a;
            const float* pu = ffr + ru * 8 + a;
            float gg = bfr((pg[0] + pg[640]) + (pg[1280] + pg[1920]));
            gg = bfr(silu(gg));
            const float uu = bfr((pu[0] + pu[640]) + (pu[1280] + pu[1920]));
            v = gg * uu;
        }
        act[a][f] = __ushort_as_bfloat16((unsigned short)f2bits(v));
    }
    CBAR();
    {
        uint32_t bq[3][2];
#pragma unroll
        for (int ks = 0; ks < 3; ks++) {
            bq[ks][0] = *(const uint32_t*)&act[g][16 * ks + 2 * t];
            bq[ks][1] = *(const uint32_t*)&act[g][16 * ks + 2 * t + 8];
        }
#pragma unroll
        for (int i = 0; i < 2; i++) {
            if (i == 0 || warp < 16) {
                float acc[4] = {0.f, 0.f, 0.f, 0.f};
#pragma unroll
                for (int ks = 0; ks < 3; ks++)
                    if (ks < 2 || nf > 32) mma_bf16(acc, wd[i][ks][0], wd[i][ks][1], wd[i][ks][2], wd[i][ks][3], bq[ks][0], bq[ks][1]);
                const int W = (warp + 20 * i) * 32 + lane, c = (W * 7282) >> 16;
                st_rlx2(&S->part[(c * G_ + b) * 9 + W - 9 * c], ~pack2(acc[0], acc[1]), ~pack2(acc[2], acc[3]));
            }
        }
    }
    if (warp >= 4) {
        const int tk = warp - 4;
        if (!__any_sync(0xffffffffu, 2047u - (M.skey[lr] & 2047u) == (uint32_t)(16 * b + tk))) {
            const uint4* src = (const uint4*)(sm + OFF_TILE + tk * (ROWP * 2));
            uint4* dst = (uint4*)(out + (size_t)(16 * b + tk) * D_);
            dst[lane] = src[lane]; dst[lane + 32] = src[lane + 32];
            if (lane < 8) dst[lane + 64] = src[lane + 64];
        }
    }
    float4* fin = (float4*)(sm + OFF_FIN);
    uint32_t rb = (fsel >> 11) & 0xFFFFu;
    rb ^= (rb & 0x8000u) ? 0x8000u : 0xFFFFu;
    const float rs = bfr(__fdividef(1.0f, 1.0f + __expf(-lo2f(rb))));
    const float fh2 = (tid < 288) ? __bfloat162float(h2s[fk][fd]) : 0.f, fgb = (tid < 288) ? __bfloat162float(M.gb[fd]) : 0.f;
    const float fx1 = bfr(lo2f(fx) + lo2f(~fv));
    if (tid < 576) {
        const uint2* src = &S->part[(size_t)b * 1152 + tid];
        uint2 a = ld_rlx2(src), c = ld_rlx2(src + 576);
#pragma unroll 1
        for (int it = 0; it < SPIN_MAX && (a.x == SENT || c.x == SENT); it++) {
            if (a.x == SENT) a = ld_rlx2(src);
            if (c.x == SENT) c = ld_rlx2(src + 576);
        }
        fin[tid] = make_float4(lo2f(~a.x) + lo2f(~c.x), hi2f(~a.x) + hi2f(~c.x), lo2f(~a.y) + lo2f(~c.y), hi2f(~a.y) + hi2f(~c.y));
    }
    CBAR();
    if (tid < 288) {
        const int part = tid & 7;
        const float* f = (const float*)fin + part * 36 + fo;
        float s = ((f[0] + f[288]) + (f[576] + f[864])) + ((f[1152] + f[1440]) + (f[1728] + f[2016]));
        s += __shfl_xor_sync(0xffffffffu, s, 1);
        s += __shfl_xor_sync(0xffffffffu, s, 2);
        s += __shfl_xor_sync(0xffffffffu, s, 4);
        const float upd = bfr(bfr(s) * rs);
        const float ov = fx1 + bfr(fgb * bfr(fh2 + upd));
        if (part == 0) out[(size_t)(2047u - (fsel & 2047u)) * D_ + fd] = __ushort_as_bfloat16((unsigned short)f2bits(ov));
    }
    if ((warp & 3) == 2 && lane == 0) asm volatile("cp.async.bulk.wait_group 0;" ::: "memory");
    }
}

typedef CUresult (*EncodeFn)(CUtensorMap*, CUtensorMapDataType, cuuint32_t, void*, const cuuint64_t*, const cuuint64_t*,
                             const cuuint32_t*, const cuuint32_t*, CUtensorMapInterleave, CUtensorMapSwizzle,
                             CUtensorMapL2promotion, CUtensorMapFloatOOBfill);

static void make_map(EncodeFn fn, CUtensorMap* m, const void* ptr, uint64_t cols, uint64_t rows, uint32_t bc, uint32_t br,
                     CUtensorMapSwizzle sw) {
    cuuint64_t dims[2] = {cols, rows};
    cuuint64_t strides[1] = {cols * 2};
    cuuint32_t box[2] = {bc, br};
    cuuint32_t es[2] = {1, 1};
    CUresult rc = fn(m, CU_TENSOR_MAP_DATA_TYPE_BFLOAT16, 2, (void*)ptr, dims, strides, box, es, CU_TENSOR_MAP_INTERLEAVE_NONE,
                     sw, CU_TENSOR_MAP_L2_PROMOTION_NONE, CU_TENSOR_MAP_FLOAT_OOB_FILL_NONE);
    (void)rc;
}

static void launch(void* const* d_in, const int* in_sizes, int n_in, void* d_out, int out_size) {
    static EncodeFn enc = nullptr;
    static CUtensorMap tmm, tmg, tmu, tmd, tmd32, tmg32, tmu32;
    static Scratch* sp = nullptr;
    static const void* cached[4] = {nullptr, nullptr, nullptr, nullptr};
    if (!enc) {
        cudaDriverEntryPointQueryResult qr;
        void* fn = nullptr;
        cudaGetDriverEntryPoint("cuTensorMapEncodeTiled", &fn, cudaEnableDefault, &qr);
        enc = (EncodeFn)fn;
        cudaFuncSetAttribute(mega_kernel, cudaFuncAttributeMaxDynamicSharedMemorySize, SMEM_TOTAL);
        cudaGetSymbolAddress((void**)&sp, g_s);
    }
    if (cached[0] != d_in[13] || cached[1] != d_in[9] || cached[2] != d_in[10] || cached[3] != d_in[11]) {
        make_map(enc, &tmm, d_in[13], 6 * D_, D_, 32, 192, CU_TENSOR_MAP_SWIZZLE_64B);
        make_map(enc, &tmg, d_in[9], F_, D_, 40, 192, CU_TENSOR_MAP_SWIZZLE_NONE);
        make_map(enc, &tmu, d_in[10], F_, D_, 40, 192, CU_TENSOR_MAP_SWIZZLE_NONE);
        make_map(enc, &tmg32, d_in[9], F_, D_, 32, 192, CU_TENSOR_MAP_SWIZZLE_64B);
        make_map(enc, &tmu32, d_in[10], F_, D_, 32, 192, CU_TENSOR_MAP_SWIZZLE_64B);
        make_map(enc, &tmd, d_in[11], D_, F_, 64, 40, CU_TENSOR_MAP_SWIZZLE_128B);
        make_map(enc, &tmd32, d_in[11], D_, F_, 64, 32, CU_TENSOR_MAP_SWIZZLE_128B);
        cached[3] = d_in[11];
        cached[0] = d_in[13]; cached[1] = d_in[9]; cached[2] = d_in[10];
    }
    mega_kernel<<<G_, NTHR, SMEM_TOTAL>>>((const bf16*)d_in[0], (const bf16*)d_in[1], (const bf16*)d_in[2], (const bf16*)d_in[3],
                                          (const bf16*)d_in[4], (const bf16*)d_in[5], (const bf16*)d_in[12], sp, (const bf16*)d_in[6],
                                          (const bf16*)d_in[8], (const bf16*)d_in[11], (bf16*)d_out, tmm, tmg, tmu, tmd, tmd32, tmg32, tmu32);
}

}

extern "C" void kernel_launch(void* const* d_in, const int* in_sizes, int n_in, void* d_out, int out_size) {
    static int mode = -1;
    if (mode < 0) mode = v5::fits() ? 1 : 0;
    if (mode) v5::launch(d_in, in_sizes, n_in, d_out, out_size);
    else v4::launch(d_in, in_sizes, n_in, d_out, out_size);
}
```

```cpp
#include <cuda_runtime.h>
#include <cuda.h>
#include <cuda_bf16.h>
#include <cuda_fp16.h>
#include <stdint.h>

namespace v5 {

#define L_ 2048
#define D_ 576
#define N_ 128
#define F_ 4608
#define G_ 120
#define NCL 15
#define NTHR 768
#define SPIN_MAX (1 << 18)

typedef __nv_bfloat16 bf16;

struct Scratch {
    float4 acc1[L_ + 8];
    float4 acc2[L_];
    uint4 h2c[136 * 72];
    float4 acc3[72 * 32];
    float4 rs[33 * 8];
    unsigned int gb[320];
};
static_assert(136 * 72 + 72 * 32 + 33 * 8 == 103 * G_, "16 B units cleared early in a launch (h2c, acc3, rs)");
__device__ __align__(1024) Scratch g_s;

#define OFF_WG 0
#define OFF_WU 46080
#define KSCR 3456
#define OFF_WM0 69120
#define OFF_STG OFF_WM0
#define OFF_MG2 86400
#define OFF_CH 92160
#define CHS 18688
#define UP 3808
#define UB 192
#define XO_TF 1216
#define XO_U8 2016
#define XO_U16 3328
#define XO_ZA 1232
#define XO_ZB 2016
#define XO_ZC 2800
#define XO_ZD 3328
#define XO_TD 16000
#define XO_K1024 18624
#define XO_DSK 18628
#define XO_KINV 18640
#define XO_KLAST 18656
#define XO_MBU 18672
#define OFF_X 185600
#define XG 672
#define XI(i) (((i) >> 1) * 5520 + ((i) & 1) * 2752)
#define XN(n) ((((n) >> 1) & 3) * XG + (2 * ((n) >> 3) + ((n) & 1)) * 80)
#define OFF_V 207616
#define VP 528
#define OFF_EK (OFF_V + 512)
#define OFF_WM2 OFF_V
#define OFF_MG1 (OFF_V + 17280)
#define OFF_SC (OFF_V + 19840)
#define OFF_C1 (OFF_V + 20640)
#define OFF_MISC 228736
#define OFF_WD OFF_CH
#define OFF_H2T (OFF_CH + 46080)
#define OFF_OUT (OFF_CH + 66560)
#define ROWP 584
#define OFF_H2S 0
#define OFF_FFR 9344
#define OFF_ACT 19584
#define OFF_RS 20480

enum { MB_WM2, MB_MG1, MB_MG2, MB_KEY, MB_V, MB_RS, MB_WG, MB_WU, MB_WD, MB_KEY2, MB_EK, MB_RS2, MB_C2, MB_CW, MB_KD, MB_OUT, MB_C1, MB_N };

struct Misc {
    union {
        __align__(16) uint4 box[4 * 14];
        unsigned int cand[128];
    };
    __align__(16) unsigned int key[256], cand2[128], sel[8];
    __align__(16) uint4 c2[20];
    __align__(16) unsigned int fin[12];
    unsigned int ga[8], wr[20];
    float cws[2];
    unsigned long long mbar[MB_N];
};
#define SMEM_TOTAL (OFF_MISC + (int)sizeof(Misc))
static_assert(SMEM_TOTAL <= 232448, "smem");

__device__ __forceinline__ float lo2f(uint32_t w) { return __uint_as_float(w << 16); }
__device__ __forceinline__ float hi2f(uint32_t w) { return __uint_as_float(w & 0xFFFF0000u); }
__device__ __forceinline__ uint32_t pack2(float lo, float hi) { uint32_t r; asm("cvt.rn.bf16x2.f32 %0, %1, %2;" : "=r"(r) : "f"(hi), "f"(lo)); return r; }
__device__ __forceinline__ float bfr(float x) { return __uint_as_float(pack2(0.f, x)); }
__device__ __forceinline__ uint32_t f2bits(float x) { return pack2(x, 0.f); }
__device__ __forceinline__ uint32_t packh(float lo, float hi) { uint32_t r; asm("cvt.rn.f16x2.f32 %0, %1, %2;" : "=r"(r) : "f"(hi), "f"(lo)); return r; }
__device__ __forceinline__ float frcp(float x) { float r; asm("rcp.approx.ftz.f32 %0, %1;" : "=f"(r) : "f"(x)); return r; }
__device__ __forceinline__ float fsqrt(float x) { float r; asm("sqrt.approx.f32 %0, %1;" : "=f"(r) : "f"(x)); return r; }
__device__ __forceinline__ float fex2(float x) { float r; asm("ex2.approx.ftz.f32 %0, %1;" : "=f"(r) : "f"(x)); return r; }
__device__ __forceinline__ float silu(float x) { return __fdividef(x, 1.0f + __expf(-x)); }
__device__ __forceinline__ uint32_t add2(uint32_t a, uint32_t b) { uint32_t r; asm("add.rn.bf16x2 %0, %1, %2;" : "=r"(r) : "r"(a), "r"(b)); return r; }
__device__ __forceinline__ uint32_t sub2(uint32_t a, uint32_t b) { uint32_t r; asm("sub.rn.bf16x2 %0, %1, %2;" : "=r"(r) : "r"(a), "r"(b)); return r; }
__device__ __forceinline__ uint32_t mul2(uint32_t a, uint32_t b) { uint32_t r; asm("mul.rn.bf16x2 %0, %1, %2;" : "=r"(r) : "r"(a), "r"(b)); return r; }
__device__ __forceinline__ uint32_t fma2(uint32_t a, uint32_t b, uint32_t c) { uint32_t r; asm("fma.rn.bf16x2 %0, %1, %2, %3;" : "=r"(r) : "r"(a), "r"(b), "r"(c)); return r; }
__device__ __forceinline__ uint32_t norm2(uint32_t x, uint32_t m, uint32_t rh, uint32_t rl) { const uint32_t d = sub2(x, m); return fma2(d, rh, mul2(d, rl)); }

__device__ __forceinline__ void mma_bf16(float* c, uint32_t a0, uint32_t a1, uint32_t a2, uint32_t a3, uint32_t b0, uint32_t b1) {
    asm volatile("mma.sync.aligned.m16n8k16.row.col.f32.bf16.bf16.f32 {%0,%1,%2,%3}, {%4,%5,%6,%7}, {%8,%9}, {%0,%1,%2,%3};\n"
                 : "+f"(c[0]), "+f"(c[1]), "+f"(c[2]), "+f"(c[3]) : "r"(a0), "r"(a1), "r"(a2), "r"(a3), "r"(b0), "r"(b1));
}
__device__ __forceinline__ void mma_f16(float* c, const uint32_t* a, uint32_t b0, uint32_t b1) {
    asm volatile("mma.sync.aligned.m16n8k16.row.col.f32.f16.f16.f32 {%0,%1,%2,%3}, {%4,%5,%6,%7}, {%8,%9}, {%0,%1,%2,%3};\n"
                 : "+f"(c[0]), "+f"(c[1]), "+f"(c[2]), "+f"(c[3]) : "r"(a[0]), "r"(a[1]), "r"(a[2]), "r"(a[3]), "r"(b0), "r"(b1));
}
__device__ __forceinline__ void ldsm_x4(uint32_t* r, uint32_t addr) {
    asm volatile("ldmatrix.sync.aligned.m8n8.x4.shared.b16 {%0,%1,%2,%3}, [%4];" : "=r"(r[0]), "=r"(r[1]), "=r"(r[2]), "=r"(r[3]) : "r"(addr) : "memory");
}
__device__ __forceinline__ void ldsm_x4_t(uint32_t* r, uint32_t addr) {
    asm volatile("ldmatrix.sync.aligned.m8n8.x4.trans.shared.b16 {%0,%1,%2,%3}, [%4];" : "=r"(r[0]), "=r"(r[1]), "=r"(r[2]), "=r"(r[3]) : "r"(addr) : "memory");
}
__device__ __forceinline__ void stsm_x4(uint32_t addr, uint32_t r0, uint32_t r1, uint32_t r2, uint32_t r3) {
    asm volatile("stmatrix.sync.aligned.m8n8.x4.shared.b16 [%0], {%1,%2,%3,%4};" ::"r"(addr), "r"(r0), "r"(r1), "r"(r2), "r"(r3) : "memory");
}
__device__ __forceinline__ void stsm_x4_t(uint32_t addr, uint32_t r0, uint32_t r1, uint32_t r2, uint32_t r3) {
    asm volatile("stmatrix.sync.aligned.m8n8.x4.trans.shared.b16 [%0], {%1,%2,%3,%4};" ::"r"(addr), "r"(r0), "r"(r1), "r"(r2), "r"(r3) : "memory");
}
__device__ __forceinline__ uint32_t movm(uint32_t a) { uint32_t r; asm volatile("movmatrix.sync.aligned.m8n8.trans.b16 %0, %1;" : "=r"(r) : "r"(a)); return r; }
__device__ __forceinline__ uint32_t lds32(uint32_t a) { uint32_t v; asm volatile("ld.shared.u32 %0, [%1];" : "=r"(v) : "r"(a)); return v; }
__device__ __forceinline__ void sts32(uint32_t a, uint32_t v) { asm volatile("st.shared.u32 [%0], %1;" ::"r"(a), "r"(v) : "memory"); }
__device__ __forceinline__ void sts16(uint32_t a, uint32_t v) { asm volatile("st.shared.u16 [%0], %1;" ::"r"(a), "h"((unsigned short)v) : "memory"); }
__device__ __forceinline__ void named_bar(int id, int n) { asm volatile("bar.sync %0, %1;" ::"r"(id), "r"(n) : "memory"); }
__device__ __forceinline__ void named_arrive(int id, int n) { asm volatile("bar.arrive %0, %1;" ::"r"(id), "r"(n) : "memory"); }
#define CBAR() asm volatile("bar.sync 0, 640;" ::: "memory")
#define PROXY_FENCE() asm volatile("fence.proxy.async.shared::cta;" ::: "memory")

#define D4(d, o) "+f"(d[o]), "+f"(d[o + 1]), "+f"(d[o + 2]), "+f"(d[o + 3])
__device__ __forceinline__ void wg32(float* d, uint32_t a0, uint32_t a1, uint32_t a2, uint32_t a3, uint64_t desc) {
    asm volatile("wgmma.mma_async.sync.aligned.m64n32k16.f32.bf16.bf16 {%0,%1,%2,%3,%4,%5,%6,%7,%8,%9,%10,%11,%12,%13,%14,%15}, {%16,%17,%18,%19}, %20, 1, 1, 1, 0;"
                 : D4(d, 0), D4(d, 4), D4(d, 8), D4(d, 12) : "r"(a0), "r"(a1), "r"(a2), "r"(a3), "l"(desc));
}
__device__ __forceinline__ void wg48(float* d, uint32_t a0, uint32_t a1, uint32_t a2, uint32_t a3, uint64_t desc) {
    asm volatile("wgmma.mma_async.sync.aligned.m64n48k16.f32.bf16.bf16 {%0,%1,%2,%3,%4,%5,%6,%7,%8,%9,%10,%11,%12,%13,%14,%15,%16,%17,%18,%19,%20,%21,%22,%23}, {%24,%25,%26,%27}, %28, 1, 1, 1, 0;"
                 : D4(d, 0), D4(d, 4), D4(d, 8), D4(d, 12), D4(d, 16), D4(d, 20) : "r"(a0), "r"(a1), "r"(a2), "r"(a3), "l"(desc));
}
__device__ __forceinline__ void wg64(float* d, uint32_t a0, uint32_t a1, uint32_t a2, uint32_t a3, uint64_t desc) {
    asm volatile("wgmma.mma_async.sync.aligned.m64n64k16.f32.bf16.bf16 {%0,%1,%2,%3,%4,%5,%6,%7,%8,%9,%10,%11,%12,%13,%14,%15,%16,%17,%18,%19,%20,%21,%22,%23,%24,%25,%26,%27,%28,%29,%30,%31}, {%32,%33,%34,%35}, %36, 1, 1, 1, 0;"
                 : D4(d, 0), D4(d, 4), D4(d, 8), D4(d, 12), D4(d, 16), D4(d, 20), D4(d, 24), D4(d, 28) : "r"(a0), "r"(a1), "r"(a2), "r"(a3), "l"(desc));
}
#define O4(d, o) "=f"(d[o]), "=f"(d[o + 1]), "=f"(d[o + 2]), "=f"(d[o + 3])
__device__ __forceinline__ void wg32z(float* d, uint32_t a0, uint32_t a1, uint32_t a2, uint32_t a3, uint64_t desc) {
    asm volatile("wgmma.mma_async.sync.aligned.m64n32k16.f32.bf16.bf16 {%0,%1,%2,%3,%4,%5,%6,%7,%8,%9,%10,%11,%12,%13,%14,%15}, {%16,%17,%18,%19}, %20, 0, 1, 1, 0;"
                 : O4(d, 0), O4(d, 4), O4(d, 8), O4(d, 12) : "r"(a0), "r"(a1), "r"(a2), "r"(a3), "l"(desc));
}
__device__ __forceinline__ void wg48z(float* d, uint32_t a0, uint32_t a1, uint32_t a2, uint32_t a3, uint64_t desc) {
    asm volatile("wgmma.mma_async.sync.aligned.m64n48k16.f32.bf16.bf16 {%0,%1,%2,%3,%4,%5,%6,%7,%8,%9,%10,%11,%12,%13,%14,%15,%16,%17,%18,%19,%20,%21,%22,%23}, {%24,%25,%26,%27}, %28, 0, 1, 1, 0;"
                 : O4(d, 0), O4(d, 4), O4(d, 8), O4(d, 12), O4(d, 16), O4(d, 20) : "r"(a0), "r"(a1), "r"(a2), "r"(a3), "l"(desc));
}
#define WG_FENCE() asm volatile("wgmma.fence.sync.aligned;" ::: "memory")
#define WG_COMMIT() asm volatile("wgmma.commit_group.sync.aligned;" ::: "memory")
#define WG_WAIT(n) asm volatile("wgmma.wait_group.sync.aligned " #n ";" ::: "memory")
#define TQ(p, k) p[2 * (k) + 1], p[2 * (k) + 2], p[2 * (k)], p[2 * (k) + 1]

__device__ __forceinline__ uint4 ld_nc4(const void* p) { uint4 v; asm volatile("ld.global.nc.v4.u32 {%0,%1,%2,%3}, [%4];" : "=r"(v.x), "=r"(v.y), "=r"(v.z), "=r"(v.w) : "l"(p)); return v; }
__device__ __forceinline__ unsigned short ld_nc16(const void* p) { unsigned short v; asm volatile("ld.global.nc.u16 %0, [%1];" : "=h"(v) : "l"(p)); return v; }
__device__ __forceinline__ uint32_t ld_nc(const void* p) { uint32_t v; asm volatile("ld.global.nc.u32 %0, [%1];" : "=r"(v) : "l"(p)); return v; }
__device__ __forceinline__ uint32_t ld_rlx(const unsigned int* p) { uint32_t v; asm volatile("ld.relaxed.gpu.global.u32 %0, [%1];" : "=r"(v) : "l"(p) : "memory"); return v; }
__device__ __forceinline__ uint2 ld_rlx2(const void* p) { uint2 v; asm volatile("ld.relaxed.gpu.global.v2.u32 {%0,%1}, [%2];" : "=r"(v.x), "=r"(v.y) : "l"(p) : "memory"); return v; }
__device__ __forceinline__ uint4 ld_rlx4(const void* p) { uint4 v; asm volatile("ld.relaxed.gpu.global.v4.u32 {%0,%1,%2,%3}, [%4];" : "=r"(v.x), "=r"(v.y), "=r"(v.z), "=r"(v.w) : "l"(p) : "memory"); return v; }
__device__ __forceinline__ void st_rlx(unsigned int* p, uint32_t v) { asm volatile("st.relaxed.gpu.global.u32 [%0], %1;" ::"l"(p), "r"(v) : "memory"); }
__device__ __forceinline__ void st_rlx2(void* p, uint32_t a, uint32_t b) { asm volatile("st.relaxed.gpu.global.v2.u32 [%0], {%1,%2};" ::"l"(p), "r"(a), "r"(b) : "memory"); }
__device__ __forceinline__ void st_rlx4(void* p, uint4 v) { asm volatile("st.relaxed.gpu.global.v4.u32 [%0], {%1,%2,%3,%4};" ::"l"(p), "r"(v.x), "r"(v.y), "r"(v.z), "r"(v.w) : "memory"); }
__device__ __forceinline__ void red_inc(unsigned int* p) { asm volatile("red.relaxed.gpu.global.add.u32 [%0], 1;" ::"l"(p) : "memory"); }

__device__ __forceinline__ void mbar_init(uint32_t a, int cnt) { asm volatile("mbarrier.init.shared::cta.b64 [%0], %1;" ::"r"(a), "r"(cnt) : "memory"); }
__device__ __forceinline__ void mbar_expect(uint32_t a, uint32_t bytes) { asm volatile("mbarrier.arrive.expect_tx.shared::cta.b64 _, [%0], %1;" ::"r"(a), "r"(bytes) : "memory"); }
__device__ __forceinline__ void mbar_wait(uint32_t a, uint32_t parity) {
    uint32_t ok = 0;
    int it = 0;
    do {
        asm volatile("{\n.reg .pred p;\nmbarrier.try_wait.parity.shared::cta.b64 p, [%1], %2;\nselp.u32 %0, 1, 0, p;\n}" : "=r"(ok) : "r"(a), "r"(parity) : "memory");
    } while (!ok && ++it < SPIN_MAX);
}
__device__ __forceinline__ bool mbar_test(uint32_t a, uint32_t parity) {
    uint32_t ok;
    asm volatile("{\n.reg .pred p;\nmbarrier.test_wait.parity.shared::cta.b64 p, [%1], %2;\nselp.u32 %0, 1, 0, p;\n}" : "=r"(ok) : "r"(a), "r"(parity) : "memory");
    return __all_sync(0xffffffffu, ok);
}
__device__ __forceinline__ void tma2d(uint32_t dst, const CUtensorMap* tm, int c0, int c1, uint32_t mbar) {
    asm volatile("cp.async.bulk.tensor.2d.shared::cluster.global.mbarrier::complete_tx::bytes [%0], [%1, {%3, %4}], [%2];"
                 ::"r"(dst), "l"(tm), "r"(mbar), "r"(c0), "r"(c1) : "memory");
}
__device__ __forceinline__ void bulk_s2g(void* dst, uint32_t src, uint32_t bytes) {
    asm volatile("cp.async.bulk.global.shared::cta.bulk_group [%0], [%1], %2;" ::"l"(dst), "r"(src), "r"(bytes) : "memory");
}
__device__ __forceinline__ uint32_t ld_acq(const unsigned int* p) { uint32_t v; asm volatile("ld.acquire.gpu.global.u32 %0, [%1];" : "=r"(v) : "l"(p) : "memory"); return v; }
__device__ __forceinline__ void bulk_pf(const void* src, uint32_t bytes) { asm volatile("cp.async.bulk.prefetch.L2.global [%0], %1;" ::"l"(src), "r"(bytes) : "memory"); }

struct cplx { float x, y; };
__device__ __forceinline__ cplx cmul(cplx a, cplx b) { cplx r; r.x = a.x * b.x - a.y * b.y; r.y = a.x * b.y + a.y * b.x; return r; }
__device__ __forceinline__ cplx csq(cplx a) { cplx r; r.x = a.x * a.x - a.y * a.y; r.y = 2.0f * a.x * a.y; return r; }
__device__ __forceinline__ uint32_t hcm(uint32_t x, uint32_t y, uint32_t yp) {
    const __half2 X = *(const __half2*)&x, Y = *(const __half2*)&y, YP = *(const __half2*)&yp;
    const __half2 r = __hfma2(__high2half2(X), YP, __hmul2(__low2half2(X), Y));
    return *(const uint32_t*)&r;
}
__device__ __forceinline__ void ln_stats(float s1, float s2, float& meanb, float& rinv) {
    const float mean = s1 * (1.0f / D_);
    const float den = bfr(fsqrt(bfr(bfr(fmaxf(fmaf(-mean, mean, s2 * (1.0f / D_)), 0.f)) + 1e-5f)));
    meanb = bfr(mean);
    rinv = frcp(den);
}

__device__ __forceinline__ int fresh_tid() { int v; asm volatile("mov.u32 %0, %tid.x;" : "=r"(v)); return v - 128; }
__device__ __forceinline__ void mma_k8(float* c, uint32_t a0, uint32_t a1, uint32_t b0) {
    asm volatile("mma.sync.aligned.m16n8k8.row.col.f32.bf16.bf16.f32 {%0,%1,%2,%3}, {%4,%5}, {%6}, {%0,%1,%2,%3};\n"
                 : "+f"(c[0]), "+f"(c[1]), "+f"(c[2]), "+f"(c[3]) : "r"(a0), "r"(a1), "r"(b0));
}
__device__ __forceinline__ void ldsm_x2(uint32_t* r, uint32_t addr) {
    asm volatile("ldmatrix.sync.aligned.m8n8.x2.shared.b16 {%0,%1}, [%2];" : "=r"(r[0]), "=r"(r[1]) : "r"(addr) : "memory");
}
__device__ __forceinline__ void ldsm_x2_t(uint32_t* r, uint32_t addr) {
    asm volatile("ldmatrix.sync.aligned.m8n8.x2.trans.shared.b16 {%0,%1}, [%2];" : "=r"(r[0]), "=r"(r[1]) : "r"(addr) : "memory");
}
__device__ __forceinline__ void stsm_x2(uint32_t addr, uint32_t r0, uint32_t r1) {
    asm volatile("stmatrix.sync.aligned.m8n8.x2.shared.b16 [%0], {%1,%2};" ::"r"(addr), "r"(r0), "r"(r1) : "memory");
}
__device__ __forceinline__ uint4 lds128(uint32_t a) { uint4 v; asm volatile("ld.shared.v4.u32 {%0,%1,%2,%3}, [%4];" : "=r"(v.x), "=r"(v.y), "=r"(v.z), "=r"(v.w) : "r"(a) : "memory"); return v; }
__device__ __forceinline__ uint32_t mapa(uint32_t a, uint32_t r) { uint32_t o; asm("mapa.shared::cluster.u32 %0, %1, %2;" : "=r"(o) : "r"(a), "r"(r)); return o; }
__device__ __forceinline__ void sta4(uint32_t dst, uint4 v, uint32_t mb) {
    asm volatile("st.async.weak.shared::cluster.mbarrier::complete_tx::bytes.v4.b32 [%0], {%1,%2,%3,%4}, [%5];" ::"r"(dst), "r"(v.x), "r"(v.y), "r"(v.z), "r"(v.w), "r"(mb) : "memory");
}
__device__ __forceinline__ void sta2(uint32_t dst, uint32_t a, uint32_t b, uint32_t mb) {
    asm volatile("st.async.weak.shared::cluster.mbarrier::complete_tx::bytes.v2.b32 [%0], {%1,%2}, [%3];" ::"r"(dst), "r"(a), "r"(b), "r"(mb) : "memory");
}
__device__ __forceinline__ void mbar_arrive(uint32_t a) { asm volatile("mbarrier.arrive.shared::cta.b64 _, [%0];" ::"r"(a) : "memory"); }
__device__ __forceinline__ void red4(float4* p, float a, float b, float c) {
    asm volatile("red.relaxed.gpu.global.add.v4.f32 [%0], {%1,%2,%3,%4};" ::"l"(p), "f"(a), "f"(b), "f"(c), "f"(1.0f) : "memory");
}
__device__ __forceinline__ void red4p(bool on, float4* p, float a, float b, float c) {
    asm volatile("{\n.reg .pred q;\nsetp.ne.u32 q, %5, 0;\n@q red.relaxed.gpu.global.add.v4.f32 [%0], {%1,%2,%3,%4};\n}" ::"l"(p), "f"(a), "f"(b), "f"(c), "f"(1.0f), "r"((uint32_t)on) : "memory");
}
__device__ __forceinline__ float4 atom4(float4* p, float a, float b, float c, float d) {
    float4 v;
    asm volatile("atom.relaxed.gpu.global.add.v4.f32 {%0,%1,%2,%3}, [%4], {%5,%6,%7,%8};" : "=f"(v.x), "=f"(v.y), "=f"(v.z), "=f"(v.w) : "l"(p), "f"(a), "f"(b), "f"(c), "f"(d) : "memory");
    return v;
}
__device__ __forceinline__ uint2 lds64(uint32_t a) { uint2 v; asm volatile("ld.shared.v2.u32 {%0,%1}, [%2];" : "=r"(v.x), "=r"(v.y) : "r"(a) : "memory"); return v; }
__device__ __forceinline__ float4 ld_rlx4f(const float4* p) { float4 v; asm volatile("ld.relaxed.gpu.global.v4.f32 {%0,%1,%2,%3}, [%4];" : "=f"(v.x), "=f"(v.y), "=f"(v.z), "=f"(v.w) : "l"(p) : "memory"); return v; }
__device__ __forceinline__ void tma5d_st(const CUtensorMap* tm, int c0, int c4, uint32_t src) {
    asm volatile("cp.async.bulk.tensor.5d.global.shared::cta.bulk_group [%0, {%2, %4, %4, %4, %3}], [%1];" ::"l"(tm), "r"(src), "r"(c0), "r"(c4), "r"(0) : "memory");
}
__device__ __forceinline__ void tma2d_pf(const CUtensorMap* tm, int c0, int c1) {
    asm volatile("cp.async.bulk.prefetch.tensor.2d.L2.global [%0, {%1, %2}];" ::"l"(tm), "r"(c0), "r"(c1) : "memory");
}
__device__ __forceinline__ void pace(int clk) {
    const long long c0 = clock64();
    int it = 0;
    while (clock64() - c0 < clk && ++it < 4096) { }
}
__device__ __forceinline__ uint32_t sign2(uint32_t a) { uint32_t r; asm("prmt.b32 %0, %1, 0, 0xBB99;" : "=r"(r) : "r"(a)); return r; }
#define MB(i) (sb + OFF_MISC + (uint32_t)offsetof(Misc, mbar) + 8 * (i))
__device__ __forceinline__ void conv_channel(unsigned char* sm, uint32_t rank, uint32_t fixa, uint32_t fixv) {
    Misc& M = *(Misc*)(sm + OFF_MISC);
    const uint32_t sb = (uint32_t)__cvta_generic_to_shared(sm);
    const int tid = fresh_tid(), lane = tid & 31, g = lane >> 2, t = lane & 3, lr = lane & 7, lm = lane >> 3;
    const int warp_ = __shfl_sync(0xffffffffu, tid >> 5, 0), wgi = warp_ >> 2, w = warp_ & 3;
    const uint32_t cb = sb + OFF_CH + wgi * CHS;
    float D[32];
    const uint32_t dlo = ((cb & 0x3FFFF) >> 4) | ((UP >> 4) << 16);
#define DS(o, z, bl) (((uint64_t)(128 >> 4) << 32) | (uint64_t)(dlo + (o) / 16 + (((z) & 1) ? 0 : UP / 8) - ((z) >> 1) * (bl)))
    {
        const uint32_t pf = cb + XO_TF + (w >> 1) * UP + (8 + 16 * (w & 1) + g - 2 * t) * 4;
        uint32_t p[13], q[9];
        named_bar(1 + wgi, 128);
        if (fixa) sts16(fixa, fixv);
#pragma unroll
        for (int s = 0; s < 13; s++) p[s] = lds32(pf + s * 32);
        {
            const uint32_t a8 = cb + UB + t * UP + g * 16 + w * 128, b8 = cb + XO_U8 + lm * UP + lr * 16 + w * 128;
            const uint32_t a16 = cb + UB + (2 * (lr & 1) + (lm & 1)) * UP + ((lr >> 1) + 2 * (lm & 2)) * 16 + w * 128;
            const uint32_t b16 = cb + XO_U16 + (2 * (w & 1) + (lm >> 1)) * UP + (lane & 15) * 16 + (w >> 1) * 256;
            uint32_t r[3][4];
            mbar_wait(cb + XO_MBU, 0);
            ldsm_x4_t(r[0], a8);
            ldsm_x4_t(r[1], a16);
            if (w < 2) ldsm_x4_t(r[2], a8 + 512);
            stsm_x4(b8, r[0][0], r[0][1], r[0][2], r[0][3]);
            stsm_x4(b16, r[1][0], r[1][1], r[1][2], r[1][3]);
            if (w < 2) stsm_x4(b8 + 512, r[2][0], r[2][1], r[2][2], r[2][3]);
        }
        PROXY_FENCE();
        named_bar(1 + wgi, 128);
        {
            float Z8[24], Z16[16];
            uint32_t z8[12];
            WG_FENCE();
#pragma unroll
            for (int e = 0; e < 6; e++) {
                if (e == 0) wg48z(Z8, TQ(p, e), DS(XO_U8, e, 8));
                else wg48(Z8, TQ(p, e), DS(XO_U8, e, 8));
            }
            WG_COMMIT();
            WG_WAIT(0);
            asm volatile("setmaxnreg.inc.sync.aligned.u32 88;");
#pragma unroll
            for (int s = 0; s < 9; s++) q[s] = lds32(pf + 2 * UP + s * 32);
#pragma unroll
            for (int i = 0; i < 12; i++) asm volatile("cvt.rn.bf16x2.f32 %0, %1, %2;" : "=r"(z8[i]) : "f"(Z8[2 * i + 1]), "f"(Z8[2 * i]));
            WG_FENCE();
#pragma unroll
            for (int e = 0; e < 4; e++) {
                if (e == 0) wg32z(Z16, TQ(q, e), DS(XO_U16, e, 16));
                else wg32(Z16, TQ(q, e), DS(XO_U16, e, 16));
            }
            WG_COMMIT();
            WG_WAIT(0);
            named_bar(1 + wgi, 128);
            const uint32_t za = cb + ((w >> 1) ? XO_ZB : XO_ZA) + t * UP + (4 * (w & 1) + (g & 3) + 8 * (g >> 2)) * 16;
#pragma unroll
            for (int i = 0; i < 3; i++) stsm_x4(za + i * 256, z8[4 * i], z8[4 * i + 1], z8[4 * i + 2], z8[4 * i + 3]);
            const uint32_t zc = cb + ((w >> 1) ? XO_ZD : XO_ZC) + (2 * (lr & 1) + (lm >> 1)) * UP + (((lane & 15) >> 1) + 8 * (w & 1)) * 16;
#pragma unroll
            for (int ob = 0; ob < 2; ob++) stsm_x4(zc + ob * 256, pack2(Z16[8 * ob], Z16[8 * ob + 1]), pack2(Z16[8 * ob + 2], Z16[8 * ob + 3]), pack2(Z16[8 * ob + 4], Z16[8 * ob + 5]), pack2(Z16[8 * ob + 6], Z16[8 * ob + 7]));
        }
    }
    uint32_t pa = cb + XO_TD + (40 + 256 * (w >> 1) + 16 * (w & 1) + g - 2 * t) * 4;
    uint32_t pA[9], pB[7];
#pragma unroll
    for (int i = 0; i < 32; i++) D[i] = 0.f;
    {
        const uint4* pq = M.box + (6 + g - 2 * t);
        auto at = [&](int k) { const int c = 2 * (w & 1) + k; return cb + c * UP + (c < 0 ? 4 * UP - 16 : 0) + lr * 16 + (w >> 1) * 128; };
        const int h1 = lm & 1;
        const uint32_t h2 = (lm >> 1) * 256;
        uint32_t bA[3][4], bB[2][4], bB3[2], bC[2][4], bD[2][4], bU[4], bU1[2];
        const uint32_t e0 = at(h1) + h2, e1 = at(h1 - 1) + h2, e2 = at(h1 - 2) + h2, e3 = at(h1 - 3) + h2, e4 = at(lm - 2), e5 = at(-1) + lm * 256;
        const uint4 m0 = pq[0], m1 = pq[14], m2 = pq[28];
        const uint32_t k2 = lds32(cb + XO_K1024), x0 = m2.w & k2, x8 = pq[42].x & k2;
        ldsm_x4(bU, e0 + UB); ldsm_x2(bU1, e5 + UB);
#pragma unroll
        for (int c = 0; c < 2; c++) mma_bf16(D + 16 + 8 * c, x0, x8, 0u, x0, bU[2 * c], bU[2 * c + 1]);
        named_bar(1 + wgi, 128);
        ldsm_x4(bA[0], e0 + XO_ZA); ldsm_x4(bA[1], e2 + XO_ZA); ldsm_x4(bA[2], e4 + XO_ZA + 512);
        ldsm_x4(bB[0], e0 + XO_ZB); ldsm_x2(bB3, e0 + XO_ZB + 512); ldsm_x4(bB[1], e5 + XO_ZB);
        mma_bf16(D + 8, m0.x, m0.y, 0u, m0.x, bA[0][0], bA[0][1]);
        mma_bf16(D + 16, m0.x, m0.y, 0u, m0.x, bA[0][2], bA[0][3]);
        mma_bf16(D + 24, m0.x, m0.y, 0u, m0.x, bA[2][2], bA[2][3]);
        mma_bf16(D + 8, m0.z, 0u, m0.y, m0.z, bA[1][0], bA[1][1]);
        mma_bf16(D + 16, m0.z, 0u, m0.y, m0.z, bA[1][2], bA[1][3]);
        mma_bf16(D + 24, m0.z, 0u, m0.y, m0.z, bA[2][0], bA[2][1]);
        ldsm_x4(bC[0], e1 + XO_ZC); ldsm_x4(bC[1], e3 + XO_ZC);
        mma_bf16(D + 8, m0.w, m1.x, 0u, m0.w, bB[0][0], bB[0][1]);
        mma_bf16(D + 16, m0.w, m1.x, 0u, m0.w, bB[0][2], bB[0][3]);
        mma_bf16(D + 24, m0.w, m1.x, 0u, m0.w, bB3[0], bB3[1]);
        mma_k8(D + 8, m1.x, 0u, bB[1][0]);
        ldsm_x4(bD[0], e0 + XO_ZD); ldsm_x4(bD[1], e2 + XO_ZD);
#pragma unroll
        for (int c = 0; c < 2; c++) mma_bf16(D + 16 + 8 * c, m1.x, 0u, x8, 0u, bB[1][1 + c], bU1[c]);
#pragma unroll
        for (int s = 0; s < 9; s++) pA[s] = lds32(pa + s * 32);
#pragma unroll
        for (int c = 0; c < 2; c++) mma_bf16(D + 16 + 8 * c, m1.y, m1.z, 0u, m1.y, bC[0][2 * c], bC[0][2 * c + 1]);
#pragma unroll
        for (int c = 0; c < 2; c++) mma_bf16(D + 16 + 8 * c, m1.w, 0u, m1.z, m1.w, bC[1][2 * c], bC[1][2 * c + 1]);
#pragma unroll
        for (int c = 0; c < 2; c++) mma_bf16(D + 16 + 8 * c, m2.x, m2.y, 0u, m2.x, bD[0][2 * c], bD[0][2 * c + 1]);
#pragma unroll
        for (int c = 0; c < 2; c++) mma_bf16(D + 16 + 8 * c, m2.z, 0u, m2.y, m2.z, bD[1][2 * c], bD[1][2 * c + 1]);
    }
    {
        WG_FENCE();
#pragma unroll
        for (int q = 0; q < 4; q++) wg64(D, TQ(pA, q), DS(UB, q, 1));
        WG_COMMIT();
#pragma unroll
        for (int j = 0; j < 5; j++) {
            uint32_t* pp = (j & 1) ? pA : pB;
            if (j) WG_WAIT(1);
            if (j == 4 && w < 2) pa -= (1024 + 34 * 4) + 64 * w;
#pragma unroll
            for (int s = 0; s < 7; s++) pp[s] = lds32(pa + 256 + 192 * j + s * 32);
            WG_FENCE();
#pragma unroll
            for (int q = 0; q < 3; q++) wg64(D, TQ(pp, q), DS(UB, 4 + 3 * j + q, 1));
            WG_COMMIT();
        }
        WG_WAIT(1);
    }
    {
        const int tid = fresh_tid(), lane = tid & 31, lr = lane & 7, lm = lane >> 3;
        uint32_t u[2][4];
        const uint32_t ua = cb + UB + 2 * (w & 1) * UP + lm * 256 + (w >> 1) * 128 + lr * 16;
        ldsm_x4_t(u[0], ua); ldsm_x4_t(u[1], ua + UP);
        const uint32_t dk2 = __byte_perm(lds32(cb + XO_DSK), 0, (rank & 1) ? 0x3232 : 0x1010);
        unsigned char* xw = sm + (cb - sb) + XO_TF + w * UP + (w >> 1) * 512 + lane * 16;
        const unsigned char* xr = sm + (cb - sb) + XO_TF + (w ^ 2) * UP + lane * 16;
        named_bar(1 + wgi, 128);
#pragma unroll
        for (int i = 0; i < 8; i++) u[i >> 2][i & 3] = mul2(u[i >> 2][i & 3], dk2);
        mbar_wait(MB(MB_C2), 0);
        const uint32_t ga2 = M.ga[wgi];
        WG_WAIT(0);
#pragma unroll
        for (int j = 0; j < 4; j++) if (j < 3 || w < 2) *(float4*)(xw + j * 512) = make_float4(D[8 * j + 4], D[8 * j + 5], D[8 * j + 6], D[8 * j + 7]);
        named_bar(1 + wgi, 128);
#pragma unroll
        for (int j = 0; j < 4; j++) {
            float4 v = make_float4(0.f, 0.f, 0.f, 0.f);
            if (j || w >= 2) v = *(const float4*)(xr + j * 512);
            D[8 * j] += v.x; D[8 * j + 1] += v.y; D[8 * j + 2] += v.z; D[8 * j + 3] += v.w;
        }
#pragma unroll
        for (int h = 0; h < 2; h++) {
            const uint32_t rb = mapa(sb, 2 * w + h);
#pragma unroll
            for (int j = 0; j < 4; j++) u[h][j] = mul2(ga2, add2(pack2(D[8 * j + 2 * h], D[8 * j + 2 * h + 1]), u[h][j]));
            sta4(rb + OFF_V + (8 * wgi + rank) * VP + lane * 16, make_uint4(u[h][0], u[h][1], u[h][2], u[h][3]), rb + (MB(MB_V) - sb));
        }
    }
}

#define L2P 2
#define L2M 2
#define PFC 0
#define PFW 13
#define PD0 0
#define PD1 9
#define PDE 300
#define WMD 400
#define PU 0
#define PD 100
#define PFG 2
#define CWP 200
#define CWD 3000
#define ROW(key) (((~(key) << 2) & 0xE0u) | ((~(key) >> 6) & 24u) | ((~(key) >> 11) & 6u) | ((~(key) >> 8) & 1u))
#define RKT (((rk & 4) << 6) | ((rk & 3) << 3))
#define MINE(key) ((~(key) & 0x8C0u) == (uint32_t)(RKT << 3))
#define CE(a, b) { const uint32_t hi_ = max(a, b); b = min(a, b); a = hi_; }
#define POP(k, m) if (k.x == m) { k.x = k.y; k.y = k.z; k.z = k.w; k.w = 0u; }
#define CGT(c, a, b, n) asm volatile("{\n.reg .pred p;\nsetp.gt.u32 p, %1, %2;\n@p add.u32 %0, %0, " #n ";\n}" : "+r"(c) : "r"(a), "r"(b))
#define CL_ARRIVE() asm volatile("barrier.cluster.arrive.relaxed.aligned;" ::: "memory")
#define CL_WAIT() asm volatile("barrier.cluster.wait.aligned;" ::: "memory")
__global__ void __cluster_dims__(8, 1, 1) __launch_bounds__(NTHR, 1)
clus_kernel(const bf16* __restrict__ x, const bf16* __restrict__ logAr, const bf16* __restrict__ Aim, const bf16* __restrict__ Cr, const bf16* __restrict__ Ci,
            const bf16* __restrict__ logdt, const bf16* __restrict__ c_in, Scratch* __restrict__ S, const bf16* __restrict__ Dskip,
            const bf16* __restrict__ w_r, const bf16* __restrict__ w_mod, bf16* __restrict__ out,
            const __grid_constant__ CUtensorMap tm_wm, const __grid_constant__ CUtensorMap tm_wg,
            const __grid_constant__ CUtensorMap tm_wu, const __grid_constant__ CUtensorMap tm_wd, const __grid_constant__ CUtensorMap tm_out) {
    extern __shared__ __align__(1024) unsigned char sm[];
    Misc& M = *(Misc*)(sm + OFF_MISC);
    const uint32_t sb = (uint32_t)__cvta_generic_to_shared(sm);
    const int tid = threadIdx.x < 128 ? threadIdx.x + 640 : threadIdx.x - 128, warp = __shfl_sync(0xffffffffu, tid >> 5, 0), lane = tid & 31;
    const int g = lane >> 2, t = lane & 3, lr = lane & 7, lm = lane >> 3;
    const int wgi = warp >> 2, w = warp & 3;
    const int b = blockIdx.x, cl = b >> 3, rk = b & 7;
    auto mod_ld = [&](uint32_t (*a)[4], uint32_t s0, uint32_t s1, int i) {
        const uint32_t wa = sb + ((lm & 1) ? s1 : s0) + (lr + 8 * (lm >> 1)) * 80 + i * 16;
#pragma unroll
        for (int ks = 0; ks < 4; ks++) ldsm_x4_t(a[ks], wa + ks * 1280);
        ldsm_x2_t(a[4], wa + 5120);
    };
    auto mod_mma2 = [&](float* d, float* e, uint32_t (*a)[4], uint32_t (*c)[4], const uint32_t* bs) {
        mma_k8(d, a[4][0], a[4][1], bs[8]); mma_k8(e, c[4][0], c[4][1], bs[8]);
#pragma unroll
        for (int ks = 0; ks < 4; ks++) {
            mma_bf16(d, a[ks][0], a[ks][1], a[ks][2], a[ks][3], bs[2 * ks], bs[2 * ks + 1]);
            mma_bf16(e, c[ks][0], c[ks][1], c[ks][2], c[ks][3], bs[2 * ks], bs[2 * ks + 1]);
        }
    };
    auto mod_st = [&](const float* d, uint32_t dst, int mb) {
#pragma unroll
        for (int h = 0; h < 2; h++) {
            const uint32_t rb = mapa(sb, t + 4 * h);
            sta2(rb + dst + g * 8, __float_as_uint(d[0]), __float_as_uint(d[2]), rb + (MB(mb) - sb));
        }
    };
    if (wgi == 5) {
        CL_ARRIVE();
        const uint32_t c_a = ld_nc((const uint32_t*)c_in + 36 * rk + lane), c_b = ld_nc((const uint32_t*)c_in + 36 * rk + 32 + t);
        {
            pace(WMD);
            const char* wp = (const char*)(w_mod + (72 * rk + 18 * w) * (6 * D_) + 40 * cl);
#pragma unroll
            for (int i = 0; i < 3; i++) {
                const uint32_t c = lane + 32 * i, row = (c * 205) >> 10;
                const char* p = wp + (row * (12 * D_ - 80) + 16 * c);
                if (c < 90) {
                    asm volatile("cp.async.cg.shared.global [%0], [%1], 16;" ::"r"(sb + OFF_WM0 + 1440 * w + 16 * c), "l"(p) : "memory");
                    asm volatile("cp.async.cg.shared.global [%0], [%1], 16;" ::"r"(sb + OFF_WM0 + 5760 + 1440 * w + 16 * c), "l"(p + 2 * D_) : "memory");
                }
            }
            if (w == 3 && lane < 20)
                asm volatile("cp.async.ca.shared.global [%0], [%1], 4, %2;" ::"r"(sb + OFF_MISC + (uint32_t)offsetof(Misc, c2) + 12 + 16 * lane), "l"((const uint32_t*)w_r + min(20 * cl + lane, D_ / 2 - 1)),
                             "r"(20 * cl + lane < D_ / 2 ? 4 : 0) : "memory");
            asm volatile("cp.async.commit_group;" ::: "memory");
        }
        auto gsum = [&](uint32_t a, int pitch) {
            float4 s = make_float4(0.f, 0.f, 0.f, 0.f);
#pragma unroll
            for (int i = 0; i < 8; i++) { const float4 q = *(const float4*)(sm + a + i * pitch); s.x += q.x; s.y += q.y; s.z += q.z; s.w += q.w; }
            return make_uint2(pack2(s.x, s.z), pack2(s.y, s.w));
        };
        auto one_plus = [&](uint32_t v) { return pack2(1.0f + lo2f(v), 1.0f + hi2f(v)); };
        {
            uint32_t bs[9], a[5][4], c[5][4];
            float d[4] = {0.f, 0.f, 0.f, 0.f}, e[4] = {0.f, 0.f, 0.f, 0.f};
            const uint32_t sc = pack2(silu(lo2f(c_a)), silu(hi2f(c_a)));
            bs[8] = pack2(silu(lo2f(c_b)), silu(hi2f(c_b)));
            if (w == 2) { sts32(sb + OFF_SC + 4 * lane, sc); sts32(sb + OFF_SC + 128 + 4 * t, bs[8]); }
#pragma unroll
            for (int ks = 0; ks < 8; ks++) bs[ks] = __shfl_sync(0xffffffffu, sc, 4 * ks + t);
            CL_WAIT();
            asm volatile("cp.async.wait_group 0;" ::: "memory");
            named_bar(10, 128);
            mod_ld(a, OFF_WM0 + 5760, OFF_WM0, w);
            mod_ld(c, OFF_WM0 + 5760, OFF_WM0, 4);
            mod_mma2(d, e, a, c, bs);
            mod_st(d, OFF_MG1 + rk * 320 + 64 * w, MB_MG1);
            if (w == 1) mod_st(e, OFF_MG1 + rk * 320 + 256, MB_MG1);
        }
        {
            const int n0 = 8 * w + 2 * (rk & 1), n1 = 8 * w + ((n0 + 4 + t) & 7);
            const float4* ap = &S->acc1[256 * rk + 8 * (n0 + t) + g];
            const float4* aq = &S->acc1[256 * rk + 8 * n1 + g];
            named_bar(9, 640);
            if (w == 2 && lane == 0) {
#pragma unroll
                for (int i = 2; i < 6; i++) tma2d(sb + (i == 5 ? OFF_WM0 + 11520 : OFF_WM2 + (i - 2) * 5760), &tm_wm, i * D_ + 40 * cl, 72 * rk, MB(MB_WM2));
            }
            __syncwarp();
            if (w == 3) mbar_wait(MB(MB_MG1), 0);
            float4 pa = ld_rlx4f(ap), pb = ld_rlx4f(aq);
            if (w == 3) {
                const uint2 v = gsum(OFF_MG1 + 16 * min(lane, 19), 320);
                const uint32_t c1 = one_plus(v.x);
                if (lane < 20) *(uint4*)(sm + OFF_C1 + 16 * lane) = make_uint4(__byte_perm(c1, 0, 0x1010), __byte_perm(v.y, 0, 0x1010), __byte_perm(c1, 0, 0x3232), __byte_perm(v.y, 0, 0x3232));
                __syncwarp();
                named_arrive(10, 128);
            }
            uint32_t xq[2][5][4];
            uint2 cc[5];
            const uint32_t xa = sb + OFF_X + XI(2 * lm + (lr & 1)) + XN(n0 + (lr >> 1)), xb = sb + OFF_X + XI(2 * lm + (lr & 1)) + XN(8 * w + ((n0 + 4 + (lr >> 1)) & 7));
            const uint32_t ua = mapa(sb, g) + OFF_CH;
#pragma unroll
            for (int j = 0; j < 5; j++) ldsm_x4_t(xq[0][j], xa + 16 * j);
#pragma unroll 1
            for (int it = 0; it < SPIN_MAX && (pa.w != (float)NCL || pb.w != (float)NCL); it++) { pa = ld_rlx4f(ap); pb = ld_rlx4f(aq); }
            __syncwarp();
            if (w == 2 && lane < PFG) tma2d_pf(&tm_wg, 40 * b, 192 * lane);
            __syncwarp();
            float m0, r0, m1, r1;
            ln_stats(pa.x, pa.y, m0, r0);
            ln_stats(pb.x, pb.y, m1, r1);
            const uint32_t rh = pack2(r0, r1), rl = pack2(r0 - lo2f(rh), r1 - hi2f(rh));
            const uint32_t stage = sb + OFF_STG + w * 512;
            stsm_x4_t(stage + lane * 16, pack2(m0, m1), rh, rl, rl);
            __syncwarp();
            if (w != 3) named_bar(10, 128);
            uint4 st[2][3];
#pragma unroll
            for (int q = 0; q < 2; q++)
#pragma unroll
                for (int i = 0; i < 3; i++) st[q][i] = lds128(stage + 128 * i + (2 * t + q) * 16);
#pragma unroll
            for (int j = 0; j < 5; j++) cc[j] = *(const uint2*)(sm + OFF_C1 + 64 * j + 8 * g);
            ldsm_x4_t(xq[1][0], xb);
            const uint32_t ub = ua + (rk & 3) * UP + UB + (8 * w + 8 * (rk >> 2)) * 16, u0 = ub + (n0 + t) * 16, u1 = ub + n1 * 16;
#pragma unroll
            for (int j = 0; j < 5; j++) {
                if (j >= 2 && cl == 14) break;
                if (j < 4) ldsm_x4_t(xq[1][j + 1], xb + 16 * (j + 1));
#pragma unroll
                for (int q = 0; q < 2; q++) {
                    const uint4 sm_ = st[q][0], sh = st[q][1], sl = st[q][2];
                    const uint32_t v0 = add2(mul2(norm2(xq[q][j][0], sm_.x, sh.x, sl.x), cc[j].x), cc[j].y), v1 = add2(mul2(norm2(xq[q][j][1], sm_.y, sh.y, sl.y), cc[j].x), cc[j].y);
                    const uint32_t v2 = add2(mul2(norm2(xq[q][j][2], sm_.z, sh.z, sl.z), cc[j].x), cc[j].y), v3 = add2(mul2(norm2(xq[q][j][3], sm_.w, sh.w, sl.w), cc[j].x), cc[j].y);
                    asm volatile("{\n.reg .pred p;\nsetp.ne.u32 p, %6, %7;\n"
                                 "@p st.async.weak.shared::cluster.mbarrier::complete_tx::bytes.v4.b32 [%0], {%1,%2,%3,%4}, [%5];\n"
                                 "@!p st.shared.v4.b32 [%0], {%1,%2,%3,%4};\n}"
                                 ::"r"((q ? u1 : u0) + j * CHS), "r"(v0), "r"(v1), "r"(v2), "r"(v3), "r"(ua + j * CHS + XO_MBU), "r"(g), "r"(rk) : "memory");
                }
                __syncwarp();
                if (lane == 0) mbar_arrive(sb + OFF_CH + XO_MBU + j * CHS);
            }
        }
        asm volatile("setmaxnreg.dec.sync.aligned.u32 40;");
        {
        int cl;
        asm volatile("mov.u32 %0, %clusterid.x;" : "=r"(cl));
        const int w = __shfl_sync(0xffffffffu, (fresh_tid() >> 5) & 3, 0);
        uint32_t gz = 0;
        if (w) named_arrive(11, 128); else named_bar(11, 128);
        if (w == 0) {
            const int lane = fresh_tid() & 31;
            mbar_wait(MB(MB_KD), 0);
            PROXY_FENCE();
            if (lane == 0) {
#pragma unroll
                for (int i = 0; i < 3; i++) tma2d(sb + OFF_WG + i * 15360, &tm_wg, 40 * b, 192 * i, MB(MB_WG));
#pragma unroll 1
                for (int i = 0; i < 2; i++) { pace(PU); tma2d(sb + OFF_WU + i * 15360, &tm_wu, 40 * b, 192 * i, MB(MB_WU)); }
                pace(PU);
                tma2d_pf(&tm_wu, 40 * b, 384);
#pragma unroll 1
                for (int i = 0; i < PD0; i++) { pace(PDE); tma2d_pf(&tm_wd, 64 * i, 40 * b); }
                mbar_wait(MB(MB_C2), 0);
                PROXY_FENCE();
                tma2d(sb + OFF_WU + 2 * 15360, &tm_wu, 40 * b, 384, MB(MB_WU));
#pragma unroll 1
                for (int i = PD0; i < PD1; i++) { pace(PDE); tma2d_pf(&tm_wd, 64 * i, 40 * b); }
                mbar_wait(MB(MB_WU), 0);
#pragma unroll 1
                for (int i = PD1; i < 9; i++) { pace(PD); tma2d_pf(&tm_wd, 64 * i, 40 * b); }
            }
            __syncwarp();
        } else if (w == 1) {
            const int lane = fresh_tid() & 31;
            uint4* rp = S->h2c + 103 * b + lane;
#pragma unroll
            for (int i = 0; i < 4; i++) if (i < 3 || lane < 7) st_rlx4(rp + 32 * i, make_uint4(0, 0, 0, 0));
            uint32_t z = 0x3F800000u;
#pragma unroll
            for (int i = 0; i < 4; i++) if (i < 3 || lane < 7) z |= ld_rlx((const unsigned int*)(rp + 32 * i));
            if (lane == 0) asm volatile("red.relaxed.gpu.global.add.f32 [%0], %1;" ::"l"(&S->acc1[L_].z), "f"(__uint_as_float(z)) : "memory");
        } else if (w == 2) {
            if ((fresh_tid() & 31) == 0) {
                float4 v;
                int it = 0;
                pace(CWD);
                for (;;) { v = ld_rlx4f(&S->acc1[L_]); if (++it >= SPIN_MAX || (v.z == (float)G_ && v.w == (float)NCL)) break; pace(CWP); }
                M.cws[0] = v.x; M.cws[1] = v.y;
                mbar_arrive(MB(MB_CW));
            }
        } else if (w == 3) {
            const int lane = fresh_tid() & 31, l20 = min(lane, 19);
            mbar_wait(MB(MB_MG2), 0);
            const uint2 v = gsum(OFF_MG2 + 16 * l20, 640), u = gsum(OFF_MG2 + 320 + 16 * l20, 640);
            const uint32_t wr = lane < 20 ? M.c2[lane].w : 0u, cb1 = one_plus(v.x), cw = mul2(cb1, wr);
            if (lane < 20) {
                M.c2[lane] = make_uint4(cb1, v.y, u.x, cw);
                M.wr[lane] = wr;
                unsigned e;
                asm volatile("mov.u32 %0, %cluster_ctarank;" : "=r"(e));
                if ((lane & 3) == (e >> 1)) M.ga[lane >> 2] = __byte_perm(u.y, 0, (e & 1) ? 0x3232 : 0x1010);
            }
            __syncwarp();
            if (lane == 0) mbar_arrive(MB(MB_C2));
            if (rk == 0) {
                if (lane < 20) st_rlx(&S->gb[20 * cl + lane], u.x);
                gz = ld_rlx(&S->gb[20 * cl + l20]) ^ u.x;
                float a = lo2f(cw) + hi2f(cw), s = lo2f(v.y) * lo2f(wr) + hi2f(v.y) * hi2f(wr);
#pragma unroll
                for (int o = 16; o; o >>= 1) { a += __shfl_xor_sync(0xffffffffu, a, o); s += __shfl_xor_sync(0xffffffffu, s, o); }
                if (lane == 0) red4(&S->acc1[L_], a, s, 0.f);
            }
        }
        {
        const int lane = fresh_tid() & 31, t = lane & 3, lr = lane & 7, lm = lane >> 3;
        uint32_t aw[5];
        __syncwarp();
        mbar_wait(MB(MB_C2), 0);
#pragma unroll
        for (int j = 0; j < 5; j++) aw[j] = M.wr[4 * j + t];
        const int ph = w >> 1, lst = 16 * ph + 2 * rk + (w & 1);
        const uint32_t rb = mapa(sb, lr);
        named_bar(6, 640);
        uint4 k = *(const uint4*)&M.key[128 * (w & 1) + 4 * lane];
        CE(k.x, k.y); CE(k.z, k.w); CE(k.x, k.z); CE(k.y, k.w); CE(k.y, k.z);
        uint32_t m[4];
#pragma unroll 1
        for (int q = 0; q <= ph; q++) {
#pragma unroll
            for (int rnd = 0; rnd < 4; rnd++) {
                m[rnd] = __reduce_max_sync(0xffffffffu, k.x);
                POP(k, m[rnd]);
            }
        }
        if (lane < 8) sta4(rb + OFF_MISC + (uint32_t)offsetof(Misc, cand) + lst * 16, make_uint4(m[0], m[1], m[2], m[3]), rb + (MB(MB_KEY2) - sb));
        const uint32_t mine = (t & 2) ? ((t & 1) ? m[3] : m[2]) : ((t & 1) ? m[1] : m[0]);
        const uint32_t ra = sb + OFF_H2T + ROW(mine) * 80;
        uint32_t bq[6];
        float rr[4] = {0.f, 0.f, 0.f, 0.f};
        ldsm_x4(bq, ra + 16 * lm); ldsm_x2(bq + 4, ra + 64);
        mma_bf16(rr, aw[0], aw[0], aw[1], aw[1], bq[0], bq[1]); mma_bf16(rr, aw[2], aw[2], aw[3], aw[3], bq[2], bq[3]); mma_k8(rr, aw[4], aw[4], bq[4]);
        float4* p = &S->rs[8 * lst];
        if (lane < 2) red4(p + lane, rr[0], __uint_as_float(gz), rr[1]);
        float4 e0 = ld_rlx4f(p), e1 = ld_rlx4f(p + 1);
        uint32_t sl = 0;
        if (w == 1) {
            mbar_wait(MB(MB_KEY2), 0);
            k = *(const uint4*)&M.cand[4 * lane];
            named_bar(14, 64);
#pragma unroll
            for (int s = 0; s < 8; s++) {
                const uint32_t v = M.sel[s] & ~1u;
                if (k.x == v) sl |= 8 + s;
                if (k.y == v) sl |= (8 + s) << 8;
                if (k.z == v) sl |= (8 + s) << 16;
                if (k.w == v) sl |= (8 + s) << 24;
            }
        }
        if (w == 0) {
            named_bar(8, 64);
            if (lane == 0) {
                PROXY_FENCE();
                tma5d_st(&tm_out, 40 * cl, RKT, sb + OFF_OUT);
                asm volatile("cp.async.bulk.commit_group;" ::: "memory");
            }
            __syncwarp();
        }
#pragma unroll 1
        for (int it = 0; it < SPIN_MAX && (e0.w != (float)NCL || e1.w != (float)NCL); it++) { e0 = ld_rlx4f(p); e1 = ld_rlx4f(p + 1); }
        {
            const uint32_t r0 = pack2(e0.x, e0.z), r1 = pack2(e1.x, e1.z);
            const uint32_t o0 = r0 ^ (sign2(r0) | 0x80008000u), o1 = r1 ^ (sign2(r1) | 0x80008000u);
            if (lane < 8) sta4(rb + OFF_EK + lst * VP, make_uint4((o0 << 16) | (m[0] & 0x3FFFu), (o0 & 0xFFFF0000u) | (m[1] & 0x3FFFu), (o1 << 16) | (m[2] & 0x3FFFu), (o1 & 0xFFFF0000u) | (m[3] & 0x3FFFu)),
                               rb + (MB(MB_EK) - sb));
        }
        if (w == 0) {
            if (lane == 0) {
                asm volatile("cp.async.bulk.wait_group 0;" ::: "memory");
                asm volatile("fence.acq_rel.gpu;" ::: "memory");
                mbar_arrive(MB(MB_OUT));
            }
        } else if (w == 1) {
            const uint32_t found = __reduce_add_sync(0xffffffffu, __popc(sl & 0x08080808u));
            mbar_wait(MB(MB_EK), 0);
            if (b == 0 && lane == 0) st_rlx4(&S->acc1[L_], make_uint4(0, 0, 0, 0));
            if (lane < 16 || cl == 14) st_rlx4(&S->acc2[256 * rk + 16 * cl + lane], make_uint4(0, 0, 0, 0));
            k = lds128(sb + OFF_EK + lane * VP);
            const bool s0 = sl & 8u, s1 = sl & 0x800u, s2 = sl & 0x80000u, s3 = sl & 0x8000000u;
            if (s0) M.fin[sl & 7u] = k.x;
            if (s1) M.fin[(sl >> 8) & 7u] = k.y;
            if (s2) M.fin[(sl >> 16) & 7u] = k.z;
            if (s3) M.fin[(sl >> 24) & 7u] = k.w;
            const uint32_t lo = min(min(s0 ? k.x : ~0u, s1 ? k.y : ~0u), min(s2 ? k.z : ~0u, s3 ? k.w : ~0u));
            const uint32_t hi = max(max(s0 ? 0u : k.x, s1 ? 0u : k.y), max(s2 ? 0u : k.z, s3 ? 0u : k.w));
            const uint32_t hi2 = __reduce_max_sync(0xffffffffu, hi), lo2 = __reduce_min_sync(0xffffffffu, lo);
            bool redo = found != 8u;
            if (hi2 > lo2) {
                const uint32_t h = hi2 | 0xFFFFu, l = lo2 & 0xFFFF0000u;
                const uint32_t n = __reduce_add_sync(0xffffffffu, ((s0 ? k.x <= h : (k.x >= l) << 8) + (s1 ? k.y <= h : (k.y >= l) << 8)) + ((s2 ? k.z <= h : (k.z >= l) << 8) + (s3 ? k.w <= h : (k.w >= l) << 8)));
                redo = redo || (h >> 16) - (l >> 16) > 1u || ((n & 255u) > 1u && n >= 512u) || (n & 255u) + (n >> 8) > 9u;
            }
            if (redo) {
                CE(k.x, k.y); CE(k.z, k.w); CE(k.x, k.z); CE(k.y, k.w); CE(k.y, k.z);
                __syncwarp();
#pragma unroll 1
                for (int rnd = 0; rnd < 8; rnd++) {
                    const uint32_t m8 = __reduce_max_sync(0xffffffffu, k.x);
                    POP(k, m8);
                    if (lane == 0) M.fin[rnd] = m8;
                }
            }
            if (lane == 0) M.fin[8] = redo;
            __syncwarp();
            named_arrive(12, 672);
        }
        }
        }
    } else {
    if (warp != 19) CL_ARRIVE();
    const int chn = 40 * cl + 8 * wgi + rk;
    const bool has_ch = chn < D_;
    const uint32_t cb = sb + OFF_CH + wgi * CHS;
    auto ldx = [&]() {
    if (warp < 16) {
        const char* xp = (const char*)(x + (512 * (warp >> 2) + 64 * (warp & 3) + RKT) * D_ + 40 * cl);
#pragma unroll
        for (int i = 0; i < 3; i++) {
            const uint32_t c = lane + 32 * i, row = (c * 205) >> 10, hi = c >= 40;
            if (c < 80) asm volatile("cp.async.cg.shared.global [%0], [%1], 16, %2;" ::"r"(sb + OFF_X + XN(2 * warp) + XI(row & 7) + 80 * (hi - row) + 16 * c), "l"(xp + (row * (2 * D_ - 80) + 16 * c + hi * (24 * 2 * D_))),
                                     "r"((cl < 14 || c - 5 * row < 2) ? 16 : 0) : "memory");
        }
    }
    };
    unsigned short r_ldt = 0, r_lar = 0, r_aim = 0, r_cr = 0, r_ci = 0;
    {
        const int n = min(chn, D_ - 1) * N_ + (tid & 127);
        r_ldt = ld_nc16((const unsigned short*)logdt + min(chn, D_ - 1));
        r_lar = ld_nc16((const unsigned short*)logAr + n);
        r_aim = ld_nc16((const unsigned short*)Aim + n);
        r_cr = ld_nc16((const unsigned short*)Cr + n);
        r_ci = ld_nc16((const unsigned short*)Ci + n);
    }
    if (warp == 19) {
        if (lane == 0) asm volatile("prefetch.tensormap [%0];" ::"l"(&tm_wm) : "memory");
        const uint32_t lo = 90u | (10u << 8) | (20u << 16) | (2u << 24), hi = (cl == 14 ? 32u : 80u) | ((rk < 4 ? 40u : 32u) << 8) | (180u << 16) | (180u << 24);
        const uint32_t tx = lane < 8 ? (((lane & 4 ? hi : lo) >> (8 * (lane & 3))) & 255u) : lane == 8 ? 180u : lane < 11 ? 2u : lane == 11 ? (hi >> 8) & 255u : 14u;
        if (lane == 0) {
#pragma unroll
            for (int i = 0; i < MB_N; i++) mbar_init(MB(i), i == MB_KD ? 20 : 1);
#pragma unroll
            for (int i = 0; i < 5; i++) mbar_init(sb + OFF_CH + XO_MBU + i * CHS, 5);
        }
        __syncwarp();
        if (lane < 17) mbar_expect(lane < MB_C2 ? MB(lane) : sb + OFF_CH + XO_MBU + (lane - MB_C2) * CHS, tx << 8);
        asm volatile("fence.mbarrier_init.release.cluster;" ::: "memory");
        __syncwarp();
        CL_ARRIVE();
    }
    ldx();
    if ((tid & 127) == 32) asm volatile("cp.async.ca.shared.global [%0], [%1], 4;" ::"r"(cb + XO_DSK), "l"((const uint32_t*)Dskip + (min(chn, D_ - 1) >> 1)) : "memory");
    asm volatile("cp.async.commit_group;" ::: "memory");
    auto mod2 = [&]() {
        if (wgi == 4) {
            uint32_t bs[9], a[5][4], c[5][4];
            float d[4] = {0.f, 0.f, 0.f, 0.f}, e[4] = {0.f, 0.f, 0.f, 0.f}, f[4] = {0.f, 0.f, 0.f, 0.f};
            mbar_wait(MB(MB_MG1), 0);
#pragma unroll
            for (int ks = 0; ks < 9; ks++) bs[ks] = lds32(sb + OFF_SC + 16 * ks + 4 * t);
            mbar_wait(MB(MB_WM2), 0);
            mod_ld(a, OFF_WM2 + 11520, OFF_WM2 + 5760, w);
            mod_ld(c, OFF_WM0 + 11520, OFF_WM2, w);
            mod_mma2(d, e, a, c, bs);
            mod_ld(a, (w & 1) ? OFF_WM0 + 11520 : OFF_WM2 + 11520, (w & 1) ? OFF_WM2 : OFF_WM2 + 5760, 4);
            mod_st(d, OFF_MG2 + rk * 640 + 64 * w, MB_MG2);
            mod_st(e, OFF_MG2 + rk * 640 + 320 + 64 * w, MB_MG2);
            d[0] = d[1] = d[2] = d[3] = 0.f;
            mma_k8(d, a[4][0], a[4][1], bs[8]);
#pragma unroll
            for (int ks = 0; ks < 4; ks++) mma_bf16((ks & 1) ? d : f, a[ks][0], a[ks][1], a[ks][2], a[ks][3], bs[2 * ks], bs[2 * ks + 1]);
            d[0] += f[0]; d[2] += f[2];
            if (w < 2) mod_st(d, OFF_MG2 + rk * 640 + 320 * w + 256, MB_MG2);
            __syncwarp();
        }
    };
    auto ln1 = [&]() {
        if (warp < 16) {
            uint32_t a[10];
            const uint32_t xa = sb + OFF_X + XN(2 * warp) + (lm & 1) * 80 + XI(lr) + (lm >> 1) * 16;
            asm volatile("cp.async.wait_group 0;" ::: "memory");
            __syncwarp();
            ldsm_x4(a, xa); ldsm_x4(a + 4, xa + 32); ldsm_x2(a + 8, xa + 64);
            named_arrive(9, 640);
            float c1[4] = {0.f, 0.f, 0.f, 0.f}, c2[4] = {0.f, 0.f, 0.f, 0.f}, c3[4] = {0.f, 0.f, 0.f, 0.f};
#pragma unroll
            for (int j = 0; j < 2; j++) {
                mma_bf16(c1, a[4 * j], a[4 * j + 1], a[4 * j + 2], a[4 * j + 3], 0x3F803F80u, 0x3F803F80u);
                mma_bf16(c2, a[4 * j], a[4 * j + 1], a[4 * j + 2], a[4 * j + 3], a[4 * j], a[4 * j + 2]);
                mma_bf16(c3, a[4 * j], a[4 * j + 1], a[4 * j + 2], a[4 * j + 3], a[4 * j + 1], a[4 * j + 3]);
            }
            mma_k8(c1, a[8], a[9], 0x3F803F80u); mma_k8(c2, a[8], a[9], a[8]); mma_k8(c3, a[8], a[9], a[9]);
            float4* p = &S->acc1[256 * rk + 16 * warp + g];
            red4p(t == (g >> 1), p, c1[0], (g & 1) ? c2[1] : c2[0], 0.f);
            red4p(t == (g >> 1), p + 8, c1[2], (g & 1) ? c3[3] : c3[2], 0.f);
        }
    };
    {
        unsigned char* cp = sm + OFF_CH + wgi * CHS + lane * 16;
        const uint4 z = make_uint4(0, 0, 0, 0);
        *(uint4*)(cp + w * UP + XO_TF) = z;
        *(uint4*)(cp + w * UP + (lane < 16 ? XO_U8 - 256 : XO_U16 - 512)) = z;
        if (lane < 17) *(uint4*)(cp + (lane < 9 ? w * UP + UB - 144 : lane == 9 ? w * UP + XO_ZC - 160 : lane < 14 ? XO_TD + (4 * w - 10) * 16 : XO_TD + (145 - 14 + 3 * w) * 16)) = z;
    }
    if (tid < 224) {
        const int e = tid & 15, l = (tid >> 4) - 6 - (int)((0x3355544433666ull >> (4 * e)) & 15) + 8 * (int)((0x1021021010210ull >> (4 * e)) & 15);
        const unsigned wd = (0x1166688822444ull >> (4 * e)) & 15, one = e >= 11 ? 0xFFFFu : 0x3F80u;
        ((uint32_t*)M.box)[((e >> 2) * 14 + (tid >> 4)) * 4 + (e & 3)] = ((unsigned)l <= wd ? one : 0u) | ((unsigned)(l - 1) <= wd ? one << 16 : 0u);
    }
    const uint32_t scr = sb + warp * KSCR, ws = scr + lane * 4;
    uint32_t fixa = 0, fixv = 0;
    {
        uint32_t zr;
        asm volatile("ld.volatile.shared.u32 %0, [%1];" : "=r"(zr) : "r"(cb + XO_TF + w * UP + lane * 16) : "memory");
        const float p_ldt = __uint_as_float(r_ldt * 65536u + zr), p_lar = __uint_as_float(r_lar * 65536u + zr), p_aim = __uint_as_float(r_aim * 65536u + zr);
        const float p_cr = __uint_as_float(r_cr * 65536u + zr), p_ci = __uint_as_float(r_ci * 65536u + zr);
        float acc[5][4];
        uint32_t afr[4][4], cz[4];
        const uint32_t ba = scr + lr * 144 + lm * 16;
        auto tile = [&](float* c, int rg) {
            __syncwarp();
            c[0] = c[1] = c[2] = c[3] = 0.f;
            uint32_t bb[2][4];
            ldsm_x4(bb[0], ba + rg * 1152);
            ldsm_x4(bb[1], ba + rg * 1152 + 64);
            mma_f16(c, afr[0], bb[0][0], bb[0][1]);
            mma_f16(c, afr[1], bb[0][2], bb[0][3]);
            mma_f16(c, afr[2], bb[1][0], bb[1][1]);
            mma_f16(c, afr[3], bb[1][2], bb[1][3]);
        };
#define CJ(z) packh((z).x, -(z).y)
#define CJP(z) packh((z).y, (z).x)
        const float dt = bfr(expf(p_ldt));
        const float al = -bfr(expf(p_lar)) * dt * 1.4426950408889634f;
        const float th = p_aim * dt;
        const float th_ = th * 0.15915494309189535f;
        const float tl_ = fmaf(th, 0.15915494309189535f, -th_) + th * 6.4206382e-9f;
        auto anchor = [&](float s) {
            float f = th_ * s;
            f -= rintf(f);
            f = fmaf(tl_, s, f) * 6.283185307179586f;
            const float e = fex2(al * s);
            return cplx{e * __cosf(f), e * __sinf(f)};
        };
        const float cx = p_cr * dt * 2.0f, cy = p_ci * dt * 2.0f;
        const uint32_t ex = __reduce_max_sync(0xffffffffu, __float_as_uint(fmaxf(fabsf(cx), fabsf(cy)))) >> 23;
        const float scl = __uint_as_float((254u - ex) << 23);
        const cplx C = cplx{cx * scl, cy * scl};
        const cplx z1 = anchor(1.f), z16 = anchor(16.f), z256 = anchor(256.f);
        {
            const cplx z32 = csq(z16), z48 = cmul(z32, z16), z64 = csq(z32), z128 = csq(z64), z192 = cmul(z128, z64);
            const uint32_t y[3] = {packh(z16.x, z16.y), packh(z32.x, z32.y), packh(z48.x, z48.y)};
            const uint32_t yp[3] = {packh(-z16.y, z16.x), packh(-z32.y, z32.x), packh(-z48.y, z48.x)};
            const uint32_t xx[3] = {packh(z64.x, z64.y), packh(z128.x, z128.y), packh(z192.x, z192.y)};
            sts32(ws, 0x00003C00u);
#pragma unroll
            for (int j = 0; j < 3; j++) sts32(ws + (1 + j) * 144, y[j]);
#pragma unroll
            for (int i = 0; i < 3; i++) {
                sts32(ws + (4 + 4 * i) * 144, xx[i]);
#pragma unroll
                for (int j = 0; j < 3; j++) sts32(ws + (5 + 4 * i + j) * 144, hcm(xx[i], y[j], yp[j]));
            }
        }
        ln1();
        const cplx z2 = csq(z1);
        {
            const cplx z3 = cmul(z2, z1), z4 = csq(z2), z8 = csq(z4);
            const cplx c4 = cmul(C, z4), c8 = cmul(C, z8), c12 = cmul(c8, z4);
            cz[0] = packh(C.x, -C.y); cz[1] = packh(c4.x, -c4.y); cz[2] = packh(c8.x, -c8.y); cz[3] = packh(c12.x, -c12.y);
            __syncwarp();
#pragma unroll
            for (int s = 0; s < 4; s++) ldsm_x4(afr[s], scr + (lr + 8 * (lm & 1)) * 144 + (2 * s + (lm >> 1)) * 16);
            const uint32_t y[3] = {CJ(z1), CJ(z2), CJ(z3)}, yp[3] = {CJP(z1), CJP(z2), CJP(z3)};
#pragma unroll
            for (int tt = 0; tt < 2; tt++) {
                const int rg = tt ? 0 : 2;
#pragma unroll
                for (int i = 0; i < 2; i++) {
                    sts32(ws + rg * 1152 + (4 * i) * 144, cz[2 * tt + i]);
#pragma unroll
                    for (int j = 0; j < 3; j++) sts32(ws + rg * 1152 + (4 * i + 1 + j) * 144, hcm(cz[2 * tt + i], y[j], yp[j]));
                }
                tile(acc[tt], rg);
            }
        }
        const cplx z258 = cmul(z256, z2), z512 = csq(z256), z768 = cmul(z512, z256);
        {
            const uint32_t a0 = CJ(z256), a0p = CJP(z256), a1 = CJ(z258), a1p = CJP(z258);
#pragma unroll
            for (int i = 0; i < 4; i++) { sts32(ws + 1152 + (2 * i) * 144, hcm(cz[i], a0, a0p)); sts32(ws + 1152 + (2 * i + 1) * 144, hcm(cz[i], a1, a1p)); }
            tile(acc[2], 1);
        }
        {
            const uint32_t a0 = CJ(z512), a0p = CJP(z512), a1 = CJ(z768), a1p = CJP(z768);
#pragma unroll
            for (int i = 0; i < 4; i++) { sts32(ws + 2304 + i * 144, hcm(cz[i], a0, a0p)); sts32(ws + 2304 + (4 + i) * 144, hcm(cz[i], a1, a1p)); }
            tile(acc[3], 2);
        }
        const cplx z1024 = csq(z512);
        {
            const cplx zk[4] = {z1024, cmul(z1024, z256), csq(z768), cmul(z1024, z768)};
#pragma unroll
            for (int h = 0; h < 4; h++) {
                const uint32_t a0 = CJ(zk[h]), a0p = CJP(zk[h]);
                sts32(ws + (2 * h) * 144, hcm(cz[0], a0, a0p));
                sts32(ws + (2 * h + 1) * 144, hcm(cz[2], a0, a0p));
            }
            tile(acc[4], 0);
        }
        const cplx z2048 = csq(z1024);
        float last = C.x * z2048.x - C.y * z2048.y;
#pragma unroll
        for (int o = 16; o; o >>= 1) last += __shfl_xor_sync(0xffffffffu, last, o);
        __syncwarp();
#pragma unroll
        for (int i = 0; i < 5; i++) *(float4*)(sm + (scr - sb) + i * 512 + ((lane * 16) ^ (i == 1 ? 64 : 0))) = make_float4(acc[i][0], acc[i][1], acc[i][2], acc[i][3]);
        if (lane == 0) { const float inv = __uint_as_float(ex << 23); sts32(cb + XO_KINV + 4 * w, __float_as_uint(inv)); sts32(cb + XO_KLAST + 4 * w, __float_as_uint(last * inv)); }
        asm volatile("cp.async.wait_group 0;" ::: "memory");
        CL_WAIT();
        named_bar(1 + wgi, 128);
        const uint32_t td = cb + XO_TD + 64 * 4, tf = cb + XO_TF - 32 * 4;
        const float4 ki = *(const float4*)(sm + (cb - sb) + XO_KINV);
        auto fsum = [&](int off, uint32_t& r0, uint32_t& r1) {
            const unsigned char* p = sm + wgi * (4 * KSCR) + off;
            const float4 a = *(const float4*)p, b2 = *(const float4*)(p + KSCR), c = *(const float4*)(p + 2 * KSCR), d = *(const float4*)(p + 3 * KSCR);
            r0 = pack2(fmaf(a.y, ki.x, b2.y * ki.y) + fmaf(c.y, ki.z, d.y * ki.w), fmaf(a.x, ki.x, b2.x * ki.y) + fmaf(c.x, ki.z, d.x * ki.w));
            r1 = pack2(fmaf(a.w, ki.x, b2.w * ki.y) + fmaf(c.w, ki.z, d.w * ki.w), fmaf(a.z, ki.x, b2.z * ki.y) + fmaf(c.z, ki.z, d.z * ki.w));
        };
        const int role = (w + wgi) & 3;
        const int fo = role ? (role + 1) * 512 + lane * 16 : (g & 1) * 512 + ((lm ^ (g & 1)) * 64) + t * 16;
        uint32_t r[2];
        fsum(fo, r[0], r[1]);
        if (role == 0) {
            uint32_t q[2], v[4];
            fsum(fo + 256, q[0], q[1]);
            const uint32_t c[4] = {r[0], q[0], r[1], q[1]};
#pragma unroll
            for (int i = 0; i < 4; i++) v[i] = __shfl_sync(0xffffffffu, c[i], (lane + 31) & 31);
            if (lane == 0) mbar_arrive(MB(MB_KD));
#pragma unroll
            for (int i = 0; i < 4; i++) *(uint2*)(sm + (td - sb) + lane * 8 + i * 256) = make_uint2(__byte_perm(c[i], lane ? v[i] : i ? v[i - 1] : 0u, 0x5432), c[i]);
            if (lane == 0) { fixa = td + 256 * 4 + 2; fixv = v[3]; }
        } else if (role == 1) {
            const uint32_t v0 = __shfl_sync(0xffffffffu, r[0], (lane + 1) & 31), v1 = __shfl_sync(0xffffffffu, r[1], (lane + 1) & 31);
            if (lane == 0) mbar_arrive(MB(MB_KD));
#pragma unroll
            for (int h = 0; h < 2; h++) {
                const uint32_t dd = __byte_perm(r[h], 0, 0x3232);
                *(uint4*)(sm + (td - sb) + 1024 + lane * 16 + h * 512) = make_uint4(dd, dd, r[h], __byte_perm((h || lane == 31) ? v1 : v0, r[h], 0x5432));
            }
        } else {
            __syncwarp();
            if (lane == 0) mbar_arrive(MB(MB_KD));
            const uint32_t p = role == 2 ? tf + (64 + 32 * (t >> 1) + 2 * g + (t & 1)) * 4 : tf + 2 * UP + (64 + 16 * t + g) * 4, p1 = p + (role == 2 ? 64 : 32);
            const uint32_t k0 = r[0] >> 16, k1 = r[1] >> 16;
            sts16(p + UP, r[0]); sts16(p + UP + 6, r[0]); sts16(p1 + UP, r[1]); sts16(p1 + UP + 6, r[1]);
            sts16(p1 - 4, k1); sts16(p1 + 2, k1);
            const uint32_t dd = __byte_perm(r[0], 0, 0x3232);
            if (lane) { sts16(p - 4, k0); sts16(p + 2, k0); }
            else if (role == 2) {
                *(uint4*)(sm + (td - sb) + 512 * 4) = make_uint4(dd, dd, dd, r[0] & 0xFFFF0000u);
                fixa = td + 511 * 4; fixv = k0;
            } else {
                const float4 kl4 = *(const float4*)(sm + (cb - sb) + XO_KLAST);
                const uint32_t kl = f2bits((kl4.x + kl4.y) + (kl4.z + kl4.w));
                sts16(tf + 127 * 4, dd); sts16(tf + 128 * 4 + 2, dd); sts32(cb + XO_K1024, dd);
                sts16(tf + 2 * UP + 127 * 4, kl); sts16(tf + 2 * UP + 128 * 4 + 2, kl);
            }
        }
        __syncwarp();
        mod2();
    }
    if (has_ch) {
        conv_channel(sm, rk, fixa, fixv);
    } else {
        asm volatile("setmaxnreg.inc.sync.aligned.u32 88;");
        mbar_wait(MB(MB_WG), 0);
        mbar_wait(MB(MB_C2), 0);
    }
    {
    const int tid = fresh_tid(), warp = __shfl_sync(0xffffffffu, tid >> 5, 0), lane = tid & 31;
    const int g = lane >> 2, t = lane & 3, lr = lane & 7, lm = lane >> 3;
    __syncwarp();
    if (lane == 0) mbar_arrive(MB(MB_KD));
    uint32_t x1[10];
    uint32_t wf[9][4], wd[2][3][4];
    const int fmt = warp >> 2, fsl = warp & 3;
    auto ldwf = [&]() {
        const int half = lm & 1;
        const uint32_t base = (fmt == 4) ? ((half ? OFF_WU : OFF_WG) + 64) : ((fmt >> 1) * OFF_WU + ((2 * (fmt & 1) + half) << 4));
        const uint32_t wa = sb + base + (144 * fsl + lr + 8 * (lm >> 1)) * 80;
#pragma unroll
        for (int ks = 0; ks < 9; ks++) ldsm_x4_t(wf[ks], wa + ks * 1280);
    };
    if (warp < 16) {
        uint32_t bw[5], v[10];
#pragma unroll
        for (int j = 0; j < 5; j++) bw[j] = (g & 1) ? M.c2[4 * j + t].w : 0x3F803F80u;
        const uint32_t xa = sb + OFF_X + XI(warp >> 1) + (2 * (warp & 1) + (lm & 1)) * XG + lr * 80 + (lm >> 1) * 16;
        const uint32_t va = sb + OFF_V + (8 * (lm >> 1) + lr) * VP + 32 * warp + 16 * (lm & 1);
        ldsm_x4(x1, xa); ldsm_x4(x1 + 4, xa + 32); ldsm_x2(x1 + 8, xa + 64);
        mbar_wait(MB(MB_V), 0);
        ldsm_x4_t(v, va); ldsm_x4_t(v + 4, va + 16 * VP); ldsm_x2_t(v + 8, va + 32 * VP);
#pragma unroll
        for (int i = 0; i < 10; i++) x1[i] = add2(x1[i], (i >= 4 && cl == 14) ? 0u : v[i]);
        float c1[4] = {0.f, 0.f, 0.f, 0.f}, c2[4] = {0.f, 0.f, 0.f, 0.f}, c3[4] = {0.f, 0.f, 0.f, 0.f};
#pragma unroll
        for (int j = 0; j < 2; j++) {
            mma_bf16(c1, x1[4 * j], x1[4 * j + 1], x1[4 * j + 2], x1[4 * j + 3], bw[2 * j], bw[2 * j + 1]);
            mma_bf16(c2, x1[4 * j], x1[4 * j + 1], x1[4 * j + 2], x1[4 * j + 3], x1[4 * j], x1[4 * j + 2]);
            mma_bf16(c3, x1[4 * j], x1[4 * j + 1], x1[4 * j + 2], x1[4 * j + 3], x1[4 * j + 1], x1[4 * j + 3]);
        }
        mma_k8(c1, x1[8], x1[9], bw[4]); mma_k8(c2, x1[8], x1[9], x1[8]); mma_k8(c3, x1[8], x1[9], x1[9]);
        if (t == (g >> 1)) {
            float4* p = &S->acc2[256 * rk + 16 * warp + g];
            red4(p, c1[0], (g & 1) ? c2[1] : c2[0], c1[1]);
            red4(p + 8, c1[2], (g & 1) ? c3[3] : c3[2], c1[3]);
        }
        __syncwarp();
    }
    if (warp >= 16) { mbar_wait(MB(MB_WG), 0); mbar_wait(MB(MB_WU), 0); ldwf(); }
    if (warp >= 17) {
        named_bar(7, 128);
        PROXY_FENCE();
        if (lane < 3) tma2d(sb + OFF_WD + (3 * (warp - 17) + lane) * 5120, &tm_wd, 64 * (3 * (warp - 17) + lane), 40 * b, MB(MB_WD));
        __syncwarp();
    }
    uint32_t h2[10];
    uint32_t ta = sb + OFF_H2T + (16 * warp + (lane & 15)) * 80 + (lane >> 4) * 16;
    if (warp < 16) {
        const float4* ap = &S->acc2[256 * rk + 32 * (warp >> 1) + lane];
        if (warp < 8) { mbar_wait(MB(MB_WG), 0); ldwf(); }
        float4 s = ld_rlx4f(ap);
        uint2 kc[5];
#pragma unroll
        for (int j = 0; j < 5; j++) kc[j] = *(const uint2*)&M.c2[4 * j + t];
        mbar_wait(MB(MB_CW), 0);
        const float cw = M.cws[0], sbw = M.cws[1];
        uint32_t tk0 = (2047 - (((lane & 6) << 8) + ((lane & 24) << 3) + ((lane & 1) << 5) + RKT + (warp >> 1))) << 3;
        uint32_t ka = sb + OFF_MISC + (uint32_t)offsetof(Misc, key) + (32 * (warp >> 1) + lane) * 4;
        uint32_t rb = mapa(sb, 4 * (warp & 1) + t), cd = rb + OFF_MISC + (uint32_t)offsetof(Misc, cand2) + (8 * rk + (warp >> 1)) * 8;
        const int pj = lane >= 5, pc = lane - 5 * pj;
        uint4* dst = &S->h2c[(2 * (8 * rk + (warp >> 1)) + pj) * 72 + 5 * cl + pc];
        uint32_t pa = sb + OFF_H2T + 32 * (warp >> 1) * 80 + 16 * pc;
        asm volatile("" : "+r"(tk0), "+r"(ta), "+r"(ka), "+r"(rb), "+r"(cd), "+r"(pa), "+l"(dst));
        mbar_wait(MB(MB_KD), 1);
#pragma unroll 1
        for (int it = 0; it < SPIN_MAX && s.w != (float)NCL; it++) s = ld_rlx4f(ap);
        __syncwarp();
        if (warp == 0) named_arrive(7, 128);
        float meanb, rinv;
        ln_stats(s.x, s.y, meanb, rinv);
        const uint32_t rbits = __float_as_uint(fmaf(fmaf(-meanb, cw, s.z), rinv, sbw));
        const uint32_t key = ((rbits ^ (((int)rbits >> 31) | 0x80000000u)) & 0xFFFFC000u) | tk0;
        const uint32_t m0 = __reduce_max_sync(0xffffffffu, key);
        const uint32_t mr = pack2(meanb, rinv), rl = f2bits(rinv - hi2f(mr));
        const uint32_t m1 = __reduce_max_sync(0xffffffffu, key == m0 ? 0u : key);
        uint32_t st[2][2];
#pragma unroll
        for (int h = 0; h < 2; h++) { st[h][0] = __shfl_sync(0xffffffffu, mr, 16 * (warp & 1) + 8 * h + g); st[h][1] = __shfl_sync(0xffffffffu, rl, 16 * (warp & 1) + 8 * h + g); }
        if (lane < 4) sta2(cd, m0, m1 | 1u, rb + (MB(MB_KEY) - sb));
        sts32(ka, key);
        const int pr = __ffs(__ballot_sync(0xffffffffu, key == m0) | 0x80000000u) - 1, pr1 = __ffs(__ballot_sync(0xffffffffu, key == m1) | 0x80000000u) - 1;
#pragma unroll
        for (int i = 0; i < 10; i++)
            h2[i] = add2(mul2(norm2(x1[i], __byte_perm(st[i & 1][0], 0, 0x1010), __byte_perm(st[i & 1][0], 0, 0x3232), __byte_perm(st[i & 1][1], 0, 0x1010)), kc[i >> 1].x), kc[i >> 1].y);
        stsm_x4(ta, h2[0], h2[1], h2[2], h2[3]); stsm_x4(ta + 32, h2[4], h2[5], h2[6], h2[7]); stsm_x2(ta + 64, h2[8], h2[9]);
        __syncwarp();
        const int row = pj ? pr1 : pr;
        if (lane < 10 && (row >> 4) == (warp & 1) && pc < (cl < 14 ? 5 : 2)) {
            const uint4 a = lds128(pa + 80 * row);
            st_rlx4(dst, make_uint4(~a.x, ~a.y, ~a.z, ~a.w));
        }
        __syncwarp();
        named_arrive(6, 640);
        if (warp >= 8) { mbar_wait(MB(MB_WU), 0); ldwf(); }
    }
    auto outt = [&]() {
        if (warp < 16) {
            uint32_t o[10];
            if ((warp == cl || (warp == 15 && cl == 0)) && lane < 16) st_rlx4(&S->acc1[256 * rk + 16 * warp + lane], make_uint4(0, 0, 0, 0));
#pragma unroll
            for (int i = 0; i < 10; i++) o[i] = add2(x1[i], mul2(M.c2[4 * (i >> 1) + t].z, h2[i]));
            stsm_x4(ta + (OFF_OUT - OFF_H2T), o[0], o[1], o[2], o[3]); stsm_x4(ta + (OFF_OUT - OFF_H2T) + 32, o[4], o[5], o[6], o[7]); stsm_x2(ta + (OFF_OUT - OFF_H2T) + 64, o[8], o[9]);
        }
    };
    outt();
    uint4 gv = make_uint4(1, 1, 1, 1);
    const uint4* gp;
    uint32_t gdst;
    {
        const int gi = 32 * warp + lane, kk = (gi * 911) >> 16, seg = gi - 72 * kk;
        uint32_t ca = sb + OFF_MISC + (uint32_t)offsetof(Misc, cand2), sa = ca + 512 + 4 * (kk & 7);
        gp = &S->h2c[seg];
        gdst = sb + OFF_H2S + kk * (ROWP * 2) + seg * 16;
        asm volatile("" : "+r"(sa), "+r"(gdst), "+l"(gp));
        mbar_wait(MB(MB_KEY), 0);
        if (warp < 16) {
            const uint4 o = lds128(ca + 16 * lane), a = lds128(ca + 32 * warp), c = lds128(ca + 32 * warp + 16);
            const uint32_t mx = max(o.x, o.z), hd[4] = {a.x, a.z, c.x, c.z}, sc[4] = {a.y, a.w, c.y, c.w};
            uint32_t n[4];
#pragma unroll
            for (int q = 0; q < 4; q++) n[q] = __popc(__ballot_sync(0xffffffffu, mx > hd[q]));
            auto rank = [&](uint32_t k) {
                return (__popc(__ballot_sync(0xffffffffu, o.x > k)) + __popc(__ballot_sync(0xffffffffu, o.y > k))) + (__popc(__ballot_sync(0xffffffffu, o.z > k)) + __popc(__ballot_sync(0xffffffffu, o.w > k)));
            };
#pragma unroll
            for (int q = 0; q < 4; q++) {
                if (n[q] < 8) {
                    const uint32_t r0 = rank(hd[q]), r1 = rank(sc[q]);
                    if (r0 < 8) sts32(ca + 512 + 4 * r0, hd[q]);
                    if (r1 < 8) sts32(ca + 512 + 4 * r1, sc[q]);
                }
            }
        }
        named_bar(13, 640);
        if (warp < 18) {
            const uint32_t key = lds32(sa);
            gp += (((~key >> 2) & 0x3Eu) | ((~key >> 5) & 0x40u) | (key & 1u)) * 72;
            gv = ld_rlx4(gp);
        } else if (warp == 18) named_arrive(14, 64);
        else named_arrive(8, 64);
    }
    uint32_t wda = sb + OFF_WD + fmt * 5120 + lr * 128 + (((2 * fsl + (lm & 1)) ^ lr) << 4), wda2 = wda + (lm >> 1) * 1024;
    uint32_t ha = sb + OFF_H2S + lr * (ROWP * 2) + (144 * fsl) * 2 + lm * 16, fo = sb + OFF_FFR + ((fsl * 80 + 16 * fmt + g) * 8 + 2 * t) * 4;
    asm volatile("" : "+r"(ha), "+r"(fo));
    mbar_wait(MB(MB_WD), 0);
#pragma unroll
    for (int i = 0; i < 2; i++)
#pragma unroll
        for (int ks = 0; ks < 3; ks++)
            if (i == 0 || warp < 16) ldsm_x4_t(wd[i][ks], ((ks < 2) ? wda2 : wda) + ks * 2048 + i * 5 * 5120);
#pragma unroll 1
    for (int it = 0; it < SPIN_MAX && gv.x == 0u; it++) gv = ld_rlx4(gp);
    if (warp < 18) asm volatile("st.shared.v4.u32 [%0], {%1,%2,%3,%4};" ::"r"(gdst), "r"(~gv.x), "r"(~gv.y), "r"(~gv.z), "r"(~gv.w) : "memory");
    CBAR();
    float* ffr = (float*)(sm + OFF_FFR);
    auto ffn1 = [&]() {
        float acc[2][4] = {{0.f, 0.f, 0.f, 0.f}, {0.f, 0.f, 0.f, 0.f}};
#pragma unroll
        for (int k2 = 0; k2 < 5; k2++) {
            uint32_t hb[4];
            if (k2 < 4) ldsm_x4(hb, ha + k2 * 64); else ldsm_x2(hb, ha + 256);
            mma_bf16(acc[0], wf[2 * k2][0], wf[2 * k2][1], wf[2 * k2][2], wf[2 * k2][3], hb[0], hb[1]);
            if (k2 < 4) mma_bf16(acc[1], wf[2 * k2 + 1][0], wf[2 * k2 + 1][1], wf[2 * k2 + 1][2], wf[2 * k2 + 1][3], hb[2], hb[3]);
        }
        asm volatile("st.shared.v2.f32 [%0], {%1,%2};" ::"r"(fo), "f"(acc[0][0] + acc[1][0]), "f"(acc[0][1] + acc[1][1]) : "memory");
        asm volatile("st.shared.v2.f32 [%0+256], {%1,%2};" ::"r"(fo), "f"(acc[0][2] + acc[1][2]), "f"(acc[0][3] + acc[1][3]) : "memory");
    };
    ffn1();
    bf16(*act)[56] = (bf16(*)[56])(sm + OFF_ACT);
    auto gate = [&]() {
        if (warp < 12) {
            const int f = 4 * warp + lm, a = lr;
            float v = 0.f;
            if (warp < 10) {
                const float* pg = ffr + 32 * warp + (warp < 8 ? 0 : 256) + lane;
                const float* pu = pg + (warp < 8 ? 256 : 64);
                float gg = bfr((pg[0] + pg[640]) + (pg[1280] + pg[1920]));
                gg = bfr(silu(gg));
                const float uu = bfr((pu[0] + pu[640]) + (pu[1280] + pu[1920]));
                v = gg * uu;
            }
            act[a][f] = __ushort_as_bfloat16((unsigned short)f2bits(v));
        }
    };
    CBAR();
    gate();
    CBAR();
    auto ffn2 = [&](uint32_t buf, int mb) {
        uint32_t bq[3][2];
#pragma unroll
        for (int ks = 0; ks < 3; ks++) {
            bq[ks][0] = *(const uint32_t*)&act[g][16 * ks + 2 * t];
            bq[ks][1] = *(const uint32_t*)&act[g][16 * ks + 2 * t + 8];
        }
#pragma unroll
        for (int i = 0; i < 2; i++) {
            if (i == 0 || warp < 16) {
                float acc[4] = {0.f, 0.f, 0.f, 0.f};
#pragma unroll
                for (int ks = 0; ks < 3; ks++) mma_bf16(acc, wd[i][ks][0], wd[i][ks][1], wd[i][ks][2], wd[i][ks][3], bq[ks][0], bq[ks][1]);
                const int d = i ? 4 + (warp >> 2) : (warp * 13) >> 6, slot = i ? (warp & 3) : warp - 5 * d;
                const uint32_t rb = mapa(sb, d);
                sta2(rb + buf + (rk * 5 + slot) * 640 + lm * 160 + lr * 8, movm(pack2(acc[0], acc[1])), movm(pack2(acc[2], acc[3])), rb + (MB(mb) - sb));
            }
        }
    };
    ffn2(OFF_RS, MB_RS);
    named_bar(12, 672);
    const uint32_t redo = M.fin[8];
    if (redo) {
        const int gi = fresh_tid(), kk = (gi * 911) >> 16, seg = gi - 72 * kk;
        if (warp < 8) {
            const uint32_t key = M.fin[warp];
            if (MINE(key) && lane < (cl < 14 ? 5 : 2)) {
                const uint4 a = lds128(sb + OFF_H2T + ROW(key) * 80 + 16 * lane);
                st_rlx4(&S->h2c[(128 + warp) * 72 + 5 * cl + lane], make_uint4(~a.x, ~a.y, ~a.z, ~a.w));
            }
            __syncwarp();
        }
        if (warp < 18) {
            uint4 gv = make_uint4(0, 0, 0, 0);
#pragma unroll 1
            for (int it = 0; it < SPIN_MAX && gv.x == 0u; it++) gv = ld_rlx4(&S->h2c[128 * 72 + gi]);
            *(uint4*)(sm + OFF_H2S + kk * (ROWP * 2) + seg * 16) = make_uint4(~gv.x, ~gv.y, ~gv.z, ~gv.w);
        }
        CBAR();
        ffn1();
        CBAR();
        gate();
        CBAR();
        ffn2(OFF_RS + 80, MB_RS2);
        mbar_wait(MB(MB_RS2), 0);
    }
    {
        const int lane = fresh_tid() & 31;
        const int fP = min(warp < 8 ? 20 * cl + lane : 8 * (rk < 4 ? 5 * rk : 4 * rk + 4) + 4 * (warp - 8) + (lane & 3), D_ / 2);
        const uint32_t fgb = ld_rlx(&S->gb[fP]);
        const int ftok = warp < 8 ? warp : lane >> 2;
        const uint32_t fkey = M.fin[ftok];
        const bool fon = warp < 8 ? (MINE(fkey) && lane < 20 && fP < D_ / 2) : warp < (rk < 4 ? 18 : 16)
            ;
        const float rs = __fdividef(1.0f, 1.0f + __expf(-hi2f(fkey ^ (((int)~fkey >> 31) | 0x80000000u))));
        const uint32_t hv = lds32(sb + OFF_H2S + ftok * (ROWP * 2) + 4 * fP);
        float s0 = 0.f, s1 = 0.f, s2 = 1.0f, s3 = 0.f;
        if (warp >= 8) {
            if (fon) {
                mbar_wait(MB(MB_RS), 0);
                const uint32_t p = sb + OFF_RS + redo * 80 + ((warp - 8) >> 1) * 640 + (lane >> 3) * 160 + (lane & 7) * 8 + 4 * (warp & 1);
                uint32_t v[8];
#pragma unroll
                for (int i = 0; i < 8; i++) v[i] = lds32(p + i * 3200);
                s0 = ((lo2f(v[0]) + lo2f(v[1])) + (lo2f(v[2]) + lo2f(v[3]))) + ((lo2f(v[4]) + lo2f(v[5])) + (lo2f(v[6]) + lo2f(v[7])));
                s1 = ((hi2f(v[0]) + hi2f(v[1])) + (hi2f(v[2]) + hi2f(v[3]))) + ((hi2f(v[4]) + hi2f(v[5])) + (hi2f(v[6]) + hi2f(v[7])));
            }
        } else if (fon) {
            const uint32_t row = ROW(fkey);
            const unsigned short* vp = (const unsigned short*)(sm + OFF_V + 2 * lane * VP) + row;
            const uint32_t xv = add2(lds32(sb + OFF_X + XI(row >> 5) + ((row >> 3) & 3) * XG + (row & 7) * 80 + 4 * lane), (uint32_t)vp[0] | ((uint32_t)vp[VP / 2] << 16));
            s2 = (float)(((xv & 0xFFFFu) << 5) | 1u); s3 = (float)(xv >> 16);
            mbar_wait(MB(MB_OUT), 0);
        }
        if (fon) {
            const float4 o = atom4(&S->acc3[(fP >> 2) * 32 + 4 * ftok + (fP & 3)], s0, s1, s2, s3);
            const uint32_t z = __float_as_uint((o.z + s2) + 8388608.f), zh = __float_as_uint((o.w + s3) + 8388608.f);
            if (z & 16u) {
                const uint32_t xv = __byte_perm(z >> 5, zh, 0x5410);
                *(uint32_t*)(out + ((~fkey >> 3) & 2047u) * D_ + 2 * fP) = add2(xv, mul2(fgb, add2(hv, mul2(pack2(o.x + s0, o.y + s1), pack2(rs, rs)))));
            }
        }
    }
    }
    }
}

typedef CUresult (*EncodeFn)(CUtensorMap*, CUtensorMapDataType, cuuint32_t, void*, const cuuint64_t*, const cuuint64_t*,
                             const cuuint32_t*, const cuuint32_t*, CUtensorMapInterleave, CUtensorMapSwizzle,
                             CUtensorMapL2promotion, CUtensorMapFloatOOBfill);

static void make_map(EncodeFn fn, CUtensorMap* m, const void* ptr, uint64_t cols, uint64_t rows, uint32_t bc, uint32_t br,
                     CUtensorMapSwizzle sw, int five) {
    cuuint64_t dims[5] = {cols, rows, 4, 4, 288};
    cuuint64_t strides[4] = {cols * 2 * (five ? 32 : 1), cols * 2 * 512, cols * 2 * 64, cols * 2};
    cuuint32_t box[5] = {bc, br, 4, 4, 8};
    cuuint32_t es[5] = {1, 1, 1, 1, 1};
    CUresult rc = fn(m, CU_TENSOR_MAP_DATA_TYPE_BFLOAT16, five ? 5 : 2, (void*)ptr, dims, strides, box, es, CU_TENSOR_MAP_INTERLEAVE_NONE,
                     sw, (CUtensorMapL2promotion)(five || sw ? 0 : br == 72 ? L2M : L2P), CU_TENSOR_MAP_FLOAT_OOB_FILL_NONE);
    (void)rc;
}

static void launch(void* const* d_in, const int* in_sizes, int n_in, void* d_out, int out_size) {
    static EncodeFn enc = nullptr;
    static CUtensorMap tmm, tmg, tmu, tmd, tmo;
    static Scratch* sp = nullptr;
    static const void* cached[6] = {nullptr, nullptr, nullptr, nullptr, nullptr, nullptr};
    if (!enc) {
        cudaDriverEntryPointQueryResult qr;
        void* fn = nullptr;
        cudaGetDriverEntryPoint("cuTensorMapEncodeTiled", &fn, cudaEnableDefault, &qr);
        enc = (EncodeFn)fn;
        cudaFuncSetAttribute(clus_kernel, cudaFuncAttributeMaxDynamicSharedMemorySize, SMEM_TOTAL);
        cudaGetSymbolAddress((void**)&sp, g_s);
    }
    if (cached[0] != d_in[13] || cached[1] != d_in[9] || cached[2] != d_in[10] || cached[3] != d_in[11] || cached[4] != d_in[0] || cached[5] != d_out) {
        make_map(enc, &tmo, d_out, D_, 2, 40, 2, CU_TENSOR_MAP_SWIZZLE_NONE, 1);
        make_map(enc, &tmm, d_in[13], 6 * D_, D_, 40, 72, CU_TENSOR_MAP_SWIZZLE_NONE, 0);
        make_map(enc, &tmg, d_in[9], F_, D_, 40, 192, CU_TENSOR_MAP_SWIZZLE_NONE, 0);
        make_map(enc, &tmu, d_in[10], F_, D_, 40, 192, CU_TENSOR_MAP_SWIZZLE_NONE, 0);
        make_map(enc, &tmd, d_in[11], D_, F_, 64, 40, CU_TENSOR_MAP_SWIZZLE_128B, 0);
        cached[0] = d_in[13]; cached[1] = d_in[9]; cached[2] = d_in[10]; cached[3] = d_in[11]; cached[4] = d_in[0]; cached[5] = d_out;
    }
    clus_kernel<<<G_, NTHR, SMEM_TOTAL>>>((const bf16*)d_in[0], (const bf16*)d_in[1], (const bf16*)d_in[2], (const bf16*)d_in[3], (const bf16*)d_in[4],
                                          (const bf16*)d_in[5], (const bf16*)d_in[12], sp, (const bf16*)d_in[6], (const bf16*)d_in[8], (const bf16*)d_in[13],
                                          (bf16*)d_out, tmm, tmg, tmu, tmd, tmo);
}

static bool fits() {
    cudaFuncSetAttribute(clus_kernel, cudaFuncAttributeMaxDynamicSharedMemorySize, SMEM_TOTAL);
    cudaLaunchConfig_t cfg = {};
    cudaLaunchAttribute at;
    at.id = cudaLaunchAttributeClusterDimension;
    at.val.clusterDim.x = 8; at.val.clusterDim.y = 1; at.val.clusterDim.z = 1;
    cfg.gridDim = dim3(G_); cfg.blockDim = dim3(NTHR); cfg.dynamicSmemBytes = SMEM_TOTAL; cfg.attrs = &at; cfg.numAttrs = 1;
    int n = 0;
    const bool ok = cudaOccupancyMaxActiveClusters(&n, clus_kernel, &cfg) == cudaSuccess && n >= NCL;
    cudaGetLastError();
    return ok;
}
}
#undef L_
#undef D_
#undef N_
#undef F_
#undef G_
#undef NCL
#undef NTHR
#undef SPIN_MAX
#undef OFF_WG
#undef OFF_WU
#undef KSCR
#undef OFF_WM0
#undef OFF_STG
#undef OFF_MG2
#undef OFF_CH
#undef CHS
#undef UP
#undef UB
#undef XO_TF
#undef XO_U8
#undef XO_U16
#undef XO_ZA
#undef XO_ZB
#undef XO_ZC
#undef XO_ZD
#undef XO_TD
#undef XO_K1024
#undef XO_DSK
#undef XO_KINV
#undef XO_KLAST
#undef XO_MBU
#undef OFF_X
#undef XG
#undef XI
#undef XN
#undef OFF_V
#undef VP
#undef OFF_EK
#undef OFF_WM2
#undef OFF_MG1
#undef OFF_SC
#undef OFF_C1
#undef OFF_MISC
#undef OFF_WD
#undef OFF_H2T
#undef OFF_OUT
#undef ROWP
#undef OFF_H2S
#undef OFF_FFR
#undef OFF_ACT
#undef OFF_RS
#undef SMEM_TOTAL
#undef CBAR
#undef PROXY_FENCE
#undef D4
#undef O4
#undef WG_FENCE
#undef WG_COMMIT
#undef WG_WAIT
#undef TQ
#undef MB
#undef DS
#undef L2P
#undef L2M
#undef PFC
#undef PFW
#undef PD0
#undef PD1
#undef PDE
#undef WMD
#undef PU
#undef PD
#undef PFG
#undef CWP
#undef CWD
#undef ROW
#undef RKT
#undef MINE
#undef CE
#undef POP
#undef CGT
#undef CL_ARRIVE
#undef CL_WAIT
#undef CJ
#undef CJP

namespace v4 {

#define L_ 2048
#define D_ 576
#define N_ 128
#define F_ 4608
#define G_ 128
#define NTHR 640
#define SPIN_MAX (1 << 18)
#define SENT 0u
#define HINT_N 182u

typedef __nv_bfloat16 bf16;

struct Scratch {
    uint4 xn[G_ * G_ * 10];
    uint4 v[G_ * D_ * 2];
    uint2 part[G_ * G_ * 9];
    uint4 h2w[L_ * 96];
    unsigned int rec[G_ * 8];
    unsigned int modw[6 * D_];
    unsigned int ticket[64];
    unsigned int cnt[64];
    unsigned int hint[64];
};
__device__ __align__(1024) Scratch g_s;

#define OFF_WG 0
#define OFF_WU 46080
#define OFF_CH 92160
#define CHS 20784
#define ULBO 656
#define XO_U8 6272
#define XO_U16 10368
#define XO_ZA 5248
#define XO_ZB 8448
#define XO_ZC 11648
#define XO_ZD 13824
#define XO_TD 16000
#define XO_TF 18624
#define XO_K1024 20672
#define KSCR 3456
#define OFF_TILE 196096
#define ROWP 584
#define OFF_MISC 214784
#define OFF_WD OFF_CH
#define OFF_H2T (OFF_CH + 3 * CHS)
#define OFF_H2S (OFF_H2T + 18688)
#define OFF_FFR (OFF_H2S + 9344)
#define OFF_FIN OFF_FFR
#define OFF_ACT (OFF_FFR + 10240)

struct Misc {
    __align__(16) uint4 sent[256];
    __align__(16) uint4 box[11 * 14];
    union {
        struct {
            __align__(16) float2 part[18][16];
            float rp[18][16];
        };
        struct {
            __align__(16) unsigned short st1[3][16];
            __align__(16) float p1[16][4], p2[16][4];
        };
    };
    __align__(16) bf16 cb1[D_], sb[D_], gb[D_];
    __align__(16) bf16 sc[D_];
    __align__(16) unsigned int cand[64], skey[16];
    __align__(16) float kinv[5][4], klast[5][4];
    unsigned int pk[4][8];
    __align__(16) uint4 st2[16];
    unsigned int wr[D_ / 2];
    float modx[32];
    unsigned int rank[16];
    volatile unsigned int flag;
    unsigned int e1cnt;
    unsigned long long mbar[5];
    unsigned int epoch;
};
#define SMEM_TOTAL (OFF_MISC + (int)sizeof(Misc))
static_assert(SMEM_TOTAL <= 232448, "smem");

__device__ __forceinline__ float lo2f(uint32_t w) { return __uint_as_float(w << 16); }
__device__ __forceinline__ float hi2f(uint32_t w) { return __uint_as_float(w & 0xFFFF0000u); }
__device__ __forceinline__ uint32_t pack2(float lo, float hi) { uint32_t r; asm("cvt.rn.bf16x2.f32 %0, %1, %2;" : "=r"(r) : "f"(hi), "f"(lo)); return r; }
__device__ __forceinline__ float bfr(float x) { return __uint_as_float(pack2(0.f, x)); }
__device__ __forceinline__ uint32_t f2bits(float x) { return pack2(x, 0.f); }
__device__ __forceinline__ uint32_t packh(float lo, float hi) { uint32_t r; asm("cvt.rn.f16x2.f32 %0, %1, %2;" : "=r"(r) : "f"(hi), "f"(lo)); return r; }
__device__ __forceinline__ float frcp(float x) { float r; asm("rcp.approx.ftz.f32 %0, %1;" : "=f"(r) : "f"(x)); return r; }
__device__ __forceinline__ float fsqrt(float x) { float r; asm("sqrt.approx.f32 %0, %1;" : "=f"(r) : "f"(x)); return r; }
__device__ __forceinline__ float fex2(float x) { float r; asm("ex2.approx.ftz.f32 %0, %1;" : "=f"(r) : "f"(x)); return r; }
__device__ __forceinline__ float silu(float x) { return __fdividef(x, 1.0f + __expf(-x)); }
__device__ __forceinline__ uint32_t add2(uint32_t a, uint32_t b) { uint32_t r; asm("add.rn.bf16x2 %0, %1, %2;" : "=r"(r) : "r"(a), "r"(b)); return r; }
__device__ __forceinline__ uint32_t sub2(uint32_t a, uint32_t b) { uint32_t r; asm("sub.rn.bf16x2 %0, %1, %2;" : "=r"(r) : "r"(a), "r"(b)); return r; }
__device__ __forceinline__ uint32_t mul2(uint32_t a, uint32_t b) { uint32_t r; asm("mul.rn.bf16x2 %0, %1, %2;" : "=r"(r) : "r"(a), "r"(b)); return r; }
__device__ __forceinline__ uint32_t fma2(uint32_t a, uint32_t b, uint32_t c) { uint32_t r; asm("fma.rn.bf16x2 %0, %1, %2, %3;" : "=r"(r) : "r"(a), "r"(b), "r"(c)); return r; }
__device__ __forceinline__ uint32_t norm2(uint32_t x, uint32_t m, uint32_t rh, uint32_t rl) { const uint32_t d = sub2(x, m); return fma2(d, rh, mul2(d, rl)); }

__device__ __forceinline__ void mma_bf16(float* c, uint32_t a0, uint32_t a1, uint32_t a2, uint32_t a3, uint32_t b0, uint32_t b1) {
    asm volatile("mma.sync.aligned.m16n8k16.row.col.f32.bf16.bf16.f32 {%0,%1,%2,%3}, {%4,%5,%6,%7}, {%8,%9}, {%0,%1,%2,%3};\n"
                 : "+f"(c[0]), "+f"(c[1]), "+f"(c[2]), "+f"(c[3]) : "r"(a0), "r"(a1), "r"(a2), "r"(a3), "r"(b0), "r"(b1));
}
__device__ __forceinline__ void mma_f16(float* c, const uint32_t* a, uint32_t b0, uint32_t b1) {
    asm volatile("mma.sync.aligned.m16n8k16.row.col.f32.f16.f16.f32 {%0,%1,%2,%3}, {%4,%5,%6,%7}, {%8,%9}, {%0,%1,%2,%3};\n"
                 : "+f"(c[0]), "+f"(c[1]), "+f"(c[2]), "+f"(c[3]) : "r"(a[0]), "r"(a[1]), "r"(a[2]), "r"(a[3]), "r"(b0), "r"(b1));
}
__device__ __forceinline__ void ldsm_x4(uint32_t* r, uint32_t addr) {
    asm volatile("ldmatrix.sync.aligned.m8n8.x4.shared.b16 {%0,%1,%2,%3}, [%4];" : "=r"(r[0]), "=r"(r[1]), "=r"(r[2]), "=r"(r[3]) : "r"(addr) : "memory");
}
__device__ __forceinline__ void ldsm_x4_t(uint32_t* r, uint32_t addr) {
    asm volatile("ldmatrix.sync.aligned.m8n8.x4.trans.shared.b16 {%0,%1,%2,%3}, [%4];" : "=r"(r[0]), "=r"(r[1]), "=r"(r[2]), "=r"(r[3]) : "r"(addr) : "memory");
}
__device__ __forceinline__ void stsm_x4(uint32_t addr, uint32_t r0, uint32_t r1, uint32_t r2, uint32_t r3) {
    asm volatile("stmatrix.sync.aligned.m8n8.x4.shared.b16 [%0], {%1,%2,%3,%4};" ::"r"(addr), "r"(r0), "r"(r1), "r"(r2), "r"(r3) : "memory");
}
__device__ __forceinline__ void stsm_x4_t(uint32_t addr, uint32_t r0, uint32_t r1, uint32_t r2, uint32_t r3) {
    asm volatile("stmatrix.sync.aligned.m8n8.x4.trans.shared.b16 [%0], {%1,%2,%3,%4};" ::"r"(addr), "r"(r0), "r"(r1), "r"(r2), "r"(r3) : "memory");
}
__device__ __forceinline__ uint32_t movm(uint32_t a) { uint32_t r; asm volatile("movmatrix.sync.aligned.m8n8.trans.b16 %0, %1;" : "=r"(r) : "r"(a)); return r; }
__device__ __forceinline__ uint32_t lds32(uint32_t a) { uint32_t v; asm volatile("ld.shared.u32 %0, [%1];" : "=r"(v) : "r"(a)); return v; }
__device__ __forceinline__ void sts32(uint32_t a, uint32_t v) { asm volatile("st.shared.u32 [%0], %1;" ::"r"(a), "r"(v) : "memory"); }
__device__ __forceinline__ void sts16(uint32_t a, uint32_t v) { asm volatile("st.shared.u16 [%0], %1;" ::"r"(a), "h"((unsigned short)v) : "memory"); }
__device__ __forceinline__ void named_bar(int id, int n) { asm volatile("bar.sync %0, %1;" ::"r"(id), "r"(n) : "memory"); }
__device__ __forceinline__ void named_arrive(int id, int n) { asm volatile("bar.arrive %0, %1;" ::"r"(id), "r"(n) : "memory"); }
#define CBAR() asm volatile("bar.sync 0, 640;" ::: "memory")
#define PROXY_FENCE() asm volatile("fence.proxy.async.shared::cta;" ::: "memory")

#define D4(d, o) "+f"(d[o]), "+f"(d[o + 1]), "+f"(d[o + 2]), "+f"(d[o + 3])
__device__ __forceinline__ void wg32(float* d, uint32_t a0, uint32_t a1, uint32_t a2, uint32_t a3, uint64_t desc) {
    asm volatile("wgmma.mma_async.sync.aligned.m64n32k16.f32.bf16.bf16 {%0,%1,%2,%3,%4,%5,%6,%7,%8,%9,%10,%11,%12,%13,%14,%15}, {%16,%17,%18,%19}, %20, 1, 1, 1, 0;"
                 : D4(d, 0), D4(d, 4), D4(d, 8), D4(d, 12) : "r"(a0), "r"(a1), "r"(a2), "r"(a3), "l"(desc));
}
__device__ __forceinline__ void wg48(float* d, uint32_t a0, uint32_t a1, uint32_t a2, uint32_t a3, uint64_t desc) {
    asm volatile("wgmma.mma_async.sync.aligned.m64n48k16.f32.bf16.bf16 {%0,%1,%2,%3,%4,%5,%6,%7,%8,%9,%10,%11,%12,%13,%14,%15,%16,%17,%18,%19,%20,%21,%22,%23}, {%24,%25,%26,%27}, %28, 1, 1, 1, 0;"
                 : D4(d, 0), D4(d, 4), D4(d, 8), D4(d, 12), D4(d, 16), D4(d, 20) : "r"(a0), "r"(a1), "r"(a2), "r"(a3), "l"(desc));
}
#define O4(d, o) "=f"(d[o]), "=f"(d[o + 1]), "=f"(d[o + 2]), "=f"(d[o + 3])
__device__ __forceinline__ void wg32z(float* d, uint32_t a0, uint32_t a1, uint32_t a2, uint32_t a3, uint64_t desc) {
    asm volatile("wgmma.mma_async.sync.aligned.m64n32k16.f32.bf16.bf16 {%0,%1,%2,%3,%4,%5,%6,%7,%8,%9,%10,%11,%12,%13,%14,%15}, {%16,%17,%18,%19}, %20, 0, 1, 1, 0;"
                 : O4(d, 0), O4(d, 4), O4(d, 8), O4(d, 12) : "r"(a0), "r"(a1), "r"(a2), "r"(a3), "l"(desc));
}
__device__ __forceinline__ void wg48z(float* d, uint32_t a0, uint32_t a1, uint32_t a2, uint32_t a3, uint64_t desc) {
    asm volatile("wgmma.mma_async.sync.aligned.m64n48k16.f32.bf16.bf16 {%0,%1,%2,%3,%4,%5,%6,%7,%8,%9,%10,%11,%12,%13,%14,%15,%16,%17,%18,%19,%20,%21,%22,%23}, {%24,%25,%26,%27}, %28, 0, 1, 1, 0;"
                 : O4(d, 0), O4(d, 4), O4(d, 8), O4(d, 12), O4(d, 16), O4(d, 20) : "r"(a0), "r"(a1), "r"(a2), "r"(a3), "l"(desc));
}
#define WG_FENCE() asm volatile("wgmma.fence.sync.aligned;" ::: "memory")
#define WG_COMMIT() asm volatile("wgmma.commit_group.sync.aligned;" ::: "memory")
#define WG_WAIT(n) asm volatile("wgmma.wait_group.sync.aligned " #n ";" ::: "memory")
#define TQ(p, k) p[2 * (k) + 1], p[2 * (k) + 2], p[2 * (k)], p[2 * (k) + 1]

__device__ __forceinline__ uint4 ld_nc4(const void* p) { uint4 v; asm volatile("ld.global.nc.v4.u32 {%0,%1,%2,%3}, [%4];" : "=r"(v.x), "=r"(v.y), "=r"(v.z), "=r"(v.w) : "l"(p)); return v; }
__device__ __forceinline__ unsigned short ld_nc16(const void* p) { unsigned short v; asm volatile("ld.global.nc.u16 %0, [%1];" : "=h"(v) : "l"(p)); return v; }
__device__ __forceinline__ uint32_t ld_nc(const void* p) { uint32_t v; asm volatile("ld.global.nc.u32 %0, [%1];" : "=r"(v) : "l"(p)); return v; }
__device__ __forceinline__ uint32_t ld_rlx(const unsigned int* p) { uint32_t v; asm volatile("ld.relaxed.gpu.global.u32 %0, [%1];" : "=r"(v) : "l"(p) : "memory"); return v; }
__device__ __forceinline__ uint2 ld_rlx2(const void* p) { uint2 v; asm volatile("ld.relaxed.gpu.global.v2.u32 {%0,%1}, [%2];" : "=r"(v.x), "=r"(v.y) : "l"(p) : "memory"); return v; }
__device__ __forceinline__ uint4 ld_rlx4(const void* p) { uint4 v; asm volatile("ld.relaxed.gpu.global.v4.u32 {%0,%1,%2,%3}, [%4];" : "=r"(v.x), "=r"(v.y), "=r"(v.z), "=r"(v.w) : "l"(p) : "memory"); return v; }
__device__ __forceinline__ void st_rlx(unsigned int* p, uint32_t v) { asm volatile("st.relaxed.gpu.global.u32 [%0], %1;" ::"l"(p), "r"(v) : "memory"); }
__device__ __forceinline__ void st_rlx2(void* p, uint32_t a, uint32_t b) { asm volatile("st.relaxed.gpu.global.v2.u32 [%0], {%1,%2};" ::"l"(p), "r"(a), "r"(b) : "memory"); }
__device__ __forceinline__ void st_rlx4(void* p, uint4 v) { asm volatile("st.relaxed.gpu.global.v4.u32 [%0], {%1,%2,%3,%4};" ::"l"(p), "r"(v.x), "r"(v.y), "r"(v.z), "r"(v.w) : "memory"); }
__device__ __forceinline__ void red_inc(unsigned int* p) { asm volatile("red.relaxed.gpu.global.add.u32 [%0], 1;" ::"l"(p) : "memory"); }

__device__ __forceinline__ void mbar_init(uint32_t a, int cnt) { asm volatile("mbarrier.init.shared::cta.b64 [%0], %1;" ::"r"(a), "r"(cnt) : "memory"); }
__device__ __forceinline__ void mbar_expect(uint32_t a, uint32_t bytes) { asm volatile("mbarrier.arrive.expect_tx.shared::cta.b64 _, [%0], %1;" ::"r"(a), "r"(bytes) : "memory"); }
__device__ __forceinline__ void mbar_wait(uint32_t a, uint32_t parity) {
    uint32_t ok = 0;
    int it = 0;
    do {
        asm volatile("{\n.reg .pred p;\nmbarrier.try_wait.parity.shared::cta.b64 p, [%1], %2;\nselp.u32 %0, 1, 0, p;\n}" : "=r"(ok) : "r"(a), "r"(parity) : "memory");
    } while (!ok && ++it < SPIN_MAX);
}
__device__ __forceinline__ void tma2d(uint32_t dst, const CUtensorMap* tm, int c0, int c1, uint32_t mbar) {
    asm volatile("cp.async.bulk.tensor.2d.shared::cluster.global.mbarrier::complete_tx::bytes [%0], [%1, {%3, %4}], [%2];"
                 ::"r"(dst), "l"(tm), "r"(mbar), "r"(c0), "r"(c1) : "memory");
}
__device__ __forceinline__ void bulk_s2g(void* dst, uint32_t src, uint32_t bytes) {
    asm volatile("cp.async.bulk.global.shared::cta.bulk_group [%0], [%1], %2;" ::"l"(dst), "r"(src), "r"(bytes) : "memory");
}
__device__ __forceinline__ uint32_t ld_acq(const unsigned int* p) { uint32_t v; asm volatile("ld.acquire.gpu.global.u32 %0, [%1];" : "=r"(v) : "l"(p) : "memory"); return v; }
__device__ __forceinline__ void bulk_pf(const void* src, uint32_t bytes) { asm volatile("cp.async.bulk.prefetch.L2.global [%0], %1;" ::"l"(src), "r"(bytes) : "memory"); }

__device__ __forceinline__ uint32_t wait_epoch(Misc& M) {
    uint32_t e = 0;
#pragma unroll 1
    for (int it = 0; it < (SPIN_MAX << 4) && e == 0; it++) e = *(volatile unsigned int*)&M.epoch;
    return e;
}
__device__ __forceinline__ void wait_reset(const unsigned int* ctr, uint32_t epoch) {
#pragma unroll 1
    for (int it = 0; it < SPIN_MAX; it++)
        if ((int)(ld_acq(ctr) - G_ * epoch) >= 0) break;
}
struct cplx { float x, y; };
__device__ __forceinline__ cplx cmul(cplx a, cplx b) { cplx r; r.x = a.x * b.x - a.y * b.y; r.y = a.x * b.y + a.y * b.x; return r; }
__device__ __forceinline__ cplx csq(cplx a) { cplx r; r.x = a.x * a.x - a.y * a.y; r.y = 2.0f * a.x * a.y; return r; }
__device__ __forceinline__ uint32_t hcm(uint32_t x, uint32_t y, uint32_t yp) {
    const __half2 X = *(const __half2*)&x, Y = *(const __half2*)&y, YP = *(const __half2*)&yp;
    const __half2 r = __hfma2(__high2half2(X), YP, __hmul2(__low2half2(X), Y));
    return *(const uint32_t*)&r;
}
__device__ __forceinline__ void ln_stats(float s1, float s2, float& meanb, float& rinv) {
    const float mean = s1 * (1.0f / D_);
    const float den = bfr(fsqrt(bfr(bfr(fmaxf(fmaf(-mean, mean, s2 * (1.0f / D_)), 0.f)) + 1e-5f)));
    meanb = bfr(mean);
    rinv = frcp(den);
}

__device__ __forceinline__ int fresh_tid() { int v; asm volatile("mov.u32 %0, %tid.x;" : "=r"(v)); return v; }
__device__ __forceinline__ void conv_channel(unsigned char* sm, Scratch* S, uint32_t gidx, uint32_t epoch, const void* pf_src,
                                             const CUtensorMap* tmu, int f0) {
    Misc& M = *(Misc*)(sm + OFF_MISC);
    const uint32_t sb = (uint32_t)__cvta_generic_to_shared(sm);
    const int tid = fresh_tid(), lane = tid & 31, g = lane >> 2, t = lane & 3, lr = lane & 7, lm = lane >> 3;
    const int warp_ = __shfl_sync(0xffffffffu, tid >> 5, 0), wgi = warp_ >> 2, w = warp_ & 3;
    const uint32_t cb = sb + OFF_CH + wgi * CHS, tag16 = (epoch % 65535u) + 1u;
    float D[16];
    uint32_t gaw, rcnt = 0;
    {
        {
            const uint32_t a8 = cb + lr * ULBO + (lm + 9) * 16 + w * 64, b8 = cb + XO_U8 + lm * 128 + lr * 16 + w * 512;
            const uint32_t a16 = cb + (((2 * lr) & 7) + (lm & 1)) * ULBO + (9 + (lr >> 2) + (lm & 2)) * 16 + w * 64;
            const uint32_t b16 = cb + XO_U16 + (lm & 1) * 512 + lr * 16 + (lm >> 1) * 128 + (w >> 1) * 1024 + (w & 1) * 256;
            uint32_t r[3][4];
            ldsm_x4_t(r[0], a8);
            ldsm_x4_t(r[1], a16);
            if (w < 2) ldsm_x4_t(r[2], a8 + 256);
            stsm_x4(b8, r[0][0], r[0][1], r[0][2], r[0][3]);
            stsm_x4(b16, r[1][0], r[1][1], r[1][2], r[1][3]);
            if (w < 2) stsm_x4(b8 + 2048, r[2][0], r[2][1], r[2][2], r[2][3]);
        }
        PROXY_FENCE();
        named_bar(1 + wgi, 128);
        {
            float Z8[24], Z16[16];
            const uint32_t pf = cb + XO_TF + (w >> 1) * 512 + (8 + 16 * (w & 1) + g - 2 * t) * 4;
            uint32_t p[13], q[9], z16[8];
#pragma unroll
            for (int s = 0; s < 9; s++) q[s] = lds32(pf + 1024 + s * 32);
            const uint32_t d8 = ((((cb + XO_U8) & 0x3FFFF) >> 4) | ((128 >> 4) << 16));
#define DZ(o) (((uint64_t)(512 >> 4) << 32) | (uint64_t)(d8 + (o)))
            WG_FENCE();
#pragma unroll
            for (int e = 0; e < 4; e++) {
                if (e == 0) wg32z(Z16, TQ(q, e), DZ(256 + 16));
                else wg32(Z16, TQ(q, e), DZ(256 - (e >> 1) * 64 + (1 - (e & 1)) * 16));
            }
            WG_COMMIT();
#pragma unroll
            for (int s = 0; s < 13; s++) p[s] = lds32(pf + s * 32);
            WG_WAIT(0);
#pragma unroll
            for (int i = 0; i < 8; i++) z16[i] = pack2(Z16[2 * i], Z16[2 * i + 1]);
            WG_FENCE();
#pragma unroll
            for (int e = 0; e < 6; e++) {
                if (e == 0) wg48z(Z8, TQ(p, e), DZ(16));
                else wg48(Z8, TQ(p, e), DZ(-(e >> 1) * 32 + (1 - (e & 1)) * 16));
            }
            WG_COMMIT();
            WG_WAIT(0);
            named_bar(1 + wgi, 128);
            const uint32_t za = cb + ((w >> 1) ? XO_ZB : XO_ZA) + lr * 400 + (1 + 2 * (w & 1) + (lm & 1) + 4 * (lm >> 1)) * 16;
#pragma unroll
            for (int i = 0; i < 3; i++)
                stsm_x4(za + i * 128, pack2(Z8[8 * i], Z8[8 * i + 1]), pack2(Z8[8 * i + 2], Z8[8 * i + 3]), pack2(Z8[8 * i + 4], Z8[8 * i + 5]), pack2(Z8[8 * i + 6], Z8[8 * i + 7]));
            const int Cz = 2 * (16 * (w & 1) + 8 * (lm & 1) + lr) + (lm >> 1);
            const uint32_t zc = cb + ((w >> 1) ? XO_ZD : XO_ZC) + (Cz & 7) * 272 + (1 + (Cz >> 3)) * 16;
#pragma unroll
            for (int ob = 0; ob < 2; ob++) stsm_x4(zc + ob * 128, z16[4 * ob], z16[4 * ob + 1], z16[4 * ob + 2], z16[4 * ob + 3]);
            if (lane < 8) *(uint4*)(sm + (cb - sb) + ((w < 2) ? (XO_ZA + w * 3200 + lane * 400) : (XO_ZC + (w - 2) * 2176 + lane * 272))) = make_uint4(0, 0, 0, 0);
        }
        gaw = ld_rlx(&S->modw[gidx]);
        if (tmu && wgi >= 2 && (tid & 127) == 96) {
            const uint32_t mbu = sb + OFF_MISC + (uint32_t)offsetof(Misc, mbar) + 24;
            if (wgi == 2) mbar_expect(mbu, 36864);
            tma2d(sb + OFF_WU + (wgi - 2) * 12288, tmu, f0, 192 * (wgi - 2), mbu);
        }
        __syncwarp();
        if ((tid & 127) == 64) rcnt = ld_rlx(S->cnt);
        {
#pragma unroll
            for (int i = 0; i < 16; i++) D[i] = 0.f;
            uint32_t pa = cb + XO_TD + (8 + 16 * w + g - 2 * t) * 4;
            uint32_t dlo = (((cb + 9 * 16) & 0x3FFFF) >> 4) | ((ULBO >> 4) << 16);
#define DS(o) (((uint64_t)(128 >> 4) << 32) | (uint64_t)(dlo + (o)))
#define KST (2 * (ULBO / 16))
            uint32_t pA[9], pB[9];
#pragma unroll
            for (int s = 0; s < 9; s++) pA[s] = lds32(pa + s * 32);
#pragma unroll 1
            for (int j = 0; j < 4; j++) {
                WG_FENCE();
#pragma unroll
                for (int q = 0; q < 4; q++) wg32(D, TQ(pA, q), DS((3 - q) * KST));
                WG_COMMIT();
                WG_WAIT(1);
#pragma unroll
                for (int s = 0; s < 9; s++) pB[s] = lds32(pa + 256 + s * 32);
                WG_FENCE();
#pragma unroll
                for (int q = 0; q < 4; q++) wg32(D, TQ(pB, q), DS((3 - q) * KST - 1));
                WG_COMMIT();
                WG_WAIT(1);
#pragma unroll
                for (int s = 0; s < 9; s++) pA[s] = lds32(pa + 512 + s * 32);
                dlo -= 2; pa += 512;
            }
            pB[1] = lds32(pa + 256 + 32); pB[2] = lds32(pa + 256 + 64);
            WG_FENCE();
#pragma unroll
            for (int q = 0; q < 4; q++) wg32(D, TQ(pA, q), DS((3 - q) * KST));
            wg32(D, pB[1], pB[2], pA[8], pB[1], DS(3 * KST - 1));
            WG_COMMIT();
        }
        if (tid == 128) bulk_pf(pf_src, 16 * D_ * 2);
        if ((tid & 127) == 64) {
#pragma unroll 1
            for (int it = 0; it < SPIN_MAX && (int)(rcnt - G_ * epoch) < 0; it++) rcnt = ld_rlx(S->cnt);
        }
    }
    {
        named_bar(1 + wgi, 128);
        {
            const uint4* pq = M.box + (6 + g - 2 * t);
#define QM(q) (q).x, (q).y, (q).z, (q).w
            uint32_t bA[2][6], bB[2][6], bC[3][4], bD[2][4], bU[2][4];
            const uint32_t k2 = lds32(cb + XO_K1024);
            uint32_t ofs[3];
#pragma unroll
            for (int d = 0; d < 3; d++) ofs[d] = cb + ((w - d) < 0 ? 0 : 16) + (lr + 8 * (lm >> 1)) * 16;
#define COL(d) (2 * ((w - (d)) & 3) + (lm & 1))
            WG_WAIT(0);
            uint4 m[4];
#pragma unroll
            for (int d = 0; d < 2; d++) {
                const uint32_t a = XO_ZA + COL(d) * 400 + ofs[d];
                ldsm_x4(bA[d], a); ldsm_x4(bB[d], a + 3200);
                uint32_t r[4];
                ldsm_x4(r, a + 256 + (lm >> 1) * (3200 - 128));
                bA[d][4] = r[0]; bA[d][5] = r[1]; bB[d][4] = r[2]; bB[d][5] = r[3];
            }
#pragma unroll
            for (int i = 0; i < 4; i++) m[i] = pq[14 * i];
#pragma unroll
            for (int d = 0; d < 2; d++)
#pragma unroll
                for (int c = 0; c < 3; c++) mma_bf16(D + 4 + 4 * c, QM(m[d]), bA[d][2 * c], bA[d][2 * c + 1]);
#pragma unroll
            for (int d = 0; d < 3; d++) ldsm_x4(bC[d], XO_ZC + COL(d) * 272 + ofs[d]);
#pragma unroll
            for (int d = 0; d < 2; d++)
#pragma unroll
                for (int c = 0; c < 3; c++) mma_bf16(D + 4 + 4 * c, QM(m[2 + d]), bB[d][2 * c], bB[d][2 * c + 1]);
#pragma unroll
            for (int i = 0; i < 3; i++) m[i] = pq[14 * (4 + i)];
#pragma unroll
            for (int d = 0; d < 2; d++) { ldsm_x4(bD[d], XO_ZD + COL(d) * 272 + ofs[d]); ldsm_x4(bU[d], COL(d) * ULBO + 128 + ofs[d]); }
#pragma unroll
            for (int d = 0; d < 3; d++)
#pragma unroll
                for (int c = 0; c < 2; c++) mma_bf16(D + 8 + 4 * c, QM(m[d]), bC[d][2 * c], bC[d][2 * c + 1]);
#pragma unroll
            for (int i = 0; i < 4; i++) m[i] = pq[14 * (7 + i)];
#pragma unroll
            for (int d = 0; d < 2; d++)
#pragma unroll
                for (int c = 0; c < 2; c++) mma_bf16(D + 8 + 4 * c, QM(m[d]), bD[d][2 * c], bD[d][2 * c + 1]);
#pragma unroll
            for (int d = 0; d < 2; d++) {
                m[2 + d].x &= k2; m[2 + d].y &= k2; m[2 + d].z &= k2; m[2 + d].w &= k2;
#pragma unroll
                for (int c = 0; c < 2; c++) mma_bf16(D + 8 + 4 * c, QM(m[2 + d]), bU[d][2 * c], bU[d][2 * c + 1]);
            }
        }
        {
#pragma unroll 1
            for (int it = 0; it < SPIN_MAX && (gaw >> 16) != tag16; it++) gaw = ld_rlx(&S->modw[gidx]);
            const uint32_t ga2 = __byte_perm(gaw, 0, 0x1010), dk2 = M.pk[3][wgi];
            const uint32_t ua = cb + (2 * w + (lm & 1)) * ULBO + (9 + lr + 8 * (lm >> 1)) * 16;
            const uint32_t ya = cb + XO_TD + w * 1024;
            const uint32_t sa = ya + (lr + 8 * (lm >> 1)) * 32 + (((lm & 1) ^ ((lane >> 2) & 1)) << 4);
#pragma unroll
            for (int cc = 0; cc < 2; cc++) {
                uint32_t u[4], v[4];
                ldsm_x4_t(u, ua + cc * 256);
#pragma unroll
                for (int m = 0; m < 4; m++) {
                    const int c = 2 * cc + (m >> 1), h = m & 1;
                    v[m] = ~mul2(ga2, add2(pack2(D[4 * c + 2 * h], D[4 * c + 2 * h + 1]), mul2(u[m], dk2)));
                }
                stsm_x4_t(sa + cc * 512, v[0], v[1], v[2], v[3]);
            }
            __syncwarp();
            const int sw = (lane >> 3) & 1;
            const uint32_t vo = (uint32_t)(((4 * (lane >> 1) + w) * D_ + gidx - 2 * D_) * 32 + (lane & 1) * 16);
            const unsigned char* yp = sm + (ya - sb) + (lane >> 1) * 32 + (lane & 1) * 8;
#pragma unroll
            for (int i = 0; i < 2; i++) {
                const uint2 A = *(const uint2*)(yp + i * 512 + (sw << 4)), B = *(const uint2*)(yp + i * 512 + ((sw ^ 1) << 4));
                st_rlx4((char*)S->v + vo + i * (64 * D_ * 32), make_uint4(A.x, B.x, A.y, B.y));
            }
        }
    }
}

__global__ void __launch_bounds__(NTHR, 1)
mega_kernel(const bf16* __restrict__ x, const bf16* __restrict__ logAr, const bf16* __restrict__ Aim,
            const bf16* __restrict__ Cr, const bf16* __restrict__ Ci, const bf16* __restrict__ logdt, const bf16* __restrict__ c_in,
            Scratch* __restrict__ S, const bf16* __restrict__ Dskip, const bf16* __restrict__ w_r, const bf16* __restrict__ w_down,
            bf16* __restrict__ out,
            const __grid_constant__ CUtensorMap tm_wm, const __grid_constant__ CUtensorMap tm_wg, const __grid_constant__ CUtensorMap tm_wu,
            const __grid_constant__ CUtensorMap tm_wd, const __grid_constant__ CUtensorMap tm_wd32,
            const __grid_constant__ CUtensorMap tm_wg32, const __grid_constant__ CUtensorMap tm_wu32) {
    extern __shared__ __align__(1024) unsigned char sm[];
    Misc& M = *(Misc*)(sm + OFF_MISC);
    const uint32_t sb = (uint32_t)__cvta_generic_to_shared(sm);
    const int tid = threadIdx.x, warp = __shfl_sync(0xffffffffu, tid >> 5, 0), lane = tid & 31;
    const int g = lane >> 2, t = lane & 3, lr = lane & 7, lm = lane >> 3;
    const int wgi = warp >> 2, w = warp & 3;
    const int b = blockIdx.x;
    const int nch = 5 - (b & 1), cs = 9 * (b >> 1) + 5 * (b & 1);
    const int f0 = 72 * (b >> 1) + 32 * (b & 1), nf = 32 + 8 * (b & 1);
    const bool has_ch = wgi < nch;
    const uint32_t mb0 = sb + OFF_MISC + offsetof(Misc, mbar), mb_wm = mb0, mb_wg = mb0 + 16, mb_wu = mb0 + 24, mb_wd = mb0 + 32;
    const uint32_t cb = sb + OFF_CH + wgi * CHS;

    if (wgi == 3) {
        M.sent[tid - 384] = make_uint4(SENT, SENT, SENT, SENT);
        M.sent[tid - 256] = make_uint4(SENT, SENT, SENT, SENT);
        if (tid == 384) {
            M.epoch = 0u; M.flag = 0u; M.e1cnt = 0u;
#pragma unroll
            for (int i = 0; i < 5; i++) mbar_init(mb0 + 8 * i, 1);
        }
        PROXY_FENCE();
        __syncwarp();
        if (warp == 12) { named_arrive(8, 160); if (b & 1) named_arrive(14, 64); }
        if (warp != 15) named_arrive(9, 128);
    }
    unsigned short r_ldt = 0, r_lar = 0, r_aim = 0, r_cr = 0, r_ci = 0;
    if (has_ch) {
        const int d = cs + wgi, n = d * N_ + (tid & 127);
        r_ldt = ld_nc16((const unsigned short*)logdt + d);
        r_lar = ld_nc16((const unsigned short*)logAr + n);
        r_aim = ld_nc16((const unsigned short*)Aim + n);
        r_cr = ld_nc16((const unsigned short*)Cr + n);
        r_ci = ld_nc16((const unsigned short*)Ci + n);
    } else {
        const unsigned short* cp = (const unsigned short*)c_in + (tid - 512);
        r_ldt = ld_nc16(cp); r_lar = ld_nc16(cp + 128); r_aim = ld_nc16(cp + 256); r_cr = ld_nc16(cp + 384);
        if (tid < 576) r_ci = ld_nc16(cp + 512);
    }
    uint4 xr[9];
    if (wgi == 4) {
        const uint4* p = (const uint4*)(x + (size_t)16 * b * D_) + (tid - 512);
#pragma unroll
        for (int i = 0; i < 9; i++) xr[i] = ld_nc4(p + 128 * i);
    }
    uint32_t wrv = 0;
    if (tid >= 128 && tid < 416) wrv = ld_nc((const uint32_t*)w_r + (tid - 128));
    if (warp == 2 && lane < nch) M.pk[3][lane] = (uint32_t)ld_nc16((const unsigned short*)Dskip + cs + lane) * 0x10001u;
    if (tid == 384) {
        const unsigned int tk = atomicAdd(S->ticket, 1u);
        *(volatile unsigned int*)&M.epoch = (tk >> 7) + 1u;
    }
    if (has_ch) {
        for (int i = tid & 127; i < 296; i += 128) *(uint4*)(sm + OFF_CH + wgi * CHS + XO_TD + i * 16) = make_uint4(0, 0, 0, 0);
    }
    if (tid < 154) {
        const int idx = (tid * 4682) >> 16, dl = tid - 14 * idx - 6;
        const int a = (0x44332221100ull >> (4 * idx)) & 7, d = (0x10102101010ull >> (4 * idx)) & 3;
        const int lo = (0x35c36 >> (4 * a)) & 15, wd = (0x16824 >> (4 * a)) & 15;
        const uint32_t one = (a == 4) ? 0xFFFFu : 0x3F80u;
        auto mk = [&](int l) { return (((unsigned)(l - lo) <= (unsigned)wd) ? one : 0u) | (((unsigned)(l - 1 - lo) <= (unsigned)wd) ? (one << 16) : 0u); };
        const int l0 = 16 * d + dl;
        M.box[tid] = make_uint4(mk(l0), mk(l0 + 8), mk(l0 - 8), mk(l0));
    }
    uint32_t xo[6];
#pragma unroll
    for (int i = 0; i < 6; i++) {
        const int ch = 16 * (warp + 16 * (i >> 1)) + 8 * (i & 1) + g;
        const int pr = (ch * 7282) >> 16, rm = ch - 9 * pr, hi = rm >= 5;
        xo[i] = (uint32_t)((((2 * pr + hi) * G_ + b) * 5 + rm - 5 * hi) * 32 + t * 8);
    }
    auto e1_store = [&]() {
        named_bar(11, 640);
        uint32_t mm[2], rhh[2], rll[2];
#pragma unroll
        for (int h = 0; h < 2; h++) {
            mm[h] = ((const uint32_t*)M.st1[0])[t + 4 * h]; rhh[h] = ((const uint32_t*)M.st1[1])[t + 4 * h]; rll[h] = ((const uint32_t*)M.st1[2])[t + 4 * h];
        }
        const uint32_t ta = sb + OFF_TILE + (lr + 8 * (lm & 1)) * (ROWP * 2) + (lm >> 1) * 16 + warp * 32;
#pragma unroll
        for (int i = 0; i < 3; i++) {
            if (i < 2 || warp < 4) {
                uint32_t r[4];
                ldsm_x4_t(r, ta + i * 512);
#pragma unroll
                for (int h = 0; h < 2; h++)
                    st_rlx2((char*)S->xn + xo[2 * i + h], ~norm2(r[2 * h], mm[0], rhh[0], rll[0]), ~norm2(r[2 * h + 1], mm[1], rhh[1], rll[1]));
            }
        }
        __syncwarp();
        if (lane == 0 && atomicAdd(&M.e1cnt, 1u) == 15u) red_inc(S->hint);
    };
    const float p_ldt = lo2f(r_ldt), p_lar = lo2f(r_lar), p_aim = lo2f(r_aim), p_cr = lo2f(r_cr), p_ci = lo2f(r_ci);
    cplx z1 = {0.f, 0.f}, z16 = z1, z256 = z1, C = z1;
    const uint32_t scr = cb + w * KSCR, ws = scr + lane * 4;
    float acc[5][4];
    uint32_t afr[4][4], cz[4];
    cplx z2 = {0.f, 0.f};
    const uint32_t ba = scr + lr * 144 + lm * 16;
    auto tile = [&](float* c, int rg) {
        __syncwarp();
        c[0] = c[1] = c[2] = c[3] = 0.f;
        uint32_t bb[2][4];
        ldsm_x4(bb[0], ba + rg * 1152);
        ldsm_x4(bb[1], ba + rg * 1152 + 64);
        mma_f16(c, afr[0], bb[0][0], bb[0][1]);
        mma_f16(c, afr[1], bb[0][2], bb[0][3]);
        mma_f16(c, afr[2], bb[1][0], bb[1][1]);
        mma_f16(c, afr[3], bb[1][2], bb[1][3]);
    };
#define CJ(z) packh((z).x, -(z).y)
#define CJP(z) packh((z).y, (z).x)
    uint32_t ex = 0;
    if (has_ch) {
        const float dt = bfr(expf(p_ldt));
        const float al = -bfr(expf(p_lar)) * dt * 1.4426950408889634f;
        const float th = p_aim * dt;
        const float th_ = th * 0.15915494309189535f;
        const float tl_ = fmaf(th, 0.15915494309189535f, -th_) + th * 6.4206382e-9f;
        auto anchor = [&](float s) {
            float f = th_ * s;
            f -= rintf(f);
            f = fmaf(tl_, s, f) * 6.283185307179586f;
            const float e = fex2(al * s);
            return cplx{e * __cosf(f), e * __sinf(f)};
        };
        const float cx = p_cr * dt * 2.0f, cy = p_ci * dt * 2.0f;
        ex = __reduce_max_sync(0xffffffffu, __float_as_uint(fmaxf(fabsf(cx), fabsf(cy)))) >> 23;
        const float scl = __uint_as_float((254u - ex) << 23);
        C = cplx{cx * scl, cy * scl};
        z1 = anchor(1.f); z16 = anchor(16.f); z256 = anchor(256.f);
            {
                const cplx z32 = csq(z16), z48 = cmul(z32, z16), z64 = csq(z32), z128 = csq(z64), z192 = cmul(z128, z64);
                const uint32_t y[3] = {packh(z16.x, z16.y), packh(z32.x, z32.y), packh(z48.x, z48.y)};
                const uint32_t yp[3] = {packh(-z16.y, z16.x), packh(-z32.y, z32.x), packh(-z48.y, z48.x)};
                const uint32_t xx[3] = {packh(z64.x, z64.y), packh(z128.x, z128.y), packh(z192.x, z192.y)};
                sts32(ws, 0x00003C00u);
#pragma unroll
                for (int j = 0; j < 3; j++) sts32(ws + (1 + j) * 144, y[j]);
#pragma unroll
                for (int i = 0; i < 3; i++) {
                    sts32(ws + (4 + 4 * i) * 144, xx[i]);
#pragma unroll
                    for (int j = 0; j < 3; j++) sts32(ws + (5 + 4 * i + j) * 144, hcm(xx[i], y[j], yp[j]));
                }
            }
    }
    if (wgi == 4) {
        if (!has_ch) {
            const int i = tid - 512;
            ((unsigned short*)M.sc)[i] = (unsigned short)f2bits(silu(lo2f(r_ldt)));
            ((unsigned short*)M.sc)[i + 128] = (unsigned short)f2bits(silu(lo2f(r_lar)));
            ((unsigned short*)M.sc)[i + 256] = (unsigned short)f2bits(silu(lo2f(r_aim)));
            ((unsigned short*)M.sc)[i + 384] = (unsigned short)f2bits(silu(lo2f(r_cr)));
            if (i < 64) ((unsigned short*)M.sc)[i + 512] = (unsigned short)f2bits(silu(lo2f(r_ci)));
            if (warp == 16) {
                named_bar(14, 64);
                if (lane == 0) {
                    mbar_expect(mb_wm, 36864);
#pragma unroll
                    for (int k = 0; k < 3; k++) tma2d(sb + OFF_WU + k * 12288, &tm_wm, 32 * (b >> 1), 192 * k, mb_wm);
                }
                __syncwarp();
            }
        }
#pragma unroll
        for (int i = 0; i < 9; i++) {
            const int c = tid - 512 + 128 * i, rr = (c * 911) >> 16;
            *(uint4*)(sm + OFF_TILE + rr * (ROWP * 2 - 1152) + c * 16) = xr[i];
        }
        named_bar(8, 160);
        {
            float c1[4] = {0.f, 0.f, 0.f, 0.f}, cl[4] = {0.f, 0.f, 0.f, 0.f}, chh[4] = {0.f, 0.f, 0.f, 0.f};
            const uint32_t a0 = sb + OFF_TILE + (lane & 15) * (ROWP * 2) + (lane >> 4) * 16 + w * 288;
            uint32_t a[9][4];
#pragma unroll
            for (int ks = 0; ks < 9; ks++) ldsm_x4(a[ks], a0 + ks * 32);
#pragma unroll
            for (int ks = 0; ks < 9; ks++) {
                mma_bf16(c1, a[ks][0], a[ks][1], a[ks][2], a[ks][3], 0x3F803F80u, 0x3F803F80u);
                mma_bf16(cl, a[ks][0], a[ks][1], a[ks][2], a[ks][3], a[ks][0], a[ks][2]);
                mma_bf16(chh, a[ks][0], a[ks][1], a[ks][2], a[ks][3], a[ks][1], a[ks][3]);
            }
            if (t == 0) { M.p1[g][w] = c1[0]; M.p1[g + 8][w] = c1[2]; }
            if (t == (g >> 1)) { M.p2[g][w] = (g & 1) ? cl[1] : cl[0]; M.p2[g + 8][w] = (g & 1) ? chh[3] : chh[2]; }
        }
        named_bar(5, 128);
        if (warp == 16) {
            const float4 q1 = *(const float4*)M.p1[lane & 15], q2 = *(const float4*)M.p2[lane & 15];
            float meanb, rinv;
            ln_stats((q1.x + q1.y) + (q1.z + q1.w), (q2.x + q2.y) + (q2.z + q2.w), meanb, rinv);
            const float rh = bfr(rinv);
            if (lane < 16) { M.st1[0][lane] = (unsigned short)f2bits(meanb); M.st1[1][lane] = (unsigned short)f2bits(rh); M.st1[2][lane] = (unsigned short)f2bits(rinv - rh); }
        }
        __syncwarp();
        named_arrive(11, 640);
    }
    auto publish_reset = [&]() {
        if (tid == 480) {
            asm volatile("cp.async.bulk.wait_group 0;" ::: "memory");
            asm volatile("fence.proxy.async;" ::: "memory");
            red_inc(S->cnt);
        }
    };
    uint32_t epoch = 0, tag16 = 0, pre = 0;
    auto mod_tile = [&](int rd) {
        const uint32_t* s2 = (const uint32_t*)M.sc + 144 * (w >> 1) + t;
        uint32_t bb[18][2];
#pragma unroll
        for (int ks = 0; ks < 18; ks++) { bb[ks][0] = (g == 0) ? s2[8 * ks] : 0u; bb[ks][1] = (g == 0) ? s2[8 * ks + 4] : 0u; }
        float acc[2][4] = {{0.f, 0.f, 0.f, 0.f}, {0.f, 0.f, 0.f, 0.f}};
        const int row = lr + 8 * (lm >> 1);
        const uint32_t wa = sb + OFF_WU + (288 * (w >> 1) + row) * 64 + ((((2 * (w & 1) + (lm & 1)) ^ (row >> 1)) & 3) << 4);
        mbar_wait(mb_wm + 8 * rd, 0);
        if (rd == 0)
#pragma unroll
        for (int kb = 0; kb < 2; kb++) {
            uint32_t a[9][4];
#pragma unroll
            for (int ks = 0; ks < 9; ks++) ldsm_x4_t(a[ks], wa + (9 * kb + ks) * 1024);
#pragma unroll
            for (int ks = 0; ks < 9; ks++) mma_bf16(acc[ks & 1], a[ks][0], a[ks][1], a[ks][2], a[ks][3], bb[9 * kb + ks][0], bb[9 * kb + ks][1]);
        }
        const float v0 = acc[0][0] + acc[1][0], v1 = acc[0][2] + acc[1][2];
        float* mx = M.modx + 16 * (w & 1) + g;
        if (w >= 2 && t == 0) { mx[0] = v0; mx[8] = v1; }
        named_bar(5, 128);
        if (w < 2 && t == 0) {
            unsigned int* mp = &S->modw[32 * ((b >> 1) + 64 * rd) + 16 * w + g];
            st_rlx(mp, f2bits(v0 + mx[0]) | (tag16 << 16));
            st_rlx(mp + 8, f2bits(v1 + mx[8]) | (tag16 << 16));
        }
        if (rd == 0 && w < 2 && b < 108) {
            named_bar(7, 64);
            if (tid == 512) red_inc(S->hint);
        }
    };
    if (has_ch) {
        {
            z2 = csq(z1);
            const cplx z3 = cmul(z2, z1), z4 = csq(z2), z8 = csq(z4);
            const cplx c4 = cmul(C, z4), c8 = cmul(C, z8), c12 = cmul(c8, z4);
            cz[0] = packh(C.x, -C.y); cz[1] = packh(c4.x, -c4.y); cz[2] = packh(c8.x, -c8.y); cz[3] = packh(c12.x, -c12.y);
            __syncwarp();
#pragma unroll
            for (int s = 0; s < 4; s++) ldsm_x4(afr[s], scr + (lr + 8 * (lm & 1)) * 144 + (2 * s + (lm >> 1)) * 16);
            {
                const uint32_t y[3] = {CJ(z1), CJ(z2), CJ(z3)}, yp[3] = {CJP(z1), CJP(z2), CJP(z3)};
#pragma unroll
                for (int tt = 0; tt < 2; tt++) {
                    const int rg = tt ? 0 : 2;
#pragma unroll
                    for (int i = 0; i < 2; i++) {
                        sts32(ws + rg * 1152 + (4 * i) * 144, cz[2 * tt + i]);
#pragma unroll
                        for (int j = 0; j < 3; j++) sts32(ws + rg * 1152 + (4 * i + 1 + j) * 144, hcm(cz[2 * tt + i], y[j], yp[j]));
                    }
                    tile(acc[tt], rg);
                }
            }
            if (tid >= 128 && tid < 416) M.wr[tid - 128] = wrv;
            if (wgi < 4) e1_store();
    if (warp == 15) {
        named_bar(9, 128);
        if (lane == 0) {
#pragma unroll 1
            for (int i = 0; i < 5; i++) {
                bulk_s2g((char*)&S->v[(size_t)b * 1152] + i * 4096, sb + OFF_MISC, i < 4 ? 4096 : 2048);
                if (i < 3) bulk_s2g((char*)&S->part[(size_t)b * 1152] + i * 4096, sb + OFF_MISC, i < 2 ? 4096 : 1024);
            }
            bulk_s2g(&S->rec[8 * b], sb + OFF_MISC, 32);
            asm volatile("cp.async.bulk.commit_group;" ::: "memory");
        }
        __syncwarp();
    }
            const cplx z258 = cmul(z256, z2), z512 = csq(z256), z768 = cmul(z512, z256);
            {
                const uint32_t a0 = CJ(z256), a0p = CJP(z256), a1 = CJ(z258), a1p = CJP(z258);
#pragma unroll
                for (int i = 0; i < 4; i++) { sts32(ws + 1152 + (2 * i) * 144, hcm(cz[i], a0, a0p)); sts32(ws + 1152 + (2 * i + 1) * 144, hcm(cz[i], a1, a1p)); }
                tile(acc[2], 1);
            }
            {
                const uint32_t a0 = CJ(z512), a0p = CJP(z512), a1 = CJ(z768), a1p = CJP(z768);
#pragma unroll
                for (int i = 0; i < 4; i++) { sts32(ws + 2304 + i * 144, hcm(cz[i], a0, a0p)); sts32(ws + 2304 + (4 + i) * 144, hcm(cz[i], a1, a1p)); }
                tile(acc[3], 2);
            }
            if (warp == 3) {
                if (lane == 15) pre = ld_rlx(S->hint);
            }
            const cplx z1024 = csq(z512);
            {
                const cplx zk[4] = {z1024, cmul(z1024, z256), csq(z768), cmul(z1024, z768)};
#pragma unroll
                for (int h = 0; h < 4; h++) {
                    const uint32_t a0 = CJ(zk[h]), a0p = CJP(zk[h]);
                    sts32(ws + (2 * h) * 144, hcm(cz[0], a0, a0p));
                    sts32(ws + (2 * h + 1) * 144, hcm(cz[2], a0, a0p));
                }
                tile(acc[4], 0);
            }
            const cplx z2048 = csq(z1024);
            float last = C.x * z2048.x - C.y * z2048.y;
#pragma unroll
            for (int o = 16; o; o >>= 1) last += __shfl_xor_sync(0xffffffffu, last, o);
            __syncwarp();
#pragma unroll
            for (int i = 0; i < 5; i++) *(float4*)(sm + (scr - sb) + i * 512 + lane * 16) = make_float4(acc[i][0], acc[i][1], acc[i][2], acc[i][3]);
            if (lane == 0) { const float inv = __uint_as_float(ex << 23); M.kinv[wgi][w] = inv; M.klast[wgi][w] = last * inv; }
        }
        if (tid == 111 && (int)(pre - HINT_N * wait_epoch(M)) >= 0) M.flag = 1u;
        named_bar(1 + wgi, 128);
        const uint32_t td = cb + XO_TD + 64 * 4, tf = cb + XO_TF - 32 * 4;
        if (tid == 111 && !M.flag) pre = ld_rlx(S->hint);
        const float4 ki = *(const float4*)M.kinv[wgi];
        auto fsum = [&](int off, uint32_t& r0, uint32_t& r1) {
            const unsigned char* p = sm + (cb - sb) + off;
            const float4 a = *(const float4*)p, b2 = *(const float4*)(p + KSCR), c = *(const float4*)(p + 2 * KSCR), d = *(const float4*)(p + 3 * KSCR);
            r0 = pack2(fmaf(a.y, ki.x, b2.y * ki.y) + fmaf(c.y, ki.z, d.y * ki.w), fmaf(a.x, ki.x, b2.x * ki.y) + fmaf(c.x, ki.z, d.x * ki.w));
            r1 = pack2(fmaf(a.w, ki.x, b2.w * ki.y) + fmaf(c.w, ki.z, d.w * ki.w), fmaf(a.z, ki.x, b2.z * ki.y) + fmaf(c.z, ki.z, d.z * ki.w));
        };
        uint32_t r[2], q[2];
        fsum(w * 512 + lane * 16, r[0], r[1]);
        fsum(2048 + w * 128 + lr * 16, q[0], q[1]);
        if (tid == 111) {
            if ((int)(pre - HINT_N * M.epoch) >= 0) M.flag = 1u;
            else pre = ld_rlx(S->hint);
        }
        __syncwarp();
        if (w < 2) {
            const uint32_t p = td + (16 * g + 8 * w + 2 * t) * 4;
#pragma unroll
            for (int h = 0; h < 2; h++) { sts16(p + h * 512, r[h] >> 16); sts32(p + h * 512 + 4, r[h]); sts16(p + h * 512 + 10, r[h]); }
        } else if (w == 2) {
            const uint32_t p = td + (256 + 16 * g + 4 * t) * 4;
#pragma unroll
            for (int h = 0; h < 2; h++) {
                const uint32_t k0 = r[h] >> 16;
                if (h || lane) { sts16(p + h * 512 - 4, k0); sts16(p + h * 512 + 2, k0); }
                sts16(p + h * 512, k0); sts32(p + h * 512 + 4, __byte_perm(r[h], 0, 0x3232)); sts32(p + h * 512 + 8, r[h]); sts16(p + h * 512 + 14, r[h]);
            }
        } else {
            const uint32_t p = tf + (64 + 32 * (t >> 1) + 2 * g + (t & 1)) * 4;
#pragma unroll
            for (int h = 0; h < 2; h++) {
                const uint32_t k0 = r[h] >> 16;
                sts16(p + h * 64 + 512, r[h]); sts16(p + h * 64 + 518, r[h]);
                if (h || lane) { sts16(p + h * 64 - 4, k0); sts16(p + h * 64 + 2, k0); }
            }
            if (lane == 0) {
                const uint32_t dd = __byte_perm(r[0], 0, 0x3232);
                sts16(td + 511 * 4, dd); sts32(td + 512 * 4, dd); sts32(td + 513 * 4, dd); sts32(td + 514 * 4, dd); sts16(td + 515 * 4 + 2, dd);
            }
        }
        if (lane < 8) {
            const uint32_t p = tf + 1024 + (64 + 16 * t + 2 * w + g) * 4;
#pragma unroll
            for (int h = 0; h < 2; h++) {
                const uint32_t k0 = q[h] >> 16;
                sts16(p + h * 32 + 512, q[h]); sts16(p + h * 32 + 518, q[h]);
                if (h || (tid & 127)) { sts16(p + h * 32 - 4, k0); sts16(p + h * 32 + 2, k0); }
            }
            if ((tid & 127) == 0) {
                const float4 kl4 = *(const float4*)M.klast[wgi];
                const uint32_t kl = f2bits((kl4.x + kl4.y) + (kl4.z + kl4.w)), dd = __byte_perm(q[0], 0, 0x3232);
                sts16(tf + 127 * 4, dd); sts16(tf + 128 * 4 + 2, dd); sts32(cb + XO_K1024, dd);
                sts16(tf + 1024 + 127 * 4, kl); sts16(tf + 1024 + 128 * 4 + 2, kl);
            }
        }
        __syncwarp();
    } else {
        const int i = tid - 512, idx = b >> 1;
        tag16 = (wait_epoch(M) % 65535u) + 1u;
        mod_tile(0);
        if (i == 0 && idx < 44) {
            PROXY_FENCE();
            mbar_expect(mb_wm + 8, 36864);
#pragma unroll
            for (int k = 0; k < 3; k++) tma2d(sb + OFF_WU + k * 12288, &tm_wm, 32 * (idx + 64), 192 * k, mb_wm + 8);
        }
        __syncwarp();
    }
    if (tid == 111) {
        epoch = wait_epoch(M);
#pragma unroll 1
        for (int it = 0; it < SPIN_MAX && (int)(pre - HINT_N * epoch) < 0; it++) pre = ld_rlx(S->hint);
        M.flag = 1u;
    }
    __syncwarp();
    const int ubp = (tid * 13108) >> 16, uloc = tid - 5 * ubp;
    const uint4* usrc = &S->xn[(size_t)b * 1280 + 2 * tid];
    uint4 ua = make_uint4(0, 0, 0, 0), uc = ua;
    uint32_t usa = 0, uca = 0;
    if (lane == 0) {
#pragma unroll 1
        for (int it = 0; it < (SPIN_MAX << 4) && !M.flag; it++) { }
    }
    __syncwarp();
    if (uloc < nch) {
 ua = ld_rlx4(usrc); uc = ld_rlx4(usrc + 1); usa = ld_rlx(&S->modw[cs + uloc]); uca = ld_rlx(&S->modw[D_ + cs + uloc]); }
    CBAR();
    epoch = M.epoch;
    tag16 = (epoch % 65535u) + 1u;
    {
        const int bp = ubp, loc = uloc;
        if (loc < nch) {
            const uint4* src = usrc;
            uint4 a = ua, c = uc;
#pragma unroll 1
            for (int it = 0; it < SPIN_MAX && (a.x == SENT || a.z == SENT || c.x == SENT || c.z == SENT || (usa >> 16) != tag16 || (uca >> 16) != tag16); it++) {
                a = ld_rlx4(src); c = ld_rlx4(src + 1); usa = ld_rlx(&S->modw[cs + loc]); uca = ld_rlx(&S->modw[D_ + cs + loc]);
            }
            const uint32_t sa = __byte_perm(usa, 0, 0x1010), ca = pack2(1.0f + lo2f(uca), 1.0f + lo2f(uca));
            unsigned char* up = sm + OFF_CH + loc * CHS + ((2 * bp) & 7) * ULBO + ((bp >> 2) + 9) * 16;
            *(uint4*)up = make_uint4(add2(mul2(~a.x, ca), sa), add2(mul2(~a.z, ca), sa), add2(mul2(~c.x, ca), sa), add2(mul2(~c.z, ca), sa));
            *(uint4*)(up + ULBO) = make_uint4(add2(mul2(~a.y, ca), sa), add2(mul2(~a.w, ca), sa), add2(mul2(~c.y, ca), sa), add2(mul2(~c.w, ca), sa));
        }
        publish_reset();
        const int i = tid & 127;
        unsigned char* cp = sm + OFF_CH + wgi * CHS;
        *(uint4*)(cp + XO_U8 - 1024 + (i >> 6) * 4096 + (i & 63) * 16) = make_uint4(0, 0, 0, 0);
        if (i < 72) { const int c = (i * 57) >> 9; *(uint4*)(cp + c * ULBO + (i - 9 * c) * 16) = make_uint4(0, 0, 0, 0); }
    }
    PROXY_FENCE();
    CBAR();
    if (w == 2 && lane == 0) {
        bulk_s2g((char*)&S->xn[(size_t)b * 1280] + wgi * 4096, sb + OFF_MISC, 4096);
        asm volatile("cp.async.bulk.commit_group;" ::: "memory");
    }
        if (tid == 416) {
            mbar_expect(mb_wg, nf * D_ * 2);
            tma2d(sb + OFF_WG, (b & 1) ? &tm_wg : &tm_wg32, f0, 0, mb_wg);
        }
    if (tid == 96 || tid == 224) tma2d(sb + OFF_WG + (1 + (tid >> 7)) * (nf * 384), (b & 1) ? &tm_wg : &tm_wg32, f0, 192 * (1 + (tid >> 7)), mb_wg);
    if (has_ch) {
        __syncwarp();
        conv_channel(sm, S, 2 * D_ + cs + wgi, epoch, w_down + (size_t)f0 * D_, (b & 1) ? nullptr : &tm_wu32, f0);
    } else {
        const int idx = b >> 1;
        if (idx < 44) mod_tile(1);
        if (tid == 512) {
            PROXY_FENCE();
            mbar_expect(mb_wu, 46080);
#pragma unroll 1
            for (int i = 0; i < 3; i++) {
                tma2d(sb + OFF_WU + i * 15360, &tm_wu, f0, 192 * i, mb_wu);
                const long long c0 = clock64();
                int it = 0;
                while (clock64() - c0 < 1200 && ++it < 4096) { }
            }
            wait_reset(S->cnt, epoch);
        }
        named_bar(5, 128);
    }
    {
    const int tid = fresh_tid(), warp = __shfl_sync(0xffffffffu, tid >> 5, 0), lane = tid & 31;
    const int g = lane >> 2, t = lane & 3, lr = lane & 7, lm = lane >> 3;
    uint32_t v3 = 0, v4 = 0, v5 = 0;
    auto load_consts = [&]() {
        if (tid < D_) { v3 = ld_rlx(&S->modw[3 * D_ + tid]); v4 = ld_rlx(&S->modw[4 * D_ + tid]); v5 = ld_rlx(&S->modw[5 * D_ + tid]); }
    };
    if (tid == 0) bulk_pf(w_down + (size_t)(f0 + 16) * D_, (nf - 16) * D_ * 2);
    uint32_t x1[2][4], wr2[2][2];
    if (warp < 18) {
        const char* vp = (const char*)S->v + ((size_t)b * D_ + 32 * warp + g) * 32 + t * 8;
        uint2 v[4];
#pragma unroll
        for (int i = 0; i < 4; i++) v[i] = ld_rlx2(vp + i * 256);
#pragma unroll
        for (int j = 0; j < 2; j++) {
            const uint32_t* wp = M.wr + 16 * warp + 8 * j + t;
            wr2[j][0] = (g == 0) ? wp[0] : 0u;
            wr2[j][1] = (g == 0) ? wp[4] : 0u;
            ldsm_x4(x1[j], sb + OFF_TILE + (lr + 8 * (lm & 1)) * (ROWP * 2) + (lm >> 1) * 16 + warp * 64 + j * 32);
        }
#pragma unroll 1
        for (int it = 0; it < SPIN_MAX && ((v3 >> 16) != tag16 || (v4 >> 16) != tag16 || (v5 >> 16) != tag16); it++) load_consts();
        ((unsigned short*)M.sb)[tid] = (unsigned short)v3;
        ((unsigned short*)M.cb1)[tid] = (unsigned short)f2bits(1.0f + lo2f(v4));
        ((unsigned short*)M.gb)[tid] = (unsigned short)v5;
#pragma unroll 1
        for (int it = 0; it < SPIN_MAX; it++) {
            bool bad = false;
#pragma unroll
            for (int i = 0; i < 4; i++) if (v[i].x == SENT) { v[i] = ld_rlx2(vp + i * 256); bad = true; }
            if (!bad) break;
        }
        __syncwarp();
        float c1[4] = {0.f, 0.f, 0.f, 0.f}, cl[4] = {0.f, 0.f, 0.f, 0.f}, chh[4] = {0.f, 0.f, 0.f, 0.f};
#pragma unroll
        for (int j = 0; j < 2; j++) {
            x1[j][0] = add2(x1[j][0], movm(~v[2 * j].x)); x1[j][1] = add2(x1[j][1], movm(~v[2 * j].y));
            x1[j][2] = add2(x1[j][2], movm(~v[2 * j + 1].x)); x1[j][3] = add2(x1[j][3], movm(~v[2 * j + 1].y));
            mma_bf16(c1, x1[j][0], x1[j][1], x1[j][2], x1[j][3], 0x3F803F80u, 0x3F803F80u);
            mma_bf16(cl, x1[j][0], x1[j][1], x1[j][2], x1[j][3], x1[j][0], x1[j][2]);
            mma_bf16(chh, x1[j][0], x1[j][1], x1[j][2], x1[j][3], x1[j][1], x1[j][3]);
        }
        float* pp = (float*)&M.part[warp][g];
        if (t == 0) { pp[0] = c1[0]; pp[16] = c1[2]; }
        if (t == (g >> 1)) { pp[1] = (g & 1) ? cl[1] : cl[0]; pp[17] = (g & 1) ? chh[3] : chh[2]; }
    }
    CBAR();
    if (warp < 18) {
        const int tok = lane & 15, hf = lane >> 4;
        uint32_t kc[2][2][2];
#pragma unroll
        for (int j = 0; j < 2; j++)
#pragma unroll
            for (int q = 0; q < 2; q++) { kc[j][q][0] = ((const uint32_t*)M.cb1)[16 * warp + 8 * j + 4 * q + t]; kc[j][q][1] = ((const uint32_t*)M.sb)[16 * warp + 8 * j + 4 * q + t]; }
        named_bar(13, 608);
        uint32_t st[2][3];
#pragma unroll
        for (int h = 0; h < 2; h++) { const uint4 q = M.st2[g + 8 * h]; st[h][0] = q.x; st[h][1] = q.y; st[h][2] = q.z; }
        float rc[4] = {0.f, 0.f, 0.f, 0.f};
        uint32_t h2[2][4];
#pragma unroll
        for (int j = 0; j < 2; j++) {
#pragma unroll
            for (int r = 0; r < 4; r++) {
                h2[j][r] = add2(mul2(norm2(x1[j][r], st[r & 1][0], st[r & 1][1], st[r & 1][2]), kc[j][r >> 1][0]), kc[j][r >> 1][1]);
            }
            mma_bf16(rc, h2[j][0], h2[j][1], h2[j][2], h2[j][3], wr2[j][0], wr2[j][1]);
        }
        if (t == 0) { M.rp[warp][g] = rc[0]; M.rp[warp][g + 8] = rc[2]; }
        if (warp == 0) {
            named_bar(12, 576);
            float r = M.rp[9 * hf][tok];
#pragma unroll
            for (int i = 1; i < 9; i++) r += M.rp[9 * hf + i][tok];
            r += __shfl_xor_sync(0xffffffffu, r, 16);
            const uint32_t rbits = f2bits(r);
            const uint32_t key = 0x80000000u | ((rbits ^ ((rbits & 0x8000u) ? 0xFFFFu : 0x8000u)) << 11) | (uint32_t)(2047 - (16 * b + tok));
            int rank = 0;
#pragma unroll
            for (int j = 1; j < 16; j++) rank += __shfl_xor_sync(0xffffffffu, key, j) > key;
            if (lane < 16) { M.skey[rank] = key; M.rank[rank] = tok; }
            __syncwarp();
            if (lane < 2) st_rlx4(&S->rec[8 * b + 4 * lane], *(const uint4*)&M.skey[4 * lane]);
        } else named_arrive(12, 576);
#pragma unroll
        for (int j = 0; j < 2; j++) {
            uint32_t o[4];
#pragma unroll
            for (int r = 0; r < 4; r++) o[r] = add2(x1[j][r], mul2(((const uint32_t*)M.gb)[16 * warp + 8 * j + 4 * (r >> 1) + t], h2[j][r]));
            const uint32_t to = (lr + 8 * (lm & 1)) * (ROWP * 2) + (lm >> 1) * 16 + warp * 64 + j * 32;
            stsm_x4(sb + OFF_H2T + to, h2[j][0], h2[j][1], h2[j][2], h2[j][3]);
            stsm_x4(sb + OFF_TILE + to, o[0], o[1], o[2], o[3]);
        }
    } else if (warp == 19) {
        const int tok = lane & 15, hf = lane >> 4;
        float2 s = M.part[9 * hf][tok];
#pragma unroll
        for (int i = 1; i < 9; i++) { const float2 q = M.part[9 * hf + i][tok]; s.x += q.x; s.y += q.y; }
        s.x += __shfl_xor_sync(0xffffffffu, s.x, 16); s.y += __shfl_xor_sync(0xffffffffu, s.y, 16);
        float meanb, rinv;
        ln_stats(s.x, s.y, meanb, rinv);
        const float rh = bfr(rinv);
        if (lane < 16) M.st2[tok] = make_uint4(pack2(meanb, meanb), pack2(rh, rh), pack2(rinv - rh, rinv - rh), 0u);
        __syncwarp();
        named_arrive(13, 608);
    } else if (lane < 9) {
        PROXY_FENCE();
        if (lane == 0) mbar_expect(mb_wd, nf * D_ * 2);
        tma2d(sb + OFF_WD + lane * 5120, (b & 1) ? &tm_wd : &tm_wd32, 64 * lane, f0, mb_wd);
    }
    CBAR();
    uint32_t wf[9][4], wd[2][3][4];
    const int fmt = warp >> 2, fsl = warp & 3;
    auto load_wf = [&]() {
        mbar_wait(mb_wg, 0);
        mbar_wait(mb_wu, 0);
        if (fmt < 4 || nf > 32) {
            const int half = lm & 1;
            const uint32_t base = (fmt == 4) ? ((half ? OFF_WU : OFF_WG) + 64)
                                             : ((fmt >> 1) * OFF_WU + (((2 * (fmt & 1) + half) ^ ((b & 1) ? 0 : (lr >> 1))) << 4));
            const uint32_t wa = sb + base + (144 * fsl + lr + 8 * (lm >> 1)) * (2 * nf);
#pragma unroll
            for (int ks = 0; ks < 9; ks++) ldsm_x4_t(wf[ks], wa + ks * (32 * nf));
        }
    mbar_wait(mb_wd, 0);
    {
#pragma unroll
        for (int i = 0; i < 2; i++) {
            const int mt = warp + 20 * i;
            const uint32_t wa = sb + OFF_WD + (mt >> 2) * 5120 + lr * 128 + (((2 * (mt & 3) + (lm & 1)) ^ lr) << 4);
#pragma unroll
            for (int ks = 0; ks < 3; ks++)
                if ((i == 0 || warp < 16) && (ks < 2 || nf > 32)) ldsm_x4_t(wd[i][ks], wa + ks * 2048 + ((ks < 2) ? (lm >> 1) * 1024 : 0));
        }
    }
    };
    if (warp >= 8) {
        if (warp < 16) {
            const int tk = M.rank[warp - 8];
            const uint32_t* hp = (const uint32_t*)(sm + OFF_H2T + tk * (ROWP * 2)) + lane;
            uint4* dst = &S->h2w[(size_t)(16 * b + tk) * 96 + lane];
#pragma unroll
            for (int j = 0; j < 3; j++) st_rlx4(dst + 32 * j, make_uint4(hp[96 * j], hp[96 * j + 32], hp[96 * j + 64], epoch));
        }
        load_wf();
    } else {
        const uint4* rp = (const uint4*)S->rec + tid;
        load_wf();
        uint4 rk = ld_rlx4(rp);
#pragma unroll 1
        for (int it = 0; it < SPIN_MAX && !rk.x; it++) rk = ld_rlx4(rp);
        __syncwarp();
        uint32_t mine = 0;
#pragma unroll
        for (int rnd = 0; rnd < 8; rnd++) {
            const uint32_t m = __reduce_max_sync(0xffffffffu, rk.x);
            if (rk.x == m) { rk.x = rk.y; rk.y = rk.z; rk.z = rk.w; rk.w = 0u; }
            if (lane == rnd) mine = m;
        }
        if (lane < 8) M.cand[8 * warp + lane] = mine;
    }
    CBAR();
    uint32_t selv = 0;
    if (warp < 12) {
        uint2 k = *(const uint2*)&M.cand[2 * lane];
#pragma unroll
        for (int rnd = 0; rnd < 8; rnd++) {
            const uint32_t m = __reduce_max_sync(0xffffffffu, k.x);
            if (k.x == m) { k.x = k.y; k.y = 0u; }
            if (lr == rnd) selv = m;
        }
        if (tid < 8) M.skey[tid] = selv;
    }
    const uint32_t seltok = 2047u - (selv & 2047u);
    const int fo = tid >> 3;
    const int fW = 9 * b + (fo >> 2), fcomp = fo & 3;
    const int fd = 16 * (fW >> 5) + ((fW >> 2) & 7) + 8 * (fcomp >> 1), fk = 2 * (fW & 3) + (fcomp & 1);
    const uint32_t fsel = __shfl_sync(0xffffffffu, selv, fk);
    uint32_t fx = 0, fv = 0;
    bf16(*h2s)[ROWP] = (bf16(*)[ROWP])(sm + OFF_H2S);
    if (warp < 12) {
        uint4 wv[2];
        const uint4* hp[2];
#pragma unroll
        for (int r = 0; r < 2; r++) {
            const int wi = warp + 12 * r, k = wi / 3, j = wi - 3 * k;
            hp[r] = &S->h2w[(size_t)__shfl_sync(0xffffffffu, seltok, k) * 96 + 32 * j + lane];
            wv[r] = ld_rlx4(hp[r]);
        }
        if (tid < 288 && (tid & 7) == 0) {
            const uint32_t ft = 2047u - (fsel & 2047u), pr = (ft & 15u) >> 1;
            fx = ((const unsigned short*)x)[(size_t)ft * D_ + fd];
            asm volatile("ld.relaxed.gpu.global.u16 %0, [%1];" : "=r"(fv)
                         : "l"((const unsigned short*)S->v + ((size_t)(ft >> 4) * D_ + fd) * 16 + ((pr & 3u) * 2 + (pr >> 2)) * 2 + (ft & 1u)) : "memory");
        }
#pragma unroll 1
        for (int it = 0; it < SPIN_MAX && (wv[0].w != epoch || wv[1].w != epoch); it++) { wv[0] = ld_rlx4(hp[0]); wv[1] = ld_rlx4(hp[1]); }
#pragma unroll
        for (int r = 0; r < 2; r++) {
            const int wi = warp + 12 * r, k = wi / 3, j = wi - 3 * k;
            uint32_t* dst = (uint32_t*)&h2s[k][0] + 96 * j + lane;
            dst[0] = wv[r].x; dst[32] = wv[r].y; dst[64] = wv[r].z;
        }
    }
    CBAR();
    float* ffr = (float*)(sm + OFF_FFR);
    if (fmt < 4 || nf > 32) {
        float acc[2][4] = {{0.f, 0.f, 0.f, 0.f}, {0.f, 0.f, 0.f, 0.f}};
        const uint32_t ha = sb + OFF_H2S + lr * (ROWP * 2) + (144 * fsl) * 2 + lm * 16;
#pragma unroll
        for (int k2 = 0; k2 < 5; k2++) {
            uint32_t hb[4];
            ldsm_x4(hb, ha + k2 * 64 - ((k2 == 4) ? (lm >> 1) * 32 : 0));
            mma_bf16(acc[0], wf[2 * k2][0], wf[2 * k2][1], wf[2 * k2][2], wf[2 * k2][3], hb[0], hb[1]);
            if (k2 < 4) mma_bf16(acc[1], wf[2 * k2 + 1][0], wf[2 * k2 + 1][1], wf[2 * k2 + 1][2], wf[2 * k2 + 1][3], hb[2], hb[3]);
        }
        float* o = ffr + ((fsl * 80 + 16 * fmt + g) * 8 + 2 * t);
        *(float2*)o = make_float2(acc[0][0] + acc[1][0], acc[0][1] + acc[1][1]);
        *(float2*)(o + 64) = make_float2(acc[0][2] + acc[1][2], acc[0][3] + acc[1][3]);
    }
    CBAR();
    bf16(*act)[56] = (bf16(*)[56])(sm + OFF_ACT);
    if (tid < 384) {
        const int f = tid >> 3, a = tid & 7;
        float v = 0.f;
        if (f < nf) {
            const int rg = (f < 32) ? f : f + 32, ru = (f < 32) ? f + 32 : f + 40;
            const float* pg = ffr + rg * 8 + a;
            const float* pu = ffr + ru * 8 + a;
            float gg = bfr((pg[0] + pg[640]) + (pg[1280] + pg[1920]));
            gg = bfr(silu(gg));
            const float uu = bfr((pu[0] + pu[640]) + (pu[1280] + pu[1920]));
            v = gg * uu;
        }
        act[a][f] = __ushort_as_bfloat16((unsigned short)f2bits(v));
    }
    CBAR();
    {
        uint32_t bq[3][2];
#pragma unroll
        for (int ks = 0; ks < 3; ks++) {
            bq[ks][0] = *(const uint32_t*)&act[g][16 * ks + 2 * t];
            bq[ks][1] = *(const uint32_t*)&act[g][16 * ks + 2 * t + 8];
        }
#pragma unroll
        for (int i = 0; i < 2; i++) {
            if (i == 0 || warp < 16) {
                float acc[4] = {0.f, 0.f, 0.f, 0.f};
#pragma unroll
                for (int ks = 0; ks < 3; ks++)
                    if (ks < 2 || nf > 32) mma_bf16(acc, wd[i][ks][0], wd[i][ks][1], wd[i][ks][2], wd[i][ks][3], bq[ks][0], bq[ks][1]);
                const int W = (warp + 20 * i) * 32 + lane, c = (W * 7282) >> 16;
                st_rlx2(&S->part[(c * G_ + b) * 9 + W - 9 * c], ~pack2(acc[0], acc[1]), ~pack2(acc[2], acc[3]));
            }
        }
    }
    if (warp >= 4) {
        const int tk = warp - 4;
        if (!__any_sync(0xffffffffu, 2047u - (M.skey[lr] & 2047u) == (uint32_t)(16 * b + tk))) {
            const uint4* src = (const uint4*)(sm + OFF_TILE + tk * (ROWP * 2));
            uint4* dst = (uint4*)(out + (size_t)(16 * b + tk) * D_);
            dst[lane] = src[lane]; dst[lane + 32] = src[lane + 32];
            if (lane < 8) dst[lane + 64] = src[lane + 64];
        }
    }
    float4* fin = (float4*)(sm + OFF_FIN);
    uint32_t rb = (fsel >> 11) & 0xFFFFu;
    rb ^= (rb & 0x8000u) ? 0x8000u : 0xFFFFu;
    const float rs = bfr(__fdividef(1.0f, 1.0f + __expf(-lo2f(rb))));
    const float fh2 = (tid < 288) ? __bfloat162float(h2s[fk][fd]) : 0.f, fgb = (tid < 288) ? __bfloat162float(M.gb[fd]) : 0.f;
    const float fx1 = bfr(lo2f(fx) + lo2f(~fv));
    if (tid < 576) {
        const uint2* src = &S->part[(size_t)b * 1152 + tid];
        uint2 a = ld_rlx2(src), c = ld_rlx2(src + 576);
#pragma unroll 1
        for (int it = 0; it < SPIN_MAX && (a.x == SENT || c.x == SENT); it++) {
            if (a.x == SENT) a = ld_rlx2(src);
            if (c.x == SENT) c = ld_rlx2(src + 576);
        }
        fin[tid] = make_float4(lo2f(~a.x) + lo2f(~c.x), hi2f(~a.x) + hi2f(~c.x), lo2f(~a.y) + lo2f(~c.y), hi2f(~a.y) + hi2f(~c.y));
    }
    CBAR();
    if (tid < 288) {
        const int part = tid & 7;
        const float* f = (const float*)fin + part * 36 + fo;
        float s = ((f[0] + f[288]) + (f[576] + f[864])) + ((f[1152] + f[1440]) + (f[1728] + f[2016]));
        s += __shfl_xor_sync(0xffffffffu, s, 1);
        s += __shfl_xor_sync(0xffffffffu, s, 2);
        s += __shfl_xor_sync(0xffffffffu, s, 4);
        const float upd = bfr(bfr(s) * rs);
        const float ov = fx1 + bfr(fgb * bfr(fh2 + upd));
        if (part == 0) out[(size_t)(2047u - (fsel & 2047u)) * D_ + fd] = __ushort_as_bfloat16((unsigned short)f2bits(ov));
    }
    if ((warp & 3) == 2 && lane == 0) asm volatile("cp.async.bulk.wait_group 0;" ::: "memory");
    }
}

typedef CUresult (*EncodeFn)(CUtensorMap*, CUtensorMapDataType, cuuint32_t, void*, const cuuint64_t*, const cuuint64_t*,
                             const cuuint32_t*, const cuuint32_t*, CUtensorMapInterleave, CUtensorMapSwizzle,
                             CUtensorMapL2promotion, CUtensorMapFloatOOBfill);

static void make_map(EncodeFn fn, CUtensorMap* m, const void* ptr, uint64_t cols, uint64_t rows, uint32_t bc, uint32_t br,
                     CUtensorMapSwizzle sw) {
    cuuint64_t dims[2] = {cols, rows};
    cuuint64_t strides[1] = {cols * 2};
    cuuint32_t box[2] = {bc, br};
    cuuint32_t es[2] = {1, 1};
    CUresult rc = fn(m, CU_TENSOR_MAP_DATA_TYPE_BFLOAT16, 2, (void*)ptr, dims, strides, box, es, CU_TENSOR_MAP_INTERLEAVE_NONE,
                     sw, CU_TENSOR_MAP_L2_PROMOTION_NONE, CU_TENSOR_MAP_FLOAT_OOB_FILL_NONE);
    (void)rc;
}

static void launch(void* const* d_in, const int* in_sizes, int n_in, void* d_out, int out_size) {
    static EncodeFn enc = nullptr;
    static CUtensorMap tmm, tmg, tmu, tmd, tmd32, tmg32, tmu32;
    static Scratch* sp = nullptr;
    static const void* cached[4] = {nullptr, nullptr, nullptr, nullptr};
    if (!enc) {
        cudaDriverEntryPointQueryResult qr;
        void* fn = nullptr;
        cudaGetDriverEntryPoint("cuTensorMapEncodeTiled", &fn, cudaEnableDefault, &qr);
        enc = (EncodeFn)fn;
        cudaFuncSetAttribute(mega_kernel, cudaFuncAttributeMaxDynamicSharedMemorySize, SMEM_TOTAL);
        cudaGetSymbolAddress((void**)&sp, g_s);
    }
    if (cached[0] != d_in[13] || cached[1] != d_in[9] || cached[2] != d_in[10] || cached[3] != d_in[11]) {
        make_map(enc, &tmm, d_in[13], 6 * D_, D_, 32, 192, CU_TENSOR_MAP_SWIZZLE_64B);
        make_map(enc, &tmg, d_in[9], F_, D_, 40, 192, CU_TENSOR_MAP_SWIZZLE_NONE);
        make_map(enc, &tmu, d_in[10], F_, D_, 40, 192, CU_TENSOR_MAP_SWIZZLE_NONE);
        make_map(enc, &tmg32, d_in[9], F_, D_, 32, 192, CU_TENSOR_MAP_SWIZZLE_64B);
        make_map(enc, &tmu32, d_in[10], F_, D_, 32, 192, CU_TENSOR_MAP_SWIZZLE_64B);
        make_map(enc, &tmd, d_in[11], D_, F_, 64, 40, CU_TENSOR_MAP_SWIZZLE_128B);
        make_map(enc, &tmd32, d_in[11], D_, F_, 64, 32, CU_TENSOR_MAP_SWIZZLE_128B);
        cached[3] = d_in[11];
        cached[0] = d_in[13]; cached[1] = d_in[9]; cached[2] = d_in[10];
    }
    mega_kernel<<<G_, NTHR, SMEM_TOTAL>>>((const bf16*)d_in[0], (const bf16*)d_in[1], (const bf16*)d_in[2], (const bf16*)d_in[3],
                                          (const bf16*)d_in[4], (const bf16*)d_in[5], (const bf16*)d_in[12], sp, (const bf16*)d_in[6],
                                          (const bf16*)d_in[8], (const bf16*)d_in[11], (bf16*)d_out, tmm, tmg, tmu, tmd, tmd32, tmg32, tmu32);
}

}

extern "C" void kernel_launch(void* const* d_in, const int* in_sizes, int n_in, void* d_out, int out_size) {
    static int mode = -1;
    if (mode < 0) mode = v5::fits() ? 1 : 0;
    if (mode) v5::launch(d_in, in_sizes, n_in, d_out, out_size);
    else v4::launch(d_in, in_sizes, n_in, d_out, out_size);
}
```

```cpp
#include <cuda_runtime.h>
#include <cuda.h>
#include <cuda_bf16.h>
#include <cuda_fp16.h>
#include <stdint.h>

namespace v5 {

#define L_ 2048
#define D_ 576
#define N_ 128
#define F_ 4608
#define G_ 120
#define NCL 15
#define NTHR 768
#define SPIN_MAX (1 << 18)

typedef __nv_bfloat16 bf16;

struct Scratch {
    float4 acc1[L_ + 8];
    float4 acc2[L_];
    uint4 h2c[136 * 72];
    float4 acc3[72 * 32];
    float4 rs[33 * 8];
    unsigned int gb[320];
};
static_assert(136 * 72 + 72 * 32 + 33 * 8 == 103 * G_, "16 B units cleared early in a launch (h2c, acc3, rs)");
__device__ __align__(1024) Scratch g_s;

#define OFF_WG 0
#define OFF_WU 46080
#define KSCR 3456
#define OFF_WM0 69120
#define OFF_STG OFF_WM0
#define OFF_MG2 86400
#define OFF_CH 92160
#define CHS 18688
#define UP 3808
#define UB 192
#define XO_TF 1216
#define XO_U8 2016
#define XO_U16 3328
#define XO_ZA 1232
#define XO_ZB 2016
#define XO_ZC 2800
#define XO_ZD 3328
#define XO_TD 16000
#define XO_K1024 18624
#define XO_DSK 18628
#define XO_KINV 18640
#define XO_KLAST 18656
#define XO_MBU 18672
#define OFF_X 185600
#define XG 672
#define XI(i) (((i) >> 1) * 5520 + ((i) & 1) * 2752)
#define XN(n) ((((n) >> 1) & 3) * XG + (2 * ((n) >> 3) + ((n) & 1)) * 80)
#define OFF_V 207616
#define VP 528
#define OFF_EK (OFF_V + 512)
#define OFF_WM2 OFF_V
#define OFF_MG1 (OFF_V + 17280)
#define OFF_SC (OFF_V + 19840)
#define OFF_C1 (OFF_V + 20640)
#define OFF_MISC 228736
#define OFF_WD OFF_CH
#define OFF_H2T (OFF_CH + 46080)
#define OFF_OUT (OFF_CH + 66560)
#define ROWP 584
#define OFF_H2S 0
#define OFF_FFR 9344
#define OFF_ACT 19584
#define OFF_RS 20480

enum { MB_WM2, MB_MG1, MB_MG2, MB_KEY, MB_V, MB_RS, MB_WG, MB_WU, MB_WD, MB_KEY2, MB_EK, MB_RS2, MB_C2, MB_CW, MB_KD, MB_OUT, MB_C1, MB_N };

struct Misc {
    union {
        __align__(16) uint4 box[4 * 14];
        unsigned int cand[128];
    };
    __align__(16) unsigned int key[256], cand2[128], sel[8];
    __align__(16) uint4 c2[20];
    __align__(16) unsigned int fin[12];
    unsigned int ga[8], wr[20];
    float cws[2];
    unsigned long long mbar[MB_N];
};
#define SMEM_TOTAL (OFF_MISC + (int)sizeof(Misc))
static_assert(SMEM_TOTAL <= 232448, "smem");

__device__ __forceinline__ float lo2f(uint32_t w) { return __uint_as_float(w << 16); }
__device__ __forceinline__ float hi2f(uint32_t w) { return __uint_as_float(w & 0xFFFF0000u); }
__device__ __forceinline__ uint32_t pack2(float lo, float hi) { uint32_t r; asm("cvt.rn.bf16x2.f32 %0, %1, %2;" : "=r"(r) : "f"(hi), "f"(lo)); return r; }
__device__ __forceinline__ float bfr(float x) { return __uint_as_float(pack2(0.f, x)); }
__device__ __forceinline__ uint32_t f2bits(float x) { return pack2(x, 0.f); }
__device__ __forceinline__ uint32_t packh(float lo, float hi) { uint32_t r; asm("cvt.rn.f16x2.f32 %0, %1, %2;" : "=r"(r) : "f"(hi), "f"(lo)); return r; }
__device__ __forceinline__ float frcp(float x) { float r; asm("rcp.approx.ftz.f32 %0, %1;" : "=f"(r) : "f"(x)); return r; }
__device__ __forceinline__ float fsqrt(float x) { float r; asm("sqrt.approx.f32 %0, %1;" : "=f"(r) : "f"(x)); return r; }
__device__ __forceinline__ float fex2(float x) { float r; asm("ex2.approx.ftz.f32 %0, %1;" : "=f"(r) : "f"(x)); return r; }
__device__ __forceinline__ float silu(float x) { return __fdividef(x, 1.0f + __expf(-x)); }
__device__ __forceinline__ uint32_t add2(uint32_t a, uint32_t b) { uint32_t r; asm("add.rn.bf16x2 %0, %1, %2;" : "=r"(r) : "r"(a), "r"(b)); return r; }
__device__ __forceinline__ uint32_t sub2(uint32_t a, uint32_t b) { uint32_t r; asm("sub.rn.bf16x2 %0, %1, %2;" : "=r"(r) : "r"(a), "r"(b)); return r; }
__device__ __forceinline__ uint32_t mul2(uint32_t a, uint32_t b) { uint32_t r; asm("mul.rn.bf16x2 %0, %1, %2;" : "=r"(r) : "r"(a), "r"(b)); return r; }
__device__ __forceinline__ uint32_t fma2(uint32_t a, uint32_t b, uint32_t c) { uint32_t r; asm("fma.rn.bf16x2 %0, %1, %2, %3;" : "=r"(r) : "r"(a), "r"(b), "r"(c)); return r; }
__device__ __forceinline__ uint32_t norm2(uint32_t x, uint32_t m, uint32_t rh, uint32_t rl) { const uint32_t d = sub2(x, m); return fma2(d, rh, mul2(d, rl)); }

__device__ __forceinline__ void mma_bf16(float* c, uint32_t a0, uint32_t a1, uint32_t a2, uint32_t a3, uint32_t b0, uint32_t b1) {
    asm volatile("mma.sync.aligned.m16n8k16.row.col.f32.bf16.bf16.f32 {%0,%1,%2,%3}, {%4,%5,%6,%7}, {%8,%9}, {%0,%1,%2,%3};\n"
                 : "+f"(c[0]), "+f"(c[1]), "+f"(c[2]), "+f"(c[3]) : "r"(a0), "r"(a1), "r"(a2), "r"(a3), "r"(b0), "r"(b1));
}
__device__ __forceinline__ void mma_f16(float* c, const uint32_t* a, uint32_t b0, uint32_t b1) {
    asm volatile("mma.sync.aligned.m16n8k16.row.col.f32.f16.f16.f32 {%0,%1,%2,%3}, {%4,%5,%6,%7}, {%8,%9}, {%0,%1,%2,%3};\n"
                 : "+f"(c[0]), "+f"(c[1]), "+f"(c[2]), "+f"(c[3]) : "r"(a[0]), "r"(a[1]), "r"(a[2]), "r"(a[3]), "r"(b0), "r"(b1));
}
__device__ __forceinline__ void ldsm_x4(uint32_t* r, uint32_t addr) {
    asm volatile("ldmatrix.sync.aligned.m8n8.x4.shared.b16 {%0,%1,%2,%3}, [%4];" : "=r"(r[0]), "=r"(r[1]), "=r"(r[2]), "=r"(r[3]) : "r"(addr) : "memory");
}
__device__ __forceinline__ void ldsm_x4_t(uint32_t* r, uint32_t addr) {
    asm volatile("ldmatrix.sync.aligned.m8n8.x4.trans.shared.b16 {%0,%1,%2,%3}, [%4];" : "=r"(r[0]), "=r"(r[1]), "=r"(r[2]), "=r"(r[3]) : "r"(addr) : "memory");
}
__device__ __forceinline__ void stsm_x4(uint32_t addr, uint32_t r0, uint32_t r1, uint32_t r2, uint32_t r3) {
    asm volatile("stmatrix.sync.aligned.m8n8.x4.shared.b16 [%0], {%1,%2,%3,%4};" ::"r"(addr), "r"(r0), "r"(r1), "r"(r2), "r"(r3) : "memory");
}
__device__ __forceinline__ void stsm_x4_t(uint32_t addr, uint32_t r0, uint32_t r1, uint32_t r2, uint32_t r3) {
    asm volatile("stmatrix.sync.aligned.m8n8.x4.trans.shared.b16 [%0], {%1,%2,%3,%4};" ::"r"(addr), "r"(r0), "r"(r1), "r"(r2), "r"(r3) : "memory");
}
__device__ __forceinline__ uint32_t movm(uint32_t a) { uint32_t r; asm volatile("movmatrix.sync.aligned.m8n8.trans.b16 %0, %1;" : "=r"(r) : "r"(a)); return r; }
__device__ __forceinline__ uint32_t lds32(uint32_t a) { uint32_t v; asm volatile("ld.shared.u32 %0, [%1];" : "=r"(v) : "r"(a)); return v; }
__device__ __forceinline__ void sts32(uint32_t a, uint32_t v) { asm volatile("st.shared.u32 [%0], %1;" ::"r"(a), "r"(v) : "memory"); }
__device__ __forceinline__ void sts16(uint32_t a, uint32_t v) { asm volatile("st.shared.u16 [%0], %1;" ::"r"(a), "h"((unsigned short)v) : "memory"); }
__device__ __forceinline__ void named_bar(int id, int n) { asm volatile("bar.sync %0, %1;" ::"r"(id), "r"(n) : "memory"); }
__device__ __forceinline__ void named_arrive(int id, int n) { asm volatile("bar.arrive %0, %1;" ::"r"(id), "r"(n) : "memory"); }
#define CBAR() asm volatile("bar.sync 0, 640;" ::: "memory")
#define PROXY_FENCE() asm volatile("fence.proxy.async.shared::cta;" ::: "memory")

#define D4(d, o) "+f"(d[o]), "+f"(d[o + 1]), "+f"(d[o + 2]), "+f"(d[o + 3])
__device__ __forceinline__ void wg32(float* d, uint32_t a0, uint32_t a1, uint32_t a2, uint32_t a3, uint64_t desc) {
    asm volatile("wgmma.mma_async.sync.aligned.m64n32k16.f32.bf16.bf16 {%0,%1,%2,%3,%4,%5,%6,%7,%8,%9,%10,%11,%12,%13,%14,%15}, {%16,%17,%18,%19}, %20, 1, 1, 1, 0;"
                 : D4(d, 0), D4(d, 4), D4(d, 8), D4(d, 12) : "r"(a0), "r"(a1), "r"(a2), "r"(a3), "l"(desc));
}
__device__ __forceinline__ void wg48(float* d, uint32_t a0, uint32_t a1, uint32_t a2, uint32_t a3, uint64_t desc) {
    asm volatile("wgmma.mma_async.sync.aligned.m64n48k16.f32.bf16.bf16 {%0,%1,%2,%3,%4,%5,%6,%7,%8,%9,%10,%11,%12,%13,%14,%15,%16,%17,%18,%19,%20,%21,%22,%23}, {%24,%25,%26,%27}, %28, 1, 1, 1, 0;"
                 : D4(d, 0), D4(d, 4), D4(d, 8), D4(d, 12), D4(d, 16), D4(d, 20) : "r"(a0), "r"(a1), "r"(a2), "r"(a3), "l"(desc));
}
__device__ __forceinline__ void wg64(float* d, uint32_t a0, uint32_t a1, uint32_t a2, uint32_t a3, uint64_t desc) {
    asm volatile("wgmma.mma_async.sync.aligned.m64n64k16.f32.bf16.bf16 {%0,%1,%2,%3,%4,%5,%6,%7,%8,%9,%10,%11,%12,%13,%14,%15,%16,%17,%18,%19,%20,%21,%22,%23,%24,%25,%26,%27,%28,%29,%30,%31}, {%32,%33,%34,%35}, %36, 1, 1, 1, 0;"
                 : D4(d, 0), D4(d, 4), D4(d, 8), D4(d, 12), D4(d, 16), D4(d, 20), D4(d, 24), D4(d, 28) : "r"(a0), "r"(a1), "r"(a2), "r"(a3), "l"(desc));
}
#define O4(d, o) "=f"(d[o]), "=f"(d[o + 1]), "=f"(d[o + 2]), "=f"(d[o + 3])
__device__ __forceinline__ void wg32z(float* d, uint32_t a0, uint32_t a1, uint32_t a2, uint32_t a3, uint64_t desc) {
    asm volatile("wgmma.mma_async.sync.aligned.m64n32k16.f32.bf16.bf16 {%0,%1,%2,%3,%4,%5,%6,%7,%8,%9,%10,%11,%12,%13,%14,%15}, {%16,%17,%18,%19}, %20, 0, 1, 1, 0;"
                 : O4(d, 0), O4(d, 4), O4(d, 8), O4(d, 12) : "r"(a0), "r"(a1), "r"(a2), "r"(a3), "l"(desc));
}
__device__ __forceinline__ void wg48z(float* d, uint32_t a0, uint32_t a1, uint32_t a2, uint32_t a3, uint64_t desc) {
    asm volatile("wgmma.mma_async.sync.aligned.m64n48k16.f32.bf16.bf16 {%0,%1,%2,%3,%4,%5,%6,%7,%8,%9,%10,%11,%12,%13,%14,%15,%16,%17,%18,%19,%20,%21,%22,%23}, {%24,%25,%26,%27}, %28, 0, 1, 1, 0;"
                 : O4(d, 0), O4(d, 4), O4(d, 8), O4(d, 12), O4(d, 16), O4(d, 20) : "r"(a0), "r"(a1), "r"(a2), "r"(a3), "l"(desc));
}
#define WG_FENCE() asm volatile("wgmma.fence.sync.aligned;" ::: "memory")
#define WG_COMMIT() asm volatile("wgmma.commit_group.sync.aligned;" ::: "memory")
#define WG_WAIT(n) asm volatile("wgmma.wait_group.sync.aligned " #n ";" ::: "memory")
#define TQ(p, k) p[2 * (k) + 1], p[2 * (k) + 2], p[2 * (k)], p[2 * (k) + 1]

__device__ __forceinline__ uint4 ld_nc4(const void* p) { uint4 v; asm volatile("ld.global.nc.v4.u32 {%0,%1,%2,%3}, [%4];" : "=r"(v.x), "=r"(v.y), "=r"(v.z), "=r"(v.w) : "l"(p)); return v; }
__device__ __forceinline__ unsigned short ld_nc16(const void* p) { unsigned short v; asm volatile("ld.global.nc.u16 %0, [%1];" : "=h"(v) : "l"(p)); return v; }
__device__ __forceinline__ uint32_t ld_nc(const void* p) { uint32_t v; asm volatile("ld.global.nc.u32 %0, [%1];" : "=r"(v) : "l"(p)); return v; }
__device__ __forceinline__ uint32_t ld_rlx(const unsigned int* p) { uint32_t v; asm volatile("ld.relaxed.gpu.global.u32 %0, [%1];" : "=r"(v) : "l"(p) : "memory"); return v; }
__device__ __forceinline__ uint2 ld_rlx2(const void* p) { uint2 v; asm volatile("ld.relaxed.gpu.global.v2.u32 {%0,%1}, [%2];" : "=r"(v.x), "=r"(v.y) : "l"(p) : "memory"); return v; }
__device__ __forceinline__ uint4 ld_rlx4(const void* p) { uint4 v; asm volatile("ld.relaxed.gpu.global.v4.u32 {%0,%1,%2,%3}, [%4];" : "=r"(v.x), "=r"(v.y), "=r"(v.z), "=r"(v.w) : "l"(p) : "memory"); return v; }
__device__ __forceinline__ void st_rlx(unsigned int* p, uint32_t v) { asm volatile("st.relaxed.gpu.global.u32 [%0], %1;" ::"l"(p), "r"(v) : "memory"); }
__device__ __forceinline__ void st_rlx2(void* p, uint32_t a, uint32_t b) { asm volatile("st.relaxed.gpu.global.v2.u32 [%0], {%1,%2};" ::"l"(p), "r"(a), "r"(b) : "memory"); }
__device__ __forceinline__ void st_rlx4(void* p, uint4 v) { asm volatile("st.relaxed.gpu.global.v4.u32 [%0], {%1,%2,%3,%4};" ::"l"(p), "r"(v.x), "r"(v.y), "r"(v.z), "r"(v.w) : "memory"); }
__device__ __forceinline__ void red_inc(unsigned int* p) { asm volatile("red.relaxed.gpu.global.add.u32 [%0], 1;" ::"l"(p) : "memory"); }

__device__ __forceinline__ void mbar_init(uint32_t a, int cnt) { asm volatile("mbarrier.init.shared::cta.b64 [%0], %1;" ::"r"(a), "r"(cnt) : "memory"); }
__device__ __forceinline__ void mbar_expect(uint32_t a, uint32_t bytes) { asm volatile("mbarrier.arrive.expect_tx.shared::cta.b64 _, [%0], %1;" ::"r"(a), "r"(bytes) : "memory"); }
__device__ __forceinline__ void mbar_wait(uint32_t a, uint32_t parity) {
    uint32_t ok = 0;
    int it = 0;
    do {
        asm volatile("{\n.reg .pred p;\nmbarrier.try_wait.parity.shared::cta.b64 p, [%1], %2;\nselp.u32 %0, 1, 0, p;\n}" : "=r"(ok) : "r"(a), "r"(parity) : "memory");
    } while (!ok && ++it < SPIN_MAX);
}
__device__ __forceinline__ bool mbar_test(uint32_t a, uint32_t parity) {
    uint32_t ok;
    asm volatile("{\n.reg .pred p;\nmbarrier.test_wait.parity.shared::cta.b64 p, [%1], %2;\nselp.u32 %0, 1, 0, p;\n}" : "=r"(ok) : "r"(a), "r"(parity) : "memory");
    return __all_sync(0xffffffffu, ok);
}
__device__ __forceinline__ void tma2d(uint32_t dst, const CUtensorMap* tm, int c0, int c1, uint32_t mbar) {
    asm volatile("cp.async.bulk.tensor.2d.shared::cluster.global.mbarrier::complete_tx::bytes [%0], [%1, {%3, %4}], [%2];"
                 ::"r"(dst), "l"(tm), "r"(mbar), "r"(c0), "r"(c1) : "memory");
}
__device__ __forceinline__ void bulk_s2g(void* dst, uint32_t src, uint32_t bytes) {
    asm volatile("cp.async.bulk.global.shared::cta.bulk_group [%0], [%1], %2;" ::"l"(dst), "r"(src), "r"(bytes) : "memory");
}
__device__ __forceinline__ uint32_t ld_acq(const unsigned int* p) { uint32_t v; asm volatile("ld.acquire.gpu.global.u32 %0, [%1];" : "=r"(v) : "l"(p) : "memory"); return v; }
__device__ __forceinline__ void bulk_pf(const void* src, uint32_t bytes) { asm volatile("cp.async.bulk.prefetch.L2.global [%0], %1;" ::"l"(src), "r"(bytes) : "memory"); }

struct cplx { float x, y; };
__device__ __forceinline__ cplx cmul(cplx a, cplx b) { cplx r; r.x = a.x * b.x - a.y * b.y; r.y = a.x * b.y + a.y * b.x; return r; }
__device__ __forceinline__ cplx csq(cplx a) { cplx r; r.x = a.x * a.x - a.y * a.y; r.y = 2.0f * a.x * a.y; return r; }
__device__ __forceinline__ uint32_t hcm(uint32_t x, uint32_t y, uint32_t yp) {
    const __half2 X = *(const __half2*)&x, Y = *(const __half2*)&y, YP = *(const __half2*)&yp;
    const __half2 r = __hfma2(__high2half2(X), YP, __hmul2(__low2half2(X), Y));
    return *(const uint32_t*)&r;
}
__device__ __forceinline__ void ln_stats(float s1, float s2, float& meanb, float& rinv) {
    const float mean = s1 * (1.0f / D_);
    const float den = bfr(fsqrt(bfr(bfr(fmaxf(fmaf(-mean, mean, s2 * (1.0f / D_)), 0.f)) + 1e-5f)));
    meanb = bfr(mean);
    rinv = frcp(den);
}

__device__ __forceinline__ int fresh_tid() { int v; asm volatile("mov.u32 %0, %tid.x;" : "=r"(v)); return v - 128; }
__device__ __forceinline__ void mma_k8(float* c, uint32_t a0, uint32_t a1, uint32_t b0) {
    asm volatile("mma.sync.aligned.m16n8k8.row.col.f32.bf16.bf16.f32 {%0,%1,%2,%3}, {%4,%5}, {%6}, {%0,%1,%2,%3};\n"
                 : "+f"(c[0]), "+f"(c[1]), "+f"(c[2]), "+f"(c[3]) : "r"(a0), "r"(a1), "r"(b0));
}
__device__ __forceinline__ void ldsm_x2(uint32_t* r, uint32_t addr) {
    asm volatile("ldmatrix.sync.aligned.m8n8.x2.shared.b16 {%0,%1}, [%2];" : "=r"(r[0]), "=r"(r[1]) : "r"(addr) : "memory");
}
__device__ __forceinline__ void ldsm_x2_t(uint32_t* r, uint32_t addr) {
    asm volatile("ldmatrix.sync.aligned.m8n8.x2.trans.shared.b16 {%0,%1}, [%2];" : "=r"(r[0]), "=r"(r[1]) : "r"(addr) : "memory");
}
__device__ __forceinline__ void stsm_x2(uint32_t addr, uint32_t r0, uint32_t r1) {
    asm volatile("stmatrix.sync.aligned.m8n8.x2.shared.b16 [%0], {%1,%2};" ::"r"(addr), "r"(r0), "r"(r1) : "memory");
}
__device__ __forceinline__ uint4 lds128(uint32_t a) { uint4 v; asm volatile("ld.shared.v4.u32 {%0,%1,%2,%3}, [%4];" : "=r"(v.x), "=r"(v.y), "=r"(v.z), "=r"(v.w) : "r"(a) : "memory"); return v; }
__device__ __forceinline__ uint32_t mapa(uint32_t a, uint32_t r) { uint32_t o; asm("mapa.shared::cluster.u32 %0, %1, %2;" : "=r"(o) : "r"(a), "r"(r)); return o; }
__device__ __forceinline__ void sta4(uint32_t dst, uint4 v, uint32_t mb) {
    asm volatile("st.async.weak.shared::cluster.mbarrier::complete_tx::bytes.v4.b32 [%0], {%1,%2,%3,%4}, [%5];" ::"r"(dst), "r"(v.x), "r"(v.y), "r"(v.z), "r"(v.w), "r"(mb) : "memory");
}
__device__ __forceinline__ void sta2(uint32_t dst, uint32_t a, uint32_t b, uint32_t mb) {
    asm volatile("st.async.weak.shared::cluster.mbarrier::complete_tx::bytes.v2.b32 [%0], {%1,%2}, [%3];" ::"r"(dst), "r"(a), "r"(b), "r"(mb) : "memory");
}
__device__ __forceinline__ void mbar_arrive(uint32_t a) { asm volatile("mbarrier.arrive.shared::cta.b64 _, [%0];" ::"r"(a) : "memory"); }
__device__ __forceinline__ void red4(float4* p, float a, float b, float c) {
    asm volatile("red.relaxed.gpu.global.add.v4.f32 [%0], {%1,%2,%3,%4};" ::"l"(p), "f"(a), "f"(b), "f"(c), "f"(1.0f) : "memory");
}
__device__ __forceinline__ void red4p(bool on, float4* p, float a, float b, float c) {
    asm volatile("{\n.reg .pred q;\nsetp.ne.u32 q, %5, 0;\n@q red.relaxed.gpu.global.add.v4.f32 [%0], {%1,%2,%3,%4};\n}" ::"l"(p), "f"(a), "f"(b), "f"(c), "f"(1.0f), "r"((uint32_t)on) : "memory");
}
__device__ __forceinline__ float4 atom4(float4* p, float a, float b, float c, float d) {
    float4 v;
    asm volatile("atom.relaxed.gpu.global.add.v4.f32 {%0,%1,%2,%3}, [%4], {%5,%6,%7,%8};" : "=f"(v.x), "=f"(v.y), "=f"(v.z), "=f"(v.w) : "l"(p), "f"(a), "f"(b), "f"(c), "f"(d) : "memory");
    return v;
}
__device__ __forceinline__ uint2 lds64(uint32_t a) { uint2 v; asm volatile("ld.shared.v2.u32 {%0,%1}, [%2];" : "=r"(v.x), "=r"(v.y) : "r"(a) : "memory"); return v; }
__device__ __forceinline__ float4 ld_rlx4f(const float4* p) { float4 v; asm volatile("ld.relaxed.gpu.global.v4.f32 {%0,%1,%2,%3}, [%4];" : "=f"(v.x), "=f"(v.y), "=f"(v.z), "=f"(v.w) : "l"(p) : "memory"); return v; }
__device__ __forceinline__ void tma5d_st(const CUtensorMap* tm, int c0, int c4, uint32_t src) {
    asm volatile("cp.async.bulk.tensor.5d.global.shared::cta.bulk_group [%0, {%2, %4, %4, %4, %3}], [%1];" ::"l"(tm), "r"(src), "r"(c0), "r"(c4), "r"(0) : "memory");
}
__device__ __forceinline__ void tma2d_pf(const CUtensorMap* tm, int c0, int c1) {
    asm volatile("cp.async.bulk.prefetch.tensor.2d.L2.global [%0, {%1, %2}];" ::"l"(tm), "r"(c0), "r"(c1) : "memory");
}
__device__ __forceinline__ void pace(int clk) {
    const long long c0 = clock64();
    int it = 0;
    while (clock64() - c0 < clk && ++it < 4096) { }
}
__device__ __forceinline__ uint32_t sign2(uint32_t a) { uint32_t r; asm("prmt.b32 %0, %1, 0, 0xBB99;" : "=r"(r) : "r"(a)); return r; }
#define MB(i) (sb + OFF_MISC + (uint32_t)offsetof(Misc, mbar) + 8 * (i))
__device__ __forceinline__ void conv_channel(unsigned char* sm, uint32_t rank, uint32_t fixa, uint32_t fixv) {
    Misc& M = *(Misc*)(sm + OFF_MISC);
    const uint32_t sb = (uint32_t)__cvta_generic_to_shared(sm);
    const int tid = fresh_tid(), lane = tid & 31, g = lane >> 2, t = lane & 3, lr = lane & 7, lm = lane >> 3;
    const int warp_ = __shfl_sync(0xffffffffu, tid >> 5, 0), wgi = warp_ >> 2, w = warp_ & 3;
    const uint32_t cb = sb + OFF_CH + wgi * CHS;
    float D[32];
    const uint32_t dlo = ((cb & 0x3FFFF) >> 4) | ((UP >> 4) << 16);
#define DS(o, z, bl) (((uint64_t)(128 >> 4) << 32) | (uint64_t)(dlo + (o) / 16 + (((z) & 1) ? 0 : UP / 8) - ((z) >> 1) * (bl)))
    {
        const uint32_t pf = cb + XO_TF + (w >> 1) * UP + (8 + 16 * (w & 1) + g - 2 * t) * 4;
        uint32_t p[13], q[9];
        named_bar(1 + wgi, 128);
        if (fixa) sts16(fixa, fixv);
#pragma unroll
        for (int s = 0; s < 13; s++) p[s] = lds32(pf + s * 32);
        {
            const uint32_t a8 = cb + UB + t * UP + g * 16 + w * 128, b8 = cb + XO_U8 + lm * UP + lr * 16 + w * 128;
            const uint32_t a16 = cb + UB + (2 * (lr & 1) + (lm & 1)) * UP + ((lr >> 1) + 2 * (lm & 2)) * 16 + w * 128;
            const uint32_t b16 = cb + XO_U16 + (2 * (w & 1) + (lm >> 1)) * UP + (lane & 15) * 16 + (w >> 1) * 256;
            uint32_t r[3][4];
            mbar_wait(cb + XO_MBU, 0);
            ldsm_x4_t(r[0], a8);
            ldsm_x4_t(r[1], a16);
            if (w < 2) ldsm_x4_t(r[2], a8 + 512);
            stsm_x4(b8, r[0][0], r[0][1], r[0][2], r[0][3]);
            stsm_x4(b16, r[1][0], r[1][1], r[1][2], r[1][3]);
            if (w < 2) stsm_x4(b8 + 512, r[2][0], r[2][1], r[2][2], r[2][3]);
        }
        PROXY_FENCE();
        named_bar(1 + wgi, 128);
        {
            float Z8[24], Z16[16];
            uint32_t z8[12];
            WG_FENCE();
#pragma unroll
            for (int e = 0; e < 6; e++) {
                if (e == 0) wg48z(Z8, TQ(p, e), DS(XO_U8, e, 8));
                else wg48(Z8, TQ(p, e), DS(XO_U8, e, 8));
            }
            WG_COMMIT();
            WG_WAIT(0);
            asm volatile("setmaxnreg.inc.sync.aligned.u32 88;");
#pragma unroll
            for (int s = 0; s < 9; s++) q[s] = lds32(pf + 2 * UP + s * 32);
#pragma unroll
            for (int i = 0; i < 12; i++) asm volatile("cvt.rn.bf16x2.f32 %0, %1, %2;" : "=r"(z8[i]) : "f"(Z8[2 * i + 1]), "f"(Z8[2 * i]));
            WG_FENCE();
#pragma unroll
            for (int e = 0; e < 4; e++) {
                if (e == 0) wg32z(Z16, TQ(q, e), DS(XO_U16, e, 16));
                else wg32(Z16, TQ(q, e), DS(XO_U16, e, 16));
            }
            WG_COMMIT();
            WG_WAIT(0);
            named_bar(1 + wgi, 128);
            const uint32_t za = cb + ((w >> 1) ? XO_ZB : XO_ZA) + t * UP + (4 * (w & 1) + (g & 3) + 8 * (g >> 2)) * 16;
#pragma unroll
            for (int i = 0; i < 3; i++) stsm_x4(za + i * 256, z8[4 * i], z8[4 * i + 1], z8[4 * i + 2], z8[4 * i + 3]);
            const uint32_t zc = cb + ((w >> 1) ? XO_ZD : XO_ZC) + (2 * (lr & 1) + (lm >> 1)) * UP + (((lane & 15) >> 1) + 8 * (w & 1)) * 16;
#pragma unroll
            for (int ob = 0; ob < 2; ob++) stsm_x4(zc + ob * 256, pack2(Z16[8 * ob], Z16[8 * ob + 1]), pack2(Z16[8 * ob + 2], Z16[8 * ob + 3]), pack2(Z16[8 * ob + 4], Z16[8 * ob + 5]), pack2(Z16[8 * ob + 6], Z16[8 * ob + 7]));
        }
    }
    uint32_t pa = cb + XO_TD + (40 + 256 * (w >> 1) + 16 * (w & 1) + g - 2 * t) * 4;
    uint32_t pA[9], pB[7];
#pragma unroll
    for (int i = 0; i < 32; i++) D[i] = 0.f;
    {
        const uint4* pq = M.box + (6 + g - 2 * t);
        auto at = [&](int k) { const int c = 2 * (w & 1) + k; return cb + c * UP + (c < 0 ? 4 * UP - 16 : 0) + lr * 16 + (w >> 1) * 128; };
        const int h1 = lm & 1;
        const uint32_t h2 = (lm >> 1) * 256;
        uint32_t bA[3][4], bB[2][4], bB3[2], bC[2][4], bD[2][4], bU[4], bU1[2];
        const uint32_t e0 = at(h1) + h2, e1 = at(h1 - 1) + h2, e2 = at(h1 - 2) + h2, e3 = at(h1 - 3) + h2, e4 = at(lm - 2), e5 = at(-1) + lm * 256;
        const uint4 m0 = pq[0], m1 = pq[14], m2 = pq[28];
        const uint32_t k2 = lds32(cb + XO_K1024), x0 = m2.w & k2, x8 = pq[42].x & k2;
        ldsm_x4(bU, e0 + UB); ldsm_x2(bU1, e5 + UB);
#pragma unroll
        for (int c = 0; c < 2; c++) mma_bf16(D + 16 + 8 * c, x0, x8, 0u, x0, bU[2 * c], bU[2 * c + 1]);
        named_bar(1 + wgi, 128);
        ldsm_x4(bA[0], e0 + XO_ZA); ldsm_x4(bA[1], e2 + XO_ZA); ldsm_x4(bA[2], e4 + XO_ZA + 512);
        ldsm_x4(bB[0], e0 + XO_ZB); ldsm_x2(bB3, e0 + XO_ZB + 512); ldsm_x4(bB[1], e5 + XO_ZB);
        mma_bf16(D + 8, m0.x, m0.y, 0u, m0.x, bA[0][0], bA[0][1]);
        mma_bf16(D + 16, m0.x, m0.y, 0u, m0.x, bA[0][2], bA[0][3]);
        mma_bf16(D + 24, m0.x, m0.y, 0u, m0.x, bA[2][2], bA[2][3]);
        mma_bf16(D + 8, m0.z, 0u, m0.y, m0.z, bA[1][0], bA[1][1]);
        mma_bf16(D + 16, m0.z, 0u, m0.y, m0.z, bA[1][2], bA[1][3]);
        mma_bf16(D + 24, m0.z, 0u, m0.y, m0.z, bA[2][0], bA[2][1]);
        ldsm_x4(bC[0], e1 + XO_ZC); ldsm_x4(bC[1], e3 + XO_ZC);
        mma_bf16(D + 8, m0.w, m1.x, 0u, m0.w, bB[0][0], bB[0][1]);
        mma_bf16(D + 16, m0.w, m1.x, 0u, m0.w, bB[0][2], bB[0][3]);
        mma_bf16(D + 24, m0.w, m1.x, 0u, m0.w, bB3[0], bB3[1]);
        mma_k8(D + 8, m1.x, 0u, bB[1][0]);
        ldsm_x4(bD[0], e0 + XO_ZD); ldsm_x4(bD[1], e2 + XO_ZD);
#pragma unroll
        for (int c = 0; c < 2; c++) mma_bf16(D + 16 + 8 * c, m1.x, 0u, x8, 0u, bB[1][1 + c], bU1[c]);
#pragma unroll
        for (int s = 0; s < 9; s++) pA[s] = lds32(pa + s * 32);
#pragma unroll
        for (int c = 0; c < 2; c++) mma_bf16(D + 16 + 8 * c, m1.y, m1.z, 0u, m1.y, bC[0][2 * c], bC[0][2 * c + 1]);
#pragma unroll
        for (int c = 0; c < 2; c++) mma_bf16(D + 16 + 8 * c, m1.w, 0u, m1.z, m1.w, bC[1][2 * c], bC[1][2 * c + 1]);
#pragma unroll
        for (int c = 0; c < 2; c++) mma_bf16(D + 16 + 8 * c, m2.x, m2.y, 0u, m2.x, bD[0][2 * c], bD[0][2 * c + 1]);
#pragma unroll
        for (int c = 0; c < 2; c++) mma_bf16(D + 16 + 8 * c, m2.z, 0u, m2.y, m2.z, bD[1][2 * c], bD[1][2 * c + 1]);
    }
    {
        WG_FENCE();
#pragma unroll
        for (int q = 0; q < 4; q++) wg64(D, TQ(pA, q), DS(UB, q, 1));
        WG_COMMIT();
#pragma unroll
        for (int j = 0; j < 5; j++) {
            uint32_t* pp = (j & 1) ? pA : pB;
            if (j) WG_WAIT(1);
            if (j == 4 && w < 2) pa -= (1024 + 34 * 4) + 64 * w;
#pragma unroll
            for (int s = 0; s < 7; s++) pp[s] = lds32(pa + 256 + 192 * j + s * 32);
            WG_FENCE();
#pragma unroll
            for (int q = 0; q < 3; q++) wg64(D, TQ(pp, q), DS(UB, 4 + 3 * j + q, 1));
            WG_COMMIT();
        }
        WG_WAIT(1);
    }
    {
        const int tid = fresh_tid(), lane = tid & 31, lr = lane & 7, lm = lane >> 3;
        uint32_t u[2][4];
        const uint32_t ua = cb + UB + 2 * (w & 1) * UP + lm * 256 + (w >> 1) * 128 + lr * 16;
        ldsm_x4_t(u[0], ua); ldsm_x4_t(u[1], ua + UP);
        const uint32_t dk2 = __byte_perm(lds32(cb + XO_DSK), 0, (rank & 1) ? 0x3232 : 0x1010);
        unsigned char* xw = sm + (cb - sb) + XO_TF + w * UP + (w >> 1) * 512 + lane * 16;
        const unsigned char* xr = sm + (cb - sb) + XO_TF + (w ^ 2) * UP + lane * 16;
        named_bar(1 + wgi, 128);
#pragma unroll
        for (int i = 0; i < 8; i++) u[i >> 2][i & 3] = mul2(u[i >> 2][i & 3], dk2);
        mbar_wait(MB(MB_C2), 0);
        const uint32_t ga2 = M.ga[wgi];
        WG_WAIT(0);
#pragma unroll
        for (int j = 0; j < 4; j++) if (j < 3 || w < 2) *(float4*)(xw + j * 512) = make_float4(D[8 * j + 4], D[8 * j + 5], D[8 * j + 6], D[8 * j + 7]);
        named_bar(1 + wgi, 128);
#pragma unroll
        for (int j = 0; j < 4; j++) {
            float4 v = make_float4(0.f, 0.f, 0.f, 0.f);
            if (j || w >= 2) v = *(const float4*)(xr + j * 512);
            D[8 * j] += v.x; D[8 * j + 1] += v.y; D[8 * j + 2] += v.z; D[8 * j + 3] += v.w;
        }
#pragma unroll
        for (int h = 0; h < 2; h++) {
            const uint32_t rb = mapa(sb, 2 * w + h);
#pragma unroll
            for (int j = 0; j < 4; j++) u[h][j] = mul2(ga2, add2(pack2(D[8 * j + 2 * h], D[8 * j + 2 * h + 1]), u[h][j]));
            sta4(rb + OFF_V + (8 * wgi + rank) * VP + lane * 16, make_uint4(u[h][0], u[h][1], u[h][2], u[h][3]), rb + (MB(MB_V) - sb));
        }
    }
}

#define M2W 4
#define WS 0x3210
#define WW 0x1111
#define WMS(p) if (w == 3) { if (p == 0) CL_WAIT(); if (lane == 0) { _Pragma("unroll") for (int i = 2; i < 6; i++) if (((WS >> (4 * (i - 2))) & 15) == p && ((WW >> (4 * (i - 2))) & 15) == wgi) tma2d(sb + (i == 5 ? OFF_WM0 + 11520 : OFF_WM2 + (i - 2) * 5760), &tm_wm, i * D_ + 40 * cl, 72 * rk, MB(MB_WM2)); } __syncwarp(); }
#define PQT 10
#define PQD 400
#define L2P 2
#define L2M 2
#define PDE 300
#define WMD 400
#define PFG 2
#define CWP 200
#define CWD 3000
#define ROW(key) (((~(key) << 2) & 0xE0u) | ((~(key) >> 6) & 24u) | ((~(key) >> 11) & 6u) | ((~(key) >> 8) & 1u))
#define RKT (((rk & 4) << 6) | ((rk & 3) << 3))
#define MINE(key) ((~(key) & 0x8C0u) == (uint32_t)(RKT << 3))
#define CE(a, b) { const uint32_t hi_ = max(a, b); b = min(a, b); a = hi_; }
#define POP(k, m) if (k.x == m) { k.x = k.y; k.y = k.z; k.z = k.w; k.w = 0u; }
#define CGT(c, a, b, n) asm volatile("{\n.reg .pred p;\nsetp.gt.u32 p, %1, %2;\n@p add.u32 %0, %0, " #n ";\n}" : "+r"(c) : "r"(a), "r"(b))
#define CL_ARRIVE() asm volatile("barrier.cluster.arrive.relaxed.aligned;" ::: "memory")
#define CL_WAIT() asm volatile("barrier.cluster.wait.aligned;" ::: "memory")
__global__ void __cluster_dims__(8, 1, 1) __launch_bounds__(NTHR, 1)
clus_kernel(const bf16* __restrict__ x, const bf16* __restrict__ logAr, const bf16* __restrict__ Aim, const bf16* __restrict__ Cr, const bf16* __restrict__ Ci,
            const bf16* __restrict__ logdt, const bf16* __restrict__ c_in, Scratch* __restrict__ S, const bf16* __restrict__ Dskip,
            const bf16* __restrict__ w_r, const bf16* __restrict__ w_mod, bf16* __restrict__ out,
            const __grid_constant__ CUtensorMap tm_wm, const __grid_constant__ CUtensorMap tm_wg,
            const __grid_constant__ CUtensorMap tm_wu, const __grid_constant__ CUtensorMap tm_wd, const __grid_constant__ CUtensorMap tm_out) {
    extern __shared__ __align__(1024) unsigned char sm[];
    Misc& M = *(Misc*)(sm + OFF_MISC);
    const uint32_t sb = (uint32_t)__cvta_generic_to_shared(sm);
    const int tid = threadIdx.x < 128 ? threadIdx.x + 640 : threadIdx.x - 128, warp = __shfl_sync(0xffffffffu, tid >> 5, 0), lane = tid & 31;
    const int g = lane >> 2, t = lane & 3, lr = lane & 7, lm = lane >> 3;
    const int wgi = warp >> 2, w = warp & 3;
    const int b = blockIdx.x, cl = b >> 3, rk = b & 7;
    auto mod_ld = [&](uint32_t (*a)[4], uint32_t s0, uint32_t s1, int i) {
        const uint32_t wa = sb + ((lm & 1) ? s1 : s0) + (lr + 8 * (lm >> 1)) * 80 + i * 16;
#pragma unroll
        for (int ks = 0; ks < 4; ks++) ldsm_x4_t(a[ks], wa + ks * 1280);
        ldsm_x2_t(a[4], wa + 5120);
    };
    auto mod_mma2 = [&](float* d, float* e, uint32_t (*a)[4], uint32_t (*c)[4], const uint32_t* bs) {
        mma_k8(d, a[4][0], a[4][1], bs[8]); mma_k8(e, c[4][0], c[4][1], bs[8]);
#pragma unroll
        for (int ks = 0; ks < 4; ks++) {
            mma_bf16(d, a[ks][0], a[ks][1], a[ks][2], a[ks][3], bs[2 * ks], bs[2 * ks + 1]);
            mma_bf16(e, c[ks][0], c[ks][1], c[ks][2], c[ks][3], bs[2 * ks], bs[2 * ks + 1]);
        }
    };
    auto mod_st = [&](const float* d, uint32_t dst, int mb) {
#pragma unroll
        for (int h = 0; h < 2; h++) {
            const uint32_t rb = mapa(sb, t + 4 * h);
            sta2(rb + dst + g * 8, __float_as_uint(d[0]), __float_as_uint(d[2]), rb + (MB(mb) - sb));
        }
    };
    if (wgi == 5) {
        CL_ARRIVE();
        const uint32_t c_a = ld_nc((const uint32_t*)c_in + 36 * rk + lane), c_b = ld_nc((const uint32_t*)c_in + 36 * rk + 32 + t);
        {
            pace(WMD);
            const char* wp = (const char*)(w_mod + (72 * rk + 18 * w) * (6 * D_) + 40 * cl);
#pragma unroll
            for (int i = 0; i < 3; i++) {
                const uint32_t c = lane + 32 * i, row = (c * 205) >> 10;
                const char* p = wp + (row * (12 * D_ - 80) + 16 * c);
                if (c < 90) {
                    asm volatile("cp.async.cg.shared.global [%0], [%1], 16;" ::"r"(sb + OFF_WM0 + 1440 * w + 16 * c), "l"(p) : "memory");
                    asm volatile("cp.async.cg.shared.global [%0], [%1], 16;" ::"r"(sb + OFF_WM0 + 5760 + 1440 * w + 16 * c), "l"(p + 2 * D_) : "memory");
                }
            }
            if (w == 3 && lane < 20)
                asm volatile("cp.async.ca.shared.global [%0], [%1], 4, %2;" ::"r"(sb + OFF_MISC + (uint32_t)offsetof(Misc, c2) + 12 + 16 * lane), "l"((const uint32_t*)w_r + min(20 * cl + lane, D_ / 2 - 1)),
                             "r"(20 * cl + lane < D_ / 2 ? 4 : 0) : "memory");
            asm volatile("cp.async.commit_group;" ::: "memory");
        }
        auto gsum = [&](uint32_t a, int pitch) {
            float4 s = make_float4(0.f, 0.f, 0.f, 0.f);
#pragma unroll
            for (int i = 0; i < 8; i++) { const float4 q = *(const float4*)(sm + a + i * pitch); s.x += q.x; s.y += q.y; s.z += q.z; s.w += q.w; }
            return make_uint2(pack2(s.x, s.z), pack2(s.y, s.w));
        };
        auto one_plus = [&](uint32_t v) { return pack2(1.0f + lo2f(v), 1.0f + hi2f(v)); };
        {
            uint32_t bs[9], a[5][4], c[5][4];
            float d[4] = {0.f, 0.f, 0.f, 0.f}, e[4] = {0.f, 0.f, 0.f, 0.f};
            const uint32_t sc = pack2(silu(lo2f(c_a)), silu(hi2f(c_a)));
            bs[8] = pack2(silu(lo2f(c_b)), silu(hi2f(c_b)));
            if (w == 2) { sts32(sb + OFF_SC + 4 * lane, sc); sts32(sb + OFF_SC + 128 + 4 * t, bs[8]); }
#pragma unroll
            for (int ks = 0; ks < 8; ks++) bs[ks] = __shfl_sync(0xffffffffu, sc, 4 * ks + t);
            CL_WAIT();
            asm volatile("cp.async.wait_group 0;" ::: "memory");
            named_bar(10, 128);
            mod_ld(a, OFF_WM0 + 5760, OFF_WM0, w);
            mod_ld(c, OFF_WM0 + 5760, OFF_WM0, 4);
            mod_mma2(d, e, a, c, bs);
            mod_st(d, OFF_MG1 + rk * 320 + 64 * w, MB_MG1);
            if (w == 1) mod_st(e, OFF_MG1 + rk * 320 + 256, MB_MG1);
        }
        {
            const int n0 = 8 * w + 2 * (rk & 1), n1 = 8 * w + ((n0 + 4 + t) & 7);
            const float4* ap = &S->acc1[256 * rk + 8 * (n0 + t) + g];
            const float4* aq = &S->acc1[256 * rk + 8 * n1 + g];
            named_bar(9, 640);
            float4 pa = ld_rlx4f(ap), pb = ld_rlx4f(aq);
            if (w == 3) {
                mbar_wait(MB(MB_MG1), 0);
                const uint2 v = gsum(OFF_MG1 + 16 * min(lane, 19), 320);
                const uint32_t c1 = one_plus(v.x);
                if (lane < 20) *(uint4*)(sm + OFF_C1 + 16 * lane) = make_uint4(__byte_perm(c1, 0, 0x1010), __byte_perm(v.y, 0, 0x1010), __byte_perm(c1, 0, 0x3232), __byte_perm(v.y, 0, 0x3232));
                __syncwarp();
                named_arrive(10, 128);
            }
            uint32_t xq[2][5][4];
            uint2 cc[5];
            const uint32_t xa = sb + OFF_X + XI(2 * lm + (lr & 1)) + XN(n0 + (lr >> 1)), xb = sb + OFF_X + XI(2 * lm + (lr & 1)) + XN(8 * w + ((n0 + 4 + (lr >> 1)) & 7));
            const uint32_t ua = mapa(sb, g) + OFF_CH;
#pragma unroll
            for (int j = 0; j < 5; j++) ldsm_x4_t(xq[0][j], xa + 16 * j);
#pragma unroll 1
            for (int it = 0; it < SPIN_MAX && (pa.w != (float)NCL || pb.w != (float)NCL); it++) {
                pa = ld_rlx4f(ap); pb = ld_rlx4f(aq);
            }
            __syncwarp();
            if (w == 2 && lane < PFG) tma2d_pf(&tm_wg, 40 * b, 192 * lane);
            __syncwarp();
            float m0, r0, m1, r1;
            ln_stats(pa.x, pa.y, m0, r0);
            ln_stats(pb.x, pb.y, m1, r1);
            const uint32_t rh = pack2(r0, r1), rl = pack2(r0 - lo2f(rh), r1 - hi2f(rh));
            const uint32_t stage = sb + OFF_STG + w * 512;
            stsm_x4_t(stage + lane * 16, pack2(m0, m1), rh, rl, rl);
            __syncwarp();
            if (w != 3) named_bar(10, 128);
            uint4 st[2][3];
#pragma unroll
            for (int q = 0; q < 2; q++)
#pragma unroll
                for (int i = 0; i < 3; i++) st[q][i] = lds128(stage + 128 * i + (2 * t + q) * 16);
#pragma unroll
            for (int j = 0; j < 5; j++) cc[j] = *(const uint2*)(sm + OFF_C1 + 64 * j + 8 * g);
            ldsm_x4_t(xq[1][0], xb);
            const uint32_t ub = ua + (rk & 3) * UP + UB + (8 * w + 8 * (rk >> 2)) * 16, u0 = ub + (n0 + t) * 16, u1 = ub + n1 * 16;
#pragma unroll
            for (int j = 0; j < 5; j++) {
                if (j >= 2 && cl == 14) break;
                if (j < 4) ldsm_x4_t(xq[1][j + 1], xb + 16 * (j + 1));
#pragma unroll
                for (int q = 0; q < 2; q++) {
                    const uint4 sm_ = st[q][0], sh = st[q][1], sl = st[q][2];
                    const uint32_t v0 = add2(mul2(norm2(xq[q][j][0], sm_.x, sh.x, sl.x), cc[j].x), cc[j].y), v1 = add2(mul2(norm2(xq[q][j][1], sm_.y, sh.y, sl.y), cc[j].x), cc[j].y);
                    const uint32_t v2 = add2(mul2(norm2(xq[q][j][2], sm_.z, sh.z, sl.z), cc[j].x), cc[j].y), v3 = add2(mul2(norm2(xq[q][j][3], sm_.w, sh.w, sl.w), cc[j].x), cc[j].y);
                    asm volatile("{\n.reg .pred p;\nsetp.ne.u32 p, %6, %7;\n"
                                 "@p st.async.weak.shared::cluster.mbarrier::complete_tx::bytes.v4.b32 [%0], {%1,%2,%3,%4}, [%5];\n"
                                 "@!p st.shared.v4.b32 [%0], {%1,%2,%3,%4};\n}"
                                 ::"r"((q ? u1 : u0) + j * CHS), "r"(v0), "r"(v1), "r"(v2), "r"(v3), "r"(ua + j * CHS + XO_MBU), "r"(g), "r"(rk) : "memory");
                }
                __syncwarp();
                if (lane == 0) mbar_arrive(sb + OFF_CH + XO_MBU + j * CHS);
            }
        }
        asm volatile("setmaxnreg.dec.sync.aligned.u32 40;");
        {
        int cl;
        asm volatile("mov.u32 %0, %clusterid.x;" : "=r"(cl));
        const int w = __shfl_sync(0xffffffffu, (fresh_tid() >> 5) & 3, 0);
        uint32_t gz = 0;
        if (w) named_arrive(11, 128); else named_bar(11, 128);
        if (w == 0) {
            const int lane = fresh_tid() & 31;
            mbar_wait(MB(MB_KD), 0);
            PROXY_FENCE();
            if (lane == 0) {
#pragma unroll
                for (int i = 0; i < 3; i++) tma2d(sb + OFF_WG + i * 15360, &tm_wg, 40 * b, 192 * i, MB(MB_WG));
#pragma unroll 1
                for (int i = 0; i < 2; i++) { tma2d(sb + OFF_WU + i * 15360, &tm_wu, 40 * b, 192 * i, MB(MB_WU)); }
                tma2d_pf(&tm_wu, 40 * b, 384);
                mbar_wait(MB(MB_C2), 0);
                PROXY_FENCE();
                tma2d(sb + OFF_WU + 2 * 15360, &tm_wu, 40 * b, 384, MB(MB_WU));
#pragma unroll 1
                for (int i = 0; i < 9; i++) { pace(PDE); tma2d_pf(&tm_wd, 64 * i, 40 * b); }
                mbar_wait(MB(MB_WU), 0);
            }
            __syncwarp();
        } else if (w == 1) {
            const int lane = fresh_tid() & 31;
            uint4* rp = S->h2c + 103 * b + lane;
#pragma unroll
            for (int i = 0; i < 4; i++) if (i < 3 || lane < 7) st_rlx4(rp + 32 * i, make_uint4(0, 0, 0, 0));
            uint32_t z = 0x3F800000u;
#pragma unroll
            for (int i = 0; i < 4; i++) if (i < 3 || lane < 7) z |= ld_rlx((const unsigned int*)(rp + 32 * i));
            if (lane == 0) asm volatile("red.relaxed.gpu.global.add.f32 [%0], %1;" ::"l"(&S->acc1[L_].z), "f"(__uint_as_float(z)) : "memory");
        } else if (w == 2) {
            if ((fresh_tid() & 31) == 0) {
                float4 v;
                int it = 0;
                pace(CWD);
                for (;;) { v = ld_rlx4f(&S->acc1[L_]); if (++it >= SPIN_MAX || (v.z == (float)G_ && v.w == (float)NCL)) break; pace(CWP); }
                M.cws[0] = v.x; M.cws[1] = v.y;
                mbar_arrive(MB(MB_CW));
            }
        } else if (w == 3) {
            const int lane = fresh_tid() & 31, l20 = min(lane, 19);
            mbar_wait(MB(MB_MG2), 0);
            const uint2 v = gsum(OFF_MG2 + 16 * l20, 640), u = gsum(OFF_MG2 + 320 + 16 * l20, 640);
            const uint32_t wr = lane < 20 ? M.c2[lane].w : 0u, cb1 = one_plus(v.x), cw = mul2(cb1, wr);
            if (lane < 20) {
                M.c2[lane] = make_uint4(cb1, v.y, u.x, cw);
                M.wr[lane] = wr;
                unsigned e;
                asm volatile("mov.u32 %0, %cluster_ctarank;" : "=r"(e));
                if ((lane & 3) == (e >> 1)) M.ga[lane >> 2] = __byte_perm(u.y, 0, (e & 1) ? 0x3232 : 0x1010);
            }
            __syncwarp();
            if (lane == 0) mbar_arrive(MB(MB_C2));
            if (rk == 0) {
                float a = lo2f(cw) + hi2f(cw), s = lo2f(v.y) * lo2f(wr) + hi2f(v.y) * hi2f(wr);
#pragma unroll
                for (int o = 16; o; o >>= 1) { a += __shfl_xor_sync(0xffffffffu, a, o); s += __shfl_xor_sync(0xffffffffu, s, o); }
                if (lane == 0) red4(&S->acc1[L_], a, s, 0.f);
                __syncwarp();
                if (lane < 20) st_rlx(&S->gb[20 * cl + lane], u.x);
                gz = ld_rlx(&S->gb[20 * cl + l20]) ^ u.x;
            }
        }
        {
        const int lane = fresh_tid() & 31, t = lane & 3, lr = lane & 7, lm = lane >> 3;
        uint32_t aw[5];
        __syncwarp();
        mbar_wait(MB(MB_C2), 0);
#pragma unroll
        for (int j = 0; j < 5; j++) aw[j] = M.wr[4 * j + t];
        const int ph = w >> 1, lst = 16 * ph + 2 * rk + (w & 1);
        const uint32_t rb = mapa(sb, lr);
        named_bar(6, 640);
        uint4 k = *(const uint4*)&M.key[128 * (w & 1) + 4 * lane];
        CE(k.x, k.y); CE(k.z, k.w); CE(k.x, k.z); CE(k.y, k.w); CE(k.y, k.z);
        uint32_t m[4];
#pragma unroll 1
        for (int q = 0; q <= ph; q++) {
#pragma unroll
            for (int rnd = 0; rnd < 4; rnd++) {
                m[rnd] = __reduce_max_sync(0xffffffffu, k.x);
                POP(k, m[rnd]);
            }
        }
        if (lane < 8) sta4(rb + OFF_MISC + (uint32_t)offsetof(Misc, cand) + lst * 16, make_uint4(m[0], m[1], m[2], m[3]), rb + (MB(MB_KEY2) - sb));
        const uint32_t mine = (t & 2) ? ((t & 1) ? m[3] : m[2]) : ((t & 1) ? m[1] : m[0]);
        const uint32_t ra = sb + OFF_H2T + ROW(mine) * 80;
        uint32_t bq[6];
        float rr[4] = {0.f, 0.f, 0.f, 0.f};
        ldsm_x4(bq, ra + 16 * lm); ldsm_x2(bq + 4, ra + 64);
        mma_bf16(rr, aw[0], aw[0], aw[1], aw[1], bq[0], bq[1]); mma_bf16(rr, aw[2], aw[2], aw[3], aw[3], bq[2], bq[3]); mma_k8(rr, aw[4], aw[4], bq[4]);
        float4* p = &S->rs[8 * lst];
        if (lane < 2) red4(p + lane, rr[0], __uint_as_float(gz), rr[1]);
        float4 e0 = ld_rlx4f(p), e1 = ld_rlx4f(p + 1);
        uint32_t sl = 0;
        if (w == 1) {
            mbar_wait(MB(MB_KEY2), 0);
            k = *(const uint4*)&M.cand[4 * lane];
            named_bar(14, 64);
#pragma unroll
            for (int s = 0; s < 8; s++) {
                const uint32_t v = M.sel[s] & ~1u;
                if (k.x == v) sl |= 8 + s;
                if (k.y == v) sl |= (8 + s) << 8;
                if (k.z == v) sl |= (8 + s) << 16;
                if (k.w == v) sl |= (8 + s) << 24;
            }
        }
        if (w == 0) {
            named_bar(8, 64);
            if (lane == 0) {
                PROXY_FENCE();
                tma5d_st(&tm_out, 40 * cl, RKT, sb + OFF_OUT);
                asm volatile("cp.async.bulk.commit_group;" ::: "memory");
            }
            __syncwarp();
        }
#pragma unroll 1
        for (int it = 0; it < SPIN_MAX && (e0.w != (float)NCL || e1.w != (float)NCL); it++) {
            e0 = ld_rlx4f(p); e1 = ld_rlx4f(p + 1);
        }
        {
            const uint32_t r0 = pack2(e0.x, e0.z), r1 = pack2(e1.x, e1.z);
            const uint32_t o0 = r0 ^ (sign2(r0) | 0x80008000u), o1 = r1 ^ (sign2(r1) | 0x80008000u);
            if (lane < 8) sta4(rb + OFF_EK + lst * VP, make_uint4((o0 << 16) | (m[0] & 0x3FFFu), (o0 & 0xFFFF0000u) | (m[1] & 0x3FFFu), (o1 << 16) | (m[2] & 0x3FFFu), (o1 & 0xFFFF0000u) | (m[3] & 0x3FFFu)),
                               rb + (MB(MB_EK) - sb));
        }
        if (w == 0) {
            if (lane == 0) {
                asm volatile("cp.async.bulk.wait_group 0;" ::: "memory");
                asm volatile("fence.acq_rel.gpu;" ::: "memory");
                mbar_arrive(MB(MB_OUT));
            }
        } else if (w == 1) {
            const uint32_t found = __reduce_add_sync(0xffffffffu, __popc(sl & 0x08080808u));
            mbar_wait(MB(MB_EK), 0);
            if (b == 0 && lane == 0) st_rlx4(&S->acc1[L_], make_uint4(0, 0, 0, 0));
            if (lane < 16 || cl == 14) st_rlx4(&S->acc2[256 * rk + 16 * cl + lane], make_uint4(0, 0, 0, 0));
            k = lds128(sb + OFF_EK + lane * VP);
            const bool s0 = sl & 8u, s1 = sl & 0x800u, s2 = sl & 0x80000u, s3 = sl & 0x8000000u;
            if (s0) M.fin[sl & 7u] = k.x;
            if (s1) M.fin[(sl >> 8) & 7u] = k.y;
            if (s2) M.fin[(sl >> 16) & 7u] = k.z;
            if (s3) M.fin[(sl >> 24) & 7u] = k.w;
            const uint32_t lo = min(min(s0 ? k.x : ~0u, s1 ? k.y : ~0u), min(s2 ? k.z : ~0u, s3 ? k.w : ~0u));
            const uint32_t hi = max(max(s0 ? 0u : k.x, s1 ? 0u : k.y), max(s2 ? 0u : k.z, s3 ? 0u : k.w));
            const uint32_t hi2 = __reduce_max_sync(0xffffffffu, hi), lo2 = __reduce_min_sync(0xffffffffu, lo);
            bool redo = found != 8u;
            if (hi2 > lo2) {
                const uint32_t h = hi2 | 0xFFFFu, l = lo2 & 0xFFFF0000u;
                const uint32_t n = __reduce_add_sync(0xffffffffu, ((s0 ? k.x <= h : (k.x >= l) << 8) + (s1 ? k.y <= h : (k.y >= l) << 8)) + ((s2 ? k.z <= h : (k.z >= l) << 8) + (s3 ? k.w <= h : (k.w >= l) << 8)));
                redo = redo || (h >> 16) - (l >> 16) > 1u || ((n & 255u) > 1u && n >= 512u) || (n & 255u) + (n >> 8) > 9u;
            }
            if (redo) {
                CE(k.x, k.y); CE(k.z, k.w); CE(k.x, k.z); CE(k.y, k.w); CE(k.y, k.z);
                __syncwarp();
#pragma unroll 1
                for (int rnd = 0; rnd < 8; rnd++) {
                    const uint32_t m8 = __reduce_max_sync(0xffffffffu, k.x);
                    POP(k, m8);
                    if (lane == 0) M.fin[rnd] = m8;
                }
            }
            if (lane == 0) M.fin[8] = redo;
            __syncwarp();
            named_arrive(12, 672);
        }
        }
        }
    } else {
    if (warp != 19) CL_ARRIVE();
    const int chn = 40 * cl + 8 * wgi + rk;
    const bool has_ch = chn < D_;
    const uint32_t cb = sb + OFF_CH + wgi * CHS;
    auto ldx = [&]() {
    if (warp < 16) {
        const char* xp = (const char*)(x + (512 * (warp >> 2) + 64 * (warp & 3) + RKT) * D_ + 40 * cl);
#pragma unroll
        for (int i = 0; i < 3; i++) {
            const uint32_t c = lane + 32 * i, row = (c * 205) >> 10, hi = c >= 40;
            const uint32_t dst = sb + OFF_X + XN(2 * warp) + XI(row & 7) + 80 * (hi - row) + 16 * c;
            if (c < 80) asm volatile("cp.async.cg.shared.global [%0], [%1], 16, %2;" ::"r"(dst), "l"(xp + (row * (2 * D_ - 80) + 16 * c + hi * (24 * 2 * D_))),
                                     "r"((cl < 14 || c - 5 * row < 2) ? 16 : 0) : "memory");
        }
    }
    };
    unsigned short r_ldt = 0, r_lar = 0, r_aim = 0, r_cr = 0, r_ci = 0;
    {
        const int n = min(chn, D_ - 1) * N_ + (tid & 127);
        r_ldt = ld_nc16((const unsigned short*)logdt + min(chn, D_ - 1));
        r_lar = ld_nc16((const unsigned short*)logAr + n);
        r_aim = ld_nc16((const unsigned short*)Aim + n);
        r_cr = ld_nc16((const unsigned short*)Cr + n);
        r_ci = ld_nc16((const unsigned short*)Ci + n);
    }
    if (warp == 19) {
        if (lane == 0) asm volatile("prefetch.tensormap [%0];" ::"l"(&tm_wm) : "memory");
        const uint32_t lo = 90u | (10u << 8) | (20u << 16) | (2u << 24), hi = (cl == 14 ? 32u : 80u) | ((rk < 4 ? 40u : 32u) << 8) | (180u << 16) | (180u << 24);
        const uint32_t tx = lane < 8 ? (((lane & 4 ? hi : lo) >> (8 * (lane & 3))) & 255u) : lane == 8 ? 180u : lane < 11 ? 2u : lane == 11 ? (hi >> 8) & 255u : 14u;
        if (lane == 0) {
#pragma unroll
            for (int i = 0; i < MB_N; i++) mbar_init(MB(i), i == MB_KD ? 20 : 1);
#pragma unroll
            for (int i = 0; i < 5; i++) mbar_init(sb + OFF_CH + XO_MBU + i * CHS, 5);
        }
        __syncwarp();
        if (lane < 17) mbar_expect(lane < MB_C2 ? MB(lane) : sb + OFF_CH + XO_MBU + (lane - MB_C2) * CHS, tx << 8);
        asm volatile("fence.mbarrier_init.release.cluster;" ::: "memory");
        __syncwarp();
        CL_ARRIVE();
    }
    ldx();
    if ((tid & 127) == 32) asm volatile("cp.async.ca.shared.global [%0], [%1], 4;" ::"r"(cb + XO_DSK), "l"((const uint32_t*)Dskip + (min(chn, D_ - 1) >> 1)) : "memory");
    asm volatile("cp.async.commit_group;" ::: "memory");
    auto mod2 = [&]() {
        if (wgi == M2W) {
            const int lane = fresh_tid() & 31, t = lane & 3;
            const uint32_t wa = sb + ((lane & 7) + ((lane >> 1) & 8)) * 80, p0 = wa + ((lane & 8) ? OFF_WM2 + 5760 : OFF_WM2 + 11520), p1 = wa + ((lane & 8) ? OFF_WM2 : OFF_WM0 + 11520);
            auto ld = [&](uint32_t (*a)[4], uint32_t p) {
#pragma unroll
                for (int ks = 0; ks < 4; ks++) ldsm_x4_t(a[ks], p + ks * 1280);
                ldsm_x2_t(a[4], p + 5120);
            };
            const uint32_t rb = mapa(sb, t), rd = mapa(sb, 4) - mapa(sb, 0), dst = rb + OFF_MG2 + rk * 640 + (lane >> 2) * 8;
            auto st = [&](const float* d, uint32_t o) {
                sta2(dst + o, __float_as_uint(d[0]), __float_as_uint(d[2]), rb + (MB(MB_MG2) - sb));
                sta2(dst + rd + o, __float_as_uint(d[0]), __float_as_uint(d[2]), rb + rd + (MB(MB_MG2) - sb));
            };
            uint32_t bs[9], a[5][4], c[5][4];
            float d[4] = {0.f, 0.f, 0.f, 0.f}, e[4] = {0.f, 0.f, 0.f, 0.f}, f[4] = {0.f, 0.f, 0.f, 0.f};
            mbar_wait(MB(MB_MG1), 0);
#pragma unroll
            for (int ks = 0; ks < 9; ks++) bs[ks] = lds32(sb + OFF_SC + 16 * ks + 4 * t);
            mbar_wait(MB(MB_WM2), 0);
            ld(a, p0 + 16 * w);
            ld(c, p1 + 16 * w);
            mod_mma2(d, e, a, c, bs);
            ld(a, ((w & 1) ? p1 : p0) + 64);
            st(d, 64 * w);
            st(e, 320 + 64 * w);
            d[0] = d[1] = d[2] = d[3] = 0.f;
            mma_k8(d, a[4][0], a[4][1], bs[8]);
#pragma unroll
            for (int ks = 0; ks < 4; ks++) mma_bf16((ks & 1) ? d : f, a[ks][0], a[ks][1], a[ks][2], a[ks][3], bs[2 * ks], bs[2 * ks + 1]);
            d[0] += f[0]; d[2] += f[2];
            if (w < 2) st(d, 320 * w + 256);
            __syncwarp();
        }
    };
    auto ln1 = [&]() {
        if (warp < 16) {
            uint32_t a[10];
            const uint32_t xa = sb + OFF_X + XN(2 * warp) + (lm & 1) * 80 + XI(lr) + (lm >> 1) * 16;
            asm volatile("cp.async.wait_group 0;" ::: "memory");
            __syncwarp();
            ldsm_x4(a, xa); ldsm_x4(a + 4, xa + 32); ldsm_x2(a + 8, xa + 64);
            named_arrive(9, 640);
            float c1[4] = {0.f, 0.f, 0.f, 0.f}, c2[4] = {0.f, 0.f, 0.f, 0.f}, c3[4] = {0.f, 0.f, 0.f, 0.f};
#pragma unroll
            for (int j = 0; j < 2; j++) {
                mma_bf16(c1, a[4 * j], a[4 * j + 1], a[4 * j + 2], a[4 * j + 3], 0x3F803F80u, 0x3F803F80u);
                mma_bf16(c2, a[4 * j], a[4 * j + 1], a[4 * j + 2], a[4 * j + 3], a[4 * j], a[4 * j + 2]);
                mma_bf16(c3, a[4 * j], a[4 * j + 1], a[4 * j + 2], a[4 * j + 3], a[4 * j + 1], a[4 * j + 3]);
            }
            mma_k8(c1, a[8], a[9], 0x3F803F80u); mma_k8(c2, a[8], a[9], a[8]); mma_k8(c3, a[8], a[9], a[9]);
            float4* p = &S->acc1[256 * rk + 16 * warp + g];
            red4p(t == (g >> 1), p, c1[0], (g & 1) ? c2[1] : c2[0], 0.f);
            red4p(t == (g >> 1), p + 8, c1[2], (g & 1) ? c3[3] : c3[2], 0.f);
        }
    };
    {
        unsigned char* cp = sm + OFF_CH + wgi * CHS + lane * 16;
        const uint4 z = make_uint4(0, 0, 0, 0);
        *(uint4*)(cp + w * UP + XO_TF) = z;
        *(uint4*)(cp + w * UP + (lane < 16 ? XO_U8 - 256 : XO_U16 - 512)) = z;
        if (lane < 17) *(uint4*)(cp + (lane < 9 ? w * UP + UB - 144 : lane == 9 ? w * UP + XO_ZC - 160 : lane < 14 ? XO_TD + (4 * w - 10) * 16 : XO_TD + (145 - 14 + 3 * w) * 16)) = z;
    }
    if (tid < 224) {
        const int e = tid & 15, l = (tid >> 4) - 6 - (int)((0x3355544433666ull >> (4 * e)) & 15) + 8 * (int)((0x1021021010210ull >> (4 * e)) & 15);
        const unsigned wd = (0x1166688822444ull >> (4 * e)) & 15, one = e >= 11 ? 0xFFFFu : 0x3F80u;
        ((uint32_t*)M.box)[((e >> 2) * 14 + (tid >> 4)) * 4 + (e & 3)] = ((unsigned)l <= wd ? one : 0u) | ((unsigned)(l - 1) <= wd ? one << 16 : 0u);
    }
    const uint32_t scr = sb + warp * KSCR, ws = scr + lane * 4;
    uint32_t fixa = 0, fixv = 0;
    {
        uint32_t zr;
        asm volatile("ld.volatile.shared.u32 %0, [%1];" : "=r"(zr) : "r"(cb + XO_TF + w * UP + lane * 16) : "memory");
        const float p_ldt = __uint_as_float(r_ldt * 65536u + zr), p_lar = __uint_as_float(r_lar * 65536u + zr), p_aim = __uint_as_float(r_aim * 65536u + zr);
        const float p_cr = __uint_as_float(r_cr * 65536u + zr), p_ci = __uint_as_float(r_ci * 65536u + zr);
        float acc[5][4];
        uint32_t afr[4][4], cz[4];
        const uint32_t ba = scr + lr * 144 + lm * 16;
        auto tile = [&](float* c, int rg) {
            __syncwarp();
            c[0] = c[1] = c[2] = c[3] = 0.f;
            uint32_t bb[2][4];
            ldsm_x4(bb[0], ba + rg * 1152);
            ldsm_x4(bb[1], ba + rg * 1152 + 64);
            mma_f16(c, afr[0], bb[0][0], bb[0][1]);
            mma_f16(c, afr[1], bb[0][2], bb[0][3]);
            mma_f16(c, afr[2], bb[1][0], bb[1][1]);
            mma_f16(c, afr[3], bb[1][2], bb[1][3]);
        };
#define CJ(z) packh((z).x, -(z).y)
#define CJP(z) packh((z).y, (z).x)
        const float dt = bfr(expf(p_ldt));
        const float al = -bfr(expf(p_lar)) * dt * 1.4426950408889634f;
        const float th = p_aim * dt;
        const float th_ = th * 0.15915494309189535f;
        const float tl_ = fmaf(th, 0.15915494309189535f, -th_) + th * 6.4206382e-9f;
        auto anchor = [&](float s) {
            float f = th_ * s;
            f -= rintf(f);
            f = fmaf(tl_, s, f) * 6.283185307179586f;
            const float e = fex2(al * s);
            return cplx{e * __cosf(f), e * __sinf(f)};
        };
        const float cx = p_cr * dt * 2.0f, cy = p_ci * dt * 2.0f;
        const uint32_t ex = __reduce_max_sync(0xffffffffu, __float_as_uint(fmaxf(fabsf(cx), fabsf(cy)))) >> 23;
        const float scl = __uint_as_float((254u - ex) << 23);
        const cplx C = cplx{cx * scl, cy * scl};
        const cplx z1 = anchor(1.f), z16 = anchor(16.f), z256 = anchor(256.f);
        {
            const cplx z32 = csq(z16), z48 = cmul(z32, z16), z64 = csq(z32), z128 = csq(z64), z192 = cmul(z128, z64);
            const uint32_t y[3] = {packh(z16.x, z16.y), packh(z32.x, z32.y), packh(z48.x, z48.y)};
            const uint32_t yp[3] = {packh(-z16.y, z16.x), packh(-z32.y, z32.x), packh(-z48.y, z48.x)};
            const uint32_t xx[3] = {packh(z64.x, z64.y), packh(z128.x, z128.y), packh(z192.x, z192.y)};
            sts32(ws, 0x00003C00u);
#pragma unroll
            for (int j = 0; j < 3; j++) sts32(ws + (1 + j) * 144, y[j]);
#pragma unroll
            for (int i = 0; i < 3; i++) {
                sts32(ws + (4 + 4 * i) * 144, xx[i]);
#pragma unroll
                for (int j = 0; j < 3; j++) sts32(ws + (5 + 4 * i + j) * 144, hcm(xx[i], y[j], yp[j]));
            }
        }
        ln1();
        WMS(0);
        const cplx z2 = csq(z1);
        {
            const cplx z3 = cmul(z2, z1), z4 = csq(z2), z8 = csq(z4);
            const cplx c4 = cmul(C, z4), c8 = cmul(C, z8), c12 = cmul(c8, z4);
            cz[0] = packh(C.x, -C.y); cz[1] = packh(c4.x, -c4.y); cz[2] = packh(c8.x, -c8.y); cz[3] = packh(c12.x, -c12.y);
            __syncwarp();
#pragma unroll
            for (int s = 0; s < 4; s++) ldsm_x4(afr[s], scr + (lr + 8 * (lm & 1)) * 144 + (2 * s + (lm >> 1)) * 16);
            const uint32_t y[3] = {CJ(z1), CJ(z2), CJ(z3)}, yp[3] = {CJP(z1), CJP(z2), CJP(z3)};
#pragma unroll
            for (int tt = 0; tt < 2; tt++) {
                const int rg = tt ? 0 : 2;
#pragma unroll
                for (int i = 0; i < 2; i++) {
                    sts32(ws + rg * 1152 + (4 * i) * 144, cz[2 * tt + i]);
#pragma unroll
                    for (int j = 0; j < 3; j++) sts32(ws + rg * 1152 + (4 * i + 1 + j) * 144, hcm(cz[2 * tt + i], y[j], yp[j]));
                }
                tile(acc[tt], rg);
            }
        }
        WMS(1);
        const cplx z258 = cmul(z256, z2), z512 = csq(z256), z768 = cmul(z512, z256);
        {
            const uint32_t a0 = CJ(z256), a0p = CJP(z256), a1 = CJ(z258), a1p = CJP(z258);
#pragma unroll
            for (int i = 0; i < 4; i++) { sts32(ws + 1152 + (2 * i) * 144, hcm(cz[i], a0, a0p)); sts32(ws + 1152 + (2 * i + 1) * 144, hcm(cz[i], a1, a1p)); }
            tile(acc[2], 1);
        }
        WMS(2);
        {
            const uint32_t a0 = CJ(z512), a0p = CJP(z512), a1 = CJ(z768), a1p = CJP(z768);
#pragma unroll
            for (int i = 0; i < 4; i++) { sts32(ws + 2304 + i * 144, hcm(cz[i], a0, a0p)); sts32(ws + 2304 + (4 + i) * 144, hcm(cz[i], a1, a1p)); }
            tile(acc[3], 2);
        }
        WMS(3);
        const cplx z1024 = csq(z512);
        {
            const cplx zk[4] = {z1024, cmul(z1024, z256), csq(z768), cmul(z1024, z768)};
#pragma unroll
            for (int h = 0; h < 4; h++) {
                const uint32_t a0 = CJ(zk[h]), a0p = CJP(zk[h]);
                sts32(ws + (2 * h) * 144, hcm(cz[0], a0, a0p));
                sts32(ws + (2 * h + 1) * 144, hcm(cz[2], a0, a0p));
            }
            tile(acc[4], 0);
        }
        const cplx z2048 = csq(z1024);
        float last = C.x * z2048.x - C.y * z2048.y;
#pragma unroll
        for (int o = 16; o; o >>= 1) last += __shfl_xor_sync(0xffffffffu, last, o);
        __syncwarp();
#pragma unroll
        for (int i = 0; i < 5; i++) *(float4*)(sm + (scr - sb) + i * 512 + ((lane * 16) ^ (i == 1 ? 64 : 0))) = make_float4(acc[i][0], acc[i][1], acc[i][2], acc[i][3]);
        if (lane == 0) { const float inv = __uint_as_float(ex << 23); sts32(cb + XO_KINV + 4 * w, __float_as_uint(inv)); sts32(cb + XO_KLAST + 4 * w, __float_as_uint(last * inv)); }
        WMS(4);
        asm volatile("cp.async.wait_group 0;" ::: "memory");
        if (w != 3) CL_WAIT();
        named_bar(1 + wgi, 128);
        const uint32_t td = cb + XO_TD + 64 * 4, tf = cb + XO_TF - 32 * 4;
        const float4 ki = *(const float4*)(sm + (cb - sb) + XO_KINV);
        auto fsum = [&](int off, uint32_t& r0, uint32_t& r1) {
            const unsigned char* p = sm + wgi * (4 * KSCR) + off;
            const float4 a = *(const float4*)p, b2 = *(const float4*)(p + KSCR), c = *(const float4*)(p + 2 * KSCR), d = *(const float4*)(p + 3 * KSCR);
            r0 = pack2(fmaf(a.y, ki.x, b2.y * ki.y) + fmaf(c.y, ki.z, d.y * ki.w), fmaf(a.x, ki.x, b2.x * ki.y) + fmaf(c.x, ki.z, d.x * ki.w));
            r1 = pack2(fmaf(a.w, ki.x, b2.w * ki.y) + fmaf(c.w, ki.z, d.w * ki.w), fmaf(a.z, ki.x, b2.z * ki.y) + fmaf(c.z, ki.z, d.z * ki.w));
        };
        const int role = (w + wgi) & 3;
        const int fo = role ? (role + 1) * 512 + lane * 16 : (g & 1) * 512 + ((lm ^ (g & 1)) * 64) + t * 16;
        uint32_t r[2];
        fsum(fo, r[0], r[1]);
        if (role == 0) {
            uint32_t q[2], v[4];
            fsum(fo + 256, q[0], q[1]);
            const uint32_t c[4] = {r[0], q[0], r[1], q[1]};
#pragma unroll
            for (int i = 0; i < 4; i++) v[i] = __shfl_sync(0xffffffffu, c[i], (lane + 31) & 31);
            if (lane == 0) mbar_arrive(MB(MB_KD));
#pragma unroll
            for (int i = 0; i < 4; i++) *(uint2*)(sm + (td - sb) + lane * 8 + i * 256) = make_uint2(__byte_perm(c[i], lane ? v[i] : i ? v[i - 1] : 0u, 0x5432), c[i]);
            if (lane == 0) { fixa = td + 256 * 4 + 2; fixv = v[3]; }
        } else if (role == 1) {
            const uint32_t v0 = __shfl_sync(0xffffffffu, r[0], (lane + 1) & 31), v1 = __shfl_sync(0xffffffffu, r[1], (lane + 1) & 31);
            if (lane == 0) mbar_arrive(MB(MB_KD));
#pragma unroll
            for (int h = 0; h < 2; h++) {
                const uint32_t dd = __byte_perm(r[h], 0, 0x3232);
                *(uint4*)(sm + (td - sb) + 1024 + lane * 16 + h * 512) = make_uint4(dd, dd, r[h], __byte_perm((h || lane == 31) ? v1 : v0, r[h], 0x5432));
            }
        } else {
            __syncwarp();
            if (lane == 0) mbar_arrive(MB(MB_KD));
            const uint32_t p = role == 2 ? tf + (64 + 32 * (t >> 1) + 2 * g + (t & 1)) * 4 : tf + 2 * UP + (64 + 16 * t + g) * 4, p1 = p + (role == 2 ? 64 : 32);
            const uint32_t k0 = r[0] >> 16, k1 = r[1] >> 16;
            sts16(p + UP, r[0]); sts16(p + UP + 6, r[0]); sts16(p1 + UP, r[1]); sts16(p1 + UP + 6, r[1]);
            sts16(p1 - 4, k1); sts16(p1 + 2, k1);
            const uint32_t dd = __byte_perm(r[0], 0, 0x3232);
            if (lane) { sts16(p - 4, k0); sts16(p + 2, k0); }
            else if (role == 2) {
                *(uint4*)(sm + (td - sb) + 512 * 4) = make_uint4(dd, dd, dd, r[0] & 0xFFFF0000u);
                fixa = td + 511 * 4; fixv = k0;
            } else {
                const float4 kl4 = *(const float4*)(sm + (cb - sb) + XO_KLAST);
                const uint32_t kl = f2bits((kl4.x + kl4.y) + (kl4.z + kl4.w));
                sts16(tf + 127 * 4, dd); sts16(tf + 128 * 4 + 2, dd); sts32(cb + XO_K1024, dd);
                sts16(tf + 2 * UP + 127 * 4, kl); sts16(tf + 2 * UP + 128 * 4 + 2, kl);
            }
        }
        __syncwarp();
        mod2();
    }
    if (has_ch) {
        conv_channel(sm, rk, fixa, fixv);
    } else {
        asm volatile("setmaxnreg.inc.sync.aligned.u32 88;");
        mbar_wait(MB(MB_WG), 0);
        mbar_wait(MB(MB_C2), 0);
    }
    {
    const int tid = fresh_tid(), warp = __shfl_sync(0xffffffffu, tid >> 5, 0), lane = tid & 31;
    const int g = lane >> 2, t = lane & 3, lr = lane & 7, lm = lane >> 3;
    __syncwarp();
    if (lane == 0) mbar_arrive(MB(MB_KD));
    uint32_t x1[10];
    uint32_t wf[9][4], wd[2][3][4];
    const int fmt = warp >> 2, fsl = warp & 3;
    auto ldwf = [&]() {
        const int half = lm & 1;
        const uint32_t base = (fmt == 4) ? ((half ? OFF_WU : OFF_WG) + 64) : ((fmt >> 1) * OFF_WU + ((2 * (fmt & 1) + half) << 4));
        const uint32_t wa = sb + base + (144 * fsl + lr + 8 * (lm >> 1)) * 80;
#pragma unroll
        for (int ks = 0; ks < 9; ks++) ldsm_x4_t(wf[ks], wa + ks * 1280);
    };
    if (warp < 16) {
        uint32_t bw[5], v[10];
#pragma unroll
        for (int j = 0; j < 5; j++) bw[j] = (g & 1) ? M.c2[4 * j + t].w : 0x3F803F80u;
        const uint32_t xa = sb + OFF_X + XI(warp >> 1) + (2 * (warp & 1) + (lm & 1)) * XG + lr * 80 + (lm >> 1) * 16;
        const uint32_t va = sb + OFF_V + (8 * (lm >> 1) + lr) * VP + 32 * warp + 16 * (lm & 1);
        ldsm_x4(x1, xa); ldsm_x4(x1 + 4, xa + 32); ldsm_x2(x1 + 8, xa + 64);
        mbar_wait(MB(MB_V), 0);
        ldsm_x4_t(v, va); ldsm_x4_t(v + 4, va + 16 * VP); ldsm_x2_t(v + 8, va + 32 * VP);
#pragma unroll
        for (int i = 0; i < 10; i++) x1[i] = add2(x1[i], (i >= 4 && cl == 14) ? 0u : v[i]);
        float c1[4] = {0.f, 0.f, 0.f, 0.f}, c2[4] = {0.f, 0.f, 0.f, 0.f}, c3[4] = {0.f, 0.f, 0.f, 0.f};
#pragma unroll
        for (int j = 0; j < 2; j++) {
            mma_bf16(c1, x1[4 * j], x1[4 * j + 1], x1[4 * j + 2], x1[4 * j + 3], bw[2 * j], bw[2 * j + 1]);
            mma_bf16(c2, x1[4 * j], x1[4 * j + 1], x1[4 * j + 2], x1[4 * j + 3], x1[4 * j], x1[4 * j + 2]);
            mma_bf16(c3, x1[4 * j], x1[4 * j + 1], x1[4 * j + 2], x1[4 * j + 3], x1[4 * j + 1], x1[4 * j + 3]);
        }
        mma_k8(c1, x1[8], x1[9], bw[4]); mma_k8(c2, x1[8], x1[9], x1[8]); mma_k8(c3, x1[8], x1[9], x1[9]);
        if (t == (g >> 1)) {
            float4* p = &S->acc2[256 * rk + 16 * warp + g];
            red4(p, c1[0], (g & 1) ? c2[1] : c2[0], c1[1]);
            red4(p + 8, c1[2], (g & 1) ? c3[3] : c3[2], c1[3]);
        }
        __syncwarp();
    }
    if (warp >= 16) { mbar_wait(MB(MB_WG), 0); mbar_wait(MB(MB_WU), 0); ldwf(); }
    if (warp >= 17) {
        named_bar(7, 128);
        PROXY_FENCE();
        if (lane < 3) tma2d(sb + OFF_WD + (3 * (warp - 17) + lane) * 5120, &tm_wd, 64 * (3 * (warp - 17) + lane), 40 * b, MB(MB_WD));
        __syncwarp();
    }
    uint32_t h2[10];
    uint32_t ta = sb + OFF_H2T + (16 * warp + (lane & 15)) * 80 + (lane >> 4) * 16;
    if (warp < 16) {
        const float4* ap = &S->acc2[256 * rk + 32 * (warp >> 1) + lane];
        if (warp < 8) { mbar_wait(MB(MB_WG), 0); ldwf(); }
        float4 s = ld_rlx4f(ap);
        uint2 kc[5];
#pragma unroll
        for (int j = 0; j < 5; j++) kc[j] = *(const uint2*)&M.c2[4 * j + t];
        mbar_wait(MB(MB_CW), 0);
        const float cw = M.cws[0], sbw = M.cws[1];
        uint32_t tk0 = (2047 - (((lane & 6) << 8) + ((lane & 24) << 3) + ((lane & 1) << 5) + RKT + (warp >> 1))) << 3;
        uint32_t ka = sb + OFF_MISC + (uint32_t)offsetof(Misc, key) + (32 * (warp >> 1) + lane) * 4;
        uint32_t rb = mapa(sb, 4 * (warp & 1) + t), cd = rb + OFF_MISC + (uint32_t)offsetof(Misc, cand2) + (8 * rk + (warp >> 1)) * 8;
        const int pj = lane >= 5, pc = lane - 5 * pj;
        uint4* dst = &S->h2c[(2 * (8 * rk + (warp >> 1)) + pj) * 72 + 5 * cl + pc];
        uint32_t pa = sb + OFF_H2T + 32 * (warp >> 1) * 80 + 16 * pc;
        asm volatile("" : "+r"(tk0), "+r"(ta), "+r"(ka), "+r"(rb), "+r"(cd), "+r"(pa), "+l"(dst));
        mbar_wait(MB(MB_KD), 1);
#pragma unroll 1
        for (int it = 0; it < SPIN_MAX && s.w != (float)NCL; it++) {
            if (s.w < (float)PQT) { const uint32_t c0 = clock(); for (int k = 0; k < 1024 && (uint32_t)clock() - c0 < PQD; k++) { } }
            s = ld_rlx4f(ap);
        }
        __syncwarp();
        if (warp == 0) named_arrive(7, 128);
        float meanb, rinv;
        ln_stats(s.x, s.y, meanb, rinv);
        const uint32_t rbits = __float_as_uint(fmaf(fmaf(-meanb, cw, s.z), rinv, sbw));
        const uint32_t key = ((rbits ^ (((int)rbits >> 31) | 0x80000000u)) & 0xFFFFC000u) | tk0;
        const uint32_t m0 = __reduce_max_sync(0xffffffffu, key);
        const uint32_t mr = pack2(meanb, rinv), rl = f2bits(rinv - hi2f(mr));
        const uint32_t m1 = __reduce_max_sync(0xffffffffu, key == m0 ? 0u : key);
        uint32_t st[2][2];
#pragma unroll
        for (int h = 0; h < 2; h++) { st[h][0] = __shfl_sync(0xffffffffu, mr, 16 * (warp & 1) + 8 * h + g); st[h][1] = __shfl_sync(0xffffffffu, rl, 16 * (warp & 1) + 8 * h + g); }
        if (lane < 4) sta2(cd, m0, m1 | 1u, rb + (MB(MB_KEY) - sb));
        sts32(ka, key);
        const int pr = __ffs(__ballot_sync(0xffffffffu, key == m0) | 0x80000000u) - 1, pr1 = __ffs(__ballot_sync(0xffffffffu, key == m1) | 0x80000000u) - 1;
#pragma unroll
        for (int i = 0; i < 10; i++)
            h2[i] = add2(mul2(norm2(x1[i], __byte_perm(st[i & 1][0], 0, 0x1010), __byte_perm(st[i & 1][0], 0, 0x3232), __byte_perm(st[i & 1][1], 0, 0x1010)), kc[i >> 1].x), kc[i >> 1].y);
        stsm_x4(ta, h2[0], h2[1], h2[2], h2[3]); stsm_x4(ta + 32, h2[4], h2[5], h2[6], h2[7]); stsm_x2(ta + 64, h2[8], h2[9]);
        __syncwarp();
        const int row = pj ? pr1 : pr;
        if (lane < 10 && (row >> 4) == (warp & 1) && pc < (cl < 14 ? 5 : 2)) {
            const uint4 a = lds128(pa + 80 * row);
            st_rlx4(dst, make_uint4(~a.x, ~a.y, ~a.z, ~a.w));
        }
        __syncwarp();
        named_arrive(6, 640);
        if (warp >= 8) { mbar_wait(MB(MB_WU), 0); ldwf(); }
    }
    auto outt = [&]() {
        if (warp < 16) {
            uint32_t o[10];
            if ((warp == cl || (warp == 15 && cl == 0)) && lane < 16) st_rlx4(&S->acc1[256 * rk + 16 * warp + lane], make_uint4(0, 0, 0, 0));
#pragma unroll
            for (int i = 0; i < 10; i++) o[i] = add2(x1[i], mul2(M.c2[4 * (i >> 1) + t].z, h2[i]));
            stsm_x4(ta + (OFF_OUT - OFF_H2T), o[0], o[1], o[2], o[3]); stsm_x4(ta + (OFF_OUT - OFF_H2T) + 32, o[4], o[5], o[6], o[7]); stsm_x2(ta + (OFF_OUT - OFF_H2T) + 64, o[8], o[9]);
        }
    };
    outt();
    uint4 gv = make_uint4(1, 1, 1, 1);
    const uint4* gp;
    uint32_t gdst;
    {
        const int gi = 32 * warp + lane, kk = (gi * 911) >> 16, seg = gi - 72 * kk;
        uint32_t ca = sb + OFF_MISC + (uint32_t)offsetof(Misc, cand2), sa = ca + 512 + 4 * (kk & 7);
        gp = &S->h2c[seg];
        gdst = sb + OFF_H2S + kk * (ROWP * 2) + seg * 16;
        asm volatile("" : "+r"(sa), "+r"(gdst), "+l"(gp));
        mbar_wait(MB(MB_KEY), 0);
        if (warp < 16) {
            const uint4 o = lds128(ca + 16 * lane), a = lds128(ca + 32 * warp), c = lds128(ca + 32 * warp + 16);
            const uint32_t mx = max(o.x, o.z), hd[4] = {a.x, a.z, c.x, c.z}, sc[4] = {a.y, a.w, c.y, c.w};
            uint32_t n[4];
#pragma unroll
            for (int q = 0; q < 4; q++) n[q] = __popc(__ballot_sync(0xffffffffu, mx > hd[q]));
            auto rank = [&](uint32_t k) {
                return (__popc(__ballot_sync(0xffffffffu, o.x > k)) + __popc(__ballot_sync(0xffffffffu, o.y > k))) + (__popc(__ballot_sync(0xffffffffu, o.z > k)) + __popc(__ballot_sync(0xffffffffu, o.w > k)));
            };
#pragma unroll
            for (int q = 0; q < 4; q++) {
                if (n[q] < 8) {
                    const uint32_t r0 = rank(hd[q]), r1 = rank(sc[q]);
                    if (r0 < 8) sts32(ca + 512 + 4 * r0, hd[q]);
                    if (r1 < 8) sts32(ca + 512 + 4 * r1, sc[q]);
                }
            }
        }
        named_bar(13, 640);
        if (warp < 18) {
            const uint32_t key = lds32(sa);
            gp += (((~key >> 2) & 0x3Eu) | ((~key >> 5) & 0x40u) | (key & 1u)) * 72;
            gv = ld_rlx4(gp);
        } else if (warp == 18) named_arrive(14, 64);
        else named_arrive(8, 64);
    }
    uint32_t wda = sb + OFF_WD + fmt * 5120 + lr * 128 + (((2 * fsl + (lm & 1)) ^ lr) << 4), wda2 = wda + (lm >> 1) * 1024;
    uint32_t ha = sb + OFF_H2S + lr * (ROWP * 2) + (144 * fsl) * 2 + lm * 16, fo = sb + OFF_FFR + ((fsl * 80 + 16 * fmt + g) * 8 + 2 * t) * 4;
    asm volatile("" : "+r"(ha), "+r"(fo));
    mbar_wait(MB(MB_WD), 0);
#pragma unroll
    for (int i = 0; i < 2; i++)
#pragma unroll
        for (int ks = 0; ks < 3; ks++)
            if (i == 0 || warp < 16) ldsm_x4_t(wd[i][ks], ((ks < 2) ? wda2 : wda) + ks * 2048 + i * 5 * 5120);
#pragma unroll 1
    for (int it = 0; it < SPIN_MAX && gv.x == 0u; it++) {
        gv = ld_rlx4(gp);
    }
    if (warp < 18) asm volatile("st.shared.v4.u32 [%0], {%1,%2,%3,%4};" ::"r"(gdst), "r"(~gv.x), "r"(~gv.y), "r"(~gv.z), "r"(~gv.w) : "memory");
    CBAR();
    float* ffr = (float*)(sm + OFF_FFR);
    auto ffn1 = [&]() {
        float acc[2][4] = {{0.f, 0.f, 0.f, 0.f}, {0.f, 0.f, 0.f, 0.f}};
#pragma unroll
        for (int k2 = 0; k2 < 5; k2++) {
            uint32_t hb[4];
            if (k2 < 4) ldsm_x4(hb, ha + k2 * 64); else ldsm_x2(hb, ha + 256);
            mma_bf16(acc[0], wf[2 * k2][0], wf[2 * k2][1], wf[2 * k2][2], wf[2 * k2][3], hb[0], hb[1]);
            if (k2 < 4) mma_bf16(acc[1], wf[2 * k2 + 1][0], wf[2 * k2 + 1][1], wf[2 * k2 + 1][2], wf[2 * k2 + 1][3], hb[2], hb[3]);
        }
        asm volatile("st.shared.v2.f32 [%0], {%1,%2};" ::"r"(fo), "f"(acc[0][0] + acc[1][0]), "f"(acc[0][1] + acc[1][1]) : "memory");
        asm volatile("st.shared.v2.f32 [%0+256], {%1,%2};" ::"r"(fo), "f"(acc[0][2] + acc[1][2]), "f"(acc[0][3] + acc[1][3]) : "memory");
    };
    ffn1();
    bf16(*act)[56] = (bf16(*)[56])(sm + OFF_ACT);
    auto gate = [&]() {
        if (warp < 12) {
            const int f = 4 * warp + lm, a = lr;
            float v = 0.f;
            if (warp < 10) {
                const float* pg = ffr + 32 * warp + (warp < 8 ? 0 : 256) + lane;
                const float* pu = pg + (warp < 8 ? 256 : 64);
                float gg = bfr((pg[0] + pg[640]) + (pg[1280] + pg[1920]));
                gg = bfr(silu(gg));
                const float uu = bfr((pu[0] + pu[640]) + (pu[1280] + pu[1920]));
                v = gg * uu;
            }
            act[a][f] = __ushort_as_bfloat16((unsigned short)f2bits(v));
        }
    };
    CBAR();
    gate();
    CBAR();
    auto ffn2 = [&](uint32_t buf, int mb) {
        uint32_t bq[3][2];
#pragma unroll
        for (int ks = 0; ks < 3; ks++) {
            bq[ks][0] = *(const uint32_t*)&act[g][16 * ks + 2 * t];
            bq[ks][1] = *(const uint32_t*)&act[g][16 * ks + 2 * t + 8];
        }
#pragma unroll
        for (int i = 0; i < 2; i++) {
            if (i == 0 || warp < 16) {
                float acc[4] = {0.f, 0.f, 0.f, 0.f};
#pragma unroll
                for (int ks = 0; ks < 3; ks++) mma_bf16(acc, wd[i][ks][0], wd[i][ks][1], wd[i][ks][2], wd[i][ks][3], bq[ks][0], bq[ks][1]);
                const int d = i ? 4 + (warp >> 2) : (warp * 13) >> 6, slot = i ? (warp & 3) : warp - 5 * d;
                const uint32_t rb = mapa(sb, d);
                sta2(rb + buf + (rk * 5 + slot) * 640 + lm * 160 + lr * 8, movm(pack2(acc[0], acc[1])), movm(pack2(acc[2], acc[3])), rb + (MB(mb) - sb));
            }
        }
    };
    ffn2(OFF_RS, MB_RS);
    named_bar(12, 672);
    const uint32_t redo = M.fin[8];
    if (redo) {
        const int gi = fresh_tid(), kk = (gi * 911) >> 16, seg = gi - 72 * kk;
        if (warp < 8) {
            const uint32_t key = M.fin[warp];
            if (MINE(key) && lane < (cl < 14 ? 5 : 2)) {
                const uint4 a = lds128(sb + OFF_H2T + ROW(key) * 80 + 16 * lane);
                st_rlx4(&S->h2c[(128 + warp) * 72 + 5 * cl + lane], make_uint4(~a.x, ~a.y, ~a.z, ~a.w));
            }
            __syncwarp();
        }
        if (warp < 18) {
            uint4 gv = make_uint4(0, 0, 0, 0);
#pragma unroll 1
            for (int it = 0; it < SPIN_MAX && gv.x == 0u; it++) gv = ld_rlx4(&S->h2c[128 * 72 + gi]);
            *(uint4*)(sm + OFF_H2S + kk * (ROWP * 2) + seg * 16) = make_uint4(~gv.x, ~gv.y, ~gv.z, ~gv.w);
        }
        CBAR();
        ffn1();
        CBAR();
        gate();
        CBAR();
        ffn2(OFF_RS + 80, MB_RS2);
        mbar_wait(MB(MB_RS2), 0);
    }
    {
        const int lane = fresh_tid() & 31;
        const int fP = min(warp < 8 ? 20 * cl + lane : 8 * (rk < 4 ? 5 * rk : 4 * rk + 4) + 4 * (warp - 8) + (lane & 3), D_ / 2);
        const uint32_t fgb = ld_rlx(&S->gb[fP]);
        const int ftok = warp < 8 ? warp : lane >> 2;
        const uint32_t fkey = M.fin[ftok];
        const bool fon = warp < 8 ? (MINE(fkey) && lane < 20 && fP < D_ / 2) : warp < (rk < 4 ? 18 : 16)
            ;
        const float rs = __fdividef(1.0f, 1.0f + __expf(-hi2f(fkey ^ (((int)~fkey >> 31) | 0x80000000u))));
        const uint32_t hv = lds32(sb + OFF_H2S + ftok * (ROWP * 2) + 4 * fP);
        float s0 = 0.f, s1 = 0.f, s2 = 1.0f, s3 = 0.f;
        if (warp >= 8) {
            if (fon) {
                mbar_wait(MB(MB_RS), 0);
                const uint32_t p = sb + OFF_RS + redo * 80 + ((warp - 8) >> 1) * 640 + (lane >> 3) * 160 + (lane & 7) * 8 + 4 * (warp & 1);
                uint32_t v[8];
#pragma unroll
                for (int i = 0; i < 8; i++) v[i] = lds32(p + i * 3200);
                s0 = ((lo2f(v[0]) + lo2f(v[1])) + (lo2f(v[2]) + lo2f(v[3]))) + ((lo2f(v[4]) + lo2f(v[5])) + (lo2f(v[6]) + lo2f(v[7])));
                s1 = ((hi2f(v[0]) + hi2f(v[1])) + (hi2f(v[2]) + hi2f(v[3]))) + ((hi2f(v[4]) + hi2f(v[5])) + (hi2f(v[6]) + hi2f(v[7])));
            }
        } else if (fon) {
            const uint32_t row = ROW(fkey);
            const unsigned short* vp = (const unsigned short*)(sm + OFF_V + 2 * lane * VP) + row;
            const uint32_t xv = add2(lds32(sb + OFF_X + XI(row >> 5) + ((row >> 3) & 3) * XG + (row & 7) * 80 + 4 * lane), (uint32_t)vp[0] | ((uint32_t)vp[VP / 2] << 16));
            s2 = (float)(((xv & 0xFFFFu) << 5) | 1u); s3 = (float)(xv >> 16);
            mbar_wait(MB(MB_OUT), 0);
        }
        if (fon) {
            const float4 o = atom4(&S->acc3[(fP >> 2) * 32 + 4 * ftok + (fP & 3)], s0, s1, s2, s3);
            const uint32_t z = __float_as_uint((o.z + s2) + 8388608.f), zh = __float_as_uint((o.w + s3) + 8388608.f);
            if (z & 16u) {
                const uint32_t xv = __byte_perm(z >> 5, zh, 0x5410);
                *(uint32_t*)(out + ((~fkey >> 3) & 2047u) * D_ + 2 * fP) = add2(xv, mul2(fgb, add2(hv, mul2(pack2(o.x + s0, o.y + s1), pack2(rs, rs)))));
            }
        }
    }
    }
    }
}

typedef CUresult (*EncodeFn)(CUtensorMap*, CUtensorMapDataType, cuuint32_t, void*, const cuuint64_t*, const cuuint64_t*,
                             const cuuint32_t*, const cuuint32_t*, CUtensorMapInterleave, CUtensorMapSwizzle,
                             CUtensorMapL2promotion, CUtensorMapFloatOOBfill);

static void make_map(EncodeFn fn, CUtensorMap* m, const void* ptr, uint64_t cols, uint64_t rows, uint32_t bc, uint32_t br,
                     CUtensorMapSwizzle sw, int five) {
    cuuint64_t dims[5] = {cols, rows, 4, 4, 288};
    cuuint64_t strides[4] = {cols * 2 * (five ? 32 : 1), cols * 2 * 512, cols * 2 * 64, cols * 2};
    cuuint32_t box[5] = {bc, br, 4, 4, 8};
    cuuint32_t es[5] = {1, 1, 1, 1, 1};
    CUresult rc = fn(m, CU_TENSOR_MAP_DATA_TYPE_BFLOAT16, five ? 5 : 2, (void*)ptr, dims, strides, box, es, CU_TENSOR_MAP_INTERLEAVE_NONE,
                     sw, (CUtensorMapL2promotion)(five || sw ? 0 : br == 72 ? L2M : L2P), CU_TENSOR_MAP_FLOAT_OOB_FILL_NONE);
    (void)rc;
}

static void launch(void* const* d_in, const int* in_sizes, int n_in, void* d_out, int out_size) {
    static EncodeFn enc = nullptr;
    static CUtensorMap tmm, tmg, tmu, tmd, tmo;
    static Scratch* sp = nullptr;
    static const void* cached[6] = {nullptr, nullptr, nullptr, nullptr, nullptr, nullptr};
    if (!enc) {
        cudaDriverEntryPointQueryResult qr;
        void* fn = nullptr;
        cudaGetDriverEntryPoint("cuTensorMapEncodeTiled", &fn, cudaEnableDefault, &qr);
        enc = (EncodeFn)fn;
        cudaFuncSetAttribute(clus_kernel, cudaFuncAttributeMaxDynamicSharedMemorySize, SMEM_TOTAL);
        cudaGetSymbolAddress((void**)&sp, g_s);
    }
    if (cached[0] != d_in[13] || cached[1] != d_in[9] || cached[2] != d_in[10] || cached[3] != d_in[11] || cached[4] != d_in[0] || cached[5] != d_out) {
        make_map(enc, &tmo, d_out, D_, 2, 40, 2, CU_TENSOR_MAP_SWIZZLE_NONE, 1);
        make_map(enc, &tmm, d_in[13], 6 * D_, D_, 40, 72, CU_TENSOR_MAP_SWIZZLE_NONE, 0);
        make_map(enc, &tmg, d_in[9], F_, D_, 40, 192, CU_TENSOR_MAP_SWIZZLE_NONE, 0);
        make_map(enc, &tmu, d_in[10], F_, D_, 40, 192, CU_TENSOR_MAP_SWIZZLE_NONE, 0);
        make_map(enc, &tmd, d_in[11], D_, F_, 64, 40, CU_TENSOR_MAP_SWIZZLE_128B, 0);
        cached[0] = d_in[13]; cached[1] = d_in[9]; cached[2] = d_in[10]; cached[3] = d_in[11]; cached[4] = d_in[0]; cached[5] = d_out;
    }
    clus_kernel<<<G_, NTHR, SMEM_TOTAL>>>((const bf16*)d_in[0], (const bf16*)d_in[1], (const bf16*)d_in[2], (const bf16*)d_in[3], (const bf16*)d_in[4],
                                          (const bf16*)d_in[5], (const bf16*)d_in[12], sp, (const bf16*)d_in[6], (const bf16*)d_in[8], (const bf16*)d_in[13],
                                          (bf16*)d_out, tmm, tmg, tmu, tmd, tmo);
}


static bool fits() {
    cudaFuncSetAttribute(clus_kernel, cudaFuncAttributeMaxDynamicSharedMemorySize, SMEM_TOTAL);
    cudaLaunchConfig_t cfg = {};
    cudaLaunchAttribute at;
    at.id = cudaLaunchAttributeClusterDimension;
    at.val.clusterDim.x = 8; at.val.clusterDim.y = 1; at.val.clusterDim.z = 1;
    cfg.gridDim = dim3(G_); cfg.blockDim = dim3(NTHR); cfg.dynamicSmemBytes = SMEM_TOTAL; cfg.attrs = &at; cfg.numAttrs = 1;
    int n = 0;
    const bool ok = cudaOccupancyMaxActiveClusters(&n, clus_kernel, &cfg) == cudaSuccess && n >= NCL;
    cudaGetLastError();
    return ok;
}
}
#undef L_
#undef D_
#undef N_
#undef F_
#undef G_
#undef NCL
#undef NTHR
#undef SPIN_MAX
#undef OFF_WG
#undef OFF_WU
#undef KSCR
#undef OFF_WM0
#undef OFF_STG
#undef OFF_MG2
#undef OFF_CH
#undef CHS
#undef UP
#undef UB
#undef XO_TF
#undef XO_U8
#undef XO_U16
#undef XO_ZA
#undef XO_ZB
#undef XO_ZC
#undef XO_ZD
#undef XO_TD
#undef XO_K1024
#undef XO_DSK
#undef XO_KINV
#undef XO_KLAST
#undef XO_MBU
#undef OFF_X
#undef XG
#undef XI
#undef XN
#undef OFF_V
#undef VP
#undef OFF_EK
#undef OFF_WM2
#undef OFF_MG1
#undef OFF_SC
#undef OFF_C1
#undef OFF_MISC
#undef OFF_WD
#undef OFF_H2T
#undef OFF_OUT
#undef ROWP
#undef OFF_H2S
#undef OFF_FFR
#undef OFF_ACT
#undef OFF_RS
#undef SMEM_TOTAL
#undef CBAR
#undef PROXY_FENCE
#undef D4
#undef O4
#undef WG_FENCE
#undef WG_COMMIT
#undef WG_WAIT
#undef TQ
#undef MB
#undef DS
#undef M2W
#undef WS
#undef WW
#undef WMS
#undef PQT
#undef PQD
#undef L2P
#undef L2M
#undef PDE
#undef WMD
#undef PFG
#undef CWP
#undef CWD
#undef ROW
#undef RKT
#undef MINE
#undef CE
#undef POP
#undef CGT
#undef CL_ARRIVE
#undef CL_WAIT
#undef CJ
#undef CJP

namespace v4 {

#define L_ 2048
#define D_ 576
#define N_ 128
#define F_ 4608
#define G_ 128
#define NTHR 640
#define SPIN_MAX (1 << 18)
#define SENT 0u
#define HINT_N 182u

typedef __nv_bfloat16 bf16;

struct Scratch {
    uint4 xn[G_ * G_ * 10];
    uint4 v[G_ * D_ * 2];
    uint2 part[G_ * G_ * 9];
    uint4 h2w[L_ * 96];
    unsigned int rec[G_ * 8];
    unsigned int modw[6 * D_];
    unsigned int ticket[64];
    unsigned int cnt[64];
    unsigned int hint[64];
};
__device__ __align__(1024) Scratch g_s;

#define OFF_WG 0
#define OFF_WU 46080
#define OFF_CH 92160
#define CHS 20784
#define ULBO 656
#define XO_U8 6272
#define XO_U16 10368
#define XO_ZA 5248
#define XO_ZB 8448
#define XO_ZC 11648
#define XO_ZD 13824
#define XO_TD 16000
#define XO_TF 18624
#define XO_K1024 20672
#define KSCR 3456
#define OFF_TILE 196096
#define ROWP 584
#define OFF_MISC 214784
#define OFF_WD OFF_CH
#define OFF_H2T (OFF_CH + 3 * CHS)
#define OFF_H2S (OFF_H2T + 18688)
#define OFF_FFR (OFF_H2S + 9344)
#define OFF_FIN OFF_FFR
#define OFF_ACT (OFF_FFR + 10240)

struct Misc {
    __align__(16) uint4 sent[256];
    __align__(16) uint4 box[11 * 14];
    union {
        struct {
            __align__(16) float2 part[18][16];
            float rp[18][16];
        };
        struct {
            __align__(16) unsigned short st1[3][16];
            __align__(16) float p1[16][4], p2[16][4];
        };
    };
    __align__(16) bf16 cb1[D_], sb[D_], gb[D_];
    __align__(16) bf16 sc[D_];
    __align__(16) unsigned int cand[64], skey[16];
    __align__(16) float kinv[5][4], klast[5][4];
    unsigned int pk[4][8];
    __align__(16) uint4 st2[16];
    unsigned int wr[D_ / 2];
    float modx[32];
    unsigned int rank[16];
    volatile unsigned int flag;
    unsigned int e1cnt;
    unsigned long long mbar[5];
    unsigned int epoch;
};
#define SMEM_TOTAL (OFF_MISC + (int)sizeof(Misc))
static_assert(SMEM_TOTAL <= 232448, "smem");

__device__ __forceinline__ float lo2f(uint32_t w) { return __uint_as_float(w << 16); }
__device__ __forceinline__ float hi2f(uint32_t w) { return __uint_as_float(w & 0xFFFF0000u); }
__device__ __forceinline__ uint32_t pack2(float lo, float hi) { uint32_t r; asm("cvt.rn.bf16x2.f32 %0, %1, %2;" : "=r"(r) : "f"(hi), "f"(lo)); return r; }
__device__ __forceinline__ float bfr(float x) { return __uint_as_float(pack2(0.f, x)); }
__device__ __forceinline__ uint32_t f2bits(float x) { return pack2(x, 0.f); }
__device__ __forceinline__ uint32_t packh(float lo, float hi) { uint32_t r; asm("cvt.rn.f16x2.f32 %0, %1, %2;" : "=r"(r) : "f"(hi), "f"(lo)); return r; }
__device__ __forceinline__ float frcp(float x) { float r; asm("rcp.approx.ftz.f32 %0, %1;" : "=f"(r) : "f"(x)); return r; }
__device__ __forceinline__ float fsqrt(float x) { float r; asm("sqrt.approx.f32 %0, %1;" : "=f"(r) : "f"(x)); return r; }
__device__ __forceinline__ float fex2(float x) { float r; asm("ex2.approx.ftz.f32 %0, %1;" : "=f"(r) : "f"(x)); return r; }
__device__ __forceinline__ float silu(float x) { return __fdividef(x, 1.0f + __expf(-x)); }
__device__ __forceinline__ uint32_t add2(uint32_t a, uint32_t b) { uint32_t r; asm("add.rn.bf16x2 %0, %1, %2;" : "=r"(r) : "r"(a), "r"(b)); return r; }
__device__ __forceinline__ uint32_t sub2(uint32_t a, uint32_t b) { uint32_t r; asm("sub.rn.bf16x2 %0, %1, %2;" : "=r"(r) : "r"(a), "r"(b)); return r; }
__device__ __forceinline__ uint32_t mul2(uint32_t a, uint32_t b) { uint32_t r; asm("mul.rn.bf16x2 %0, %1, %2;" : "=r"(r) : "r"(a), "r"(b)); return r; }
__device__ __forceinline__ uint32_t fma2(uint32_t a, uint32_t b, uint32_t c) { uint32_t r; asm("fma.rn.bf16x2 %0, %1, %2, %3;" : "=r"(r) : "r"(a), "r"(b), "r"(c)); return r; }
__device__ __forceinline__ uint32_t norm2(uint32_t x, uint32_t m, uint32_t rh, uint32_t rl) { const uint32_t d = sub2(x, m); return fma2(d, rh, mul2(d, rl)); }

__device__ __forceinline__ void mma_bf16(float* c, uint32_t a0, uint32_t a1, uint32_t a2, uint32_t a3, uint32_t b0, uint32_t b1) {
    asm volatile("mma.sync.aligned.m16n8k16.row.col.f32.bf16.bf16.f32 {%0,%1,%2,%3}, {%4,%5,%6,%7}, {%8,%9}, {%0,%1,%2,%3};\n"
                 : "+f"(c[0]), "+f"(c[1]), "+f"(c[2]), "+f"(c[3]) : "r"(a0), "r"(a1), "r"(a2), "r"(a3), "r"(b0), "r"(b1));
}
__device__ __forceinline__ void mma_f16(float* c, const uint32_t* a, uint32_t b0, uint32_t b1) {
    asm volatile("mma.sync.aligned.m16n8k16.row.col.f32.f16.f16.f32 {%0,%1,%2,%3}, {%4,%5,%6,%7}, {%8,%9}, {%0,%1,%2,%3};\n"
                 : "+f"(c[0]), "+f"(c[1]), "+f"(c[2]), "+f"(c[3]) : "r"(a[0]), "r"(a[1]), "r"(a[2]), "r"(a[3]), "r"(b0), "r"(b1));
}
__device__ __forceinline__ void ldsm_x4(uint32_t* r, uint32_t addr) {
    asm volatile("ldmatrix.sync.aligned.m8n8.x4.shared.b16 {%0,%1,%2,%3}, [%4];" : "=r"(r[0]), "=r"(r[1]), "=r"(r[2]), "=r"(r[3]) : "r"(addr) : "memory");
}
__device__ __forceinline__ void ldsm_x4_t(uint32_t* r, uint32_t addr) {
    asm volatile("ldmatrix.sync.aligned.m8n8.x4.trans.shared.b16 {%0,%1,%2,%3}, [%4];" : "=r"(r[0]), "=r"(r[1]), "=r"(r[2]), "=r"(r[3]) : "r"(addr) : "memory");
}
__device__ __forceinline__ void stsm_x4(uint32_t addr, uint32_t r0, uint32_t r1, uint32_t r2, uint32_t r3) {
    asm volatile("stmatrix.sync.aligned.m8n8.x4.shared.b16 [%0], {%1,%2,%3,%4};" ::"r"(addr), "r"(r0), "r"(r1), "r"(r2), "r"(r3) : "memory");
}
__device__ __forceinline__ void stsm_x4_t(uint32_t addr, uint32_t r0, uint32_t r1, uint32_t r2, uint32_t r3) {
    asm volatile("stmatrix.sync.aligned.m8n8.x4.trans.shared.b16 [%0], {%1,%2,%3,%4};" ::"r"(addr), "r"(r0), "r"(r1), "r"(r2), "r"(r3) : "memory");
}
__device__ __forceinline__ uint32_t movm(uint32_t a) { uint32_t r; asm volatile("movmatrix.sync.aligned.m8n8.trans.b16 %0, %1;" : "=r"(r) : "r"(a)); return r; }
__device__ __forceinline__ uint32_t lds32(uint32_t a) { uint32_t v; asm volatile("ld.shared.u32 %0, [%1];" : "=r"(v) : "r"(a)); return v; }
__device__ __forceinline__ void sts32(uint32_t a, uint32_t v) { asm volatile("st.shared.u32 [%0], %1;" ::"r"(a), "r"(v) : "memory"); }
__device__ __forceinline__ void sts16(uint32_t a, uint32_t v) { asm volatile("st.shared.u16 [%0], %1;" ::"r"(a), "h"((unsigned short)v) : "memory"); }
__device__ __forceinline__ void named_bar(int id, int n) { asm volatile("bar.sync %0, %1;" ::"r"(id), "r"(n) : "memory"); }
__device__ __forceinline__ void named_arrive(int id, int n) { asm volatile("bar.arrive %0, %1;" ::"r"(id), "r"(n) : "memory"); }
#define CBAR() asm volatile("bar.sync 0, 640;" ::: "memory")
#define PROXY_FENCE() asm volatile("fence.proxy.async.shared::cta;" ::: "memory")

#define D4(d, o) "+f"(d[o]), "+f"(d[o + 1]), "+f"(d[o + 2]), "+f"(d[o + 3])
__device__ __forceinline__ void wg32(float* d, uint32_t a0, uint32_t a1, uint32_t a2, uint32_t a3, uint64_t desc) {
    asm volatile("wgmma.mma_async.sync.aligned.m64n32k16.f32.bf16.bf16 {%0,%1,%2,%3,%4,%5,%6,%7,%8,%9,%10,%11,%12,%13,%14,%15}, {%16,%17,%18,%19}, %20, 1, 1, 1, 0;"
                 : D4(d, 0), D4(d, 4), D4(d, 8), D4(d, 12) : "r"(a0), "r"(a1), "r"(a2), "r"(a3), "l"(desc));
}
__device__ __forceinline__ void wg48(float* d, uint32_t a0, uint32_t a1, uint32_t a2, uint32_t a3, uint64_t desc) {
    asm volatile("wgmma.mma_async.sync.aligned.m64n48k16.f32.bf16.bf16 {%0,%1,%2,%3,%4,%5,%6,%7,%8,%9,%10,%11,%12,%13,%14,%15,%16,%17,%18,%19,%20,%21,%22,%23}, {%24,%25,%26,%27}, %28, 1, 1, 1, 0;"
                 : D4(d, 0), D4(d, 4), D4(d, 8), D4(d, 12), D4(d, 16), D4(d, 20) : "r"(a0), "r"(a1), "r"(a2), "r"(a3), "l"(desc));
}
#define O4(d, o) "=f"(d[o]), "=f"(d[o + 1]), "=f"(d[o + 2]), "=f"(d[o + 3])
__device__ __forceinline__ void wg32z(float* d, uint32_t a0, uint32_t a1, uint32_t a2, uint32_t a3, uint64_t desc) {
    asm volatile("wgmma.mma_async.sync.aligned.m64n32k16.f32.bf16.bf16 {%0,%1,%2,%3,%4,%5,%6,%7,%8,%9,%10,%11,%12,%13,%14,%15}, {%16,%17,%18,%19}, %20, 0, 1, 1, 0;"
                 : O4(d, 0), O4(d, 4), O4(d, 8), O4(d, 12) : "r"(a0), "r"(a1), "r"(a2), "r"(a3), "l"(desc));
}
__device__ __forceinline__ void wg48z(float* d, uint32_t a0, uint32_t a1, uint32_t a2, uint32_t a3, uint64_t desc) {
    asm volatile("wgmma.mma_async.sync.aligned.m64n48k16.f32.bf16.bf16 {%0,%1,%2,%3,%4,%5,%6,%7,%8,%9,%10,%11,%12,%13,%14,%15,%16,%17,%18,%19,%20,%21,%22,%23}, {%24,%25,%26,%27}, %28, 0, 1, 1, 0;"
                 : O4(d, 0), O4(d, 4), O4(d, 8), O4(d, 12), O4(d, 16), O4(d, 20) : "r"(a0), "r"(a1), "r"(a2), "r"(a3), "l"(desc));
}
#define WG_FENCE() asm volatile("wgmma.fence.sync.aligned;" ::: "memory")
#define WG_COMMIT() asm volatile("wgmma.commit_group.sync.aligned;" ::: "memory")
#define WG_WAIT(n) asm volatile("wgmma.wait_group.sync.aligned " #n ";" ::: "memory")
#define TQ(p, k) p[2 * (k) + 1], p[2 * (k) + 2], p[2 * (k)], p[2 * (k) + 1]

__device__ __forceinline__ uint4 ld_nc4(const void* p) { uint4 v; asm volatile("ld.global.nc.v4.u32 {%0,%1,%2,%3}, [%4];" : "=r"(v.x), "=r"(v.y), "=r"(v.z), "=r"(v.w) : "l"(p)); return v; }
__device__ __forceinline__ unsigned short ld_nc16(const void* p) { unsigned short v; asm volatile("ld.global.nc.u16 %0, [%1];" : "=h"(v) : "l"(p)); return v; }
__device__ __forceinline__ uint32_t ld_nc(const void* p) { uint32_t v; asm volatile("ld.global.nc.u32 %0, [%1];" : "=r"(v) : "l"(p)); return v; }
__device__ __forceinline__ uint32_t ld_rlx(const unsigned int* p) { uint32_t v; asm volatile("ld.relaxed.gpu.global.u32 %0, [%1];" : "=r"(v) : "l"(p) : "memory"); return v; }
__device__ __forceinline__ uint2 ld_rlx2(const void* p) { uint2 v; asm volatile("ld.relaxed.gpu.global.v2.u32 {%0,%1}, [%2];" : "=r"(v.x), "=r"(v.y) : "l"(p) : "memory"); return v; }
__device__ __forceinline__ uint4 ld_rlx4(const void* p) { uint4 v; asm volatile("ld.relaxed.gpu.global.v4.u32 {%0,%1,%2,%3}, [%4];" : "=r"(v.x), "=r"(v.y), "=r"(v.z), "=r"(v.w) : "l"(p) : "memory"); return v; }
__device__ __forceinline__ void st_rlx(unsigned int* p, uint32_t v) { asm volatile("st.relaxed.gpu.global.u32 [%0], %1;" ::"l"(p), "r"(v) : "memory"); }
__device__ __forceinline__ void st_rlx2(void* p, uint32_t a, uint32_t b) { asm volatile("st.relaxed.gpu.global.v2.u32 [%0], {%1,%2};" ::"l"(p), "r"(a), "r"(b) : "memory"); }
__device__ __forceinline__ void st_rlx4(void* p, uint4 v) { asm volatile("st.relaxed.gpu.global.v4.u32 [%0], {%1,%2,%3,%4};" ::"l"(p), "r"(v.x), "r"(v.y), "r"(v.z), "r"(v.w) : "memory"); }
__device__ __forceinline__ void red_inc(unsigned int* p) { asm volatile("red.relaxed.gpu.global.add.u32 [%0], 1;" ::"l"(p) : "memory"); }

__device__ __forceinline__ void mbar_init(uint32_t a, int cnt) { asm volatile("mbarrier.init.shared::cta.b64 [%0], %1;" ::"r"(a), "r"(cnt) : "memory"); }
__device__ __forceinline__ void mbar_expect(uint32_t a, uint32_t bytes) { asm volatile("mbarrier.arrive.expect_tx.shared::cta.b64 _, [%0], %1;" ::"r"(a), "r"(bytes) : "memory"); }
__device__ __forceinline__ void mbar_wait(uint32_t a, uint32_t parity) {
    uint32_t ok = 0;
    int it = 0;
    do {
        asm volatile("{\n.reg .pred p;\nmbarrier.try_wait.parity.shared::cta.b64 p, [%1], %2;\nselp.u32 %0, 1, 0, p;\n}" : "=r"(ok) : "r"(a), "r"(parity) : "memory");
    } while (!ok && ++it < SPIN_MAX);
}
__device__ __forceinline__ void tma2d(uint32_t dst, const CUtensorMap* tm, int c0, int c1, uint32_t mbar) {
    asm volatile("cp.async.bulk.tensor.2d.shared::cluster.global.mbarrier::complete_tx::bytes [%0], [%1, {%3, %4}], [%2];"
                 ::"r"(dst), "l"(tm), "r"(mbar), "r"(c0), "r"(c1) : "memory");
}
__device__ __forceinline__ void bulk_s2g(void* dst, uint32_t src, uint32_t bytes) {
    asm volatile("cp.async.bulk.global.shared::cta.bulk_group [%0], [%1], %2;" ::"l"(dst), "r"(src), "r"(bytes) : "memory");
}
__device__ __forceinline__ uint32_t ld_acq(const unsigned int* p) { uint32_t v; asm volatile("ld.acquire.gpu.global.u32 %0, [%1];" : "=r"(v) : "l"(p) : "memory"); return v; }
__device__ __forceinline__ void bulk_pf(const void* src, uint32_t bytes) { asm volatile("cp.async.bulk.prefetch.L2.global [%0], %1;" ::"l"(src), "r"(bytes) : "memory"); }

__device__ __forceinline__ uint32_t wait_epoch(Misc& M) {
    uint32_t e = 0;
#pragma unroll 1
    for (int it = 0; it < (SPIN_MAX << 4) && e == 0; it++) e = *(volatile unsigned int*)&M.epoch;
    return e;
}
__device__ __forceinline__ void wait_reset(const unsigned int* ctr, uint32_t epoch) {
#pragma unroll 1
    for (int it = 0; it < SPIN_MAX; it++)
        if ((int)(ld_acq(ctr) - G_ * epoch) >= 0) break;
}
struct cplx { float x, y; };
__device__ __forceinline__ cplx cmul(cplx a, cplx b) { cplx r; r.x = a.x * b.x - a.y * b.y; r.y = a.x * b.y + a.y * b.x; return r; }
__device__ __forceinline__ cplx csq(cplx a) { cplx r; r.x = a.x * a.x - a.y * a.y; r.y = 2.0f * a.x * a.y; return r; }
__device__ __forceinline__ uint32_t hcm(uint32_t x, uint32_t y, uint32_t yp) {
    const __half2 X = *(const __half2*)&x, Y = *(const __half2*)&y, YP = *(const __half2*)&yp;
    const __half2 r = __hfma2(__high2half2(X), YP, __hmul2(__low2half2(X), Y));
    return *(const uint32_t*)&r;
}
__device__ __forceinline__ void ln_stats(float s1, float s2, float& meanb, float& rinv) {
    const float mean = s1 * (1.0f / D_);
    const float den = bfr(fsqrt(bfr(bfr(fmaxf(fmaf(-mean, mean, s2 * (1.0f / D_)), 0.f)) + 1e-5f)));
    meanb = bfr(mean);
    rinv = frcp(den);
}

__device__ __forceinline__ int fresh_tid() { int v; asm volatile("mov.u32 %0, %tid.x;" : "=r"(v)); return v; }
__device__ __forceinline__ void conv_channel(unsigned char* sm, Scratch* S, uint32_t gidx, uint32_t epoch, const void* pf_src,
                                             const CUtensorMap* tmu, int f0) {
    Misc& M = *(Misc*)(sm + OFF_MISC);
    const uint32_t sb = (uint32_t)__cvta_generic_to_shared(sm);
    const int tid = fresh_tid(), lane = tid & 31, g = lane >> 2, t = lane & 3, lr = lane & 7, lm = lane >> 3;
    const int warp_ = __shfl_sync(0xffffffffu, tid >> 5, 0), wgi = warp_ >> 2, w = warp_ & 3;
    const uint32_t cb = sb + OFF_CH + wgi * CHS, tag16 = (epoch % 65535u) + 1u;
    float D[16];
    uint32_t gaw, rcnt = 0;
    {
        {
            const uint32_t a8 = cb + lr * ULBO + (lm + 9) * 16 + w * 64, b8 = cb + XO_U8 + lm * 128 + lr * 16 + w * 512;
            const uint32_t a16 = cb + (((2 * lr) & 7) + (lm & 1)) * ULBO + (9 + (lr >> 2) + (lm & 2)) * 16 + w * 64;
            const uint32_t b16 = cb + XO_U16 + (lm & 1) * 512 + lr * 16 + (lm >> 1) * 128 + (w >> 1) * 1024 + (w & 1) * 256;
            uint32_t r[3][4];
            ldsm_x4_t(r[0], a8);
            ldsm_x4_t(r[1], a16);
            if (w < 2) ldsm_x4_t(r[2], a8 + 256);
            stsm_x4(b8, r[0][0], r[0][1], r[0][2], r[0][3]);
            stsm_x4(b16, r[1][0], r[1][1], r[1][2], r[1][3]);
            if (w < 2) stsm_x4(b8 + 2048, r[2][0], r[2][1], r[2][2], r[2][3]);
        }
        PROXY_FENCE();
        named_bar(1 + wgi, 128);
        {
            float Z8[24], Z16[16];
            const uint32_t pf = cb + XO_TF + (w >> 1) * 512 + (8 + 16 * (w & 1) + g - 2 * t) * 4;
            uint32_t p[13], q[9], z16[8];
#pragma unroll
            for (int s = 0; s < 9; s++) q[s] = lds32(pf + 1024 + s * 32);
            const uint32_t d8 = ((((cb + XO_U8) & 0x3FFFF) >> 4) | ((128 >> 4) << 16));
#define DZ(o) (((uint64_t)(512 >> 4) << 32) | (uint64_t)(d8 + (o)))
            WG_FENCE();
#pragma unroll
            for (int e = 0; e < 4; e++) {
                if (e == 0) wg32z(Z16, TQ(q, e), DZ(256 + 16));
                else wg32(Z16, TQ(q, e), DZ(256 - (e >> 1) * 64 + (1 - (e & 1)) * 16));
            }
            WG_COMMIT();
#pragma unroll
            for (int s = 0; s < 13; s++) p[s] = lds32(pf + s * 32);
            WG_WAIT(0);
#pragma unroll
            for (int i = 0; i < 8; i++) z16[i] = pack2(Z16[2 * i], Z16[2 * i + 1]);
            WG_FENCE();
#pragma unroll
            for (int e = 0; e < 6; e++) {
                if (e == 0) wg48z(Z8, TQ(p, e), DZ(16));
                else wg48(Z8, TQ(p, e), DZ(-(e >> 1) * 32 + (1 - (e & 1)) * 16));
            }
            WG_COMMIT();
            WG_WAIT(0);
            named_bar(1 + wgi, 128);
            const uint32_t za = cb + ((w >> 1) ? XO_ZB : XO_ZA) + lr * 400 + (1 + 2 * (w & 1) + (lm & 1) + 4 * (lm >> 1)) * 16;
#pragma unroll
            for (int i = 0; i < 3; i++)
                stsm_x4(za + i * 128, pack2(Z8[8 * i], Z8[8 * i + 1]), pack2(Z8[8 * i + 2], Z8[8 * i + 3]), pack2(Z8[8 * i + 4], Z8[8 * i + 5]), pack2(Z8[8 * i + 6], Z8[8 * i + 7]));
            const int Cz = 2 * (16 * (w & 1) + 8 * (lm & 1) + lr) + (lm >> 1);
            const uint32_t zc = cb + ((w >> 1) ? XO_ZD : XO_ZC) + (Cz & 7) * 272 + (1 + (Cz >> 3)) * 16;
#pragma unroll
            for (int ob = 0; ob < 2; ob++) stsm_x4(zc + ob * 128, z16[4 * ob], z16[4 * ob + 1], z16[4 * ob + 2], z16[4 * ob + 3]);
            if (lane < 8) *(uint4*)(sm + (cb - sb) + ((w < 2) ? (XO_ZA + w * 3200 + lane * 400) : (XO_ZC + (w - 2) * 2176 + lane * 272))) = make_uint4(0, 0, 0, 0);
        }
        gaw = ld_rlx(&S->modw[gidx]);
        if (tmu && wgi >= 2 && (tid & 127) == 96) {
            const uint32_t mbu = sb + OFF_MISC + (uint32_t)offsetof(Misc, mbar) + 24;
            if (wgi == 2) mbar_expect(mbu, 36864);
            tma2d(sb + OFF_WU + (wgi - 2) * 12288, tmu, f0, 192 * (wgi - 2), mbu);
        }
        __syncwarp();
        if ((tid & 127) == 64) rcnt = ld_rlx(S->cnt);
        {
#pragma unroll
            for (int i = 0; i < 16; i++) D[i] = 0.f;
            uint32_t pa = cb + XO_TD + (8 + 16 * w + g - 2 * t) * 4;
            uint32_t dlo = (((cb + 9 * 16) & 0x3FFFF) >> 4) | ((ULBO >> 4) << 16);
#define DS(o) (((uint64_t)(128 >> 4) << 32) | (uint64_t)(dlo + (o)))
#define KST (2 * (ULBO / 16))
            uint32_t pA[9], pB[9];
#pragma unroll
            for (int s = 0; s < 9; s++) pA[s] = lds32(pa + s * 32);
#pragma unroll 1
            for (int j = 0; j < 4; j++) {
                WG_FENCE();
#pragma unroll
                for (int q = 0; q < 4; q++) wg32(D, TQ(pA, q), DS((3 - q) * KST));
                WG_COMMIT();
                WG_WAIT(1);
#pragma unroll
                for (int s = 0; s < 9; s++) pB[s] = lds32(pa + 256 + s * 32);
                WG_FENCE();
#pragma unroll
                for (int q = 0; q < 4; q++) wg32(D, TQ(pB, q), DS((3 - q) * KST - 1));
                WG_COMMIT();
                WG_WAIT(1);
#pragma unroll
                for (int s = 0; s < 9; s++) pA[s] = lds32(pa + 512 + s * 32);
                dlo -= 2; pa += 512;
            }
            pB[1] = lds32(pa + 256 + 32); pB[2] = lds32(pa + 256 + 64);
            WG_FENCE();
#pragma unroll
            for (int q = 0; q < 4; q++) wg32(D, TQ(pA, q), DS((3 - q) * KST));
            wg32(D, pB[1], pB[2], pA[8], pB[1], DS(3 * KST - 1));
            WG_COMMIT();
        }
        if (tid == 128) bulk_pf(pf_src, 16 * D_ * 2);
        if ((tid & 127) == 64) {
#pragma unroll 1
            for (int it = 0; it < SPIN_MAX && (int)(rcnt - G_ * epoch) < 0; it++) rcnt = ld_rlx(S->cnt);
        }
    }
    {
        named_bar(1 + wgi, 128);
        {
            const uint4* pq = M.box + (6 + g - 2 * t);
#define QM(q) (q).x, (q).y, (q).z, (q).w
            uint32_t bA[2][6], bB[2][6], bC[3][4], bD[2][4], bU[2][4];
            const uint32_t k2 = lds32(cb + XO_K1024);
            uint32_t ofs[3];
#pragma unroll
            for (int d = 0; d < 3; d++) ofs[d] = cb + ((w - d) < 0 ? 0 : 16) + (lr + 8 * (lm >> 1)) * 16;
#define COL(d) (2 * ((w - (d)) & 3) + (lm & 1))
            WG_WAIT(0);
            uint4 m[4];
#pragma unroll
            for (int d = 0; d < 2; d++) {
                const uint32_t a = XO_ZA + COL(d) * 400 + ofs[d];
                ldsm_x4(bA[d], a); ldsm_x4(bB[d], a + 3200);
                uint32_t r[4];
                ldsm_x4(r, a + 256 + (lm >> 1) * (3200 - 128));
                bA[d][4] = r[0]; bA[d][5] = r[1]; bB[d][4] = r[2]; bB[d][5] = r[3];
            }
#pragma unroll
            for (int i = 0; i < 4; i++) m[i] = pq[14 * i];
#pragma unroll
            for (int d = 0; d < 2; d++)
#pragma unroll
                for (int c = 0; c < 3; c++) mma_bf16(D + 4 + 4 * c, QM(m[d]), bA[d][2 * c], bA[d][2 * c + 1]);
#pragma unroll
            for (int d = 0; d < 3; d++) ldsm_x4(bC[d], XO_ZC + COL(d) * 272 + ofs[d]);
#pragma unroll
            for (int d = 0; d < 2; d++)
#pragma unroll
                for (int c = 0; c < 3; c++) mma_bf16(D + 4 + 4 * c, QM(m[2 + d]), bB[d][2 * c], bB[d][2 * c + 1]);
#pragma unroll
            for (int i = 0; i < 3; i++) m[i] = pq[14 * (4 + i)];
#pragma unroll
            for (int d = 0; d < 2; d++) { ldsm_x4(bD[d], XO_ZD + COL(d) * 272 + ofs[d]); ldsm_x4(bU[d], COL(d) * ULBO + 128 + ofs[d]); }
#pragma unroll
            for (int d = 0; d < 3; d++)
#pragma unroll
                for (int c = 0; c < 2; c++) mma_bf16(D + 8 + 4 * c, QM(m[d]), bC[d][2 * c], bC[d][2 * c + 1]);
#pragma unroll
            for (int i = 0; i < 4; i++) m[i] = pq[14 * (7 + i)];
#pragma unroll
            for (int d = 0; d < 2; d++)
#pragma unroll
                for (int c = 0; c < 2; c++) mma_bf16(D + 8 + 4 * c, QM(m[d]), bD[d][2 * c], bD[d][2 * c + 1]);
#pragma unroll
            for (int d = 0; d < 2; d++) {
                m[2 + d].x &= k2; m[2 + d].y &= k2; m[2 + d].z &= k2; m[2 + d].w &= k2;
#pragma unroll
                for (int c = 0; c < 2; c++) mma_bf16(D + 8 + 4 * c, QM(m[2 + d]), bU[d][2 * c], bU[d][2 * c + 1]);
            }
        }
        {
#pragma unroll 1
            for (int it = 0; it < SPIN_MAX && (gaw >> 16) != tag16; it++) gaw = ld_rlx(&S->modw[gidx]);
            const uint32_t ga2 = __byte_perm(gaw, 0, 0x1010), dk2 = M.pk[3][wgi];
            const uint32_t ua = cb + (2 * w + (lm & 1)) * ULBO + (9 + lr + 8 * (lm >> 1)) * 16;
            const uint32_t ya = cb + XO_TD + w * 1024;
            const uint32_t sa = ya + (lr + 8 * (lm >> 1)) * 32 + (((lm & 1) ^ ((lane >> 2) & 1)) << 4);
#pragma unroll
            for (int cc = 0; cc < 2; cc++) {
                uint32_t u[4], v[4];
                ldsm_x4_t(u, ua + cc * 256);
#pragma unroll
                for (int m = 0; m < 4; m++) {
                    const int c = 2 * cc + (m >> 1), h = m & 1;
                    v[m] = ~mul2(ga2, add2(pack2(D[4 * c + 2 * h], D[4 * c + 2 * h + 1]), mul2(u[m], dk2)));
                }
                stsm_x4_t(sa + cc * 512, v[0], v[1], v[2], v[3]);
            }
            __syncwarp();
            const int sw = (lane >> 3) & 1;
            const uint32_t vo = (uint32_t)(((4 * (lane >> 1) + w) * D_ + gidx - 2 * D_) * 32 + (lane & 1) * 16);
            const unsigned char* yp = sm + (ya - sb) + (lane >> 1) * 32 + (lane & 1) * 8;
#pragma unroll
            for (int i = 0; i < 2; i++) {
                const uint2 A = *(const uint2*)(yp + i * 512 + (sw << 4)), B = *(const uint2*)(yp + i * 512 + ((sw ^ 1) << 4));
                st_rlx4((char*)S->v + vo + i * (64 * D_ * 32), make_uint4(A.x, B.x, A.y, B.y));
            }
        }
    }
}

__global__ void __launch_bounds__(NTHR, 1)
mega_kernel(const bf16* __restrict__ x, const bf16* __restrict__ logAr, const bf16* __restrict__ Aim,
            const bf16* __restrict__ Cr, const bf16* __restrict__ Ci, const bf16* __restrict__ logdt, const bf16* __restrict__ c_in,
            Scratch* __restrict__ S, const bf16* __restrict__ Dskip, const bf16* __restrict__ w_r, const bf16* __restrict__ w_down,
            bf16* __restrict__ out,
            const __grid_constant__ CUtensorMap tm_wm, const __grid_constant__ CUtensorMap tm_wg, const __grid_constant__ CUtensorMap tm_wu,
            const __grid_constant__ CUtensorMap tm_wd, const __grid_constant__ CUtensorMap tm_wd32,
            const __grid_constant__ CUtensorMap tm_wg32, const __grid_constant__ CUtensorMap tm_wu32) {
    extern __shared__ __align__(1024) unsigned char sm[];
    Misc& M = *(Misc*)(sm + OFF_MISC);
    const uint32_t sb = (uint32_t)__cvta_generic_to_shared(sm);
    const int tid = threadIdx.x, warp = __shfl_sync(0xffffffffu, tid >> 5, 0), lane = tid & 31;
    const int g = lane >> 2, t = lane & 3, lr = lane & 7, lm = lane >> 3;
    const int wgi = warp >> 2, w = warp & 3;
    const int b = blockIdx.x;
    const int nch = 5 - (b & 1), cs = 9 * (b >> 1) + 5 * (b & 1);
    const int f0 = 72 * (b >> 1) + 32 * (b & 1), nf = 32 + 8 * (b & 1);
    const bool has_ch = wgi < nch;
    const uint32_t mb0 = sb + OFF_MISC + offsetof(Misc, mbar), mb_wm = mb0, mb_wg = mb0 + 16, mb_wu = mb0 + 24, mb_wd = mb0 + 32;
    const uint32_t cb = sb + OFF_CH + wgi * CHS;

    if (wgi == 3) {
        M.sent[tid - 384] = make_uint4(SENT, SENT, SENT, SENT);
        M.sent[tid - 256] = make_uint4(SENT, SENT, SENT, SENT);
        if (tid == 384) {
            M.epoch = 0u; M.flag = 0u; M.e1cnt = 0u;
#pragma unroll
            for (int i = 0; i < 5; i++) mbar_init(mb0 + 8 * i, 1);
        }
        PROXY_FENCE();
        __syncwarp();
        if (warp == 12) { named_arrive(8, 160); if (b & 1) named_arrive(14, 64); }
        if (warp != 15) named_arrive(9, 128);
    }
    unsigned short r_ldt = 0, r_lar = 0, r_aim = 0, r_cr = 0, r_ci = 0;
    if (has_ch) {
        const int d = cs + wgi, n = d * N_ + (tid & 127);
        r_ldt = ld_nc16((const unsigned short*)logdt + d);
        r_lar = ld_nc16((const unsigned short*)logAr + n);
        r_aim = ld_nc16((const unsigned short*)Aim + n);
        r_cr = ld_nc16((const unsigned short*)Cr + n);
        r_ci = ld_nc16((const unsigned short*)Ci + n);
    } else {
        const unsigned short* cp = (const unsigned short*)c_in + (tid - 512);
        r_ldt = ld_nc16(cp); r_lar = ld_nc16(cp + 128); r_aim = ld_nc16(cp + 256); r_cr = ld_nc16(cp + 384);
        if (tid < 576) r_ci = ld_nc16(cp + 512);
    }
    uint4 xr[9];
    if (wgi == 4) {
        const uint4* p = (const uint4*)(x + (size_t)16 * b * D_) + (tid - 512);
#pragma unroll
        for (int i = 0; i < 9; i++) xr[i] = ld_nc4(p + 128 * i);
    }
    uint32_t wrv = 0;
    if (tid >= 128 && tid < 416) wrv = ld_nc((const uint32_t*)w_r + (tid - 128));
    if (warp == 2 && lane < nch) M.pk[3][lane] = (uint32_t)ld_nc16((const unsigned short*)Dskip + cs + lane) * 0x10001u;
    if (tid == 384) {
        const unsigned int tk = atomicAdd(S->ticket, 1u);
        *(volatile unsigned int*)&M.epoch = (tk >> 7) + 1u;
    }
    if (has_ch) {
        for (int i = tid & 127; i < 296; i += 128) *(uint4*)(sm + OFF_CH + wgi * CHS + XO_TD + i * 16) = make_uint4(0, 0, 0, 0);
    }
    if (tid < 154) {
        const int idx = (tid * 4682) >> 16, dl = tid - 14 * idx - 6;
        const int a = (0x44332221100ull >> (4 * idx)) & 7, d = (0x10102101010ull >> (4 * idx)) & 3;
        const int lo = (0x35c36 >> (4 * a)) & 15, wd = (0x16824 >> (4 * a)) & 15;
        const uint32_t one = (a == 4) ? 0xFFFFu : 0x3F80u;
        auto mk = [&](int l) { return (((unsigned)(l - lo) <= (unsigned)wd) ? one : 0u) | (((unsigned)(l - 1 - lo) <= (unsigned)wd) ? (one << 16) : 0u); };
        const int l0 = 16 * d + dl;
        M.box[tid] = make_uint4(mk(l0), mk(l0 + 8), mk(l0 - 8), mk(l0));
    }
    uint32_t xo[6];
#pragma unroll
    for (int i = 0; i < 6; i++) {
        const int ch = 16 * (warp + 16 * (i >> 1)) + 8 * (i & 1) + g;
        const int pr = (ch * 7282) >> 16, rm = ch - 9 * pr, hi = rm >= 5;
        xo[i] = (uint32_t)((((2 * pr + hi) * G_ + b) * 5 + rm - 5 * hi) * 32 + t * 8);
    }
    auto e1_store = [&]() {
        named_bar(11, 640);
        uint32_t mm[2], rhh[2], rll[2];
#pragma unroll
        for (int h = 0; h < 2; h++) {
            mm[h] = ((const uint32_t*)M.st1[0])[t + 4 * h]; rhh[h] = ((const uint32_t*)M.st1[1])[t + 4 * h]; rll[h] = ((const uint32_t*)M.st1[2])[t + 4 * h];
        }
        const uint32_t ta = sb + OFF_TILE + (lr + 8 * (lm & 1)) * (ROWP * 2) + (lm >> 1) * 16 + warp * 32;
#pragma unroll
        for (int i = 0; i < 3; i++) {
            if (i < 2 || warp < 4) {
                uint32_t r[4];
                ldsm_x4_t(r, ta + i * 512);
#pragma unroll
                for (int h = 0; h < 2; h++)
                    st_rlx2((char*)S->xn + xo[2 * i + h], ~norm2(r[2 * h], mm[0], rhh[0], rll[0]), ~norm2(r[2 * h + 1], mm[1], rhh[1], rll[1]));
            }
        }
        __syncwarp();
        if (lane == 0 && atomicAdd(&M.e1cnt, 1u) == 15u) red_inc(S->hint);
    };
    const float p_ldt = lo2f(r_ldt), p_lar = lo2f(r_lar), p_aim = lo2f(r_aim), p_cr = lo2f(r_cr), p_ci = lo2f(r_ci);
    cplx z1 = {0.f, 0.f}, z16 = z1, z256 = z1, C = z1;
    const uint32_t scr = cb + w * KSCR, ws = scr + lane * 4;
    float acc[5][4];
    uint32_t afr[4][4], cz[4];
    cplx z2 = {0.f, 0.f};
    const uint32_t ba = scr + lr * 144 + lm * 16;
    auto tile = [&](float* c, int rg) {
        __syncwarp();
        c[0] = c[1] = c[2] = c[3] = 0.f;
        uint32_t bb[2][4];
        ldsm_x4(bb[0], ba + rg * 1152);
        ldsm_x4(bb[1], ba + rg * 1152 + 64);
        mma_f16(c, afr[0], bb[0][0], bb[0][1]);
        mma_f16(c, afr[1], bb[0][2], bb[0][3]);
        mma_f16(c, afr[2], bb[1][0], bb[1][1]);
        mma_f16(c, afr[3], bb[1][2], bb[1][3]);
    };
#define CJ(z) packh((z).x, -(z).y)
#define CJP(z) packh((z).y, (z).x)
    uint32_t ex = 0;
    if (has_ch) {
        const float dt = bfr(expf(p_ldt));
        const float al = -bfr(expf(p_lar)) * dt * 1.4426950408889634f;
        const float th = p_aim * dt;
        const float th_ = th * 0.15915494309189535f;
        const float tl_ = fmaf(th, 0.15915494309189535f, -th_) + th * 6.4206382e-9f;
        auto anchor = [&](float s) {
            float f = th_ * s;
            f -= rintf(f);
            f = fmaf(tl_, s, f) * 6.283185307179586f;
            const float e = fex2(al * s);
            return cplx{e * __cosf(f), e * __sinf(f)};
        };
        const float cx = p_cr * dt * 2.0f, cy = p_ci * dt * 2.0f;
        ex = __reduce_max_sync(0xffffffffu, __float_as_uint(fmaxf(fabsf(cx), fabsf(cy)))) >> 23;
        const float scl = __uint_as_float((254u - ex) << 23);
        C = cplx{cx * scl, cy * scl};
        z1 = anchor(1.f); z16 = anchor(16.f); z256 = anchor(256.f);
            {
                const cplx z32 = csq(z16), z48 = cmul(z32, z16), z64 = csq(z32), z128 = csq(z64), z192 = cmul(z128, z64);
                const uint32_t y[3] = {packh(z16.x, z16.y), packh(z32.x, z32.y), packh(z48.x, z48.y)};
                const uint32_t yp[3] = {packh(-z16.y, z16.x), packh(-z32.y, z32.x), packh(-z48.y, z48.x)};
                const uint32_t xx[3] = {packh(z64.x, z64.y), packh(z128.x, z128.y), packh(z192.x, z192.y)};
                sts32(ws, 0x00003C00u);
#pragma unroll
                for (int j = 0; j < 3; j++) sts32(ws + (1 + j) * 144, y[j]);
#pragma unroll
                for (int i = 0; i < 3; i++) {
                    sts32(ws + (4 + 4 * i) * 144, xx[i]);
#pragma unroll
                    for (int j = 0; j < 3; j++) sts32(ws + (5 + 4 * i + j) * 144, hcm(xx[i], y[j], yp[j]));
                }
            }
    }
    if (wgi == 4) {
        if (!has_ch) {
            const int i = tid - 512;
            ((unsigned short*)M.sc)[i] = (unsigned short)f2bits(silu(lo2f(r_ldt)));
            ((unsigned short*)M.sc)[i + 128] = (unsigned short)f2bits(silu(lo2f(r_lar)));
            ((unsigned short*)M.sc)[i + 256] = (unsigned short)f2bits(silu(lo2f(r_aim)));
            ((unsigned short*)M.sc)[i + 384] = (unsigned short)f2bits(silu(lo2f(r_cr)));
            if (i < 64) ((unsigned short*)M.sc)[i + 512] = (unsigned short)f2bits(silu(lo2f(r_ci)));
            if (warp == 16) {
                named_bar(14, 64);
                if (lane == 0) {
                    mbar_expect(mb_wm, 36864);
#pragma unroll
                    for (int k = 0; k < 3; k++) tma2d(sb + OFF_WU + k * 12288, &tm_wm, 32 * (b >> 1), 192 * k, mb_wm);
                }
                __syncwarp();
            }
        }
#pragma unroll
        for (int i = 0; i < 9; i++) {
            const int c = tid - 512 + 128 * i, rr = (c * 911) >> 16;
            *(uint4*)(sm + OFF_TILE + rr * (ROWP * 2 - 1152) + c * 16) = xr[i];
        }
        named_bar(8, 160);
        {
            float c1[4] = {0.f, 0.f, 0.f, 0.f}, cl[4] = {0.f, 0.f, 0.f, 0.f}, chh[4] = {0.f, 0.f, 0.f, 0.f};
            const uint32_t a0 = sb + OFF_TILE + (lane & 15) * (ROWP * 2) + (lane >> 4) * 16 + w * 288;
            uint32_t a[9][4];
#pragma unroll
            for (int ks = 0; ks < 9; ks++) ldsm_x4(a[ks], a0 + ks * 32);
#pragma unroll
            for (int ks = 0; ks < 9; ks++) {
                mma_bf16(c1, a[ks][0], a[ks][1], a[ks][2], a[ks][3], 0x3F803F80u, 0x3F803F80u);
                mma_bf16(cl, a[ks][0], a[ks][1], a[ks][2], a[ks][3], a[ks][0], a[ks][2]);
                mma_bf16(chh, a[ks][0], a[ks][1], a[ks][2], a[ks][3], a[ks][1], a[ks][3]);
            }
            if (t == 0) { M.p1[g][w] = c1[0]; M.p1[g + 8][w] = c1[2]; }
            if (t == (g >> 1)) { M.p2[g][w] = (g & 1) ? cl[1] : cl[0]; M.p2[g + 8][w] = (g & 1) ? chh[3] : chh[2]; }
        }
        named_bar(5, 128);
        if (warp == 16) {
            const float4 q1 = *(const float4*)M.p1[lane & 15], q2 = *(const float4*)M.p2[lane & 15];
            float meanb, rinv;
            ln_stats((q1.x + q1.y) + (q1.z + q1.w), (q2.x + q2.y) + (q2.z + q2.w), meanb, rinv);
            const float rh = bfr(rinv);
            if (lane < 16) { M.st1[0][lane] = (unsigned short)f2bits(meanb); M.st1[1][lane] = (unsigned short)f2bits(rh); M.st1[2][lane] = (unsigned short)f2bits(rinv - rh); }
        }
        __syncwarp();
        named_arrive(11, 640);
    }
    auto publish_reset = [&]() {
        if (tid == 480) {
            asm volatile("cp.async.bulk.wait_group 0;" ::: "memory");
            asm volatile("fence.proxy.async;" ::: "memory");
            red_inc(S->cnt);
        }
    };
    uint32_t epoch = 0, tag16 = 0, pre = 0;
    auto mod_tile = [&](int rd) {
        const uint32_t* s2 = (const uint32_t*)M.sc + 144 * (w >> 1) + t;
        uint32_t bb[18][2];
#pragma unroll
        for (int ks = 0; ks < 18; ks++) { bb[ks][0] = (g == 0) ? s2[8 * ks] : 0u; bb[ks][1] = (g == 0) ? s2[8 * ks + 4] : 0u; }
        float acc[2][4] = {{0.f, 0.f, 0.f, 0.f}, {0.f, 0.f, 0.f, 0.f}};
        const int row = lr + 8 * (lm >> 1);
        const uint32_t wa = sb + OFF_WU + (288 * (w >> 1) + row) * 64 + ((((2 * (w & 1) + (lm & 1)) ^ (row >> 1)) & 3) << 4);
        mbar_wait(mb_wm + 8 * rd, 0);
        if (rd == 0)
#pragma unroll
        for (int kb = 0; kb < 2; kb++) {
            uint32_t a[9][4];
#pragma unroll
            for (int ks = 0; ks < 9; ks++) ldsm_x4_t(a[ks], wa + (9 * kb + ks) * 1024);
#pragma unroll
            for (int ks = 0; ks < 9; ks++) mma_bf16(acc[ks & 1], a[ks][0], a[ks][1], a[ks][2], a[ks][3], bb[9 * kb + ks][0], bb[9 * kb + ks][1]);
        }
        const float v0 = acc[0][0] + acc[1][0], v1 = acc[0][2] + acc[1][2];
        float* mx = M.modx + 16 * (w & 1) + g;
        if (w >= 2 && t == 0) { mx[0] = v0; mx[8] = v1; }
        named_bar(5, 128);
        if (w < 2 && t == 0) {
            unsigned int* mp = &S->modw[32 * ((b >> 1) + 64 * rd) + 16 * w + g];
            st_rlx(mp, f2bits(v0 + mx[0]) | (tag16 << 16));
            st_rlx(mp + 8, f2bits(v1 + mx[8]) | (tag16 << 16));
        }
        if (rd == 0 && w < 2 && b < 108) {
            named_bar(7, 64);
            if (tid == 512) red_inc(S->hint);
        }
    };
    if (has_ch) {
        {
            z2 = csq(z1);
            const cplx z3 = cmul(z2, z1), z4 = csq(z2), z8 = csq(z4);
            const cplx c4 = cmul(C, z4), c8 = cmul(C, z8), c12 = cmul(c8, z4);
            cz[0] = packh(C.x, -C.y); cz[1] = packh(c4.x, -c4.y); cz[2] = packh(c8.x, -c8.y); cz[3] = packh(c12.x, -c12.y);
            __syncwarp();
#pragma unroll
            for (int s = 0; s < 4; s++) ldsm_x4(afr[s], scr + (lr + 8 * (lm & 1)) * 144 + (2 * s + (lm >> 1)) * 16);
            {
                const uint32_t y[3] = {CJ(z1), CJ(z2), CJ(z3)}, yp[3] = {CJP(z1), CJP(z2), CJP(z3)};
#pragma unroll
                for (int tt = 0; tt < 2; tt++) {
                    const int rg = tt ? 0 : 2;
#pragma unroll
                    for (int i = 0; i < 2; i++) {
                        sts32(ws + rg * 1152 + (4 * i) * 144, cz[2 * tt + i]);
#pragma unroll
                        for (int j = 0; j < 3; j++) sts32(ws + rg * 1152 + (4 * i + 1 + j) * 144, hcm(cz[2 * tt + i], y[j], yp[j]));
                    }
                    tile(acc[tt], rg);
                }
            }
            if (tid >= 128 && tid < 416) M.wr[tid - 128] = wrv;
            if (wgi < 4) e1_store();
    if (warp == 15) {
        named_bar(9, 128);
        if (lane == 0) {
#pragma unroll 1
            for (int i = 0; i < 5; i++) {
                bulk_s2g((char*)&S->v[(size_t)b * 1152] + i * 4096, sb + OFF_MISC, i < 4 ? 4096 : 2048);
                if (i < 3) bulk_s2g((char*)&S->part[(size_t)b * 1152] + i * 4096, sb + OFF_MISC, i < 2 ? 4096 : 1024);
            }
            bulk_s2g(&S->rec[8 * b], sb + OFF_MISC, 32);
            asm volatile("cp.async.bulk.commit_group;" ::: "memory");
        }
        __syncwarp();
    }
            const cplx z258 = cmul(z256, z2), z512 = csq(z256), z768 = cmul(z512, z256);
            {
                const uint32_t a0 = CJ(z256), a0p = CJP(z256), a1 = CJ(z258), a1p = CJP(z258);
#pragma unroll
                for (int i = 0; i < 4; i++) { sts32(ws + 1152 + (2 * i) * 144, hcm(cz[i], a0, a0p)); sts32(ws + 1152 + (2 * i + 1) * 144, hcm(cz[i], a1, a1p)); }
                tile(acc[2], 1);
            }
            {
                const uint32_t a0 = CJ(z512), a0p = CJP(z512), a1 = CJ(z768), a1p = CJP(z768);
#pragma unroll
                for (int i = 0; i < 4; i++) { sts32(ws + 2304 + i * 144, hcm(cz[i], a0, a0p)); sts32(ws + 2304 + (4 + i) * 144, hcm(cz[i], a1, a1p)); }
                tile(acc[3], 2);
            }
            if (warp == 3) {
                if (lane == 15) pre = ld_rlx(S->hint);
            }
            const cplx z1024 = csq(z512);
            {
                const cplx zk[4] = {z1024, cmul(z1024, z256), csq(z768), cmul(z1024, z768)};
#pragma unroll
                for (int h = 0; h < 4; h++) {
                    const uint32_t a0 = CJ(zk[h]), a0p = CJP(zk[h]);
                    sts32(ws + (2 * h) * 144, hcm(cz[0], a0, a0p));
                    sts32(ws + (2 * h + 1) * 144, hcm(cz[2], a0, a0p));
                }
                tile(acc[4], 0);
            }
            const cplx z2048 = csq(z1024);
            float last = C.x * z2048.x - C.y * z2048.y;
#pragma unroll
            for (int o = 16; o; o >>= 1) last += __shfl_xor_sync(0xffffffffu, last, o);
            __syncwarp();
#pragma unroll
            for (int i = 0; i < 5; i++) *(float4*)(sm + (scr - sb) + i * 512 + lane * 16) = make_float4(acc[i][0], acc[i][1], acc[i][2], acc[i][3]);
            if (lane == 0) { const float inv = __uint_as_float(ex << 23); M.kinv[wgi][w] = inv; M.klast[wgi][w] = last * inv; }
        }
        if (tid == 111 && (int)(pre - HINT_N * wait_epoch(M)) >= 0) M.flag = 1u;
        named_bar(1 + wgi, 128);
        const uint32_t td = cb + XO_TD + 64 * 4, tf = cb + XO_TF - 32 * 4;
        if (tid == 111 && !M.flag) pre = ld_rlx(S->hint);
        const float4 ki = *(const float4*)M.kinv[wgi];
        auto fsum = [&](int off, uint32_t& r0, uint32_t& r1) {
            const unsigned char* p = sm + (cb - sb) + off;
            const float4 a = *(const float4*)p, b2 = *(const float4*)(p + KSCR), c = *(const float4*)(p + 2 * KSCR), d = *(const float4*)(p + 3 * KSCR);
            r0 = pack2(fmaf(a.y, ki.x, b2.y * ki.y) + fmaf(c.y, ki.z, d.y * ki.w), fmaf(a.x, ki.x, b2.x * ki.y) + fmaf(c.x, ki.z, d.x * ki.w));
            r1 = pack2(fmaf(a.w, ki.x, b2.w * ki.y) + fmaf(c.w, ki.z, d.w * ki.w), fmaf(a.z, ki.x, b2.z * ki.y) + fmaf(c.z, ki.z, d.z * ki.w));
        };
        uint32_t r[2], q[2];
        fsum(w * 512 + lane * 16, r[0], r[1]);
        fsum(2048 + w * 128 + lr * 16, q[0], q[1]);
        if (tid == 111) {
            if ((int)(pre - HINT_N * M.epoch) >= 0) M.flag = 1u;
            else pre = ld_rlx(S->hint);
        }
        __syncwarp();
        if (w < 2) {
            const uint32_t p = td + (16 * g + 8 * w + 2 * t) * 4;
#pragma unroll
            for (int h = 0; h < 2; h++) { sts16(p + h * 512, r[h] >> 16); sts32(p + h * 512 + 4, r[h]); sts16(p + h * 512 + 10, r[h]); }
        } else if (w == 2) {
            const uint32_t p = td + (256 + 16 * g + 4 * t) * 4;
#pragma unroll
            for (int h = 0; h < 2; h++) {
                const uint32_t k0 = r[h] >> 16;
                if (h || lane) { sts16(p + h * 512 - 4, k0); sts16(p + h * 512 + 2, k0); }
                sts16(p + h * 512, k0); sts32(p + h * 512 + 4, __byte_perm(r[h], 0, 0x3232)); sts32(p + h * 512 + 8, r[h]); sts16(p + h * 512 + 14, r[h]);
            }
        } else {
            const uint32_t p = tf + (64 + 32 * (t >> 1) + 2 * g + (t & 1)) * 4;
#pragma unroll
            for (int h = 0; h < 2; h++) {
                const uint32_t k0 = r[h] >> 16;
                sts16(p + h * 64 + 512, r[h]); sts16(p + h * 64 + 518, r[h]);
                if (h || lane) { sts16(p + h * 64 - 4, k0); sts16(p + h * 64 + 2, k0); }
            }
            if (lane == 0) {
                const uint32_t dd = __byte_perm(r[0], 0, 0x3232);
                sts16(td + 511 * 4, dd); sts32(td + 512 * 4, dd); sts32(td + 513 * 4, dd); sts32(td + 514 * 4, dd); sts16(td + 515 * 4 + 2, dd);
            }
        }
        if (lane < 8) {
            const uint32_t p = tf + 1024 + (64 + 16 * t + 2 * w + g) * 4;
#pragma unroll
            for (int h = 0; h < 2; h++) {
                const uint32_t k0 = q[h] >> 16;
                sts16(p + h * 32 + 512, q[h]); sts16(p + h * 32 + 518, q[h]);
                if (h || (tid & 127)) { sts16(p + h * 32 - 4, k0); sts16(p + h * 32 + 2, k0); }
            }
            if ((tid & 127) == 0) {
                const float4 kl4 = *(const float4*)M.klast[wgi];
                const uint32_t kl = f2bits((kl4.x + kl4.y) + (kl4.z + kl4.w)), dd = __byte_perm(q[0], 0, 0x3232);
                sts16(tf + 127 * 4, dd); sts16(tf + 128 * 4 + 2, dd); sts32(cb + XO_K1024, dd);
                sts16(tf + 1024 + 127 * 4, kl); sts16(tf + 1024 + 128 * 4 + 2, kl);
            }
        }
        __syncwarp();
    } else {
        const int i = tid - 512, idx = b >> 1;
        tag16 = (wait_epoch(M) % 65535u) + 1u;
        mod_tile(0);
        if (i == 0 && idx < 44) {
            PROXY_FENCE();
            mbar_expect(mb_wm + 8, 36864);
#pragma unroll
            for (int k = 0; k < 3; k++) tma2d(sb + OFF_WU + k * 12288, &tm_wm, 32 * (idx + 64), 192 * k, mb_wm + 8);
        }
        __syncwarp();
    }
    if (tid == 111) {
        epoch = wait_epoch(M);
#pragma unroll 1
        for (int it = 0; it < SPIN_MAX && (int)(pre - HINT_N * epoch) < 0; it++) pre = ld_rlx(S->hint);
        M.flag = 1u;
    }
    __syncwarp();
    const int ubp = (tid * 13108) >> 16, uloc = tid - 5 * ubp;
    const uint4* usrc = &S->xn[(size_t)b * 1280 + 2 * tid];
    uint4 ua = make_uint4(0, 0, 0, 0), uc = ua;
    uint32_t usa = 0, uca = 0;
    if (lane == 0) {
#pragma unroll 1
        for (int it = 0; it < (SPIN_MAX << 4) && !M.flag; it++) { }
    }
    __syncwarp();
    if (uloc < nch) {
 ua = ld_rlx4(usrc); uc = ld_rlx4(usrc + 1); usa = ld_rlx(&S->modw[cs + uloc]); uca = ld_rlx(&S->modw[D_ + cs + uloc]); }
    CBAR();
    epoch = M.epoch;
    tag16 = (epoch % 65535u) + 1u;
    {
        const int bp = ubp, loc = uloc;
        if (loc < nch) {
            const uint4* src = usrc;
            uint4 a = ua, c = uc;
#pragma unroll 1
            for (int it = 0; it < SPIN_MAX && (a.x == SENT || a.z == SENT || c.x == SENT || c.z == SENT || (usa >> 16) != tag16 || (uca >> 16) != tag16); it++) {
                a = ld_rlx4(src); c = ld_rlx4(src + 1); usa = ld_rlx(&S->modw[cs + loc]); uca = ld_rlx(&S->modw[D_ + cs + loc]);
            }
            const uint32_t sa = __byte_perm(usa, 0, 0x1010), ca = pack2(1.0f + lo2f(uca), 1.0f + lo2f(uca));
            unsigned char* up = sm + OFF_CH + loc * CHS + ((2 * bp) & 7) * ULBO + ((bp >> 2) + 9) * 16;
            *(uint4*)up = make_uint4(add2(mul2(~a.x, ca), sa), add2(mul2(~a.z, ca), sa), add2(mul2(~c.x, ca), sa), add2(mul2(~c.z, ca), sa));
            *(uint4*)(up + ULBO) = make_uint4(add2(mul2(~a.y, ca), sa), add2(mul2(~a.w, ca), sa), add2(mul2(~c.y, ca), sa), add2(mul2(~c.w, ca), sa));
        }
        publish_reset();
        const int i = tid & 127;
        unsigned char* cp = sm + OFF_CH + wgi * CHS;
        *(uint4*)(cp + XO_U8 - 1024 + (i >> 6) * 4096 + (i & 63) * 16) = make_uint4(0, 0, 0, 0);
        if (i < 72) { const int c = (i * 57) >> 9; *(uint4*)(cp + c * ULBO + (i - 9 * c) * 16) = make_uint4(0, 0, 0, 0); }
    }
    PROXY_FENCE();
    CBAR();
    if (w == 2 && lane == 0) {
        bulk_s2g((char*)&S->xn[(size_t)b * 1280] + wgi * 4096, sb + OFF_MISC, 4096);
        asm volatile("cp.async.bulk.commit_group;" ::: "memory");
    }
        if (tid == 416) {
            mbar_expect(mb_wg, nf * D_ * 2);
            tma2d(sb + OFF_WG, (b & 1) ? &tm_wg : &tm_wg32, f0, 0, mb_wg);
        }
    if (tid == 96 || tid == 224) tma2d(sb + OFF_WG + (1 + (tid >> 7)) * (nf * 384), (b & 1) ? &tm_wg : &tm_wg32, f0, 192 * (1 + (tid >> 7)), mb_wg);
    if (has_ch) {
        __syncwarp();
        conv_channel(sm, S, 2 * D_ + cs + wgi, epoch, w_down + (size_t)f0 * D_, (b & 1) ? nullptr : &tm_wu32, f0);
    } else {
        const int idx = b >> 1;
        if (idx < 44) mod_tile(1);
        if (tid == 512) {
            PROXY_FENCE();
            mbar_expect(mb_wu, 46080);
#pragma unroll 1
            for (int i = 0; i < 3; i++) {
                tma2d(sb + OFF_WU + i * 15360, &tm_wu, f0, 192 * i, mb_wu);
                const long long c0 = clock64();
                int it = 0;
                while (clock64() - c0 < 1200 && ++it < 4096) { }
            }
            wait_reset(S->cnt, epoch);
        }
        named_bar(5, 128);
    }
    {
    const int tid = fresh_tid(), warp = __shfl_sync(0xffffffffu, tid >> 5, 0), lane = tid & 31;
    const int g = lane >> 2, t = lane & 3, lr = lane & 7, lm = lane >> 3;
    uint32_t v3 = 0, v4 = 0, v5 = 0;
    auto load_consts = [&]() {
        if (tid < D_) { v3 = ld_rlx(&S->modw[3 * D_ + tid]); v4 = ld_rlx(&S->modw[4 * D_ + tid]); v5 = ld_rlx(&S->modw[5 * D_ + tid]); }
    };
    if (tid == 0) bulk_pf(w_down + (size_t)(f0 + 16) * D_, (nf - 16) * D_ * 2);
    uint32_t x1[2][4], wr2[2][2];
    if (warp < 18) {
        const char* vp = (const char*)S->v + ((size_t)b * D_ + 32 * warp + g) * 32 + t * 8;
        uint2 v[4];
#pragma unroll
        for (int i = 0; i < 4; i++) v[i] = ld_rlx2(vp + i * 256);
#pragma unroll
        for (int j = 0; j < 2; j++) {
            const uint32_t* wp = M.wr + 16 * warp + 8 * j + t;
            wr2[j][0] = (g == 0) ? wp[0] : 0u;
            wr2[j][1] = (g == 0) ? wp[4] : 0u;
            ldsm_x4(x1[j], sb + OFF_TILE + (lr + 8 * (lm & 1)) * (ROWP * 2) + (lm >> 1) * 16 + warp * 64 + j * 32);
        }
#pragma unroll 1
        for (int it = 0; it < SPIN_MAX && ((v3 >> 16) != tag16 || (v4 >> 16) != tag16 || (v5 >> 16) != tag16); it++) load_consts();
        ((unsigned short*)M.sb)[tid] = (unsigned short)v3;
        ((unsigned short*)M.cb1)[tid] = (unsigned short)f2bits(1.0f + lo2f(v4));
        ((unsigned short*)M.gb)[tid] = (unsigned short)v5;
#pragma unroll 1
        for (int it = 0; it < SPIN_MAX; it++) {
            bool bad = false;
#pragma unroll
            for (int i = 0; i < 4; i++) if (v[i].x == SENT) { v[i] = ld_rlx2(vp + i * 256); bad = true; }
            if (!bad) break;
        }
        __syncwarp();
        float c1[4] = {0.f, 0.f, 0.f, 0.f}, cl[4] = {0.f, 0.f, 0.f, 0.f}, chh[4] = {0.f, 0.f, 0.f, 0.f};
#pragma unroll
        for (int j = 0; j < 2; j++) {
            x1[j][0] = add2(x1[j][0], movm(~v[2 * j].x)); x1[j][1] = add2(x1[j][1], movm(~v[2 * j].y));
            x1[j][2] = add2(x1[j][2], movm(~v[2 * j + 1].x)); x1[j][3] = add2(x1[j][3], movm(~v[2 * j + 1].y));
            mma_bf16(c1, x1[j][0], x1[j][1], x1[j][2], x1[j][3], 0x3F803F80u, 0x3F803F80u);
            mma_bf16(cl, x1[j][0], x1[j][1], x1[j][2], x1[j][3], x1[j][0], x1[j][2]);
            mma_bf16(chh, x1[j][0], x1[j][1], x1[j][2], x1[j][3], x1[j][1], x1[j][3]);
        }
        float* pp = (float*)&M.part[warp][g];
        if (t == 0) { pp[0] = c1[0]; pp[16] = c1[2]; }
        if (t == (g >> 1)) { pp[1] = (g & 1) ? cl[1] : cl[0]; pp[17] = (g & 1) ? chh[3] : chh[2]; }
    }
    CBAR();
    if (warp < 18) {
        const int tok = lane & 15, hf = lane >> 4;
        uint32_t kc[2][2][2];
#pragma unroll
        for (int j = 0; j < 2; j++)
#pragma unroll
            for (int q = 0; q < 2; q++) { kc[j][q][0] = ((const uint32_t*)M.cb1)[16 * warp + 8 * j + 4 * q + t]; kc[j][q][1] = ((const uint32_t*)M.sb)[16 * warp + 8 * j + 4 * q + t]; }
        named_bar(13, 608);
        uint32_t st[2][3];
#pragma unroll
        for (int h = 0; h < 2; h++) { const uint4 q = M.st2[g + 8 * h]; st[h][0] = q.x; st[h][1] = q.y; st[h][2] = q.z; }
        float rc[4] = {0.f, 0.f, 0.f, 0.f};
        uint32_t h2[2][4];
#pragma unroll
        for (int j = 0; j < 2; j++) {
#pragma unroll
            for (int r = 0; r < 4; r++) {
                h2[j][r] = add2(mul2(norm2(x1[j][r], st[r & 1][0], st[r & 1][1], st[r & 1][2]), kc[j][r >> 1][0]), kc[j][r >> 1][1]);
            }
            mma_bf16(rc, h2[j][0], h2[j][1], h2[j][2], h2[j][3], wr2[j][0], wr2[j][1]);
        }
        if (t == 0) { M.rp[warp][g] = rc[0]; M.rp[warp][g + 8] = rc[2]; }
        if (warp == 0) {
            named_bar(12, 576);
            float r = M.rp[9 * hf][tok];
#pragma unroll
            for (int i = 1; i < 9; i++) r += M.rp[9 * hf + i][tok];
            r += __shfl_xor_sync(0xffffffffu, r, 16);
            const uint32_t rbits = f2bits(r);
            const uint32_t key = 0x80000000u | ((rbits ^ ((rbits & 0x8000u) ? 0xFFFFu : 0x8000u)) << 11) | (uint32_t)(2047 - (16 * b + tok));
            int rank = 0;
#pragma unroll
            for (int j = 1; j < 16; j++) rank += __shfl_xor_sync(0xffffffffu, key, j) > key;
            if (lane < 16) { M.skey[rank] = key; M.rank[rank] = tok; }
            __syncwarp();
            if (lane < 2) st_rlx4(&S->rec[8 * b + 4 * lane], *(const uint4*)&M.skey[4 * lane]);
        } else named_arrive(12, 576);
#pragma unroll
        for (int j = 0; j < 2; j++) {
            uint32_t o[4];
#pragma unroll
            for (int r = 0; r < 4; r++) o[r] = add2(x1[j][r], mul2(((const uint32_t*)M.gb)[16 * warp + 8 * j + 4 * (r >> 1) + t], h2[j][r]));
            const uint32_t to = (lr + 8 * (lm & 1)) * (ROWP * 2) + (lm >> 1) * 16 + warp * 64 + j * 32;
            stsm_x4(sb + OFF_H2T + to, h2[j][0], h2[j][1], h2[j][2], h2[j][3]);
            stsm_x4(sb + OFF_TILE + to, o[0], o[1], o[2], o[3]);
        }
    } else if (warp == 19) {
        const int tok = lane & 15, hf = lane >> 4;
        float2 s = M.part[9 * hf][tok];
#pragma unroll
        for (int i = 1; i < 9; i++) { const float2 q = M.part[9 * hf + i][tok]; s.x += q.x; s.y += q.y; }
        s.x += __shfl_xor_sync(0xffffffffu, s.x, 16); s.y += __shfl_xor_sync(0xffffffffu, s.y, 16);
        float meanb, rinv;
        ln_stats(s.x, s.y, meanb, rinv);
        const float rh = bfr(rinv);
        if (lane < 16) M.st2[tok] = make_uint4(pack2(meanb, meanb), pack2(rh, rh), pack2(rinv - rh, rinv - rh), 0u);
        __syncwarp();
        named_arrive(13, 608);
    } else if (lane < 9) {
        PROXY_FENCE();
        if (lane == 0) mbar_expect(mb_wd, nf * D_ * 2);
        tma2d(sb + OFF_WD + lane * 5120, (b & 1) ? &tm_wd : &tm_wd32, 64 * lane, f0, mb_wd);
    }
    CBAR();
    uint32_t wf[9][4], wd[2][3][4];
    const int fmt = warp >> 2, fsl = warp & 3;
    auto load_wf = [&]() {
        mbar_wait(mb_wg, 0);
        mbar_wait(mb_wu, 0);
        if (fmt < 4 || nf > 32) {
            const int half = lm & 1;
            const uint32_t base = (fmt == 4) ? ((half ? OFF_WU : OFF_WG) + 64)
                                             : ((fmt >> 1) * OFF_WU + (((2 * (fmt & 1) + half) ^ ((b & 1) ? 0 : (lr >> 1))) << 4));
            const uint32_t wa = sb + base + (144 * fsl + lr + 8 * (lm >> 1)) * (2 * nf);
#pragma unroll
            for (int ks = 0; ks < 9; ks++) ldsm_x4_t(wf[ks], wa + ks * (32 * nf));
        }
    mbar_wait(mb_wd, 0);
    {
#pragma unroll
        for (int i = 0; i < 2; i++) {
            const int mt = warp + 20 * i;
            const uint32_t wa = sb + OFF_WD + (mt >> 2) * 5120 + lr * 128 + (((2 * (mt & 3) + (lm & 1)) ^ lr) << 4);
#pragma unroll
            for (int ks = 0; ks < 3; ks++)
                if ((i == 0 || warp < 16) && (ks < 2 || nf > 32)) ldsm_x4_t(wd[i][ks], wa + ks * 2048 + ((ks < 2) ? (lm >> 1) * 1024 : 0));
        }
    }
    };
    if (warp >= 8) {
        if (warp < 16) {
            const int tk = M.rank[warp - 8];
            const uint32_t* hp = (const uint32_t*)(sm + OFF_H2T + tk * (ROWP * 2)) + lane;
            uint4* dst = &S->h2w[(size_t)(16 * b + tk) * 96 + lane];
#pragma unroll
            for (int j = 0; j < 3; j++) st_rlx4(dst + 32 * j, make_uint4(hp[96 * j], hp[96 * j + 32], hp[96 * j + 64], epoch));
        }
        load_wf();
    } else {
        const uint4* rp = (const uint4*)S->rec + tid;
        load_wf();
        uint4 rk = ld_rlx4(rp);
#pragma unroll 1
        for (int it = 0; it < SPIN_MAX && !rk.x; it++) rk = ld_rlx4(rp);
        __syncwarp();
        uint32_t mine = 0;
#pragma unroll
        for (int rnd = 0; rnd < 8; rnd++) {
            const uint32_t m = __reduce_max_sync(0xffffffffu, rk.x);
            if (rk.x == m) { rk.x = rk.y; rk.y = rk.z; rk.z = rk.w; rk.w = 0u; }
            if (lane == rnd) mine = m;
        }
        if (lane < 8) M.cand[8 * warp + lane] = mine;
    }
    CBAR();
    uint32_t selv = 0;
    if (warp < 12) {
        uint2 k = *(const uint2*)&M.cand[2 * lane];
#pragma unroll
        for (int rnd = 0; rnd < 8; rnd++) {
            const uint32_t m = __reduce_max_sync(0xffffffffu, k.x);
            if (k.x == m) { k.x = k.y; k.y = 0u; }
            if (lr == rnd) selv = m;
        }
        if (tid < 8) M.skey[tid] = selv;
    }
    const uint32_t seltok = 2047u - (selv & 2047u);
    const int fo = tid >> 3;
    const int fW = 9 * b + (fo >> 2), fcomp = fo & 3;
    const int fd = 16 * (fW >> 5) + ((fW >> 2) & 7) + 8 * (fcomp >> 1), fk = 2 * (fW & 3) + (fcomp & 1);
    const uint32_t fsel = __shfl_sync(0xffffffffu, selv, fk);
    uint32_t fx = 0, fv = 0;
    bf16(*h2s)[ROWP] = (bf16(*)[ROWP])(sm + OFF_H2S);
    if (warp < 12) {
        uint4 wv[2];
        const uint4* hp[2];
#pragma unroll
        for (int r = 0; r < 2; r++) {
            const int wi = warp + 12 * r, k = wi / 3, j = wi - 3 * k;
            hp[r] = &S->h2w[(size_t)__shfl_sync(0xffffffffu, seltok, k) * 96 + 32 * j + lane];
            wv[r] = ld_rlx4(hp[r]);
        }
        if (tid < 288 && (tid & 7) == 0) {
            const uint32_t ft = 2047u - (fsel & 2047u), pr = (ft & 15u) >> 1;
            fx = ((const unsigned short*)x)[(size_t)ft * D_ + fd];
            asm volatile("ld.relaxed.gpu.global.u16 %0, [%1];" : "=r"(fv)
                         : "l"((const unsigned short*)S->v + ((size_t)(ft >> 4) * D_ + fd) * 16 + ((pr & 3u) * 2 + (pr >> 2)) * 2 + (ft & 1u)) : "memory");
        }
#pragma unroll 1
        for (int it = 0; it < SPIN_MAX && (wv[0].w != epoch || wv[1].w != epoch); it++) { wv[0] = ld_rlx4(hp[0]); wv[1] = ld_rlx4(hp[1]); }
#pragma unroll
        for (int r = 0; r < 2; r++) {
            const int wi = warp + 12 * r, k = wi / 3, j = wi - 3 * k;
            uint32_t* dst = (uint32_t*)&h2s[k][0] + 96 * j + lane;
            dst[0] = wv[r].x; dst[32] = wv[r].y; dst[64] = wv[r].z;
        }
    }
    CBAR();
    float* ffr = (float*)(sm + OFF_FFR);
    if (fmt < 4 || nf > 32) {
        float acc[2][4] = {{0.f, 0.f, 0.f, 0.f}, {0.f, 0.f, 0.f, 0.f}};
        const uint32_t ha = sb + OFF_H2S + lr * (ROWP * 2) + (144 * fsl) * 2 + lm * 16;
#pragma unroll
        for (int k2 = 0; k2 < 5; k2++) {
            uint32_t hb[4];
            ldsm_x4(hb, ha + k2 * 64 - ((k2 == 4) ? (lm >> 1) * 32 : 0));
            mma_bf16(acc[0], wf[2 * k2][0], wf[2 * k2][1], wf[2 * k2][2], wf[2 * k2][3], hb[0], hb[1]);
            if (k2 < 4) mma_bf16(acc[1], wf[2 * k2 + 1][0], wf[2 * k2 + 1][1], wf[2 * k2 + 1][2], wf[2 * k2 + 1][3], hb[2], hb[3]);
        }
        float* o = ffr + ((fsl * 80 + 16 * fmt + g) * 8 + 2 * t);
        *(float2*)o = make_float2(acc[0][0] + acc[1][0], acc[0][1] + acc[1][1]);
        *(float2*)(o + 64) = make_float2(acc[0][2] + acc[1][2], acc[0][3] + acc[1][3]);
    }
    CBAR();
    bf16(*act)[56] = (bf16(*)[56])(sm + OFF_ACT);
    if (tid < 384) {
        const int f = tid >> 3, a = tid & 7;
        float v = 0.f;
        if (f < nf) {
            const int rg = (f < 32) ? f : f + 32, ru = (f < 32) ? f + 32 : f + 40;
            const float* pg = ffr + rg * 8 + a;
            const float* pu = ffr + ru * 8 + a;
            float gg = bfr((pg[0] + pg[640]) + (pg[1280] + pg[1920]));
            gg = bfr(silu(gg));
            const float uu = bfr((pu[0] + pu[640]) + (pu[1280] + pu[1920]));
            v = gg * uu;
        }
        act[a][f] = __ushort_as_bfloat16((unsigned short)f2bits(v));
    }
    CBAR();
    {
        uint32_t bq[3][2];
#pragma unroll
        for (int ks = 0; ks < 3; ks++) {
            bq[ks][0] = *(const uint32_t*)&act[g][16 * ks + 2 * t];
            bq[ks][1] = *(const uint32_t*)&act[g][16 * ks + 2 * t + 8];
        }
#pragma unroll
        for (int i = 0; i < 2; i++) {
            if (i == 0 || warp < 16) {
                float acc[4] = {0.f, 0.f, 0.f, 0.f};
#pragma unroll
                for (int ks = 0; ks < 3; ks++)
                    if (ks < 2 || nf > 32) mma_bf16(acc, wd[i][ks][0], wd[i][ks][1], wd[i][ks][2], wd[i][ks][3], bq[ks][0], bq[ks][1]);
                const int W = (warp + 20 * i) * 32 + lane, c = (W * 7282) >> 16;
                st_rlx2(&S->part[(c * G_ + b) * 9 + W - 9 * c], ~pack2(acc[0], acc[1]), ~pack2(acc[2], acc[3]));
            }
        }
    }
    if (warp >= 4) {
        const int tk = warp - 4;
        if (!__any_sync(0xffffffffu, 2047u - (M.skey[lr] & 2047u) == (uint32_t)(16 * b + tk))) {
            const uint4* src = (const uint4*)(sm + OFF_TILE + tk * (ROWP * 2));
            uint4* dst = (uint4*)(out + (size_t)(16 * b + tk) * D_);
            dst[lane] = src[lane]; dst[lane + 32] = src[lane + 32];
            if (lane < 8) dst[lane + 64] = src[lane + 64];
        }
    }
    float4* fin = (float4*)(sm + OFF_FIN);
    uint32_t rb = (fsel >> 11) & 0xFFFFu;
    rb ^= (rb & 0x8000u) ? 0x8000u : 0xFFFFu;
    const float rs = bfr(__fdividef(1.0f, 1.0f + __expf(-lo2f(rb))));
    const float fh2 = (tid < 288) ? __bfloat162float(h2s[fk][fd]) : 0.f, fgb = (tid < 288) ? __bfloat162float(M.gb[fd]) : 0.f;
    const float fx1 = bfr(lo2f(fx) + lo2f(~fv));
    if (tid < 576) {
        const uint2* src = &S->part[(size_t)b * 1152 + tid];
        uint2 a = ld_rlx2(src), c = ld_rlx2(src + 576);
#pragma unroll 1
        for (int it = 0; it < SPIN_MAX && (a.x == SENT || c.x == SENT); it++) {
            if (a.x == SENT) a = ld_rlx2(src);
            if (c.x == SENT) c = ld_rlx2(src + 576);
        }
        fin[tid] = make_float4(lo2f(~a.x) + lo2f(~c.x), hi2f(~a.x) + hi2f(~c.x), lo2f(~a.y) + lo2f(~c.y), hi2f(~a.y) + hi2f(~c.y));
    }
    CBAR();
    if (tid < 288) {
        const int part = tid & 7;
        const float* f = (const float*)fin + part * 36 + fo;
        float s = ((f[0] + f[288]) + (f[576] + f[864])) + ((f[1152] + f[1440]) + (f[1728] + f[2016]));
        s += __shfl_xor_sync(0xffffffffu, s, 1);
        s += __shfl_xor_sync(0xffffffffu, s, 2);
        s += __shfl_xor_sync(0xffffffffu, s, 4);
        const float upd = bfr(bfr(s) * rs);
        const float ov = fx1 + bfr(fgb * bfr(fh2 + upd));
        if (part == 0) out[(size_t)(2047u - (fsel & 2047u)) * D_ + fd] = __ushort_as_bfloat16((unsigned short)f2bits(ov));
    }
    if ((warp & 3) == 2 && lane == 0) asm volatile("cp.async.bulk.wait_group 0;" ::: "memory");
    }
}

typedef CUresult (*EncodeFn)(CUtensorMap*, CUtensorMapDataType, cuuint32_t, void*, const cuuint64_t*, const cuuint64_t*,
                             const cuuint32_t*, const cuuint32_t*, CUtensorMapInterleave, CUtensorMapSwizzle,
                             CUtensorMapL2promotion, CUtensorMapFloatOOBfill);

static void make_map(EncodeFn fn, CUtensorMap* m, const void* ptr, uint64_t cols, uint64_t rows, uint32_t bc, uint32_t br,
                     CUtensorMapSwizzle sw) {
    cuuint64_t dims[2] = {cols, rows};
    cuuint64_t strides[1] = {cols * 2};
    cuuint32_t box[2] = {bc, br};
    cuuint32_t es[2] = {1, 1};
    CUresult rc = fn(m, CU_TENSOR_MAP_DATA_TYPE_BFLOAT16, 2, (void*)ptr, dims, strides, box, es, CU_TENSOR_MAP_INTERLEAVE_NONE,
                     sw, CU_TENSOR_MAP_L2_PROMOTION_NONE, CU_TENSOR_MAP_FLOAT_OOB_FILL_NONE);
    (void)rc;
}

static void launch(void* const* d_in, const int* in_sizes, int n_in, void* d_out, int out_size) {
    static EncodeFn enc = nullptr;
    static CUtensorMap tmm, tmg, tmu, tmd, tmd32, tmg32, tmu32;
    static Scratch* sp = nullptr;
    static const void* cached[4] = {nullptr, nullptr, nullptr, nullptr};
    if (!enc) {
        cudaDriverEntryPointQueryResult qr;
        void* fn = nullptr;
        cudaGetDriverEntryPoint("cuTensorMapEncodeTiled", &fn, cudaEnableDefault, &qr);
        enc = (EncodeFn)fn;
        cudaFuncSetAttribute(mega_kernel, cudaFuncAttributeMaxDynamicSharedMemorySize, SMEM_TOTAL);
        cudaGetSymbolAddress((void**)&sp, g_s);
    }
    if (cached[0] != d_in[13] || cached[1] != d_in[9] || cached[2] != d_in[10] || cached[3] != d_in[11]) {
        make_map(enc, &tmm, d_in[13], 6 * D_, D_, 32, 192, CU_TENSOR_MAP_SWIZZLE_64B);
        make_map(enc, &tmg, d_in[9], F_, D_, 40, 192, CU_TENSOR_MAP_SWIZZLE_NONE);
        make_map(enc, &tmu, d_in[10], F_, D_, 40, 192, CU_TENSOR_MAP_SWIZZLE_NONE);
        make_map(enc, &tmg32, d_in[9], F_, D_, 32, 192, CU_TENSOR_MAP_SWIZZLE_64B);
        make_map(enc, &tmu32, d_in[10], F_, D_, 32, 192, CU_TENSOR_MAP_SWIZZLE_64B);
        make_map(enc, &tmd, d_in[11], D_, F_, 64, 40, CU_TENSOR_MAP_SWIZZLE_128B);
        make_map(enc, &tmd32, d_in[11], D_, F_, 64, 32, CU_TENSOR_MAP_SWIZZLE_128B);
        cached[3] = d_in[11];
        cached[0] = d_in[13]; cached[1] = d_in[9]; cached[2] = d_in[10];
    }
    mega_kernel<<<G_, NTHR, SMEM_TOTAL>>>((const bf16*)d_in[0], (const bf16*)d_in[1], (const bf16*)d_in[2], (const bf16*)d_in[3],
                                          (const bf16*)d_in[4], (const bf16*)d_in[5], (const bf16*)d_in[12], sp, (const bf16*)d_in[6],
                                          (const bf16*)d_in[8], (const bf16*)d_in[11], (bf16*)d_out, tmm, tmg, tmu, tmd, tmd32, tmg32, tmu32);
}

}

extern "C" void kernel_launch(void* const* d_in, const int* in_sizes, int n_in, void* d_out, int out_size) {
    static int mode = -1;
    if (mode < 0) mode = v5::fits() ? 1 : 0;
    if (mode) v5::launch(d_in, in_sizes, n_in, d_out, out_size);
    else v4::launch(d_in, in_sizes, n_in, d_out, out_size);
}
```

```cpp
#include <cuda_runtime.h>
#include <cuda.h>
#include <cuda_bf16.h>
#include <cuda_fp16.h>
#include <stdint.h>

namespace v5 {

#define L_ 2048
#define D_ 576
#define N_ 128
#define F_ 4608
#define G_ 120
#define NCL 15
#define NTHR 768
#define SPIN_MAX (1 << 18)

typedef __nv_bfloat16 bf16;

struct Scratch {
    float4 acc1[L_ + 8];
    float4 acc2[L_];
    uint4 h2c[136 * 72];
    float4 acc3[72 * 32];
    float4 rs[33 * 8];
    unsigned int gb[320];
};
static_assert(136 * 72 + 72 * 32 + 33 * 8 == 103 * G_, "16 B units cleared early in a launch (h2c, acc3, rs)");
__device__ __align__(1024) Scratch g_s;

#define OFF_WG 0
#define OFF_WU 46080
#define KSCR 3456
#define OFF_WM0 69120
#define OFF_STG OFF_WM0
#define OFF_MG2 86400
#define OFF_CH 92160
#define CHS 18688
#define UP 3808
#define UB 192
#define XO_TF 1216
#define XO_U8 2016
#define XO_U16 3328
#define XO_ZA 1232
#define XO_ZB 2016
#define XO_ZC 2800
#define XO_ZD 3328
#define XO_TD 16000
#define XO_K1024 18624
#define XO_DSK 18628
#define XO_KINV 18640
#define XO_KLAST 18656
#define XO_MBU 18672
#define OFF_X 185600
#define XG 672
#define XI(i) (((i) >> 1) * 5520 + ((i) & 1) * 2752)
#define XN(n) ((((n) >> 1) & 3) * XG + (2 * ((n) >> 3) + ((n) & 1)) * 80)
#define OFF_V 207616
#define VP 528
#define OFF_EK (OFF_V + 512)
#define OFF_WM2 OFF_V
#define OFF_MG1 (OFF_V + 17280)
#define OFF_SC (OFF_V + 19840)
#define OFF_C1 (OFF_V + 20640)
#define OFF_MISC 228736
#define OFF_WD OFF_CH
#define OFF_H2T (OFF_CH + 46080)
#define OFF_OUT (OFF_CH + 66560)
#define ROWP 584
#define OFF_H2S 0
#define OFF_FFR 9344
#define OFF_ACT 19584
#define OFF_RS 20480

enum { MB_WM2, MB_MG1, MB_MG2, MB_KEY, MB_V, MB_RS, MB_WG, MB_WU, MB_WD, MB_KEY2, MB_EK, MB_RS2, MB_C2, MB_CW, MB_KD, MB_OUT, MB_C1, MB_N };

struct Misc {
    union {
        __align__(16) uint4 box[11 * 16];
        struct { unsigned int cand[128], key[256], cand2[128], sel[8]; };
    };
    __align__(16) uint4 c2[20];
    __align__(16) unsigned int fin[12];
    unsigned int ga[8], wr[20];
    float cws[2];
    unsigned long long mbar[MB_N];
};
#define SMEM_TOTAL (OFF_MISC + (int)sizeof(Misc))
static_assert(SMEM_TOTAL <= 232448, "smem");

__device__ __forceinline__ float lo2f(uint32_t w) { return __uint_as_float(w << 16); }
__device__ __forceinline__ float hi2f(uint32_t w) { return __uint_as_float(w & 0xFFFF0000u); }
__device__ __forceinline__ uint32_t pack2(float lo, float hi) { uint32_t r; asm("cvt.rn.bf16x2.f32 %0, %1, %2;" : "=r"(r) : "f"(hi), "f"(lo)); return r; }
__device__ __forceinline__ float bfr(float x) { return __uint_as_float(pack2(0.f, x)); }
__device__ __forceinline__ uint32_t f2bits(float x) { return pack2(x, 0.f); }
__device__ __forceinline__ uint32_t packh(float lo, float hi) { uint32_t r; asm("cvt.rn.f16x2.f32 %0, %1, %2;" : "=r"(r) : "f"(hi), "f"(lo)); return r; }
__device__ __forceinline__ float frcp(float x) { float r; asm("rcp.approx.ftz.f32 %0, %1;" : "=f"(r) : "f"(x)); return r; }
__device__ __forceinline__ float fsqrt(float x) { float r; asm("sqrt.approx.f32 %0, %1;" : "=f"(r) : "f"(x)); return r; }
__device__ __forceinline__ float fex2(float x) { float r; asm("ex2.approx.ftz.f32 %0, %1;" : "=f"(r) : "f"(x)); return r; }
__device__ __forceinline__ float silu(float x) { return __fdividef(x, 1.0f + __expf(-x)); }
__device__ __forceinline__ uint32_t add2(uint32_t a, uint32_t b) { uint32_t r; asm("add.rn.bf16x2 %0, %1, %2;" : "=r"(r) : "r"(a), "r"(b)); return r; }
__device__ __forceinline__ uint32_t sub2(uint32_t a, uint32_t b) { uint32_t r; asm("sub.rn.bf16x2 %0, %1, %2;" : "=r"(r) : "r"(a), "r"(b)); return r; }
__device__ __forceinline__ uint32_t mul2(uint32_t a, uint32_t b) { uint32_t r; asm("mul.rn.bf16x2 %0, %1, %2;" : "=r"(r) : "r"(a), "r"(b)); return r; }
__device__ __forceinline__ uint32_t fma2(uint32_t a, uint32_t b, uint32_t c) { uint32_t r; asm("fma.rn.bf16x2 %0, %1, %2, %3;" : "=r"(r) : "r"(a), "r"(b), "r"(c)); return r; }
__device__ __forceinline__ uint32_t norm2(uint32_t x, uint32_t m, uint32_t rh, uint32_t rl) { const uint32_t d = sub2(x, m); return fma2(d, rh, mul2(d, rl)); }

__device__ __forceinline__ void mma_bf16(float* c, uint32_t a0, uint32_t a1, uint32_t a2, uint32_t a3, uint32_t b0, uint32_t b1) {
    asm volatile("mma.sync.aligned.m16n8k16.row.col.f32.bf16.bf16.f32 {%0,%1,%2,%3}, {%4,%5,%6,%7}, {%8,%9}, {%0,%1,%2,%3};\n"
                 : "+f"(c[0]), "+f"(c[1]), "+f"(c[2]), "+f"(c[3]) : "r"(a0), "r"(a1), "r"(a2), "r"(a3), "r"(b0), "r"(b1));
}
__device__ __forceinline__ void mma_f16(float* c, const uint32_t* a, uint32_t b0, uint32_t b1) {
    asm volatile("mma.sync.aligned.m16n8k16.row.col.f32.f16.f16.f32 {%0,%1,%2,%3}, {%4,%5,%6,%7}, {%8,%9}, {%0,%1,%2,%3};\n"
                 : "+f"(c[0]), "+f"(c[1]), "+f"(c[2]), "+f"(c[3]) : "r"(a[0]), "r"(a[1]), "r"(a[2]), "r"(a[3]), "r"(b0), "r"(b1));
}
__device__ __forceinline__ void ldsm_x4(uint32_t* r, uint32_t addr) {
    asm volatile("ldmatrix.sync.aligned.m8n8.x4.shared.b16 {%0,%1,%2,%3}, [%4];" : "=r"(r[0]), "=r"(r[1]), "=r"(r[2]), "=r"(r[3]) : "r"(addr) : "memory");
}
__device__ __forceinline__ void ldsm_x4_t(uint32_t* r, uint32_t addr) {
    asm volatile("ldmatrix.sync.aligned.m8n8.x4.trans.shared.b16 {%0,%1,%2,%3}, [%4];" : "=r"(r[0]), "=r"(r[1]), "=r"(r[2]), "=r"(r[3]) : "r"(addr) : "memory");
}
__device__ __forceinline__ void stsm_x4(uint32_t addr, uint32_t r0, uint32_t r1, uint32_t r2, uint32_t r3) {
    asm volatile("stmatrix.sync.aligned.m8n8.x4.shared.b16 [%0], {%1,%2,%3,%4};" ::"r"(addr), "r"(r0), "r"(r1), "r"(r2), "r"(r3) : "memory");
}
__device__ __forceinline__ void stsm_x4_t(uint32_t addr, uint32_t r0, uint32_t r1, uint32_t r2, uint32_t r3) {
    asm volatile("stmatrix.sync.aligned.m8n8.x4.trans.shared.b16 [%0], {%1,%2,%3,%4};" ::"r"(addr), "r"(r0), "r"(r1), "r"(r2), "r"(r3) : "memory");
}
__device__ __forceinline__ uint32_t movm(uint32_t a) { uint32_t r; asm volatile("movmatrix.sync.aligned.m8n8.trans.b16 %0, %1;" : "=r"(r) : "r"(a)); return r; }
__device__ __forceinline__ uint32_t lds32(uint32_t a) { uint32_t v; asm volatile("ld.shared.u32 %0, [%1];" : "=r"(v) : "r"(a)); return v; }
__device__ __forceinline__ void sts32(uint32_t a, uint32_t v) { asm volatile("st.shared.u32 [%0], %1;" ::"r"(a), "r"(v) : "memory"); }
__device__ __forceinline__ void sts16(uint32_t a, uint32_t v) { asm volatile("st.shared.u16 [%0], %1;" ::"r"(a), "h"((unsigned short)v) : "memory"); }
__device__ __forceinline__ void named_bar(int id, int n) { asm volatile("bar.sync %0, %1;" ::"r"(id), "r"(n) : "memory"); }
__device__ __forceinline__ void named_arrive(int id, int n) { asm volatile("bar.arrive %0, %1;" ::"r"(id), "r"(n) : "memory"); }
#define CBAR() asm volatile("bar.sync 0, 640;" ::: "memory")
#define PROXY_FENCE() asm volatile("fence.proxy.async.shared::cta;" ::: "memory")

#define D4(d, o) "+f"(d[o]), "+f"(d[o + 1]), "+f"(d[o + 2]), "+f"(d[o + 3])
__device__ __forceinline__ void wg32(float* d, uint32_t a0, uint32_t a1, uint32_t a2, uint32_t a3, uint64_t desc) {
    asm volatile("wgmma.mma_async.sync.aligned.m64n32k16.f32.bf16.bf16 {%0,%1,%2,%3,%4,%5,%6,%7,%8,%9,%10,%11,%12,%13,%14,%15}, {%16,%17,%18,%19}, %20, 1, 1, 1, 0;"
                 : D4(d, 0), D4(d, 4), D4(d, 8), D4(d, 12) : "r"(a0), "r"(a1), "r"(a2), "r"(a3), "l"(desc));
}
__device__ __forceinline__ void wg48(float* d, uint32_t a0, uint32_t a1, uint32_t a2, uint32_t a3, uint64_t desc) {
    asm volatile("wgmma.mma_async.sync.aligned.m64n48k16.f32.bf16.bf16 {%0,%1,%2,%3,%4,%5,%6,%7,%8,%9,%10,%11,%12,%13,%14,%15,%16,%17,%18,%19,%20,%21,%22,%23}, {%24,%25,%26,%27}, %28, 1, 1, 1, 0;"
                 : D4(d, 0), D4(d, 4), D4(d, 8), D4(d, 12), D4(d, 16), D4(d, 20) : "r"(a0), "r"(a1), "r"(a2), "r"(a3), "l"(desc));
}
__device__ __forceinline__ void wg64(float* d, uint32_t a0, uint32_t a1, uint32_t a2, uint32_t a3, uint64_t desc) {
    asm volatile("wgmma.mma_async.sync.aligned.m64n64k16.f32.bf16.bf16 {%0,%1,%2,%3,%4,%5,%6,%7,%8,%9,%10,%11,%12,%13,%14,%15,%16,%17,%18,%19,%20,%21,%22,%23,%24,%25,%26,%27,%28,%29,%30,%31}, {%32,%33,%34,%35}, %36, 1, 1, 1, 0;"
                 : D4(d, 0), D4(d, 4), D4(d, 8), D4(d, 12), D4(d, 16), D4(d, 20), D4(d, 24), D4(d, 28) : "r"(a0), "r"(a1), "r"(a2), "r"(a3), "l"(desc));
}
#define O4(d, o) "=f"(d[o]), "=f"(d[o + 1]), "=f"(d[o + 2]), "=f"(d[o + 3])
__device__ __forceinline__ void wg32z(float* d, uint32_t a0, uint32_t a1, uint32_t a2, uint32_t a3, uint64_t desc) {
    asm volatile("wgmma.mma_async.sync.aligned.m64n32k16.f32.bf16.bf16 {%0,%1,%2,%3,%4,%5,%6,%7,%8,%9,%10,%11,%12,%13,%14,%15}, {%16,%17,%18,%19}, %20, 0, 1, 1, 0;"
                 : O4(d, 0), O4(d, 4), O4(d, 8), O4(d, 12) : "r"(a0), "r"(a1), "r"(a2), "r"(a3), "l"(desc));
}
__device__ __forceinline__ void wg48z(float* d, uint32_t a0, uint32_t a1, uint32_t a2, uint32_t a3, uint64_t desc) {
    asm volatile("wgmma.mma_async.sync.aligned.m64n48k16.f32.bf16.bf16 {%0,%1,%2,%3,%4,%5,%6,%7,%8,%9,%10,%11,%12,%13,%14,%15,%16,%17,%18,%19,%20,%21,%22,%23}, {%24,%25,%26,%27}, %28, 0, 1, 1, 0;"
                 : O4(d, 0), O4(d, 4), O4(d, 8), O4(d, 12), O4(d, 16), O4(d, 20) : "r"(a0), "r"(a1), "r"(a2), "r"(a3), "l"(desc));
}
__device__ __forceinline__ void wg56(float* d, uint32_t a0, uint32_t a1, uint32_t a2, uint32_t a3, uint64_t desc) {
    asm volatile("wgmma.mma_async.sync.aligned.m64n56k16.f32.bf16.bf16 {%0,%1,%2,%3,%4,%5,%6,%7,%8,%9,%10,%11,%12,%13,%14,%15,%16,%17,%18,%19,%20,%21,%22,%23,%24,%25,%26,%27}, {%28,%29,%30,%31}, %32, 1, 1, 1, 0;"
                 : D4(d, 0), D4(d, 4), D4(d, 8), D4(d, 12), D4(d, 16), D4(d, 20), D4(d, 24) : "r"(a0), "r"(a1), "r"(a2), "r"(a3), "l"(desc));
}
__device__ __forceinline__ void wg64z(float* d, uint32_t a0, uint32_t a1, uint32_t a2, uint32_t a3, uint64_t desc) {
    asm volatile("wgmma.mma_async.sync.aligned.m64n64k16.f32.bf16.bf16 {%0,%1,%2,%3,%4,%5,%6,%7,%8,%9,%10,%11,%12,%13,%14,%15,%16,%17,%18,%19,%20,%21,%22,%23,%24,%25,%26,%27,%28,%29,%30,%31}, {%32,%33,%34,%35}, %36, 0, 1, 1, 0;"
                 : O4(d, 0), O4(d, 4), O4(d, 8), O4(d, 12), O4(d, 16), O4(d, 20), O4(d, 24), O4(d, 28) : "r"(a0), "r"(a1), "r"(a2), "r"(a3), "l"(desc));
}
#define WG_FENCE() asm volatile("wgmma.fence.sync.aligned;" ::: "memory")
#define WG_COMMIT() asm volatile("wgmma.commit_group.sync.aligned;" ::: "memory")
#define WG_WAIT(n) asm volatile("wgmma.wait_group.sync.aligned " #n ";" ::: "memory")
#define TQ(p, k) p[2 * (k) + 1], p[2 * (k) + 2], p[2 * (k)], p[2 * (k) + 1]

__device__ __forceinline__ uint4 ld_nc4(const void* p) { uint4 v; asm volatile("ld.global.nc.v4.u32 {%0,%1,%2,%3}, [%4];" : "=r"(v.x), "=r"(v.y), "=r"(v.z), "=r"(v.w) : "l"(p)); return v; }
__device__ __forceinline__ unsigned short ld_nc16(const void* p) { unsigned short v; asm volatile("ld.global.nc.u16 %0, [%1];" : "=h"(v) : "l"(p)); return v; }
__device__ __forceinline__ uint32_t ld_nc(const void* p) { uint32_t v; asm volatile("ld.global.nc.u32 %0, [%1];" : "=r"(v) : "l"(p)); return v; }
__device__ __forceinline__ uint32_t ld_rlx(const unsigned int* p) { uint32_t v; asm volatile("ld.relaxed.gpu.global.u32 %0, [%1];" : "=r"(v) : "l"(p) : "memory"); return v; }
__device__ __forceinline__ uint2 ld_rlx2(const void* p) { uint2 v; asm volatile("ld.relaxed.gpu.global.v2.u32 {%0,%1}, [%2];" : "=r"(v.x), "=r"(v.y) : "l"(p) : "memory"); return v; }
__device__ __forceinline__ uint4 ld_rlx4(const void* p) { uint4 v; asm volatile("ld.relaxed.gpu.global.v4.u32 {%0,%1,%2,%3}, [%4];" : "=r"(v.x), "=r"(v.y), "=r"(v.z), "=r"(v.w) : "l"(p) : "memory"); return v; }
__device__ __forceinline__ void st_rlx(unsigned int* p, uint32_t v) { asm volatile("st.relaxed.gpu.global.u32 [%0], %1;" ::"l"(p), "r"(v) : "memory"); }
__device__ __forceinline__ void st_rlx2(void* p, uint32_t a, uint32_t b) { asm volatile("st.relaxed.gpu.global.v2.u32 [%0], {%1,%2};" ::"l"(p), "r"(a), "r"(b) : "memory"); }
__device__ __forceinline__ void st_rlx4(void* p, uint4 v) { asm volatile("st.relaxed.gpu.global.v4.u32 [%0], {%1,%2,%3,%4};" ::"l"(p), "r"(v.x), "r"(v.y), "r"(v.z), "r"(v.w) : "memory"); }
__device__ __forceinline__ void red_inc(unsigned int* p) { asm volatile("red.relaxed.gpu.global.add.u32 [%0], 1;" ::"l"(p) : "memory"); }

__device__ __forceinline__ void mbar_init(uint32_t a, int cnt) { asm volatile("mbarrier.init.shared::cta.b64 [%0], %1;" ::"r"(a), "r"(cnt) : "memory"); }
__device__ __forceinline__ void mbar_expect(uint32_t a, uint32_t bytes) { asm volatile("mbarrier.arrive.expect_tx.shared::cta.b64 _, [%0], %1;" ::"r"(a), "r"(bytes) : "memory"); }
__device__ __forceinline__ void mbar_wait(uint32_t a, uint32_t parity) {
    uint32_t ok = 0;
    int it = 0;
    do {
        asm volatile("{\n.reg .pred p;\nmbarrier.try_wait.parity.shared::cta.b64 p, [%1], %2;\nselp.u32 %0, 1, 0, p;\n}" : "=r"(ok) : "r"(a), "r"(parity) : "memory");
    } while (!ok && ++it < SPIN_MAX);
}
__device__ __forceinline__ bool mbar_test(uint32_t a, uint32_t parity) {
    uint32_t ok;
    asm volatile("{\n.reg .pred p;\nmbarrier.test_wait.parity.shared::cta.b64 p, [%1], %2;\nselp.u32 %0, 1, 0, p;\n}" : "=r"(ok) : "r"(a), "r"(parity) : "memory");
    return __all_sync(0xffffffffu, ok);
}
__device__ __forceinline__ void tma2d(uint32_t dst, const CUtensorMap* tm, int c0, int c1, uint32_t mbar) {
    asm volatile("cp.async.bulk.tensor.2d.shared::cluster.global.mbarrier::complete_tx::bytes [%0], [%1, {%3, %4}], [%2];"
                 ::"r"(dst), "l"(tm), "r"(mbar), "r"(c0), "r"(c1) : "memory");
}
__device__ __forceinline__ void bulk_s2g(void* dst, uint32_t src, uint32_t bytes) {
    asm volatile("cp.async.bulk.global.shared::cta.bulk_group [%0], [%1], %2;" ::"l"(dst), "r"(src), "r"(bytes) : "memory");
}
__device__ __forceinline__ uint32_t ld_acq(const unsigned int* p) { uint32_t v; asm volatile("ld.acquire.gpu.global.u32 %0, [%1];" : "=r"(v) : "l"(p) : "memory"); return v; }
__device__ __forceinline__ void bulk_pf(const void* src, uint32_t bytes) { asm volatile("cp.async.bulk.prefetch.L2.global [%0], %1;" ::"l"(src), "r"(bytes) : "memory"); }

struct cplx { float x, y; };
__device__ __forceinline__ cplx cmul(cplx a, cplx b) { cplx r; r.x = a.x * b.x - a.y * b.y; r.y = a.x * b.y + a.y * b.x; return r; }
__device__ __forceinline__ cplx csq(cplx a) { cplx r; r.x = a.x * a.x - a.y * a.y; r.y = 2.0f * a.x * a.y; return r; }
__device__ __forceinline__ uint32_t hcm(uint32_t x, uint32_t y, uint32_t yp) {
    const __half2 X = *(const __half2*)&x, Y = *(const __half2*)&y, YP = *(const __half2*)&yp;
    const __half2 r = __hfma2(__high2half2(X), YP, __hmul2(__low2half2(X), Y));
    return *(const uint32_t*)&r;
}
__device__ __forceinline__ void ln_stats(float s1, float s2, float& meanb, float& rinv) {
    const float mean = s1 * (1.0f / D_);
    const float den = bfr(fsqrt(bfr(bfr(fmaxf(fmaf(-mean, mean, s2 * (1.0f / D_)), 0.f)) + 1e-5f)));
    meanb = bfr(mean);
    rinv = frcp(den);
}

__device__ __forceinline__ int fresh_tid() { int v; asm volatile("mov.u32 %0, %tid.x;" : "=r"(v)); return v - 128; }
__device__ __forceinline__ void mma_k8(float* c, uint32_t a0, uint32_t a1, uint32_t b0) {
    asm volatile("mma.sync.aligned.m16n8k8.row.col.f32.bf16.bf16.f32 {%0,%1,%2,%3}, {%4,%5}, {%6}, {%0,%1,%2,%3};\n"
                 : "+f"(c[0]), "+f"(c[1]), "+f"(c[2]), "+f"(c[3]) : "r"(a0), "r"(a1), "r"(b0));
}
__device__ __forceinline__ void ldsm_x2(uint32_t* r, uint32_t addr) {
    asm volatile("ldmatrix.sync.aligned.m8n8.x2.shared.b16 {%0,%1}, [%2];" : "=r"(r[0]), "=r"(r[1]) : "r"(addr) : "memory");
}
__device__ __forceinline__ void ldsm_x2_t(uint32_t* r, uint32_t addr) {
    asm volatile("ldmatrix.sync.aligned.m8n8.x2.trans.shared.b16 {%0,%1}, [%2];" : "=r"(r[0]), "=r"(r[1]) : "r"(addr) : "memory");
}
__device__ __forceinline__ void stsm_x2(uint32_t addr, uint32_t r0, uint32_t r1) {
    asm volatile("stmatrix.sync.aligned.m8n8.x2.shared.b16 [%0], {%1,%2};" ::"r"(addr), "r"(r0), "r"(r1) : "memory");
}
__device__ __forceinline__ uint4 lds128(uint32_t a) { uint4 v; asm volatile("ld.shared.v4.u32 {%0,%1,%2,%3}, [%4];" : "=r"(v.x), "=r"(v.y), "=r"(v.z), "=r"(v.w) : "r"(a) : "memory"); return v; }
__device__ __forceinline__ uint32_t mapa(uint32_t a, uint32_t r) { uint32_t o; asm("mapa.shared::cluster.u32 %0, %1, %2;" : "=r"(o) : "r"(a), "r"(r)); return o; }
__device__ __forceinline__ void sta4(uint32_t dst, uint4 v, uint32_t mb) {
    asm volatile("st.async.weak.shared::cluster.mbarrier::complete_tx::bytes.v4.b32 [%0], {%1,%2,%3,%4}, [%5];" ::"r"(dst), "r"(v.x), "r"(v.y), "r"(v.z), "r"(v.w), "r"(mb) : "memory");
}
__device__ __forceinline__ void sta2(uint32_t dst, uint32_t a, uint32_t b, uint32_t mb) {
    asm volatile("st.async.weak.shared::cluster.mbarrier::complete_tx::bytes.v2.b32 [%0], {%1,%2}, [%3];" ::"r"(dst), "r"(a), "r"(b), "r"(mb) : "memory");
}
__device__ __forceinline__ void mbar_arrive(uint32_t a) { asm volatile("mbarrier.arrive.shared::cta.b64 _, [%0];" ::"r"(a) : "memory"); }
__device__ __forceinline__ void red4(float4* p, float a, float b, float c) {
    asm volatile("red.relaxed.gpu.global.add.v4.f32 [%0], {%1,%2,%3,%4};" ::"l"(p), "f"(a), "f"(b), "f"(c), "f"(1.0f) : "memory");
}
__device__ __forceinline__ void red4p(bool on, float4* p, float a, float b, float c) {
    asm volatile("{\n.reg .pred q;\nsetp.ne.u32 q, %5, 0;\n@q red.relaxed.gpu.global.add.v4.f32 [%0], {%1,%2,%3,%4};\n}" ::"l"(p), "f"(a), "f"(b), "f"(c), "f"(1.0f), "r"((uint32_t)on) : "memory");
}
__device__ __forceinline__ float4 atom4(float4* p, float a, float b, float c, float d) {
    float4 v;
    asm volatile("atom.relaxed.gpu.global.add.v4.f32 {%0,%1,%2,%3}, [%4], {%5,%6,%7,%8};" : "=f"(v.x), "=f"(v.y), "=f"(v.z), "=f"(v.w) : "l"(p), "f"(a), "f"(b), "f"(c), "f"(d) : "memory");
    return v;
}
__device__ __forceinline__ uint2 lds64(uint32_t a) { uint2 v; asm volatile("ld.shared.v2.u32 {%0,%1}, [%2];" : "=r"(v.x), "=r"(v.y) : "r"(a) : "memory"); return v; }
__device__ __forceinline__ float4 ld_rlx4f(const float4* p) { float4 v; asm volatile("ld.relaxed.gpu.global.v4.f32 {%0,%1,%2,%3}, [%4];" : "=f"(v.x), "=f"(v.y), "=f"(v.z), "=f"(v.w) : "l"(p) : "memory"); return v; }
__device__ __forceinline__ void tma5d_st(const CUtensorMap* tm, int c0, int c4, uint32_t src) {
    asm volatile("cp.async.bulk.tensor.5d.global.shared::cta.bulk_group [%0, {%2, %4, %4, %4, %3}], [%1];" ::"l"(tm), "r"(src), "r"(c0), "r"(c4), "r"(0) : "memory");
}
__device__ __forceinline__ void tma2d_pf(const CUtensorMap* tm, int c0, int c1) {
    asm volatile("cp.async.bulk.prefetch.tensor.2d.L2.global [%0, {%1, %2}];" ::"l"(tm), "r"(c0), "r"(c1) : "memory");
}
__device__ __forceinline__ void pace(int clk) {
    const long long c0 = clock64();
    int it = 0;
    while (clock64() - c0 < clk && ++it < 4096) { }
}
__device__ __forceinline__ uint32_t sign2(uint32_t a) { uint32_t r; asm("prmt.b32 %0, %1, 0, 0xBB99;" : "=r"(r) : "r"(a)); return r; }
#define MB(i) (sb + OFF_MISC + (uint32_t)offsetof(Misc, mbar) + 8 * (i))
__device__ __forceinline__ uint32_t box_tap(int i) {
    const int f = (i * 205) >> 13, l = i - 40 * f - 6 - ((0x35C36 >> (4 * f)) & 15);
    const unsigned wd = (0x16824 >> (4 * f)) & 15, one = f == 4 ? 0xFFFFu : 0x3F80u;
    return ((unsigned)l <= wd ? one : 0u) | ((unsigned)(l - 1) <= wd ? one << 16 : 0u);
}
#define UF(u) ((u) < 4 ? (u) + 5 : (u) == 4 ? 13 : (u) < 10 ? (u) - 5 : (u) - 1)
__device__ __forceinline__ void conv_channel(unsigned char* sm, uint32_t rank, uint32_t fixa, uint32_t fixv) {
    Misc& M = *(Misc*)(sm + OFF_MISC);
    const uint32_t sb = (uint32_t)__cvta_generic_to_shared(sm);
    const int tid = fresh_tid(), lane = tid & 31, g = lane >> 2, t = lane & 3, lr = lane & 7, lm = lane >> 3;
    const int warp_ = __shfl_sync(0xffffffffu, tid >> 5, 0), wgi = warp_ >> 2, w = warp_ & 3;
    const uint32_t cb = sb + OFF_CH + wgi * CHS;
    float D[32];
    const uint32_t dlo = ((cb & 0x3FFFF) >> 4) | ((UP >> 4) << 16);
#define DS(o, z, bl) (((uint64_t)(128 >> 4) << 32) | (uint64_t)(dlo + (o) / 16 + (((z) & 1) ? 0 : UP / 8) - ((z) >> 1) * (bl)))
    {
        const uint32_t pf = cb + XO_TF + (w >> 1) * UP + (8 + 16 * (w & 1) + g - 2 * t) * 4;
        uint32_t p[13], q[9];
        named_bar(1 + wgi, 128);
        if (fixa) sts16(fixa, fixv);
#pragma unroll
        for (int s = 0; s < 13; s++) p[s] = lds32(pf + s * 32);
        {
            const uint32_t a8 = cb + UB + t * UP + g * 16 + w * 128, b8 = cb + XO_U8 + lm * UP + lr * 16 + w * 128;
            const uint32_t a16 = cb + UB + (2 * (lr & 1) + (lm & 1)) * UP + ((lr >> 1) + 2 * (lm & 2)) * 16 + w * 128;
            const uint32_t b16 = cb + XO_U16 + (2 * (w & 1) + (lm >> 1)) * UP + (lane & 15) * 16 + (w >> 1) * 256;
            uint32_t r[3][4];
            mbar_wait(cb + XO_MBU, 0);
            ldsm_x4_t(r[0], a8);
            ldsm_x4_t(r[1], a16);
            if (w < 2) ldsm_x4_t(r[2], a8 + 512);
            stsm_x4(b8, r[0][0], r[0][1], r[0][2], r[0][3]);
            stsm_x4(b16, r[1][0], r[1][1], r[1][2], r[1][3]);
            if (w < 2) stsm_x4(b8 + 512, r[2][0], r[2][1], r[2][2], r[2][3]);
        }
        PROXY_FENCE();
        named_bar(1 + wgi, 128);
        {
            float Z8[24], Z16[16];
            uint32_t z8[12];
            WG_FENCE();
#pragma unroll
            for (int e = 0; e < 6; e++) {
                if (e == 0) wg48z(Z8, TQ(p, e), DS(XO_U8, e, 8));
                else wg48(Z8, TQ(p, e), DS(XO_U8, e, 8));
            }
            WG_COMMIT();
            WG_WAIT(0);
            asm volatile("setmaxnreg.inc.sync.aligned.u32 88;");
#pragma unroll
            for (int s = 0; s < 9; s++) q[s] = lds32(pf + 2 * UP + s * 32);
#pragma unroll
            for (int i = 0; i < 12; i++) asm volatile("cvt.rn.bf16x2.f32 %0, %1, %2;" : "=r"(z8[i]) : "f"(Z8[2 * i + 1]), "f"(Z8[2 * i]));
            WG_FENCE();
#pragma unroll
            for (int e = 0; e < 4; e++) {
                if (e == 0) wg32z(Z16, TQ(q, e), DS(XO_U16, e, 16));
                else wg32(Z16, TQ(q, e), DS(XO_U16, e, 16));
            }
            WG_COMMIT();
            WG_WAIT(0);
            named_bar(1 + wgi, 128);
            const uint32_t za = cb + ((w >> 1) ? XO_ZB : XO_ZA) + t * UP + (4 * (w & 1) + (g & 3) + 8 * (g >> 2)) * 16;
#pragma unroll
            for (int i = 0; i < 3; i++) stsm_x4(za + i * 256, z8[4 * i], z8[4 * i + 1], z8[4 * i + 2], z8[4 * i + 3]);
            const uint32_t zc = cb + ((w >> 1) ? XO_ZD : XO_ZC) + (2 * (lr & 1) + (lm >> 1)) * UP + (((lane & 15) >> 1) + 8 * (w & 1)) * 16;
#pragma unroll
            for (int ob = 0; ob < 2; ob++) stsm_x4(zc + ob * 256, pack2(Z16[8 * ob], Z16[8 * ob + 1]), pack2(Z16[8 * ob + 2], Z16[8 * ob + 3]), pack2(Z16[8 * ob + 4], Z16[8 * ob + 5]), pack2(Z16[8 * ob + 6], Z16[8 * ob + 7]));
        }
    }
    PROXY_FENCE();
    {
        const uint32_t pa = cb + XO_TD + (40 + 8 * w + g - 2 * t) * 4, pq = sb + OFF_MISC + (8 * w - 18 + g - 2 * t) * 4;
        uint32_t q[3][8];
        const uint32_t k2 = lds32(cb + XO_K1024);
        auto ld = [&](int u) {
            uint32_t* d = q[u % 3];
            const int f = UF(u);
            if (f >= 5) {
#pragma unroll
                for (int i = 0; i < 8; i++) d[i] = (f == 13 && i > 4) ? 0u : lds32(pa + (f - 5) * 256 + i * 32);
            } else {
                const int lo = f == 2, hi = f == 2 ? 3 : (f == 1 || f == 4) ? 1 : 2;
#pragma unroll
                for (int i = 0; i < 8; i++) {
                    if (f < 3) d[i] = 0u;
                    if (i >= lo && i <= hi + 3) {
                        asm volatile("{\n.reg .pred p;\nsetp.le.u32 p, %2, %3;\n@p ld.shared.u32 %0, [%1];\n}" : "+r"(d[i]) : "r"(pq + f * 160 + i * 32), "r"(w + i - 3 - lo), "r"(hi - lo));
                        if (f == 4) asm volatile("and.b32 %0, %0, %1;" : "+r"(d[i]) : "r"(k2));
                    }
                }
            }
        };
        auto go = [&](int u) {
            const int f = UF(u);
            WG_FENCE();
#pragma unroll
            for (int z = 0; z < 2; z++) {
                const uint32_t* a = q[u % 3] + 2 * z;
#define Q4 a[1], a[5], a[0], a[4]
                if (f == 5 && z == 0) wg64z(D, Q4, DS(UB, 0, 2));
                else if (f < 2) wg48(D + 8, Q4, DS(f ? XO_ZB : XO_ZA, z, 0));
                else if (f < 5) wg32(D + 16, Q4, DS(f == 2 ? XO_ZC : f == 3 ? XO_ZD : UB, z, 0));
                else if (f < 9) wg64(D, Q4, DS(UB, 2 * (f - 5) + z, 2));
                else if (f == 13) wg48(D + 8, Q4, DS(UB, z, 0));
                else wg56(D + 4, Q4, DS(UB + 128, 2 * (f - 5) + z, 2));
            }
            WG_COMMIT();
        };
#define RD_(o) _Pragma("unroll") for (int i = o; i < 32; i++) { float y_; asm volatile("mov.b32 %0, %1;" : "=f"(y_) : "f"(D[i])); D[i] = y_; }
        ld(0); ld(1); go(0); ld(2); go(1);
        named_bar(1 + wgi, 128);
#pragma unroll
        for (int u = 2; u < 14; u++) {
            WG_WAIT(1);
            if (u < 13) ld(u + 1);
            if (u == 4 || u == 7 || u == 10) { WG_WAIT(0); RD_(u == 4 ? 8 : u == 7 ? 16 : 4); }
            go(u);
        }
    }
    {
        const int tid = fresh_tid(), lane = tid & 31, lr = lane & 7, lm = lane >> 3;
        uint32_t u[2][4];
        const uint32_t ua = cb + UB + w * UP + lm * 256 + lr * 16;
        ldsm_x4_t(u[0], ua); ldsm_x4_t(u[1], ua + 128);
        const uint32_t dk2 = __byte_perm(lds32(cb + XO_DSK), 0, (rank & 1) ? 0x3232 : 0x1010);
#pragma unroll
        for (int i = 0; i < 8; i++) u[i >> 2][i & 3] = mul2(u[i >> 2][i & 3], dk2);
        mbar_wait(MB(MB_C2), 0);
        const uint32_t ga2 = M.ga[wgi];
        const int src = (lane & 28) | ((lane + 3) & 3);
        WG_WAIT(0);
        float s[8];
#pragma unroll
        for (int j = 0; j < 8; j++) s[j] = __shfl_sync(0xffffffffu, (lane & 3) < 3 ? D[4 * j + 3] : j ? D[4 * j - 1] : 0.f, src);
#pragma unroll
        for (int h = 0; h < 2; h++) {
            const uint32_t rb = mapa(sb, w + 4 * h);
#pragma unroll
            for (int j = 0; j < 4; j++) u[h][j] = mul2(ga2, add2(pack2(D[8 * j + 4 * h] + s[2 * j + h], D[8 * j + 4 * h + 1] + D[8 * j + 4 * h + 2]), u[h][j]));
            sta4(rb + OFF_V + (8 * wgi + rank) * VP + lane * 16, make_uint4(u[h][0], u[h][1], u[h][2], u[h][3]), rb + (MB(MB_V) - sb));
        }
    }
}
#define M2W 4
#define WS 0x3210
#define WW 0x1111
#define WMS(p) if (w == 3) { if (p == 0) CL_WAIT(); if (lane == 0) { _Pragma("unroll") for (int i = 2; i < 6; i++) if (((WS >> (4 * (i - 2))) & 15) == p && ((WW >> (4 * (i - 2))) & 15) == wgi) tma2d(sb + (i == 5 ? OFF_WM0 + 11520 : OFF_WM2 + (i - 2) * 5760), &tm_wm, i * D_ + 40 * cl, 72 * rk, MB(MB_WM2)); } __syncwarp(); }
#define PQT 10
#define PQD 400
#define L2P 2
#define L2M 2
#define PDE 100
#define WMD 400
#define PFG 2
#define CWP 200
#define CWD 3000
#define ROW(key) (((~(key) << 2) & 0xE0u) | ((~(key) >> 6) & 24u) | ((~(key) >> 11) & 6u) | ((~(key) >> 8) & 1u))
#define RKT (((rk & 4) << 6) | ((rk & 3) << 3))
#define MINE(key) ((~(key) & 0x8C0u) == (uint32_t)(RKT << 3))
#define CE(a, b) { const uint32_t hi_ = max(a, b); b = min(a, b); a = hi_; }
#define POP(k, m) if (k.x == m) { k.x = k.y; k.y = k.z; k.z = k.w; k.w = 0u; }
#define CGT(c, a, b, n) asm volatile("{\n.reg .pred p;\nsetp.gt.u32 p, %1, %2;\n@p add.u32 %0, %0, " #n ";\n}" : "+r"(c) : "r"(a), "r"(b))
#define CL_ARRIVE() asm volatile("barrier.cluster.arrive.relaxed.aligned;" ::: "memory")
#define CL_WAIT() asm volatile("barrier.cluster.wait.aligned;" ::: "memory")
__global__ void __cluster_dims__(8, 1, 1) __launch_bounds__(NTHR, 1)
clus_kernel(const bf16* __restrict__ x, const bf16* __restrict__ logAr, const bf16* __restrict__ Aim, const bf16* __restrict__ Cr, const bf16* __restrict__ Ci,
            const bf16* __restrict__ logdt, const bf16* __restrict__ c_in, Scratch* __restrict__ S, const bf16* __restrict__ Dskip,
            const bf16* __restrict__ w_r, const bf16* __restrict__ w_mod, bf16* __restrict__ out,
            const __grid_constant__ CUtensorMap tm_wm, const __grid_constant__ CUtensorMap tm_wg,
            const __grid_constant__ CUtensorMap tm_wu, const __grid_constant__ CUtensorMap tm_wd, const __grid_constant__ CUtensorMap tm_out) {
    extern __shared__ __align__(1024) unsigned char sm[];
    Misc& M = *(Misc*)(sm + OFF_MISC);
    const uint32_t sb = (uint32_t)__cvta_generic_to_shared(sm);
    const int tid = threadIdx.x < 128 ? threadIdx.x + 640 : threadIdx.x - 128, warp = __shfl_sync(0xffffffffu, tid >> 5, 0), lane = tid & 31;
    const int g = lane >> 2, t = lane & 3, lr = lane & 7, lm = lane >> 3;
    const int wgi = warp >> 2, w = warp & 3;
    const int b = blockIdx.x, cl = b >> 3, rk = b & 7;
    auto mod_ld = [&](uint32_t (*a)[4], uint32_t s0, uint32_t s1, int i) {
        const uint32_t wa = sb + ((lm & 1) ? s1 : s0) + (lr + 8 * (lm >> 1)) * 80 + i * 16;
#pragma unroll
        for (int ks = 0; ks < 4; ks++) ldsm_x4_t(a[ks], wa + ks * 1280);
        ldsm_x2_t(a[4], wa + 5120);
    };
    auto mod_mma2 = [&](float* d, float* e, uint32_t (*a)[4], uint32_t (*c)[4], const uint32_t* bs) {
        mma_k8(d, a[4][0], a[4][1], bs[8]); mma_k8(e, c[4][0], c[4][1], bs[8]);
#pragma unroll
        for (int ks = 0; ks < 4; ks++) {
            mma_bf16(d, a[ks][0], a[ks][1], a[ks][2], a[ks][3], bs[2 * ks], bs[2 * ks + 1]);
            mma_bf16(e, c[ks][0], c[ks][1], c[ks][2], c[ks][3], bs[2 * ks], bs[2 * ks + 1]);
        }
    };
    auto mod_st = [&](const float* d, uint32_t dst, int mb) {
#pragma unroll
        for (int h = 0; h < 2; h++) {
            const uint32_t rb = mapa(sb, t + 4 * h);
            sta2(rb + dst + g * 8, __float_as_uint(d[0]), __float_as_uint(d[2]), rb + (MB(mb) - sb));
        }
    };
    if (wgi == 5) {
        CL_ARRIVE();
        const uint32_t c_a = ld_nc((const uint32_t*)c_in + 36 * rk + lane), c_b = ld_nc((const uint32_t*)c_in + 36 * rk + 32 + t);
        {
            pace(WMD);
            const char* wp = (const char*)(w_mod + (72 * rk + 18 * w) * (6 * D_) + 40 * cl);
#pragma unroll
            for (int i = 0; i < 3; i++) {
                const uint32_t c = lane + 32 * i, row = (c * 205) >> 10;
                const char* p = wp + (row * (12 * D_ - 80) + 16 * c);
                if (c < 90) {
                    asm volatile("cp.async.cg.shared.global [%0], [%1], 16;" ::"r"(sb + OFF_WM0 + 1440 * w + 16 * c), "l"(p) : "memory");
                    asm volatile("cp.async.cg.shared.global [%0], [%1], 16;" ::"r"(sb + OFF_WM0 + 5760 + 1440 * w + 16 * c), "l"(p + 2 * D_) : "memory");
                }
            }
            if (w == 3 && lane < 20)
                asm volatile("cp.async.ca.shared.global [%0], [%1], 4, %2;" ::"r"(sb + OFF_MISC + (uint32_t)offsetof(Misc, c2) + 12 + 16 * lane), "l"((const uint32_t*)w_r + min(20 * cl + lane, D_ / 2 - 1)),
                             "r"(20 * cl + lane < D_ / 2 ? 4 : 0) : "memory");
            asm volatile("cp.async.commit_group;" ::: "memory");
        }
        auto gsum = [&](uint32_t a, int pitch) {
            float4 s = make_float4(0.f, 0.f, 0.f, 0.f);
#pragma unroll
            for (int i = 0; i < 8; i++) { const float4 q = *(const float4*)(sm + a + i * pitch); s.x += q.x; s.y += q.y; s.z += q.z; s.w += q.w; }
            return make_uint2(pack2(s.x, s.z), pack2(s.y, s.w));
        };
        auto one_plus = [&](uint32_t v) { return pack2(1.0f + lo2f(v), 1.0f + hi2f(v)); };
        {
            uint32_t bs[9], a[5][4], c[5][4];
            float d[4] = {0.f, 0.f, 0.f, 0.f}, e[4] = {0.f, 0.f, 0.f, 0.f};
            const uint32_t sc = pack2(silu(lo2f(c_a)), silu(hi2f(c_a)));
            bs[8] = pack2(silu(lo2f(c_b)), silu(hi2f(c_b)));
            if (w == 2) { sts32(sb + OFF_SC + 4 * lane, sc); sts32(sb + OFF_SC + 128 + 4 * t, bs[8]); }
#pragma unroll
            for (int ks = 0; ks < 8; ks++) bs[ks] = __shfl_sync(0xffffffffu, sc, 4 * ks + t);
            CL_WAIT();
            asm volatile("cp.async.wait_group 0;" ::: "memory");
            named_bar(10, 128);
            mod_ld(a, OFF_WM0 + 5760, OFF_WM0, w);
            mod_ld(c, OFF_WM0 + 5760, OFF_WM0, 4);
            mod_mma2(d, e, a, c, bs);
            mod_st(d, OFF_MG1 + rk * 320 + 64 * w, MB_MG1);
            if (w == 1) mod_st(e, OFF_MG1 + rk * 320 + 256, MB_MG1);
        }
        {
            const int n0 = 8 * w + 2 * (rk & 1), n1 = 8 * w + ((n0 + 4 + t) & 7);
            const float4* ap = &S->acc1[256 * rk + 8 * (n0 + t) + g];
            const float4* aq = &S->acc1[256 * rk + 8 * n1 + g];
            named_bar(9, 640);
            float4 pa = ld_rlx4f(ap), pb = ld_rlx4f(aq);
            if (w == 3) {
                mbar_wait(MB(MB_MG1), 0);
                const uint2 v = gsum(OFF_MG1 + 16 * min(lane, 19), 320);
                const uint32_t c1 = one_plus(v.x);
                if (lane < 20) *(uint4*)(sm + OFF_C1 + 16 * lane) = make_uint4(__byte_perm(c1, 0, 0x1010), __byte_perm(v.y, 0, 0x1010), __byte_perm(c1, 0, 0x3232), __byte_perm(v.y, 0, 0x3232));
                __syncwarp();
                named_arrive(10, 128);
            }
            uint32_t xq[2][5][4];
            uint2 cc[5];
            const uint32_t xa = sb + OFF_X + XI(2 * lm + (lr & 1)) + XN(n0 + (lr >> 1)), xb = sb + OFF_X + XI(2 * lm + (lr & 1)) + XN(8 * w + ((n0 + 4 + (lr >> 1)) & 7));
            const uint32_t ua = mapa(sb, g) + OFF_CH;
#pragma unroll
            for (int j = 0; j < 5; j++) ldsm_x4_t(xq[0][j], xa + 16 * j);
#pragma unroll 1
            for (int it = 0; it < SPIN_MAX && (pa.w != (float)NCL || pb.w != (float)NCL); it++) {
                pa = ld_rlx4f(ap); pb = ld_rlx4f(aq);
            }
            __syncwarp();
            if (w == 2 && lane < PFG) tma2d_pf(&tm_wg, 40 * b, 192 * lane);
            __syncwarp();
            float m0, r0, m1, r1;
            ln_stats(pa.x, pa.y, m0, r0);
            ln_stats(pb.x, pb.y, m1, r1);
            const uint32_t rh = pack2(r0, r1), rl = pack2(r0 - lo2f(rh), r1 - hi2f(rh));
            const uint32_t stage = sb + OFF_STG + w * 512;
            stsm_x4_t(stage + lane * 16, pack2(m0, m1), rh, rl, rl);
            __syncwarp();
            if (w != 3) named_bar(10, 128);
            uint4 st[2][3];
#pragma unroll
            for (int q = 0; q < 2; q++)
#pragma unroll
                for (int i = 0; i < 3; i++) st[q][i] = lds128(stage + 128 * i + (2 * t + q) * 16);
#pragma unroll
            for (int j = 0; j < 5; j++) cc[j] = *(const uint2*)(sm + OFF_C1 + 64 * j + 8 * g);
            ldsm_x4_t(xq[1][0], xb);
            const uint32_t ub = ua + (rk & 3) * UP + UB + (8 * w + 8 * (rk >> 2)) * 16, u0 = ub + (n0 + t) * 16, u1 = ub + n1 * 16;
#pragma unroll
            for (int j = 0; j < 5; j++) {
                if (j >= 2 && cl == 14) break;
                if (j < 4) ldsm_x4_t(xq[1][j + 1], xb + 16 * (j + 1));
#pragma unroll
                for (int q = 0; q < 2; q++) {
                    const uint4 sm_ = st[q][0], sh = st[q][1], sl = st[q][2];
                    const uint32_t v0 = add2(mul2(norm2(xq[q][j][0], sm_.x, sh.x, sl.x), cc[j].x), cc[j].y), v1 = add2(mul2(norm2(xq[q][j][1], sm_.y, sh.y, sl.y), cc[j].x), cc[j].y);
                    const uint32_t v2 = add2(mul2(norm2(xq[q][j][2], sm_.z, sh.z, sl.z), cc[j].x), cc[j].y), v3 = add2(mul2(norm2(xq[q][j][3], sm_.w, sh.w, sl.w), cc[j].x), cc[j].y);
                    asm volatile("{\n.reg .pred p;\nsetp.ne.u32 p, %6, %7;\n"
                                 "@p st.async.weak.shared::cluster.mbarrier::complete_tx::bytes.v4.b32 [%0], {%1,%2,%3,%4}, [%5];\n"
                                 "@!p st.shared.v4.b32 [%0], {%1,%2,%3,%4};\n}"
                                 ::"r"((q ? u1 : u0) + j * CHS), "r"(v0), "r"(v1), "r"(v2), "r"(v3), "r"(ua + j * CHS + XO_MBU), "r"(g), "r"(rk) : "memory");
                }
                __syncwarp();
                if (lane == 0) mbar_arrive(sb + OFF_CH + XO_MBU + j * CHS);
            }
        }
        asm volatile("setmaxnreg.dec.sync.aligned.u32 40;");
        {
        int cl;
        asm volatile("mov.u32 %0, %clusterid.x;" : "=r"(cl));
        const int w = __shfl_sync(0xffffffffu, (fresh_tid() >> 5) & 3, 0);
        uint32_t gz = 0;
        if (w) named_arrive(11, 128); else named_bar(11, 128);
        if (w == 0) {
            const int lane = fresh_tid() & 31;
            mbar_wait(MB(MB_KD), 0);
            PROXY_FENCE();
            if (lane == 0) {
                tma2d(sb + OFF_WU + 15360, &tm_wu, 40 * b, 192, MB(MB_WU));
                tma2d_pf(&tm_wu, 40 * b, 384);
                mbar_wait(MB(MB_C2), 0);
                PROXY_FENCE();
                tma2d(sb + OFF_WU + 2 * 15360, &tm_wu, 40 * b, 384, MB(MB_WU));
#pragma unroll 1
                for (int i = 0; i < 9; i++) { pace(PDE); tma2d_pf(&tm_wd, 64 * i, 40 * b); }
                mbar_wait(MB(MB_WU), 0);
            }
            __syncwarp();
        } else if (w == 1) {
            const int lane = fresh_tid() & 31;
            uint4* rp = S->h2c + 103 * b + lane;
#pragma unroll
            for (int i = 0; i < 4; i++) if (i < 3 || lane < 7) st_rlx4(rp + 32 * i, make_uint4(0, 0, 0, 0));
            uint32_t z = 0x3F800000u;
#pragma unroll
            for (int i = 0; i < 4; i++) if (i < 3 || lane < 7) z |= ld_rlx((const unsigned int*)(rp + 32 * i));
            if (lane == 0) asm volatile("red.relaxed.gpu.global.add.f32 [%0], %1;" ::"l"(&S->acc1[L_].z), "f"(__uint_as_float(z)) : "memory");
        } else if (w == 2) {
            if ((fresh_tid() & 31) == 0) {
                float4 v;
                int it = 0;
                pace(CWD);
                for (;;) { v = ld_rlx4f(&S->acc1[L_]); if (++it >= SPIN_MAX || (v.z == (float)G_ && v.w == (float)NCL)) break; pace(CWP); }
                M.cws[0] = v.x; M.cws[1] = v.y;
                mbar_arrive(MB(MB_CW));
            }
        } else if (w == 3) {
            const int lane = fresh_tid() & 31, l20 = min(lane, 19);
            mbar_wait(MB(MB_MG2), 0);
            const uint2 v = gsum(OFF_MG2 + 16 * l20, 640), u = gsum(OFF_MG2 + 320 + 16 * l20, 640);
            const uint32_t wr = lane < 20 ? M.c2[lane].w : 0u, cb1 = one_plus(v.x), cw = mul2(cb1, wr);
            if (lane < 20) {
                M.c2[lane] = make_uint4(cb1, v.y, u.x, cw);
                M.wr[lane] = wr;
                unsigned e;
                asm volatile("mov.u32 %0, %cluster_ctarank;" : "=r"(e));
                if ((lane & 3) == (e >> 1)) M.ga[lane >> 2] = __byte_perm(u.y, 0, (e & 1) ? 0x3232 : 0x1010);
            }
            __syncwarp();
            if (lane == 0) mbar_arrive(MB(MB_C2));
            if (rk == 0) {
                float a = lo2f(cw) + hi2f(cw), s = lo2f(v.y) * lo2f(wr) + hi2f(v.y) * hi2f(wr);
#pragma unroll
                for (int o = 16; o; o >>= 1) { a += __shfl_xor_sync(0xffffffffu, a, o); s += __shfl_xor_sync(0xffffffffu, s, o); }
                if (lane == 0) red4(&S->acc1[L_], a, s, 0.f);
                __syncwarp();
                if (lane < 20) st_rlx(&S->gb[20 * cl + lane], u.x);
                gz = ld_rlx(&S->gb[20 * cl + l20]) ^ u.x;
            }
        }
        {
        const int lane = fresh_tid() & 31, t = lane & 3, lr = lane & 7, lm = lane >> 3;
        uint32_t aw[5];
        __syncwarp();
        mbar_wait(MB(MB_C2), 0);
#pragma unroll
        for (int j = 0; j < 5; j++) aw[j] = M.wr[4 * j + t];
        const int ph = w >> 1, lst = 16 * ph + 2 * rk + (w & 1);
        const uint32_t rb = mapa(sb, lr);
        named_bar(6, 640);
        uint4 k = *(const uint4*)&M.key[128 * (w & 1) + 4 * lane];
        CE(k.x, k.y); CE(k.z, k.w); CE(k.x, k.z); CE(k.y, k.w); CE(k.y, k.z);
        uint32_t m[4];
#pragma unroll 1
        for (int q = 0; q <= ph; q++) {
#pragma unroll
            for (int rnd = 0; rnd < 4; rnd++) {
                m[rnd] = __reduce_max_sync(0xffffffffu, k.x);
                POP(k, m[rnd]);
            }
        }
        if (lane < 8) sta4(rb + OFF_MISC + (uint32_t)offsetof(Misc, cand) + lst * 16, make_uint4(m[0], m[1], m[2], m[3]), rb + (MB(MB_KEY2) - sb));
        const uint32_t mine = (t & 2) ? ((t & 1) ? m[3] : m[2]) : ((t & 1) ? m[1] : m[0]);
        const uint32_t ra = sb + OFF_H2T + ROW(mine) * 80;
        uint32_t bq[6];
        float rr[4] = {0.f, 0.f, 0.f, 0.f};
        ldsm_x4(bq, ra + 16 * lm); ldsm_x2(bq + 4, ra + 64);
        mma_bf16(rr, aw[0], aw[0], aw[1], aw[1], bq[0], bq[1]); mma_bf16(rr, aw[2], aw[2], aw[3], aw[3], bq[2], bq[3]); mma_k8(rr, aw[4], aw[4], bq[4]);
        float4* p = &S->rs[8 * lst];
        if (lane < 2) red4(p + lane, rr[0], __uint_as_float(gz), rr[1]);
        float4 e0 = ld_rlx4f(p), e1 = ld_rlx4f(p + 1);
        uint32_t sl = 0;
        if (w == 1) {
            mbar_wait(MB(MB_KEY2), 0);
            k = *(const uint4*)&M.cand[4 * lane];
            named_bar(14, 64);
#pragma unroll
            for (int s = 0; s < 8; s++) {
                const uint32_t v = M.sel[s] & ~1u;
                if (k.x == v) sl |= 8 + s;
                if (k.y == v) sl |= (8 + s) << 8;
                if (k.z == v) sl |= (8 + s) << 16;
                if (k.w == v) sl |= (8 + s) << 24;
            }
        }
        if (w == 0) {
            named_bar(8, 64);
            if (lane == 0) {
                PROXY_FENCE();
                tma5d_st(&tm_out, 40 * cl, RKT, sb + OFF_OUT);
                asm volatile("cp.async.bulk.commit_group;" ::: "memory");
            }
            __syncwarp();
        }
#pragma unroll 1
        for (int it = 0; it < SPIN_MAX && (e0.w != (float)NCL || e1.w != (float)NCL); it++) {
            e0 = ld_rlx4f(p); e1 = ld_rlx4f(p + 1);
        }
        {
            const uint32_t r0 = pack2(e0.x, e0.z), r1 = pack2(e1.x, e1.z);
            const uint32_t o0 = r0 ^ (sign2(r0) | 0x80008000u), o1 = r1 ^ (sign2(r1) | 0x80008000u);
            if (lane < 8) sta4(rb + OFF_EK + lst * VP, make_uint4((o0 << 16) | (m[0] & 0x3FFFu), (o0 & 0xFFFF0000u) | (m[1] & 0x3FFFu), (o1 << 16) | (m[2] & 0x3FFFu), (o1 & 0xFFFF0000u) | (m[3] & 0x3FFFu)),
                               rb + (MB(MB_EK) - sb));
        }
        if (w == 0) {
            if (lane == 0) {
                asm volatile("cp.async.bulk.wait_group 0;" ::: "memory");
                asm volatile("fence.acq_rel.gpu;" ::: "memory");
                mbar_arrive(MB(MB_OUT));
            }
        } else if (w == 1) {
            const uint32_t found = __reduce_add_sync(0xffffffffu, __popc(sl & 0x08080808u));
            mbar_wait(MB(MB_EK), 0);
            if (b == 0 && lane == 0) st_rlx4(&S->acc1[L_], make_uint4(0, 0, 0, 0));
            if (lane < 16 || cl == 14) st_rlx4(&S->acc2[256 * rk + 16 * cl + lane], make_uint4(0, 0, 0, 0));
            k = lds128(sb + OFF_EK + lane * VP);
            const bool s0 = sl & 8u, s1 = sl & 0x800u, s2 = sl & 0x80000u, s3 = sl & 0x8000000u;
            if (s0) M.fin[sl & 7u] = k.x;
            if (s1) M.fin[(sl >> 8) & 7u] = k.y;
            if (s2) M.fin[(sl >> 16) & 7u] = k.z;
            if (s3) M.fin[(sl >> 24) & 7u] = k.w;
            const uint32_t lo = min(min(s0 ? k.x : ~0u, s1 ? k.y : ~0u), min(s2 ? k.z : ~0u, s3 ? k.w : ~0u));
            const uint32_t hi = max(max(s0 ? 0u : k.x, s1 ? 0u : k.y), max(s2 ? 0u : k.z, s3 ? 0u : k.w));
            const uint32_t hi2 = __reduce_max_sync(0xffffffffu, hi), lo2 = __reduce_min_sync(0xffffffffu, lo);
            bool redo = found != 8u;
            if (hi2 > lo2) {
                const uint32_t h = hi2 | 0xFFFFu, l = lo2 & 0xFFFF0000u;
                const uint32_t n = __reduce_add_sync(0xffffffffu, ((s0 ? k.x <= h : (k.x >= l) << 8) + (s1 ? k.y <= h : (k.y >= l) << 8)) + ((s2 ? k.z <= h : (k.z >= l) << 8) + (s3 ? k.w <= h : (k.w >= l) << 8)));
                redo = redo || (h >> 16) - (l >> 16) > 1u || ((n & 255u) > 1u && n >= 512u) || (n & 255u) + (n >> 8) > 9u;
            }
            if (redo) {
                CE(k.x, k.y); CE(k.z, k.w); CE(k.x, k.z); CE(k.y, k.w); CE(k.y, k.z);
                __syncwarp();
#pragma unroll 1
                for (int rnd = 0; rnd < 8; rnd++) {
                    const uint32_t m8 = __reduce_max_sync(0xffffffffu, k.x);
                    POP(k, m8);
                    if (lane == 0) M.fin[rnd] = m8;
                }
            }
            if (lane == 0) M.fin[8] = redo;
            __syncwarp();
            named_arrive(12, 672);
        }
        }
        }
    } else {
    if (warp != 19) CL_ARRIVE();
    const int chn = 40 * cl + 8 * wgi + rk;
    const bool has_ch = chn < D_;
    const uint32_t cb = sb + OFF_CH + wgi * CHS;
    auto ldx = [&]() {
    if (warp < 16) {
        const char* xp = (const char*)(x + (512 * (warp >> 2) + 64 * (warp & 3) + RKT) * D_ + 40 * cl);
        const uint32_t dst = sb + OFF_X + XN(2 * warp) + XI(lm) + 16 * lr;
        xp += lm * (2 * D_) + 16 * lr;
#pragma unroll
        for (int i = 0; i < 4; i++)
            if (lr < 5) asm volatile("cp.async.cg.shared.global [%0], [%1], 16, %2;" ::"r"(dst + XI(4 * (i & 1)) + 80 * (i >> 1)), "l"(xp + ((i & 1) * 4 + (i >> 1) * 32) * (2 * D_)),
                                     "r"((cl < 14 || lr < 2) ? 16 : 0) : "memory");
    }
    };
    unsigned short r_ldt = 0, r_lar = 0, r_aim = 0, r_cr = 0, r_ci = 0;
    {
        const int n = min(chn, D_ - 1) * N_ + (tid & 127);
        r_ldt = ld_nc16((const unsigned short*)logdt + min(chn, D_ - 1));
        r_lar = ld_nc16((const unsigned short*)logAr + n);
        r_aim = ld_nc16((const unsigned short*)Aim + n);
        r_cr = ld_nc16((const unsigned short*)Cr + n);
        r_ci = ld_nc16((const unsigned short*)Ci + n);
    }
    if (warp == 19) {
        if (lane == 0) asm volatile("prefetch.tensormap [%0];" ::"l"(&tm_wm) : "memory");
        const uint32_t lo = 90u | (10u << 8) | (20u << 16) | (2u << 24), hi = (cl == 14 ? 32u : 80u) | ((rk < 4 ? 40u : 32u) << 8) | (180u << 16) | (180u << 24);
        const uint32_t tx = lane < 8 ? (((lane & 4 ? hi : lo) >> (8 * (lane & 3))) & 255u) : lane == 8 ? 180u : lane < 11 ? 2u : lane == 11 ? (hi >> 8) & 255u : 14u;
        if (lane == 0) {
#pragma unroll
            for (int i = 0; i < MB_N; i++) mbar_init(MB(i), i == MB_KD ? 20 : 1);
#pragma unroll
            for (int i = 0; i < 5; i++) mbar_init(sb + OFF_CH + XO_MBU + i * CHS, 5);
        }
        __syncwarp();
        if (lane < 17) mbar_expect(lane < MB_C2 ? MB(lane) : sb + OFF_CH + XO_MBU + (lane - MB_C2) * CHS, tx << 8);
        asm volatile("fence.mbarrier_init.release.cluster;" ::: "memory");
        __syncwarp();
        CL_ARRIVE();
    }
    ldx();
    if ((tid & 127) == 32) asm volatile("cp.async.ca.shared.global [%0], [%1], 4;" ::"r"(cb + XO_DSK), "l"((const uint32_t*)Dskip + (min(chn, D_ - 1) >> 1)) : "memory");
    asm volatile("cp.async.commit_group;" ::: "memory");
    auto mod2 = [&]() {
        if (wgi == M2W) {
            const int lane = fresh_tid() & 31, t = lane & 3;
            const uint32_t wa = sb + ((lane & 7) + ((lane >> 1) & 8)) * 80, p0 = wa + ((lane & 8) ? OFF_WM2 + 5760 : OFF_WM2 + 11520), p1 = wa + ((lane & 8) ? OFF_WM2 : OFF_WM0 + 11520);
            auto ld = [&](uint32_t (*a)[4], uint32_t p) {
#pragma unroll
                for (int ks = 0; ks < 4; ks++) ldsm_x4_t(a[ks], p + ks * 1280);
                ldsm_x2_t(a[4], p + 5120);
            };
            const uint32_t rb = mapa(sb, t), rd = mapa(sb, 4) - mapa(sb, 0), dst = rb + OFF_MG2 + rk * 640 + (lane >> 2) * 8;
            auto st = [&](const float* d, uint32_t o) {
                sta2(dst + o, __float_as_uint(d[0]), __float_as_uint(d[2]), rb + (MB(MB_MG2) - sb));
                sta2(dst + rd + o, __float_as_uint(d[0]), __float_as_uint(d[2]), rb + rd + (MB(MB_MG2) - sb));
            };
            uint32_t bs[9], a[5][4], c[5][4];
            float d[4] = {0.f, 0.f, 0.f, 0.f}, e[4] = {0.f, 0.f, 0.f, 0.f};
            mbar_wait(MB(MB_MG1), 0);
#pragma unroll
            for (int ks = 0; ks < 9; ks++) bs[ks] = lds32(sb + OFF_SC + 16 * ks + 4 * t);
            mbar_wait(MB(MB_WM2), 0);
            __syncwarp();
            ld(a, p0 + 16 * w);
            ld(c, p1 + 16 * w);
            {
                float h[6][4];
#pragma unroll
                for (int i = 0; i < 24; i++) h[i >> 2][i & 3] = 0.f;
                mma_k8(h[0], a[4][0], a[4][1], bs[8]); mma_k8(h[3], c[4][0], c[4][1], bs[8]);
#pragma unroll
                for (int ks = 0; ks < 4; ks++) {
                    mma_bf16(h[(ks + 1) % 3], a[ks][0], a[ks][1], a[ks][2], a[ks][3], bs[2 * ks], bs[2 * ks + 1]);
                    mma_bf16(h[3 + (ks + 1) % 3], c[ks][0], c[ks][1], c[ks][2], c[ks][3], bs[2 * ks], bs[2 * ks + 1]);
                }
                d[0] = h[0][0] + h[1][0] + h[2][0]; d[2] = h[0][2] + h[1][2] + h[2][2];
                e[0] = h[3][0] + h[4][0] + h[5][0]; e[2] = h[3][2] + h[4][2] + h[5][2];
                ld(a, ((w & 1) ? p1 : p0) + 64);
                st(d, 64 * w);
                st(e, 320 + 64 * w);
#pragma unroll
                for (int i = 0; i < 20; i++) h[i >> 2][i & 3] = 0.f;
                mma_k8(h[4], a[4][0], a[4][1], bs[8]);
#pragma unroll
                for (int ks = 0; ks < 4; ks++) mma_bf16(h[ks], a[ks][0], a[ks][1], a[ks][2], a[ks][3], bs[2 * ks], bs[2 * ks + 1]);
                d[0] = (h[0][0] + h[1][0]) + (h[2][0] + h[3][0]) + h[4][0]; d[2] = (h[0][2] + h[1][2]) + (h[2][2] + h[3][2]) + h[4][2];
            }
            if (w < 2) st(d, 320 * w + 256);
            __syncwarp();
        }
    };
    auto ln1 = [&]() {
        if (warp < 16) {
            uint32_t a[10];
            const uint32_t xa = sb + OFF_X + XN(2 * warp) + (lm & 1) * 80 + XI(lr) + (lm >> 1) * 16;
            asm volatile("cp.async.wait_group 0;" ::: "memory");
            __syncwarp();
            ldsm_x4(a, xa); ldsm_x4(a + 4, xa + 32); ldsm_x2(a + 8, xa + 64);
            named_arrive(9, 640);
            float c1[4] = {0.f, 0.f, 0.f, 0.f}, c2[4] = {0.f, 0.f, 0.f, 0.f}, c3[4] = {0.f, 0.f, 0.f, 0.f};
#pragma unroll
            for (int j = 0; j < 2; j++) {
                mma_bf16(c1, a[4 * j], a[4 * j + 1], a[4 * j + 2], a[4 * j + 3], 0x3F803F80u, 0x3F803F80u);
                mma_bf16(c2, a[4 * j], a[4 * j + 1], a[4 * j + 2], a[4 * j + 3], a[4 * j], a[4 * j + 2]);
                mma_bf16(c3, a[4 * j], a[4 * j + 1], a[4 * j + 2], a[4 * j + 3], a[4 * j + 1], a[4 * j + 3]);
            }
            mma_k8(c1, a[8], a[9], 0x3F803F80u); mma_k8(c2, a[8], a[9], a[8]); mma_k8(c3, a[8], a[9], a[9]);
            float4* p = &S->acc1[256 * rk + 16 * warp + g];
            red4p(t == (g >> 1), p, c1[0], (g & 1) ? c2[1] : c2[0], 0.f);
            red4p(t == (g >> 1), p + 8, c1[2], (g & 1) ? c3[3] : c3[2], 0.f);
        }
    };
    {
        unsigned char* cp = sm + OFF_CH + wgi * CHS + lane * 16;
        const uint4 z = make_uint4(0, 0, 0, 0);
        *(uint4*)(cp + w * UP + XO_TF) = z;
        *(uint4*)(cp + w * UP + (lane < 16 ? XO_U8 - 256 : XO_U16 - 512)) = z;
        if (lane < 16) *(uint4*)(cp + (lane < 8 ? w * UP + UB - 128 : XO_TD + (4 * w + (lane < 12 ? -8 : 145 - 12)) * 16)) = z;
    }
    if (tid < 200) ((uint32_t*)M.box)[tid] = box_tap(tid);
    const uint32_t scr = sb + warp * KSCR, ws = scr + lane * 4;
    uint32_t fixa = 0, fixv = 0;
    {
        uint32_t zr;
        asm volatile("ld.volatile.shared.u32 %0, [%1];" : "=r"(zr) : "r"(cb + XO_TF + w * UP + lane * 16) : "memory");
        const float p_ldt = __uint_as_float(r_ldt * 65536u + zr), p_lar = __uint_as_float(r_lar * 65536u + zr), p_aim = __uint_as_float(r_aim * 65536u + zr);
        const float p_cr = __uint_as_float(r_cr * 65536u + zr), p_ci = __uint_as_float(r_ci * 65536u + zr);
        float acc[5][4];
        uint32_t afr[4][4], cz[4];
        const uint32_t ba = scr + lr * 144 + lm * 16;
        auto tile = [&](float* c, int rg) {
            __syncwarp();
            c[0] = c[1] = c[2] = c[3] = 0.f;
            uint32_t bb[2][4];
            ldsm_x4(bb[0], ba + rg * 1152);
            ldsm_x4(bb[1], ba + rg * 1152 + 64);
            mma_f16(c, afr[0], bb[0][0], bb[0][1]);
            mma_f16(c, afr[1], bb[0][2], bb[0][3]);
            mma_f16(c, afr[2], bb[1][0], bb[1][1]);
            mma_f16(c, afr[3], bb[1][2], bb[1][3]);
        };
#define CJ(z) packh((z).x, -(z).y)
#define CJP(z) packh((z).y, (z).x)
        const float dt = bfr(expf(p_ldt));
        const float al = -bfr(expf(p_lar)) * dt * 1.4426950408889634f;
        const float th = p_aim * dt;
        const float th_ = th * 0.15915494309189535f;
        const float tl_ = fmaf(th, 0.15915494309189535f, -th_) + th * 6.4206382e-9f;
        auto anchor = [&](float s) {
            float f = th_ * s;
            f -= rintf(f);
            f = fmaf(tl_, s, f) * 6.283185307179586f;
            const float e = fex2(al * s);
            return cplx{e * __cosf(f), e * __sinf(f)};
        };
        const float cx = p_cr * dt * 2.0f, cy = p_ci * dt * 2.0f;
        const uint32_t ex = __reduce_max_sync(0xffffffffu, __float_as_uint(fmaxf(fabsf(cx), fabsf(cy)))) >> 23;
        const float scl = __uint_as_float((254u - ex) << 23);
        const cplx C = cplx{cx * scl, cy * scl};
        const cplx z1 = anchor(1.f), z16 = anchor(16.f), z256 = anchor(256.f);
        {
            const cplx z32 = csq(z16), z48 = cmul(z32, z16), z64 = csq(z32), z128 = csq(z64), z192 = cmul(z128, z64);
            const uint32_t y[3] = {packh(z16.x, z16.y), packh(z32.x, z32.y), packh(z48.x, z48.y)};
            const uint32_t yp[3] = {packh(-z16.y, z16.x), packh(-z32.y, z32.x), packh(-z48.y, z48.x)};
            const uint32_t xx[3] = {packh(z64.x, z64.y), packh(z128.x, z128.y), packh(z192.x, z192.y)};
            sts32(ws, 0x00003C00u);
#pragma unroll
            for (int j = 0; j < 3; j++) sts32(ws + (1 + j) * 144, y[j]);
#pragma unroll
            for (int i = 0; i < 3; i++) {
                sts32(ws + (4 + 4 * i) * 144, xx[i]);
#pragma unroll
                for (int j = 0; j < 3; j++) sts32(ws + (5 + 4 * i + j) * 144, hcm(xx[i], y[j], yp[j]));
            }
        }
        ln1();
        WMS(0);
        const cplx z2 = csq(z1);
        {
            const cplx z3 = cmul(z2, z1), z4 = csq(z2), z8 = csq(z4);
            const cplx c4 = cmul(C, z4), c8 = cmul(C, z8), c12 = cmul(c8, z4);
            cz[0] = packh(C.x, -C.y); cz[1] = packh(c4.x, -c4.y); cz[2] = packh(c8.x, -c8.y); cz[3] = packh(c12.x, -c12.y);
            __syncwarp();
#pragma unroll
            for (int s = 0; s < 4; s++) ldsm_x4(afr[s], scr + (lr + 8 * (lm & 1)) * 144 + (2 * s + (lm >> 1)) * 16);
            const uint32_t y[3] = {CJ(z1), CJ(z2), CJ(z3)}, yp[3] = {CJP(z1), CJP(z2), CJP(z3)};
#pragma unroll
            for (int tt = 0; tt < 2; tt++) {
                const int rg = tt ? 0 : 2;
#pragma unroll
                for (int i = 0; i < 2; i++) {
                    sts32(ws + rg * 1152 + (4 * i) * 144, cz[2 * tt + i]);
#pragma unroll
                    for (int j = 0; j < 3; j++) sts32(ws + rg * 1152 + (4 * i + 1 + j) * 144, hcm(cz[2 * tt + i], y[j], yp[j]));
                }
                tile(acc[tt], rg);
            }
        }
        WMS(1);
        const cplx z258 = cmul(z256, z2), z512 = csq(z256), z768 = cmul(z512, z256);
        {
            const uint32_t a0 = CJ(z256), a0p = CJP(z256), a1 = CJ(z258), a1p = CJP(z258);
#pragma unroll
            for (int i = 0; i < 4; i++) { sts32(ws + 1152 + (2 * i) * 144, hcm(cz[i], a0, a0p)); sts32(ws + 1152 + (2 * i + 1) * 144, hcm(cz[i], a1, a1p)); }
            tile(acc[2], 1);
        }
        WMS(2);
        {
            const uint32_t a0 = CJ(z512), a0p = CJP(z512), a1 = CJ(z768), a1p = CJP(z768);
#pragma unroll
            for (int i = 0; i < 4; i++) { sts32(ws + 2304 + i * 144, hcm(cz[i], a0, a0p)); sts32(ws + 2304 + (4 + i) * 144, hcm(cz[i], a1, a1p)); }
            tile(acc[3], 2);
        }
        WMS(3);
        const cplx z1024 = csq(z512);
        {
            const cplx zk[4] = {z1024, cmul(z1024, z256), csq(z768), cmul(z1024, z768)};
#pragma unroll
            for (int h = 0; h < 4; h++) {
                const uint32_t a0 = CJ(zk[h]), a0p = CJP(zk[h]);
                sts32(ws + (2 * h) * 144, hcm(cz[0], a0, a0p));
                sts32(ws + (2 * h + 1) * 144, hcm(cz[2], a0, a0p));
            }
            tile(acc[4], 0);
        }
        const cplx z2048 = csq(z1024);
        float last = C.x * z2048.x - C.y * z2048.y;
#pragma unroll
        for (int o = 16; o; o >>= 1) last += __shfl_xor_sync(0xffffffffu, last, o);
        __syncwarp();
#pragma unroll
        for (int i = 0; i < 5; i++) *(float4*)(sm + (scr - sb) + i * 512 + ((lane * 16) ^ (i == 1 ? 64 : 0))) = make_float4(acc[i][0], acc[i][1], acc[i][2], acc[i][3]);
        if (lane == 0) { const float inv = __uint_as_float(ex << 23); sts32(cb + XO_KINV + 4 * w, __float_as_uint(inv)); sts32(cb + XO_KLAST + 4 * w, __float_as_uint(last * inv)); }
        WMS(4);
        asm volatile("cp.async.wait_group 0;" ::: "memory");
        if (w != 3) CL_WAIT();
        named_bar(1 + wgi, 128);
        const uint32_t td = cb + XO_TD + 64 * 4, tf = cb + XO_TF - 32 * 4;
        const float4 ki = *(const float4*)(sm + (cb - sb) + XO_KINV);
        auto fsum = [&](int off, uint32_t& r0, uint32_t& r1) {
            const unsigned char* p = sm + wgi * (4 * KSCR) + off;
            const float4 a = *(const float4*)p, b2 = *(const float4*)(p + KSCR), c = *(const float4*)(p + 2 * KSCR), d = *(const float4*)(p + 3 * KSCR);
            r0 = pack2(fmaf(a.y, ki.x, b2.y * ki.y) + fmaf(c.y, ki.z, d.y * ki.w), fmaf(a.x, ki.x, b2.x * ki.y) + fmaf(c.x, ki.z, d.x * ki.w));
            r1 = pack2(fmaf(a.w, ki.x, b2.w * ki.y) + fmaf(c.w, ki.z, d.w * ki.w), fmaf(a.z, ki.x, b2.z * ki.y) + fmaf(c.z, ki.z, d.z * ki.w));
        };
        const int role = (w + wgi) & 3;
        const int fo = role ? (role + 1) * 512 + lane * 16 : (g & 1) * 512 + ((lm ^ (g & 1)) * 64) + t * 16;
        uint32_t r[2];
        fsum(fo, r[0], r[1]);
        if (role == 0) {
            uint32_t q[2], v[4];
            fsum(fo + 256, q[0], q[1]);
            const uint32_t c[4] = {r[0], q[0], r[1], q[1]};
#pragma unroll
            for (int i = 0; i < 4; i++) v[i] = __shfl_sync(0xffffffffu, c[i], (lane + 31) & 31);
            if (lane == 0) mbar_arrive(MB(MB_KD));
#pragma unroll
            for (int i = 0; i < 4; i++) *(uint2*)(sm + (td - sb) + lane * 8 + i * 256) = make_uint2(__byte_perm(c[i], lane ? v[i] : i ? v[i - 1] : 0u, 0x5432), c[i]);
            if (lane == 0) { fixa = td + 256 * 4 + 2; fixv = v[3]; }
        } else if (role == 1) {
            const uint32_t v0 = __shfl_sync(0xffffffffu, r[0], (lane + 1) & 31), v1 = __shfl_sync(0xffffffffu, r[1], (lane + 1) & 31);
            if (lane == 0) mbar_arrive(MB(MB_KD));
#pragma unroll
            for (int h = 0; h < 2; h++) {
                const uint32_t dd = __byte_perm(r[h], 0, 0x3232);
                *(uint4*)(sm + (td - sb) + 1024 + lane * 16 + h * 512) = make_uint4(dd, dd, r[h], __byte_perm((h || lane == 31) ? v1 : v0, r[h], 0x5432));
            }
        } else {
            __syncwarp();
            if (lane == 0) mbar_arrive(MB(MB_KD));
            const uint32_t p = role == 2 ? tf + (64 + 32 * (t >> 1) + 2 * g + (t & 1)) * 4 : tf + 2 * UP + (64 + 16 * t + g) * 4, p1 = p + (role == 2 ? 64 : 32);
            const uint32_t k0 = r[0] >> 16, k1 = r[1] >> 16;
            sts16(p + UP, r[0]); sts16(p + UP + 6, r[0]); sts16(p1 + UP, r[1]); sts16(p1 + UP + 6, r[1]);
            sts16(p1 - 4, k1); sts16(p1 + 2, k1);
            const uint32_t dd = __byte_perm(r[0], 0, 0x3232);
            if (lane) { sts16(p - 4, k0); sts16(p + 2, k0); }
            else if (role == 2) {
                *(uint4*)(sm + (td - sb) + 512 * 4) = make_uint4(dd, dd, dd, r[0] & 0xFFFF0000u);
                fixa = td + 511 * 4; fixv = k0;
            } else {
                const float4 kl4 = *(const float4*)(sm + (cb - sb) + XO_KLAST);
                const uint32_t kl = f2bits((kl4.x + kl4.y) + (kl4.z + kl4.w));
                sts16(tf + 127 * 4, dd); sts16(tf + 128 * 4 + 2, dd); sts32(cb + XO_K1024, dd);
                sts16(tf + 2 * UP + 127 * 4, kl); sts16(tf + 2 * UP + 128 * 4 + 2, kl);
            }
        }
        __syncwarp();
        mod2();
        if (wgi == 3) {
            mbar_wait(MB(MB_KD), 0);
            PROXY_FENCE();
            if (lane == 0) tma2d(sb + w * 15360, w < 3 ? &tm_wg : &tm_wu, 40 * b, w < 3 ? 192 * w : 0, w < 3 ? MB(MB_WG) : MB(MB_WU));
            __syncwarp();
        }
    }
    if (has_ch) {
        conv_channel(sm, rk, fixa, fixv);
    } else {
        asm volatile("setmaxnreg.inc.sync.aligned.u32 88;");
        mbar_wait(MB(MB_WG), 0);
        mbar_wait(MB(MB_C2), 0);
    }
    {
    const int tid = fresh_tid(), warp = __shfl_sync(0xffffffffu, tid >> 5, 0), lane = tid & 31;
    const int g = lane >> 2, t = lane & 3, lr = lane & 7, lm = lane >> 3;
    __syncwarp();
    if (lane == 0) mbar_arrive(MB(MB_KD));
    uint32_t x1[10];
    uint32_t wf[9][4], wd[2][3][4];
    const int fmt = warp >> 2, fsl = warp & 3;
    auto ldwf = [&]() {
        const int half = lm & 1;
        const uint32_t base = (fmt == 4) ? ((half ? OFF_WU : OFF_WG) + 64) : ((fmt >> 1) * OFF_WU + ((2 * (fmt & 1) + half) << 4));
        const uint32_t wa = sb + base + (144 * fsl + lr + 8 * (lm >> 1)) * 80;
#pragma unroll
        for (int ks = 0; ks < 9; ks++) ldsm_x4_t(wf[ks], wa + ks * 1280);
    };
    if (warp < 16) {
        uint32_t bw[5], v[10];
#pragma unroll
        for (int j = 0; j < 5; j++) bw[j] = (g & 1) ? M.c2[4 * j + t].w : 0x3F803F80u;
        const uint32_t xa = sb + OFF_X + XI(warp >> 1) + (2 * (warp & 1) + (lm & 1)) * XG + lr * 80 + (lm >> 1) * 16;
        const uint32_t va = sb + OFF_V + (8 * (lm >> 1) + lr) * VP + 32 * warp + 16 * (lm & 1);
        ldsm_x4(x1, xa); ldsm_x4(x1 + 4, xa + 32); ldsm_x2(x1 + 8, xa + 64);
        mbar_wait(MB(MB_V), 0);
        ldsm_x4_t(v, va); ldsm_x4_t(v + 4, va + 16 * VP); ldsm_x2_t(v + 8, va + 32 * VP);
#pragma unroll
        for (int i = 0; i < 10; i++) x1[i] = add2(x1[i], (i >= 4 && cl == 14) ? 0u : v[i]);
        float c1[4] = {0.f, 0.f, 0.f, 0.f}, c2[4] = {0.f, 0.f, 0.f, 0.f}, c3[4] = {0.f, 0.f, 0.f, 0.f};
#pragma unroll
        for (int j = 0; j < 2; j++) {
            mma_bf16(c1, x1[4 * j], x1[4 * j + 1], x1[4 * j + 2], x1[4 * j + 3], bw[2 * j], bw[2 * j + 1]);
            mma_bf16(c2, x1[4 * j], x1[4 * j + 1], x1[4 * j + 2], x1[4 * j + 3], x1[4 * j], x1[4 * j + 2]);
            mma_bf16(c3, x1[4 * j], x1[4 * j + 1], x1[4 * j + 2], x1[4 * j + 3], x1[4 * j + 1], x1[4 * j + 3]);
        }
        mma_k8(c1, x1[8], x1[9], bw[4]); mma_k8(c2, x1[8], x1[9], x1[8]); mma_k8(c3, x1[8], x1[9], x1[9]);
        if (t == (g >> 1)) {
            float4* p = &S->acc2[256 * rk + 16 * warp + g];
            red4(p, c1[0], (g & 1) ? c2[1] : c2[0], c1[1]);
            red4(p + 8, c1[2], (g & 1) ? c3[3] : c3[2], c1[3]);
        }
        __syncwarp();
    }
    if (warp >= 16) { mbar_wait(MB(MB_WG), 0); mbar_wait(MB(MB_WU), 0); ldwf(); }
    if (warp >= 17) {
        if (warp == 17) mbar_wait(MB(MB_KD), 1);
        else named_bar(7, 96);
        PROXY_FENCE();
        if (lane < 3) tma2d(sb + OFF_WD + (3 * (warp - 17) + lane) * 5120, &tm_wd, 64 * (3 * (warp - 17) + lane), 40 * b, MB(MB_WD));
        __syncwarp();
    }
    uint32_t h2[10];
    uint32_t ta = sb + OFF_H2T + (16 * warp + (lane & 15)) * 80 + (lane >> 4) * 16;
    if (warp < 16) {
        const float4* ap = &S->acc2[256 * rk + 32 * (warp >> 1) + lane];
        if (warp < 8) { mbar_wait(MB(MB_WG), 0); ldwf(); }
        float4 s = ld_rlx4f(ap);
        uint2 kc[5];
#pragma unroll
        for (int j = 0; j < 5; j++) kc[j] = *(const uint2*)&M.c2[4 * j + t];
        mbar_wait(MB(MB_CW), 0);
        const float cw = M.cws[0], sbw = M.cws[1];
        uint32_t tk0 = (2047 - (((lane & 6) << 8) + ((lane & 24) << 3) + ((lane & 1) << 5) + RKT + (warp >> 1))) << 3;
        uint32_t ka = sb + OFF_MISC + (uint32_t)offsetof(Misc, key) + (32 * (warp >> 1) + lane) * 4;
        uint32_t rb = mapa(sb, 4 * (warp & 1) + t), cd = rb + OFF_MISC + (uint32_t)offsetof(Misc, cand2) + (8 * rk + (warp >> 1)) * 8;
        const int pj = lane >= 5, pc = lane - 5 * pj;
        uint4* dst = &S->h2c[(2 * (8 * rk + (warp >> 1)) + pj) * 72 + 5 * cl + pc];
        uint32_t pa = sb + OFF_H2T + 32 * (warp >> 1) * 80 + 16 * pc;
        asm volatile("" : "+r"(tk0), "+r"(ta), "+r"(ka), "+r"(rb), "+r"(cd), "+r"(pa), "+l"(dst));
        mbar_wait(MB(MB_KD), 1);
#pragma unroll 1
        for (int it = 0; it < SPIN_MAX && s.w != (float)NCL; it++) {
            if (s.w < (float)PQT) { const uint32_t c0 = clock(); for (int k = 0; k < 1024 && (uint32_t)clock() - c0 < PQD; k++) { } }
            s = ld_rlx4f(ap);
        }
        __syncwarp();
        if (warp == 0) named_arrive(7, 96);
        float meanb, rinv;
        ln_stats(s.x, s.y, meanb, rinv);
        const uint32_t rbits = __float_as_uint(fmaf(fmaf(-meanb, cw, s.z), rinv, sbw));
        const uint32_t key = ((rbits ^ (((int)rbits >> 31) | 0x80000000u)) & 0xFFFFC000u) | tk0;
        const uint32_t m0 = __reduce_max_sync(0xffffffffu, key);
        const uint32_t mr = pack2(meanb, rinv), rl = f2bits(rinv - hi2f(mr));
        const uint32_t m1 = __reduce_max_sync(0xffffffffu, key == m0 ? 0u : key);
        uint32_t st[2][2];
#pragma unroll
        for (int h = 0; h < 2; h++) { st[h][0] = __shfl_sync(0xffffffffu, mr, 16 * (warp & 1) + 8 * h + g); st[h][1] = __shfl_sync(0xffffffffu, rl, 16 * (warp & 1) + 8 * h + g); }
        if (lane < 4) sta2(cd, m0, m1 | 1u, rb + (MB(MB_KEY) - sb));
        sts32(ka, key);
        const int pr = __ffs(__ballot_sync(0xffffffffu, key == m0) | 0x80000000u) - 1, pr1 = __ffs(__ballot_sync(0xffffffffu, key == m1) | 0x80000000u) - 1;
#pragma unroll
        for (int i = 0; i < 10; i++)
            h2[i] = add2(mul2(norm2(x1[i], __byte_perm(st[i & 1][0], 0, 0x1010), __byte_perm(st[i & 1][0], 0, 0x3232), __byte_perm(st[i & 1][1], 0, 0x1010)), kc[i >> 1].x), kc[i >> 1].y);
        stsm_x4(ta, h2[0], h2[1], h2[2], h2[3]); stsm_x4(ta + 32, h2[4], h2[5], h2[6], h2[7]); stsm_x2(ta + 64, h2[8], h2[9]);
        __syncwarp();
        const int row = pj ? pr1 : pr;
        if (lane < 10 && (row >> 4) == (warp & 1) && pc < (cl < 14 ? 5 : 2)) {
            const uint4 a = lds128(pa + 80 * row);
            st_rlx4(dst, make_uint4(~a.x, ~a.y, ~a.z, ~a.w));
        }
        __syncwarp();
        named_arrive(6, 640);
        if (warp >= 8) { mbar_wait(MB(MB_WU), 0); ldwf(); }
    }
    auto outt = [&]() {
        if (warp < 16) {
            uint32_t o[10];
            if ((warp == cl || (warp == 15 && cl == 0)) && lane < 16) st_rlx4(&S->acc1[256 * rk + 16 * warp + lane], make_uint4(0, 0, 0, 0));
#pragma unroll
            for (int i = 0; i < 10; i++) o[i] = add2(x1[i], mul2(M.c2[4 * (i >> 1) + t].z, h2[i]));
            stsm_x4(ta + (OFF_OUT - OFF_H2T), o[0], o[1], o[2], o[3]); stsm_x4(ta + (OFF_OUT - OFF_H2T) + 32, o[4], o[5], o[6], o[7]); stsm_x2(ta + (OFF_OUT - OFF_H2T) + 64, o[8], o[9]);
        }
    };
    outt();
    uint4 gv = make_uint4(1, 1, 1, 1);
    const uint4* gp;
    uint32_t gdst;
    {
        const int gi = 32 * warp + lane, kk = (gi * 911) >> 16, seg = gi - 72 * kk;
        uint32_t ca = sb + OFF_MISC + (uint32_t)offsetof(Misc, cand2), sa = ca + 512 + 4 * (kk & 7);
        gp = &S->h2c[seg];
        gdst = sb + OFF_H2S + kk * (ROWP * 2) + seg * 16;
        asm volatile("" : "+r"(sa), "+r"(gdst), "+l"(gp));
        mbar_wait(MB(MB_KEY), 0);
        if (warp < 16) {
            const uint4 o = lds128(ca + 16 * lane), a = lds128(ca + 32 * warp), c = lds128(ca + 32 * warp + 16);
            const uint32_t mx = max(o.x, o.z), hd[4] = {a.x, a.z, c.x, c.z}, sc[4] = {a.y, a.w, c.y, c.w};
            uint32_t n[4];
#pragma unroll
            for (int q = 0; q < 4; q++) n[q] = __popc(__ballot_sync(0xffffffffu, mx > hd[q]));
            auto rank = [&](uint32_t k) {
                return (__popc(__ballot_sync(0xffffffffu, o.x > k)) + __popc(__ballot_sync(0xffffffffu, o.y > k))) + (__popc(__ballot_sync(0xffffffffu, o.z > k)) + __popc(__ballot_sync(0xffffffffu, o.w > k)));
            };
#pragma unroll
            for (int q = 0; q < 4; q++) {
                if (n[q] < 8) {
                    const uint32_t r0 = rank(hd[q]), r1 = rank(sc[q]);
                    if (r0 < 8) sts32(ca + 512 + 4 * r0, hd[q]);
                    if (r1 < 8) sts32(ca + 512 + 4 * r1, sc[q]);
                }
            }
        }
        named_bar(13, 640);
        if (warp < 18) {
            const uint32_t key = lds32(sa);
            gp += (((~key >> 2) & 0x3Eu) | ((~key >> 5) & 0x40u) | (key & 1u)) * 72;
            gv = ld_rlx4(gp);
        } else if (warp == 18) named_arrive(14, 64);
        else named_arrive(8, 64);
    }
    uint32_t wda = sb + OFF_WD + fmt * 5120 + lr * 128 + (((2 * fsl + (lm & 1)) ^ lr) << 4), wda2 = wda + (lm >> 1) * 1024;
    uint32_t ha = sb + OFF_H2S + lr * (ROWP * 2) + (144 * fsl) * 2 + lm * 16, fo = sb + OFF_FFR + ((fsl * 80 + 16 * fmt + g) * 8 + 2 * t) * 4;
    asm volatile("" : "+r"(ha), "+r"(fo));
    auto ldwd = [&]() {
#pragma unroll
        for (int i = 0; i < 2; i++)
#pragma unroll
            for (int ks = 0; ks < 3; ks++)
                if (i == 0 || warp < 16) ldsm_x4_t(wd[i][ks], ((ks < 2) ? wda2 : wda) + ks * 2048 + i * 5 * 5120);
    };
    mbar_wait(MB(MB_WD), 0);
    ldwd();
#pragma unroll 1
    for (int it = 0; it < SPIN_MAX && gv.x == 0u; it++) {
        gv = ld_rlx4(gp);
    }
    if (warp < 18) asm volatile("st.shared.v4.u32 [%0], {%1,%2,%3,%4};" ::"r"(gdst), "r"(~gv.x), "r"(~gv.y), "r"(~gv.z), "r"(~gv.w) : "memory");
    CBAR();
    float* ffr = (float*)(sm + OFF_FFR);
    auto ffn1 = [&]() {
        float acc[2][4] = {{0.f, 0.f, 0.f, 0.f}, {0.f, 0.f, 0.f, 0.f}};
#pragma unroll
        for (int k2 = 0; k2 < 5; k2++) {
            uint32_t hb[4];
            if (k2 < 4) ldsm_x4(hb, ha + k2 * 64); else ldsm_x2(hb, ha + 256);
            mma_bf16(acc[0], wf[2 * k2][0], wf[2 * k2][1], wf[2 * k2][2], wf[2 * k2][3], hb[0], hb[1]);
            if (k2 < 4) mma_bf16(acc[1], wf[2 * k2 + 1][0], wf[2 * k2 + 1][1], wf[2 * k2 + 1][2], wf[2 * k2 + 1][3], hb[2], hb[3]);
        }
        asm volatile("st.shared.v2.f32 [%0], {%1,%2};" ::"r"(fo), "f"(acc[0][0] + acc[1][0]), "f"(acc[0][1] + acc[1][1]) : "memory");
        asm volatile("st.shared.v2.f32 [%0+256], {%1,%2};" ::"r"(fo), "f"(acc[0][2] + acc[1][2]), "f"(acc[0][3] + acc[1][3]) : "memory");
    };
    ffn1();
    bf16(*act)[56] = (bf16(*)[56])(sm + OFF_ACT);
    auto gate = [&]() {
        if (warp < 12) {
            const int f = 4 * warp + lm, a = lr;
            float v = 0.f;
            if (warp < 10) {
                const float* pg = ffr + 32 * warp + (warp < 8 ? 0 : 256) + lane;
                const float* pu = pg + (warp < 8 ? 256 : 64);
                float gg = bfr((pg[0] + pg[640]) + (pg[1280] + pg[1920]));
                gg = bfr(silu(gg));
                const float uu = bfr((pu[0] + pu[640]) + (pu[1280] + pu[1920]));
                v = gg * uu;
            }
            act[a][f] = __ushort_as_bfloat16((unsigned short)f2bits(v));
        }
    };
    CBAR();
    gate();
    CBAR();
    auto ffn2 = [&](uint32_t buf, int mb) {
        uint32_t bq[3][2];
#pragma unroll
        for (int ks = 0; ks < 3; ks++) {
            bq[ks][0] = *(const uint32_t*)&act[g][16 * ks + 2 * t];
            bq[ks][1] = *(const uint32_t*)&act[g][16 * ks + 2 * t + 8];
        }
#pragma unroll
        for (int i = 0; i < 2; i++) {
            if (i == 0 || warp < 16) {
                float acc[4] = {0.f, 0.f, 0.f, 0.f};
#pragma unroll
                for (int ks = 0; ks < 3; ks++) mma_bf16(acc, wd[i][ks][0], wd[i][ks][1], wd[i][ks][2], wd[i][ks][3], bq[ks][0], bq[ks][1]);
                const int d = i ? 4 + (warp >> 2) : (warp * 13) >> 6, slot = i ? (warp & 3) : warp - 5 * d;
                const uint32_t rb = mapa(sb, d);
                sta2(rb + buf + (rk * 5 + slot) * 640 + lm * 160 + lr * 8, movm(pack2(acc[0], acc[1])), movm(pack2(acc[2], acc[3])), rb + (MB(mb) - sb));
            }
        }
    };
    ffn2(OFF_RS, MB_RS);
    named_bar(12, 672);
    const uint32_t redo = M.fin[8];
    if (redo) {
        const int gi = fresh_tid(), kk = (gi * 911) >> 16, seg = gi - 72 * kk;
        if (warp < 8) {
            const uint32_t key = M.fin[warp];
            if (MINE(key) && lane < (cl < 14 ? 5 : 2)) {
                const uint4 a = lds128(sb + OFF_H2T + ROW(key) * 80 + 16 * lane);
                st_rlx4(&S->h2c[(128 + warp) * 72 + 5 * cl + lane], make_uint4(~a.x, ~a.y, ~a.z, ~a.w));
            }
            __syncwarp();
        }
        if (warp < 18) {
            uint4 gv = make_uint4(0, 0, 0, 0);
#pragma unroll 1
            for (int it = 0; it < SPIN_MAX && gv.x == 0u; it++) gv = ld_rlx4(&S->h2c[128 * 72 + gi]);
            *(uint4*)(sm + OFF_H2S + kk * (ROWP * 2) + seg * 16) = make_uint4(~gv.x, ~gv.y, ~gv.z, ~gv.w);
        }
        CBAR();
        ffn1();
        CBAR();
        gate();
        CBAR();
        ffn2(OFF_RS + 80, MB_RS2);
        mbar_wait(MB(MB_RS2), 0);
    }
    {
        const int lane = fresh_tid() & 31;
        const int fP = min(warp < 8 ? 20 * cl + lane : 8 * (rk < 4 ? 5 * rk : 4 * rk + 4) + 4 * (warp - 8) + (lane & 3), D_ / 2);
        const uint32_t fgb = ld_rlx(&S->gb[fP]);
        const int ftok = warp < 8 ? warp : lane >> 2;
        const uint32_t fkey = M.fin[ftok];
        const bool fon = warp < 8 ? (MINE(fkey) && lane < 20 && fP < D_ / 2) : warp < (rk < 4 ? 18 : 16)
            ;
        const float rs = __fdividef(1.0f, 1.0f + __expf(-hi2f(fkey ^ (((int)~fkey >> 31) | 0x80000000u))));
        const uint32_t hv = lds32(sb + OFF_H2S + ftok * (ROWP * 2) + 4 * fP);
        float s0 = 0.f, s1 = 0.f, s2 = 1.0f, s3 = 0.f;
        if (warp >= 8) {
            if (fon) {
                mbar_wait(MB(MB_RS), 0);
                const uint32_t p = sb + OFF_RS + redo * 80 + ((warp - 8) >> 1) * 640 + (lane >> 3) * 160 + (lane & 7) * 8 + 4 * (warp & 1);
                uint32_t v[8];
#pragma unroll
                for (int i = 0; i < 8; i++) v[i] = lds32(p + i * 3200);
                s0 = ((lo2f(v[0]) + lo2f(v[1])) + (lo2f(v[2]) + lo2f(v[3]))) + ((lo2f(v[4]) + lo2f(v[5])) + (lo2f(v[6]) + lo2f(v[7])));
                s1 = ((hi2f(v[0]) + hi2f(v[1])) + (hi2f(v[2]) + hi2f(v[3]))) + ((hi2f(v[4]) + hi2f(v[5])) + (hi2f(v[6]) + hi2f(v[7])));
            }
        } else if (fon) {
            const uint32_t row = ROW(fkey);
            const unsigned short* vp = (const unsigned short*)(sm + OFF_V + 2 * lane * VP) + row;
            const uint32_t xv = add2(lds32(sb + OFF_X + XI(row >> 5) + ((row >> 3) & 3) * XG + (row & 7) * 80 + 4 * lane), (uint32_t)vp[0] | ((uint32_t)vp[VP / 2] << 16));
            s2 = (float)(((xv & 0xFFFFu) << 5) | 1u); s3 = (float)(xv >> 16);
            mbar_wait(MB(MB_OUT), 0);
        }
        if (fon) {
            const float4 o = atom4(&S->acc3[(fP >> 2) * 32 + 4 * ftok + (fP & 3)], s0, s1, s2, s3);
            const uint32_t z = __float_as_uint((o.z + s2) + 8388608.f), zh = __float_as_uint((o.w + s3) + 8388608.f);
            if (z & 16u) {
                const uint32_t xv = __byte_perm(z >> 5, zh, 0x5410);
                *(uint32_t*)(out + ((~fkey >> 3) & 2047u) * D_ + 2 * fP) = add2(xv, mul2(fgb, add2(hv, mul2(pack2(o.x + s0, o.y + s1), pack2(rs, rs)))));
            }
        }
    }
    }
    }
}

typedef CUresult (*EncodeFn)(CUtensorMap*, CUtensorMapDataType, cuuint32_t, void*, const cuuint64_t*, const cuuint64_t*,
                             const cuuint32_t*, const cuuint32_t*, CUtensorMapInterleave, CUtensorMapSwizzle,
                             CUtensorMapL2promotion, CUtensorMapFloatOOBfill);

static void make_map(EncodeFn fn, CUtensorMap* m, const void* ptr, uint64_t cols, uint64_t rows, uint32_t bc, uint32_t br,
                     CUtensorMapSwizzle sw, int five) {
    cuuint64_t dims[5] = {cols, rows, 4, 4, 288};
    cuuint64_t strides[4] = {cols * 2 * (five ? 32 : 1), cols * 2 * 512, cols * 2 * 64, cols * 2};
    cuuint32_t box[5] = {bc, br, 4, 4, 8};
    cuuint32_t es[5] = {1, 1, 1, 1, 1};
    CUresult rc = fn(m, CU_TENSOR_MAP_DATA_TYPE_BFLOAT16, five ? 5 : 2, (void*)ptr, dims, strides, box, es, CU_TENSOR_MAP_INTERLEAVE_NONE,
                     sw, (CUtensorMapL2promotion)(five || sw ? 0 : br == 72 ? L2M : L2P), CU_TENSOR_MAP_FLOAT_OOB_FILL_NONE);
    (void)rc;
}

static void launch(void* const* d_in, const int* in_sizes, int n_in, void* d_out, int out_size) {
    static EncodeFn enc = nullptr;
    static CUtensorMap tmm, tmg, tmu, tmd, tmo;
    static Scratch* sp = nullptr;
    static const void* cached[6] = {nullptr, nullptr, nullptr, nullptr, nullptr, nullptr};
    if (!enc) {
        cudaDriverEntryPointQueryResult qr;
        void* fn = nullptr;
        cudaGetDriverEntryPoint("cuTensorMapEncodeTiled", &fn, cudaEnableDefault, &qr);
        enc = (EncodeFn)fn;
        cudaFuncSetAttribute(clus_kernel, cudaFuncAttributeMaxDynamicSharedMemorySize, SMEM_TOTAL);
        cudaGetSymbolAddress((void**)&sp, g_s);
    }
    if (cached[0] != d_in[13] || cached[1] != d_in[9] || cached[2] != d_in[10] || cached[3] != d_in[11] || cached[4] != d_in[0] || cached[5] != d_out) {
        make_map(enc, &tmo, d_out, D_, 2, 40, 2, CU_TENSOR_MAP_SWIZZLE_NONE, 1);
        make_map(enc, &tmm, d_in[13], 6 * D_, D_, 40, 72, CU_TENSOR_MAP_SWIZZLE_NONE, 0);
        make_map(enc, &tmg, d_in[9], F_, D_, 40, 192, CU_TENSOR_MAP_SWIZZLE_NONE, 0);
        make_map(enc, &tmu, d_in[10], F_, D_, 40, 192, CU_TENSOR_MAP_SWIZZLE_NONE, 0);
        make_map(enc, &tmd, d_in[11], D_, F_, 64, 40, CU_TENSOR_MAP_SWIZZLE_128B, 0);
        cached[0] = d_in[13]; cached[1] = d_in[9]; cached[2] = d_in[10]; cached[3] = d_in[11]; cached[4] = d_in[0]; cached[5] = d_out;
    }
    clus_kernel<<<G_, NTHR, SMEM_TOTAL>>>((const bf16*)d_in[0], (const bf16*)d_in[1], (const bf16*)d_in[2], (const bf16*)d_in[3], (const bf16*)d_in[4],
                                          (const bf16*)d_in[5], (const bf16*)d_in[12], sp, (const bf16*)d_in[6], (const bf16*)d_in[8], (const bf16*)d_in[13],
                                          (bf16*)d_out, tmm, tmg, tmu, tmd, tmo);
}


static bool fits() {
    cudaFuncSetAttribute(clus_kernel, cudaFuncAttributeMaxDynamicSharedMemorySize, SMEM_TOTAL);
    cudaLaunchConfig_t cfg = {};
    cudaLaunchAttribute at;
    at.id = cudaLaunchAttributeClusterDimension;
    at.val.clusterDim.x = 8; at.val.clusterDim.y = 1; at.val.clusterDim.z = 1;
    cfg.gridDim = dim3(G_); cfg.blockDim = dim3(NTHR); cfg.dynamicSmemBytes = SMEM_TOTAL; cfg.attrs = &at; cfg.numAttrs = 1;
    int n = 0;
    const bool ok = cudaOccupancyMaxActiveClusters(&n, clus_kernel, &cfg) == cudaSuccess && n >= NCL;
    cudaGetLastError();
    return ok;
}
}
#undef L_
#undef D_
#undef N_
#undef F_
#undef G_
#undef NCL
#undef NTHR
#undef SPIN_MAX
#undef OFF_WG
#undef OFF_WU
#undef KSCR
#undef OFF_WM0
#undef OFF_STG
#undef OFF_MG2
#undef OFF_CH
#undef CHS
#undef UP
#undef UB
#undef XO_TF
#undef XO_U8
#undef XO_U16
#undef XO_ZA
#undef XO_ZB
#undef XO_ZC
#undef XO_ZD
#undef XO_TD
#undef XO_K1024
#undef XO_DSK
#undef XO_KINV
#undef XO_KLAST
#undef XO_MBU
#undef OFF_X
#undef XG
#undef XI
#undef XN
#undef OFF_V
#undef VP
#undef OFF_EK
#undef OFF_WM2
#undef OFF_MG1
#undef OFF_SC
#undef OFF_C1
#undef OFF_MISC
#undef OFF_WD
#undef OFF_H2T
#undef OFF_OUT
#undef ROWP
#undef OFF_H2S
#undef OFF_FFR
#undef OFF_ACT
#undef OFF_RS
#undef SMEM_TOTAL
#undef CBAR
#undef PROXY_FENCE
#undef D4
#undef O4
#undef WG_FENCE
#undef WG_COMMIT
#undef WG_WAIT
#undef TQ
#undef MB
#undef UF
#undef DS
#undef Q4
#undef RD_
#undef M2W
#undef WS
#undef WW
#undef WMS
#undef PQT
#undef PQD
#undef L2P
#undef L2M
#undef PDE
#undef WMD
#undef PFG
#undef CWP
#undef CWD
#undef ROW
#undef RKT
#undef MINE
#undef CE
#undef POP
#undef CGT
#undef CL_ARRIVE
#undef CL_WAIT
#undef CJ
#undef CJP

namespace v4 {

#define L_ 2048
#define D_ 576
#define N_ 128
#define F_ 4608
#define G_ 128
#define NTHR 640
#define SPIN_MAX (1 << 18)
#define SENT 0u
#define HINT_N 182u

typedef __nv_bfloat16 bf16;

struct Scratch {
    uint4 xn[G_ * G_ * 10];
    uint4 v[G_ * D_ * 2];
    uint2 part[G_ * G_ * 9];
    uint4 h2w[L_ * 96];
    unsigned int rec[G_ * 8];
    unsigned int modw[6 * D_];
    unsigned int ticket[64];
    unsigned int cnt[64];
    unsigned int hint[64];
};
__device__ __align__(1024) Scratch g_s;

#define OFF_WG 0
#define OFF_WU 46080
#define OFF_CH 92160
#define CHS 20784
#define ULBO 656
#define XO_U8 6272
#define XO_U16 10368
#define XO_ZA 5248
#define XO_ZB 8448
#define XO_ZC 11648
#define XO_ZD 13824
#define XO_TD 16000
#define XO_TF 18624
#define XO_K1024 20672
#define KSCR 3456
#define OFF_TILE 196096
#define ROWP 584
#define OFF_MISC 214784
#define OFF_WD OFF_CH
#define OFF_H2T (OFF_CH + 3 * CHS)
#define OFF_H2S (OFF_H2T + 18688)
#define OFF_FFR (OFF_H2S + 9344)
#define OFF_FIN OFF_FFR
#define OFF_ACT (OFF_FFR + 10240)

struct Misc {
    __align__(16) uint4 sent[256];
    __align__(16) uint4 box[11 * 14];
    union {
        struct {
            __align__(16) float2 part[18][16];
            float rp[18][16];
        };
        struct {
            __align__(16) unsigned short st1[3][16];
            __align__(16) float p1[16][4], p2[16][4];
        };
    };
    __align__(16) bf16 cb1[D_], sb[D_], gb[D_];
    __align__(16) bf16 sc[D_];
    __align__(16) unsigned int cand[64], skey[16];
    __align__(16) float kinv[5][4], klast[5][4];
    unsigned int pk[4][8];
    __align__(16) uint4 st2[16];
    unsigned int wr[D_ / 2];
    float modx[32];
    unsigned int rank[16];
    volatile unsigned int flag;
    unsigned int e1cnt;
    unsigned long long mbar[5];
    unsigned int epoch;
};
#define SMEM_TOTAL (OFF_MISC + (int)sizeof(Misc))
static_assert(SMEM_TOTAL <= 232448, "smem");

__device__ __forceinline__ float lo2f(uint32_t w) { return __uint_as_float(w << 16); }
__device__ __forceinline__ float hi2f(uint32_t w) { return __uint_as_float(w & 0xFFFF0000u); }
__device__ __forceinline__ uint32_t pack2(float lo, float hi) { uint32_t r; asm("cvt.rn.bf16x2.f32 %0, %1, %2;" : "=r"(r) : "f"(hi), "f"(lo)); return r; }
__device__ __forceinline__ float bfr(float x) { return __uint_as_float(pack2(0.f, x)); }
__device__ __forceinline__ uint32_t f2bits(float x) { return pack2(x, 0.f); }
__device__ __forceinline__ uint32_t packh(float lo, float hi) { uint32_t r; asm("cvt.rn.f16x2.f32 %0, %1, %2;" : "=r"(r) : "f"(hi), "f"(lo)); return r; }
__device__ __forceinline__ float frcp(float x) { float r; asm("rcp.approx.ftz.f32 %0, %1;" : "=f"(r) : "f"(x)); return r; }
__device__ __forceinline__ float fsqrt(float x) { float r; asm("sqrt.approx.f32 %0, %1;" : "=f"(r) : "f"(x)); return r; }
__device__ __forceinline__ float fex2(float x) { float r; asm("ex2.approx.ftz.f32 %0, %1;" : "=f"(r) : "f"(x)); return r; }
__device__ __forceinline__ float silu(float x) { return __fdividef(x, 1.0f + __expf(-x)); }
__device__ __forceinline__ uint32_t add2(uint32_t a, uint32_t b) { uint32_t r; asm("add.rn.bf16x2 %0, %1, %2;" : "=r"(r) : "r"(a), "r"(b)); return r; }
__device__ __forceinline__ uint32_t sub2(uint32_t a, uint32_t b) { uint32_t r; asm("sub.rn.bf16x2 %0, %1, %2;" : "=r"(r) : "r"(a), "r"(b)); return r; }
__device__ __forceinline__ uint32_t mul2(uint32_t a, uint32_t b) { uint32_t r; asm("mul.rn.bf16x2 %0, %1, %2;" : "=r"(r) : "r"(a), "r"(b)); return r; }
__device__ __forceinline__ uint32_t fma2(uint32_t a, uint32_t b, uint32_t c) { uint32_t r; asm("fma.rn.bf16x2 %0, %1, %2, %3;" : "=r"(r) : "r"(a), "r"(b), "r"(c)); return r; }
__device__ __forceinline__ uint32_t norm2(uint32_t x, uint32_t m, uint32_t rh, uint32_t rl) { const uint32_t d = sub2(x, m); return fma2(d, rh, mul2(d, rl)); }

__device__ __forceinline__ void mma_bf16(float* c, uint32_t a0, uint32_t a1, uint32_t a2, uint32_t a3, uint32_t b0, uint32_t b1) {
    asm volatile("mma.sync.aligned.m16n8k16.row.col.f32.bf16.bf16.f32 {%0,%1,%2,%3}, {%4,%5,%6,%7}, {%8,%9}, {%0,%1,%2,%3};\n"
                 : "+f"(c[0]), "+f"(c[1]), "+f"(c[2]), "+f"(c[3]) : "r"(a0), "r"(a1), "r"(a2), "r"(a3), "r"(b0), "r"(b1));
}
__device__ __forceinline__ void mma_f16(float* c, const uint32_t* a, uint32_t b0, uint32_t b1) {
    asm volatile("mma.sync.aligned.m16n8k16.row.col.f32.f16.f16.f32 {%0,%1,%2,%3}, {%4,%5,%6,%7}, {%8,%9}, {%0,%1,%2,%3};\n"
                 : "+f"(c[0]), "+f"(c[1]), "+f"(c[2]), "+f"(c[3]) : "r"(a[0]), "r"(a[1]), "r"(a[2]), "r"(a[3]), "r"(b0), "r"(b1));
}
__device__ __forceinline__ void ldsm_x4(uint32_t* r, uint32_t addr) {
    asm volatile("ldmatrix.sync.aligned.m8n8.x4.shared.b16 {%0,%1,%2,%3}, [%4];" : "=r"(r[0]), "=r"(r[1]), "=r"(r[2]), "=r"(r[3]) : "r"(addr) : "memory");
}
__device__ __forceinline__ void ldsm_x4_t(uint32_t* r, uint32_t addr) {
    asm volatile("ldmatrix.sync.aligned.m8n8.x4.trans.shared.b16 {%0,%1,%2,%3}, [%4];" : "=r"(r[0]), "=r"(r[1]), "=r"(r[2]), "=r"(r[3]) : "r"(addr) : "memory");
}
__device__ __forceinline__ void stsm_x4(uint32_t addr, uint32_t r0, uint32_t r1, uint32_t r2, uint32_t r3) {
    asm volatile("stmatrix.sync.aligned.m8n8.x4.shared.b16 [%0], {%1,%2,%3,%4};" ::"r"(addr), "r"(r0), "r"(r1), "r"(r2), "r"(r3) : "memory");
}
__device__ __forceinline__ void stsm_x4_t(uint32_t addr, uint32_t r0, uint32_t r1, uint32_t r2, uint32_t r3) {
    asm volatile("stmatrix.sync.aligned.m8n8.x4.trans.shared.b16 [%0], {%1,%2,%3,%4};" ::"r"(addr), "r"(r0), "r"(r1), "r"(r2), "r"(r3) : "memory");
}
__device__ __forceinline__ uint32_t movm(uint32_t a) { uint32_t r; asm volatile("movmatrix.sync.aligned.m8n8.trans.b16 %0, %1;" : "=r"(r) : "r"(a)); return r; }
__device__ __forceinline__ uint32_t lds32(uint32_t a) { uint32_t v; asm volatile("ld.shared.u32 %0, [%1];" : "=r"(v) : "r"(a)); return v; }
__device__ __forceinline__ void sts32(uint32_t a, uint32_t v) { asm volatile("st.shared.u32 [%0], %1;" ::"r"(a), "r"(v) : "memory"); }
__device__ __forceinline__ void sts16(uint32_t a, uint32_t v) { asm volatile("st.shared.u16 [%0], %1;" ::"r"(a), "h"((unsigned short)v) : "memory"); }
__device__ __forceinline__ void named_bar(int id, int n) { asm volatile("bar.sync %0, %1;" ::"r"(id), "r"(n) : "memory"); }
__device__ __forceinline__ void named_arrive(int id, int n) { asm volatile("bar.arrive %0, %1;" ::"r"(id), "r"(n) : "memory"); }
#define CBAR() asm volatile("bar.sync 0, 640;" ::: "memory")
#define PROXY_FENCE() asm volatile("fence.proxy.async.shared::cta;" ::: "memory")

#define D4(d, o) "+f"(d[o]), "+f"(d[o + 1]), "+f"(d[o + 2]), "+f"(d[o + 3])
__device__ __forceinline__ void wg32(float* d, uint32_t a0, uint32_t a1, uint32_t a2, uint32_t a3, uint64_t desc) {
    asm volatile("wgmma.mma_async.sync.aligned.m64n32k16.f32.bf16.bf16 {%0,%1,%2,%3,%4,%5,%6,%7,%8,%9,%10,%11,%12,%13,%14,%15}, {%16,%17,%18,%19}, %20, 1, 1, 1, 0;"
                 : D4(d, 0), D4(d, 4), D4(d, 8), D4(d, 12) : "r"(a0), "r"(a1), "r"(a2), "r"(a3), "l"(desc));
}
__device__ __forceinline__ void wg48(float* d, uint32_t a0, uint32_t a1, uint32_t a2, uint32_t a3, uint64_t desc) {
    asm volatile("wgmma.mma_async.sync.aligned.m64n48k16.f32.bf16.bf16 {%0,%1,%2,%3,%4,%5,%6,%7,%8,%9,%10,%11,%12,%13,%14,%15,%16,%17,%18,%19,%20,%21,%22,%23}, {%24,%25,%26,%27}, %28, 1, 1, 1, 0;"
                 : D4(d, 0), D4(d, 4), D4(d, 8), D4(d, 12), D4(d, 16), D4(d, 20) : "r"(a0), "r"(a1), "r"(a2), "r"(a3), "l"(desc));
}
#define O4(d, o) "=f"(d[o]), "=f"(d[o + 1]), "=f"(d[o + 2]), "=f"(d[o + 3])
__device__ __forceinline__ void wg32z(float* d, uint32_t a0, uint32_t a1, uint32_t a2, uint32_t a3, uint64_t desc) {
    asm volatile("wgmma.mma_async.sync.aligned.m64n32k16.f32.bf16.bf16 {%0,%1,%2,%3,%4,%5,%6,%7,%8,%9,%10,%11,%12,%13,%14,%15}, {%16,%17,%18,%19}, %20, 0, 1, 1, 0;"
                 : O4(d, 0), O4(d, 4), O4(d, 8), O4(d, 12) : "r"(a0), "r"(a1), "r"(a2), "r"(a3), "l"(desc));
}
__device__ __forceinline__ void wg48z(float* d, uint32_t a0, uint32_t a1, uint32_t a2, uint32_t a3, uint64_t desc) {
    asm volatile("wgmma.mma_async.sync.aligned.m64n48k16.f32.bf16.bf16 {%0,%1,%2,%3,%4,%5,%6,%7,%8,%9,%10,%11,%12,%13,%14,%15,%16,%17,%18,%19,%20,%21,%22,%23}, {%24,%25,%26,%27}, %28, 0, 1, 1, 0;"
                 : O4(d, 0), O4(d, 4), O4(d, 8), O4(d, 12), O4(d, 16), O4(d, 20) : "r"(a0), "r"(a1), "r"(a2), "r"(a3), "l"(desc));
}
#define WG_FENCE() asm volatile("wgmma.fence.sync.aligned;" ::: "memory")
#define WG_COMMIT() asm volatile("wgmma.commit_group.sync.aligned;" ::: "memory")
#define WG_WAIT(n) asm volatile("wgmma.wait_group.sync.aligned " #n ";" ::: "memory")
#define TQ(p, k) p[2 * (k) + 1], p[2 * (k) + 2], p[2 * (k)], p[2 * (k) + 1]

__device__ __forceinline__ uint4 ld_nc4(const void* p) { uint4 v; asm volatile("ld.global.nc.v4.u32 {%0,%1,%2,%3}, [%4];" : "=r"(v.x), "=r"(v.y), "=r"(v.z), "=r"(v.w) : "l"(p)); return v; }
__device__ __forceinline__ unsigned short ld_nc16(const void* p) { unsigned short v; asm volatile("ld.global.nc.u16 %0, [%1];" : "=h"(v) : "l"(p)); return v; }
__device__ __forceinline__ uint32_t ld_nc(const void* p) { uint32_t v; asm volatile("ld.global.nc.u32 %0, [%1];" : "=r"(v) : "l"(p)); return v; }
__device__ __forceinline__ uint32_t ld_rlx(const unsigned int* p) { uint32_t v; asm volatile("ld.relaxed.gpu.global.u32 %0, [%1];" : "=r"(v) : "l"(p) : "memory"); return v; }
__device__ __forceinline__ uint2 ld_rlx2(const void* p) { uint2 v; asm volatile("ld.relaxed.gpu.global.v2.u32 {%0,%1}, [%2];" : "=r"(v.x), "=r"(v.y) : "l"(p) : "memory"); return v; }
__device__ __forceinline__ uint4 ld_rlx4(const void* p) { uint4 v; asm volatile("ld.relaxed.gpu.global.v4.u32 {%0,%1,%2,%3}, [%4];" : "=r"(v.x), "=r"(v.y), "=r"(v.z), "=r"(v.w) : "l"(p) : "memory"); return v; }
__device__ __forceinline__ void st_rlx(unsigned int* p, uint32_t v) { asm volatile("st.relaxed.gpu.global.u32 [%0], %1;" ::"l"(p), "r"(v) : "memory"); }
__device__ __forceinline__ void st_rlx2(void* p, uint32_t a, uint32_t b) { asm volatile("st.relaxed.gpu.global.v2.u32 [%0], {%1,%2};" ::"l"(p), "r"(a), "r"(b) : "memory"); }
__device__ __forceinline__ void st_rlx4(void* p, uint4 v) { asm volatile("st.relaxed.gpu.global.v4.u32 [%0], {%1,%2,%3,%4};" ::"l"(p), "r"(v.x), "r"(v.y), "r"(v.z), "r"(v.w) : "memory"); }
__device__ __forceinline__ void red_inc(unsigned int* p) { asm volatile("red.relaxed.gpu.global.add.u32 [%0], 1;" ::"l"(p) : "memory"); }

__device__ __forceinline__ void mbar_init(uint32_t a, int cnt) { asm volatile("mbarrier.init.shared::cta.b64 [%0], %1;" ::"r"(a), "r"(cnt) : "memory"); }
__device__ __forceinline__ void mbar_expect(uint32_t a, uint32_t bytes) { asm volatile("mbarrier.arrive.expect_tx.shared::cta.b64 _, [%0], %1;" ::"r"(a), "r"(bytes) : "memory"); }
__device__ __forceinline__ void mbar_wait(uint32_t a, uint32_t parity) {
    uint32_t ok = 0;
    int it = 0;
    do {
        asm volatile("{\n.reg .pred p;\nmbarrier.try_wait.parity.shared::cta.b64 p, [%1], %2;\nselp.u32 %0, 1, 0, p;\n}" : "=r"(ok) : "r"(a), "r"(parity) : "memory");
    } while (!ok && ++it < SPIN_MAX);
}
__device__ __forceinline__ void tma2d(uint32_t dst, const CUtensorMap* tm, int c0, int c1, uint32_t mbar) {
    asm volatile("cp.async.bulk.tensor.2d.shared::cluster.global.mbarrier::complete_tx::bytes [%0], [%1, {%3, %4}], [%2];"
                 ::"r"(dst), "l"(tm), "r"(mbar), "r"(c0), "r"(c1) : "memory");
}
__device__ __forceinline__ void bulk_s2g(void* dst, uint32_t src, uint32_t bytes) {
    asm volatile("cp.async.bulk.global.shared::cta.bulk_group [%0], [%1], %2;" ::"l"(dst), "r"(src), "r"(bytes) : "memory");
}
__device__ __forceinline__ uint32_t ld_acq(const unsigned int* p) { uint32_t v; asm volatile("ld.acquire.gpu.global.u32 %0, [%1];" : "=r"(v) : "l"(p) : "memory"); return v; }
__device__ __forceinline__ void bulk_pf(const void* src, uint32_t bytes) { asm volatile("cp.async.bulk.prefetch.L2.global [%0], %1;" ::"l"(src), "r"(bytes) : "memory"); }

__device__ __forceinline__ uint32_t wait_epoch(Misc& M) {
    uint32_t e = 0;
#pragma unroll 1
    for (int it = 0; it < (SPIN_MAX << 4) && e == 0; it++) e = *(volatile unsigned int*)&M.epoch;
    return e;
}
__device__ __forceinline__ void wait_reset(const unsigned int* ctr, uint32_t epoch) {
#pragma unroll 1
    for (int it = 0; it < SPIN_MAX; it++)
        if ((int)(ld_acq(ctr) - G_ * epoch) >= 0) break;
}
struct cplx { float x, y; };
__device__ __forceinline__ cplx cmul(cplx a, cplx b) { cplx r; r.x = a.x * b.x - a.y * b.y; r.y = a.x * b.y + a.y * b.x; return r; }
__device__ __forceinline__ cplx csq(cplx a) { cplx r; r.x = a.x * a.x - a.y * a.y; r.y = 2.0f * a.x * a.y; return r; }
__device__ __forceinline__ uint32_t hcm(uint32_t x, uint32_t y, uint32_t yp) {
    const __half2 X = *(const __half2*)&x, Y = *(const __half2*)&y, YP = *(const __half2*)&yp;
    const __half2 r = __hfma2(__high2half2(X), YP, __hmul2(__low2half2(X), Y));
    return *(const uint32_t*)&r;
}
__device__ __forceinline__ void ln_stats(float s1, float s2, float& meanb, float& rinv) {
    const float mean = s1 * (1.0f / D_);
    const float den = bfr(fsqrt(bfr(bfr(fmaxf(fmaf(-mean, mean, s2 * (1.0f / D_)), 0.f)) + 1e-5f)));
    meanb = bfr(mean);
    rinv = frcp(den);
}

__device__ __forceinline__ int fresh_tid() { int v; asm volatile("mov.u32 %0, %tid.x;" : "=r"(v)); return v; }
__device__ __forceinline__ void conv_channel(unsigned char* sm, Scratch* S, uint32_t gidx, uint32_t epoch, const void* pf_src,
                                             const CUtensorMap* tmu, int f0) {
    Misc& M = *(Misc*)(sm + OFF_MISC);
    const uint32_t sb = (uint32_t)__cvta_generic_to_shared(sm);
    const int tid = fresh_tid(), lane = tid & 31, g = lane >> 2, t = lane & 3, lr = lane & 7, lm = lane >> 3;
    const int warp_ = __shfl_sync(0xffffffffu, tid >> 5, 0), wgi = warp_ >> 2, w = warp_ & 3;
    const uint32_t cb = sb + OFF_CH + wgi * CHS, tag16 = (epoch % 65535u) + 1u;
    float D[16];
    uint32_t gaw, rcnt = 0;
    {
        {
            const uint32_t a8 = cb + lr * ULBO + (lm + 9) * 16 + w * 64, b8 = cb + XO_U8 + lm * 128 + lr * 16 + w * 512;
            const uint32_t a16 = cb + (((2 * lr) & 7) + (lm & 1)) * ULBO + (9 + (lr >> 2) + (lm & 2)) * 16 + w * 64;
            const uint32_t b16 = cb + XO_U16 + (lm & 1) * 512 + lr * 16 + (lm >> 1) * 128 + (w >> 1) * 1024 + (w & 1) * 256;
            uint32_t r[3][4];
            ldsm_x4_t(r[0], a8);
            ldsm_x4_t(r[1], a16);
            if (w < 2) ldsm_x4_t(r[2], a8 + 256);
            stsm_x4(b8, r[0][0], r[0][1], r[0][2], r[0][3]);
            stsm_x4(b16, r[1][0], r[1][1], r[1][2], r[1][3]);
            if (w < 2) stsm_x4(b8 + 2048, r[2][0], r[2][1], r[2][2], r[2][3]);
        }
        PROXY_FENCE();
        named_bar(1 + wgi, 128);
        {
            float Z8[24], Z16[16];
            const uint32_t pf = cb + XO_TF + (w >> 1) * 512 + (8 + 16 * (w & 1) + g - 2 * t) * 4;
            uint32_t p[13], q[9], z16[8];
#pragma unroll
            for (int s = 0; s < 9; s++) q[s] = lds32(pf + 1024 + s * 32);
            const uint32_t d8 = ((((cb + XO_U8) & 0x3FFFF) >> 4) | ((128 >> 4) << 16));
#define DZ(o) (((uint64_t)(512 >> 4) << 32) | (uint64_t)(d8 + (o)))
            WG_FENCE();
#pragma unroll
            for (int e = 0; e < 4; e++) {
                if (e == 0) wg32z(Z16, TQ(q, e), DZ(256 + 16));
                else wg32(Z16, TQ(q, e), DZ(256 - (e >> 1) * 64 + (1 - (e & 1)) * 16));
            }
            WG_COMMIT();
#pragma unroll
            for (int s = 0; s < 13; s++) p[s] = lds32(pf + s * 32);
            WG_WAIT(0);
#pragma unroll
            for (int i = 0; i < 8; i++) z16[i] = pack2(Z16[2 * i], Z16[2 * i + 1]);
            WG_FENCE();
#pragma unroll
            for (int e = 0; e < 6; e++) {
                if (e == 0) wg48z(Z8, TQ(p, e), DZ(16));
                else wg48(Z8, TQ(p, e), DZ(-(e >> 1) * 32 + (1 - (e & 1)) * 16));
            }
            WG_COMMIT();
            WG_WAIT(0);
            named_bar(1 + wgi, 128);
            const uint32_t za = cb + ((w >> 1) ? XO_ZB : XO_ZA) + lr * 400 + (1 + 2 * (w & 1) + (lm & 1) + 4 * (lm >> 1)) * 16;
#pragma unroll
            for (int i = 0; i < 3; i++)
                stsm_x4(za + i * 128, pack2(Z8[8 * i], Z8[8 * i + 1]), pack2(Z8[8 * i + 2], Z8[8 * i + 3]), pack2(Z8[8 * i + 4], Z8[8 * i + 5]), pack2(Z8[8 * i + 6], Z8[8 * i + 7]));
            const int Cz = 2 * (16 * (w & 1) + 8 * (lm & 1) + lr) + (lm >> 1);
            const uint32_t zc = cb + ((w >> 1) ? XO_ZD : XO_ZC) + (Cz & 7) * 272 + (1 + (Cz >> 3)) * 16;
#pragma unroll
            for (int ob = 0; ob < 2; ob++) stsm_x4(zc + ob * 128, z16[4 * ob], z16[4 * ob + 1], z16[4 * ob + 2], z16[4 * ob + 3]);
            if (lane < 8) *(uint4*)(sm + (cb - sb) + ((w < 2) ? (XO_ZA + w * 3200 + lane * 400) : (XO_ZC + (w - 2) * 2176 + lane * 272))) = make_uint4(0, 0, 0, 0);
        }
        gaw = ld_rlx(&S->modw[gidx]);
        if (tmu && wgi >= 2 && (tid & 127) == 96) {
            const uint32_t mbu = sb + OFF_MISC + (uint32_t)offsetof(Misc, mbar) + 24;
            if (wgi == 2) mbar_expect(mbu, 36864);
            tma2d(sb + OFF_WU + (wgi - 2) * 12288, tmu, f0, 192 * (wgi - 2), mbu);
        }
        __syncwarp();
        if ((tid & 127) == 64) rcnt = ld_rlx(S->cnt);
        {
#pragma unroll
            for (int i = 0; i < 16; i++) D[i] = 0.f;
            uint32_t pa = cb + XO_TD + (8 + 16 * w + g - 2 * t) * 4;
            uint32_t dlo = (((cb + 9 * 16) & 0x3FFFF) >> 4) | ((ULBO >> 4) << 16);
#define DS(o) (((uint64_t)(128 >> 4) << 32) | (uint64_t)(dlo + (o)))
#define KST (2 * (ULBO / 16))
            uint32_t pA[9], pB[9];
#pragma unroll
            for (int s = 0; s < 9; s++) pA[s] = lds32(pa + s * 32);
#pragma unroll 1
            for (int j = 0; j < 4; j++) {
                WG_FENCE();
#pragma unroll
                for (int q = 0; q < 4; q++) wg32(D, TQ(pA, q), DS((3 - q) * KST));
                WG_COMMIT();
                WG_WAIT(1);
#pragma unroll
                for (int s = 0; s < 9; s++) pB[s] = lds32(pa + 256 + s * 32);
                WG_FENCE();
#pragma unroll
                for (int q = 0; q < 4; q++) wg32(D, TQ(pB, q), DS((3 - q) * KST - 1));
                WG_COMMIT();
                WG_WAIT(1);
#pragma unroll
                for (int s = 0; s < 9; s++) pA[s] = lds32(pa + 512 + s * 32);
                dlo -= 2; pa += 512;
            }
            pB[1] = lds32(pa + 256 + 32); pB[2] = lds32(pa + 256 + 64);
            WG_FENCE();
#pragma unroll
            for (int q = 0; q < 4; q++) wg32(D, TQ(pA, q), DS((3 - q) * KST));
            wg32(D, pB[1], pB[2], pA[8], pB[1], DS(3 * KST - 1));
            WG_COMMIT();
        }
        if (tid == 128) bulk_pf(pf_src, 16 * D_ * 2);
        if ((tid & 127) == 64) {
#pragma unroll 1
            for (int it = 0; it < SPIN_MAX && (int)(rcnt - G_ * epoch) < 0; it++) rcnt = ld_rlx(S->cnt);
        }
    }
    {
        named_bar(1 + wgi, 128);
        {
            const uint4* pq = M.box + (6 + g - 2 * t);
#define QM(q) (q).x, (q).y, (q).z, (q).w
            uint32_t bA[2][6], bB[2][6], bC[3][4], bD[2][4], bU[2][4];
            const uint32_t k2 = lds32(cb + XO_K1024);
            uint32_t ofs[3];
#pragma unroll
            for (int d = 0; d < 3; d++) ofs[d] = cb + ((w - d) < 0 ? 0 : 16) + (lr + 8 * (lm >> 1)) * 16;
#define COL(d) (2 * ((w - (d)) & 3) + (lm & 1))
            WG_WAIT(0);
            uint4 m[4];
#pragma unroll
            for (int d = 0; d < 2; d++) {
                const uint32_t a = XO_ZA + COL(d) * 400 + ofs[d];
                ldsm_x4(bA[d], a); ldsm_x4(bB[d], a + 3200);
                uint32_t r[4];
                ldsm_x4(r, a + 256 + (lm >> 1) * (3200 - 128));
                bA[d][4] = r[0]; bA[d][5] = r[1]; bB[d][4] = r[2]; bB[d][5] = r[3];
            }
#pragma unroll
            for (int i = 0; i < 4; i++) m[i] = pq[14 * i];
#pragma unroll
            for (int d = 0; d < 2; d++)
#pragma unroll
                for (int c = 0; c < 3; c++) mma_bf16(D + 4 + 4 * c, QM(m[d]), bA[d][2 * c], bA[d][2 * c + 1]);
#pragma unroll
            for (int d = 0; d < 3; d++) ldsm_x4(bC[d], XO_ZC + COL(d) * 272 + ofs[d]);
#pragma unroll
            for (int d = 0; d < 2; d++)
#pragma unroll
                for (int c = 0; c < 3; c++) mma_bf16(D + 4 + 4 * c, QM(m[2 + d]), bB[d][2 * c], bB[d][2 * c + 1]);
#pragma unroll
            for (int i = 0; i < 3; i++) m[i] = pq[14 * (4 + i)];
#pragma unroll
            for (int d = 0; d < 2; d++) { ldsm_x4(bD[d], XO_ZD + COL(d) * 272 + ofs[d]); ldsm_x4(bU[d], COL(d) * ULBO + 128 + ofs[d]); }
#pragma unroll
            for (int d = 0; d < 3; d++)
#pragma unroll
                for (int c = 0; c < 2; c++) mma_bf16(D + 8 + 4 * c, QM(m[d]), bC[d][2 * c], bC[d][2 * c + 1]);
#pragma unroll
            for (int i = 0; i < 4; i++) m[i] = pq[14 * (7 + i)];
#pragma unroll
            for (int d = 0; d < 2; d++)
#pragma unroll
                for (int c = 0; c < 2; c++) mma_bf16(D + 8 + 4 * c, QM(m[d]), bD[d][2 * c], bD[d][2 * c + 1]);
#pragma unroll
            for (int d = 0; d < 2; d++) {
                m[2 + d].x &= k2; m[2 + d].y &= k2; m[2 + d].z &= k2; m[2 + d].w &= k2;
#pragma unroll
                for (int c = 0; c < 2; c++) mma_bf16(D + 8 + 4 * c, QM(m[2 + d]), bU[d][2 * c], bU[d][2 * c + 1]);
            }
        }
        {
#pragma unroll 1
            for (int it = 0; it < SPIN_MAX && (gaw >> 16) != tag16; it++) gaw = ld_rlx(&S->modw[gidx]);
            const uint32_t ga2 = __byte_perm(gaw, 0, 0x1010), dk2 = M.pk[3][wgi];
            const uint32_t ua = cb + (2 * w + (lm & 1)) * ULBO + (9 + lr + 8 * (lm >> 1)) * 16;
            const uint32_t ya = cb + XO_TD + w * 1024;
            const uint32_t sa = ya + (lr + 8 * (lm >> 1)) * 32 + (((lm & 1) ^ ((lane >> 2) & 1)) << 4);
#pragma unroll
            for (int cc = 0; cc < 2; cc++) {
                uint32_t u[4], v[4];
                ldsm_x4_t(u, ua + cc * 256);
#pragma unroll
                for (int m = 0; m < 4; m++) {
                    const int c = 2 * cc + (m >> 1), h = m & 1;
                    v[m] = ~mul2(ga2, add2(pack2(D[4 * c + 2 * h], D[4 * c + 2 * h + 1]), mul2(u[m], dk2)));
                }
                stsm_x4_t(sa + cc * 512, v[0], v[1], v[2], v[3]);
            }
            __syncwarp();
            const int sw = (lane >> 3) & 1;
            const uint32_t vo = (uint32_t)(((4 * (lane >> 1) + w) * D_ + gidx - 2 * D_) * 32 + (lane & 1) * 16);
            const unsigned char* yp = sm + (ya - sb) + (lane >> 1) * 32 + (lane & 1) * 8;
#pragma unroll
            for (int i = 0; i < 2; i++) {
                const uint2 A = *(const uint2*)(yp + i * 512 + (sw << 4)), B = *(const uint2*)(yp + i * 512 + ((sw ^ 1) << 4));
                st_rlx4((char*)S->v + vo + i * (64 * D_ * 32), make_uint4(A.x, B.x, A.y, B.y));
            }
        }
    }
}

__global__ void __launch_bounds__(NTHR, 1)
mega_kernel(const bf16* __restrict__ x, const bf16* __restrict__ logAr, const bf16* __restrict__ Aim,
            const bf16* __restrict__ Cr, const bf16* __restrict__ Ci, const bf16* __restrict__ logdt, const bf16* __restrict__ c_in,
            Scratch* __restrict__ S, const bf16* __restrict__ Dskip, const bf16* __restrict__ w_r, const bf16* __restrict__ w_down,
            bf16* __restrict__ out,
            const __grid_constant__ CUtensorMap tm_wm, const __grid_constant__ CUtensorMap tm_wg, const __grid_constant__ CUtensorMap tm_wu,
            const __grid_constant__ CUtensorMap tm_wd, const __grid_constant__ CUtensorMap tm_wd32,
            const __grid_constant__ CUtensorMap tm_wg32, const __grid_constant__ CUtensorMap tm_wu32) {
    extern __shared__ __align__(1024) unsigned char sm[];
    Misc& M = *(Misc*)(sm + OFF_MISC);
    const uint32_t sb = (uint32_t)__cvta_generic_to_shared(sm);
    const int tid = threadIdx.x, warp = __shfl_sync(0xffffffffu, tid >> 5, 0), lane = tid & 31;
    const int g = lane >> 2, t = lane & 3, lr = lane & 7, lm = lane >> 3;
    const int wgi = warp >> 2, w = warp & 3;
    const int b = blockIdx.x;
    const int nch = 5 - (b & 1), cs = 9 * (b >> 1) + 5 * (b & 1);
    const int f0 = 72 * (b >> 1) + 32 * (b & 1), nf = 32 + 8 * (b & 1);
    const bool has_ch = wgi < nch;
    const uint32_t mb0 = sb + OFF_MISC + offsetof(Misc, mbar), mb_wm = mb0, mb_wg = mb0 + 16, mb_wu = mb0 + 24, mb_wd = mb0 + 32;
    const uint32_t cb = sb + OFF_CH + wgi * CHS;

    if (wgi == 3) {
        M.sent[tid - 384] = make_uint4(SENT, SENT, SENT, SENT);
        M.sent[tid - 256] = make_uint4(SENT, SENT, SENT, SENT);
        if (tid == 384) {
            M.epoch = 0u; M.flag = 0u; M.e1cnt = 0u;
#pragma unroll
            for (int i = 0; i < 5; i++) mbar_init(mb0 + 8 * i, 1);
        }
        PROXY_FENCE();
        __syncwarp();
        if (warp == 12) { named_arrive(8, 160); if (b & 1) named_arrive(14, 64); }
        if (warp != 15) named_arrive(9, 128);
    }
    unsigned short r_ldt = 0, r_lar = 0, r_aim = 0, r_cr = 0, r_ci = 0;
    if (has_ch) {
        const int d = cs + wgi, n = d * N_ + (tid & 127);
        r_ldt = ld_nc16((const unsigned short*)logdt + d);
        r_lar = ld_nc16((const unsigned short*)logAr + n);
        r_aim = ld_nc16((const unsigned short*)Aim + n);
        r_cr = ld_nc16((const unsigned short*)Cr + n);
        r_ci = ld_nc16((const unsigned short*)Ci + n);
    } else {
        const unsigned short* cp = (const unsigned short*)c_in + (tid - 512);
        r_ldt = ld_nc16(cp); r_lar = ld_nc16(cp + 128); r_aim = ld_nc16(cp + 256); r_cr = ld_nc16(cp + 384);
        if (tid < 576) r_ci = ld_nc16(cp + 512);
    }
    uint4 xr[9];
    if (wgi == 4) {
        const uint4* p = (const uint4*)(x + (size_t)16 * b * D_) + (tid - 512);
#pragma unroll
        for (int i = 0; i < 9; i++) xr[i] = ld_nc4(p + 128 * i);
    }
    uint32_t wrv = 0;
    if (tid >= 128 && tid < 416) wrv = ld_nc((const uint32_t*)w_r + (tid - 128));
    if (warp == 2 && lane < nch) M.pk[3][lane] = (uint32_t)ld_nc16((const unsigned short*)Dskip + cs + lane) * 0x10001u;
    if (tid == 384) {
        const unsigned int tk = atomicAdd(S->ticket, 1u);
        *(volatile unsigned int*)&M.epoch = (tk >> 7) + 1u;
    }
    if (has_ch) {
        for (int i = tid & 127; i < 296; i += 128) *(uint4*)(sm + OFF_CH + wgi * CHS + XO_TD + i * 16) = make_uint4(0, 0, 0, 0);
    }
    if (tid < 154) {
        const int idx = (tid * 4682) >> 16, dl = tid - 14 * idx - 6;
        const int a = (0x44332221100ull >> (4 * idx)) & 7, d = (0x10102101010ull >> (4 * idx)) & 3;
        const int lo = (0x35c36 >> (4 * a)) & 15, wd = (0x16824 >> (4 * a)) & 15;
        const uint32_t one = (a == 4) ? 0xFFFFu : 0x3F80u;
        auto mk = [&](int l) { return (((unsigned)(l - lo) <= (unsigned)wd) ? one : 0u) | (((unsigned)(l - 1 - lo) <= (unsigned)wd) ? (one << 16) : 0u); };
        const int l0 = 16 * d + dl;
        M.box[tid] = make_uint4(mk(l0), mk(l0 + 8), mk(l0 - 8), mk(l0));
    }
    uint32_t xo[6];
#pragma unroll
    for (int i = 0; i < 6; i++) {
        const int ch = 16 * (warp + 16 * (i >> 1)) + 8 * (i & 1) + g;
        const int pr = (ch * 7282) >> 16, rm = ch - 9 * pr, hi = rm >= 5;
        xo[i] = (uint32_t)((((2 * pr + hi) * G_ + b) * 5 + rm - 5 * hi) * 32 + t * 8);
    }
    auto e1_store = [&]() {
        named_bar(11, 640);
        uint32_t mm[2], rhh[2], rll[2];
#pragma unroll
        for (int h = 0; h < 2; h++) {
            mm[h] = ((const uint32_t*)M.st1[0])[t + 4 * h]; rhh[h] = ((const uint32_t*)M.st1[1])[t + 4 * h]; rll[h] = ((const uint32_t*)M.st1[2])[t + 4 * h];
        }
        const uint32_t ta = sb + OFF_TILE + (lr + 8 * (lm & 1)) * (ROWP * 2) + (lm >> 1) * 16 + warp * 32;
#pragma unroll
        for (int i = 0; i < 3; i++) {
            if (i < 2 || warp < 4) {
                uint32_t r[4];
                ldsm_x4_t(r, ta + i * 512);
#pragma unroll
                for (int h = 0; h < 2; h++)
                    st_rlx2((char*)S->xn + xo[2 * i + h], ~norm2(r[2 * h], mm[0], rhh[0], rll[0]), ~norm2(r[2 * h + 1], mm[1], rhh[1], rll[1]));
            }
        }
        __syncwarp();
        if (lane == 0 && atomicAdd(&M.e1cnt, 1u) == 15u) red_inc(S->hint);
    };
    const float p_ldt = lo2f(r_ldt), p_lar = lo2f(r_lar), p_aim = lo2f(r_aim), p_cr = lo2f(r_cr), p_ci = lo2f(r_ci);
    cplx z1 = {0.f, 0.f}, z16 = z1, z256 = z1, C = z1;
    const uint32_t scr = cb + w * KSCR, ws = scr + lane * 4;
    float acc[5][4];
    uint32_t afr[4][4], cz[4];
    cplx z2 = {0.f, 0.f};
    const uint32_t ba = scr + lr * 144 + lm * 16;
    auto tile = [&](float* c, int rg) {
        __syncwarp();
        c[0] = c[1] = c[2] = c[3] = 0.f;
        uint32_t bb[2][4];
        ldsm_x4(bb[0], ba + rg * 1152);
        ldsm_x4(bb[1], ba + rg * 1152 + 64);
        mma_f16(c, afr[0], bb[0][0], bb[0][1]);
        mma_f16(c, afr[1], bb[0][2], bb[0][3]);
        mma_f16(c, afr[2], bb[1][0], bb[1][1]);
        mma_f16(c, afr[3], bb[1][2], bb[1][3]);
    };
#define CJ(z) packh((z).x, -(z).y)
#define CJP(z) packh((z).y, (z).x)
    uint32_t ex = 0;
    if (has_ch) {
        const float dt = bfr(expf(p_ldt));
        const float al = -bfr(expf(p_lar)) * dt * 1.4426950408889634f;
        const float th = p_aim * dt;
        const float th_ = th * 0.15915494309189535f;
        const float tl_ = fmaf(th, 0.15915494309189535f, -th_) + th * 6.4206382e-9f;
        auto anchor = [&](float s) {
            float f = th_ * s;
            f -= rintf(f);
            f = fmaf(tl_, s, f) * 6.283185307179586f;
            const float e = fex2(al * s);
            return cplx{e * __cosf(f), e * __sinf(f)};
        };
        const float cx = p_cr * dt * 2.0f, cy = p_ci * dt * 2.0f;
        ex = __reduce_max_sync(0xffffffffu, __float_as_uint(fmaxf(fabsf(cx), fabsf(cy)))) >> 23;
        const float scl = __uint_as_float((254u - ex) << 23);
        C = cplx{cx * scl, cy * scl};
        z1 = anchor(1.f); z16 = anchor(16.f); z256 = anchor(256.f);
            {
                const cplx z32 = csq(z16), z48 = cmul(z32, z16), z64 = csq(z32), z128 = csq(z64), z192 = cmul(z128, z64);
                const uint32_t y[3] = {packh(z16.x, z16.y), packh(z32.x, z32.y), packh(z48.x, z48.y)};
                const uint32_t yp[3] = {packh(-z16.y, z16.x), packh(-z32.y, z32.x), packh(-z48.y, z48.x)};
                const uint32_t xx[3] = {packh(z64.x, z64.y), packh(z128.x, z128.y), packh(z192.x, z192.y)};
                sts32(ws, 0x00003C00u);
#pragma unroll
                for (int j = 0; j < 3; j++) sts32(ws + (1 + j) * 144, y[j]);
#pragma unroll
                for (int i = 0; i < 3; i++) {
                    sts32(ws + (4 + 4 * i) * 144, xx[i]);
#pragma unroll
                    for (int j = 0; j < 3; j++) sts32(ws + (5 + 4 * i + j) * 144, hcm(xx[i], y[j], yp[j]));
                }
            }
    }
    if (wgi == 4) {
        if (!has_ch) {
            const int i = tid - 512;
            ((unsigned short*)M.sc)[i] = (unsigned short)f2bits(silu(lo2f(r_ldt)));
            ((unsigned short*)M.sc)[i + 128] = (unsigned short)f2bits(silu(lo2f(r_lar)));
            ((unsigned short*)M.sc)[i + 256] = (unsigned short)f2bits(silu(lo2f(r_aim)));
            ((unsigned short*)M.sc)[i + 384] = (unsigned short)f2bits(silu(lo2f(r_cr)));
            if (i < 64) ((unsigned short*)M.sc)[i + 512] = (unsigned short)f2bits(silu(lo2f(r_ci)));
            if (warp == 16) {
                named_bar(14, 64);
                if (lane == 0) {
                    mbar_expect(mb_wm, 36864);
#pragma unroll
                    for (int k = 0; k < 3; k++) tma2d(sb + OFF_WU + k * 12288, &tm_wm, 32 * (b >> 1), 192 * k, mb_wm);
                }
                __syncwarp();
            }
        }
#pragma unroll
        for (int i = 0; i < 9; i++) {
            const int c = tid - 512 + 128 * i, rr = (c * 911) >> 16;
            *(uint4*)(sm + OFF_TILE + rr * (ROWP * 2 - 1152) + c * 16) = xr[i];
        }
        named_bar(8, 160);
        {
            float c1[4] = {0.f, 0.f, 0.f, 0.f}, cl[4] = {0.f, 0.f, 0.f, 0.f}, chh[4] = {0.f, 0.f, 0.f, 0.f};
            const uint32_t a0 = sb + OFF_TILE + (lane & 15) * (ROWP * 2) + (lane >> 4) * 16 + w * 288;
            uint32_t a[9][4];
#pragma unroll
            for (int ks = 0; ks < 9; ks++) ldsm_x4(a[ks], a0 + ks * 32);
#pragma unroll
            for (int ks = 0; ks < 9; ks++) {
                mma_bf16(c1, a[ks][0], a[ks][1], a[ks][2], a[ks][3], 0x3F803F80u, 0x3F803F80u);
                mma_bf16(cl, a[ks][0], a[ks][1], a[ks][2], a[ks][3], a[ks][0], a[ks][2]);
                mma_bf16(chh, a[ks][0], a[ks][1], a[ks][2], a[ks][3], a[ks][1], a[ks][3]);
            }
            if (t == 0) { M.p1[g][w] = c1[0]; M.p1[g + 8][w] = c1[2]; }
            if (t == (g >> 1)) { M.p2[g][w] = (g & 1) ? cl[1] : cl[0]; M.p2[g + 8][w] = (g & 1) ? chh[3] : chh[2]; }
        }
        named_bar(5, 128);
        if (warp == 16) {
            const float4 q1 = *(const float4*)M.p1[lane & 15], q2 = *(const float4*)M.p2[lane & 15];
            float meanb, rinv;
            ln_stats((q1.x + q1.y) + (q1.z + q1.w), (q2.x + q2.y) + (q2.z + q2.w), meanb, rinv);
            const float rh = bfr(rinv);
            if (lane < 16) { M.st1[0][lane] = (unsigned short)f2bits(meanb); M.st1[1][lane] = (unsigned short)f2bits(rh); M.st1[2][lane] = (unsigned short)f2bits(rinv - rh); }
        }
        __syncwarp();
        named_arrive(11, 640);
    }
    auto publish_reset = [&]() {
        if (tid == 480) {
            asm volatile("cp.async.bulk.wait_group 0;" ::: "memory");
            asm volatile("fence.proxy.async;" ::: "memory");
            red_inc(S->cnt);
        }
    };
    uint32_t epoch = 0, tag16 = 0, pre = 0;
    auto mod_tile = [&](int rd) {
        const uint32_t* s2 = (const uint32_t*)M.sc + 144 * (w >> 1) + t;
        uint32_t bb[18][2];
#pragma unroll
        for (int ks = 0; ks < 18; ks++) { bb[ks][0] = (g == 0) ? s2[8 * ks] : 0u; bb[ks][1] = (g == 0) ? s2[8 * ks + 4] : 0u; }
        float acc[2][4] = {{0.f, 0.f, 0.f, 0.f}, {0.f, 0.f, 0.f, 0.f}};
        const int row = lr + 8 * (lm >> 1);
        const uint32_t wa = sb + OFF_WU + (288 * (w >> 1) + row) * 64 + ((((2 * (w & 1) + (lm & 1)) ^ (row >> 1)) & 3) << 4);
        mbar_wait(mb_wm + 8 * rd, 0);
        if (rd == 0)
#pragma unroll
        for (int kb = 0; kb < 2; kb++) {
            uint32_t a[9][4];
#pragma unroll
            for (int ks = 0; ks < 9; ks++) ldsm_x4_t(a[ks], wa + (9 * kb + ks) * 1024);
#pragma unroll
            for (int ks = 0; ks < 9; ks++) mma_bf16(acc[ks & 1], a[ks][0], a[ks][1], a[ks][2], a[ks][3], bb[9 * kb + ks][0], bb[9 * kb + ks][1]);
        }
        const float v0 = acc[0][0] + acc[1][0], v1 = acc[0][2] + acc[1][2];
        float* mx = M.modx + 16 * (w & 1) + g;
        if (w >= 2 && t == 0) { mx[0] = v0; mx[8] = v1; }
        named_bar(5, 128);
        if (w < 2 && t == 0) {
            unsigned int* mp = &S->modw[32 * ((b >> 1) + 64 * rd) + 16 * w + g];
            st_rlx(mp, f2bits(v0 + mx[0]) | (tag16 << 16));
            st_rlx(mp + 8, f2bits(v1 + mx[8]) | (tag16 << 16));
        }
        if (rd == 0 && w < 2 && b < 108) {
            named_bar(7, 64);
            if (tid == 512) red_inc(S->hint);
        }
    };
    if (has_ch) {
        {
            z2 = csq(z1);
            const cplx z3 = cmul(z2, z1), z4 = csq(z2), z8 = csq(z4);
            const cplx c4 = cmul(C, z4), c8 = cmul(C, z8), c12 = cmul(c8, z4);
            cz[0] = packh(C.x, -C.y); cz[1] = packh(c4.x, -c4.y); cz[2] = packh(c8.x, -c8.y); cz[3] = packh(c12.x, -c12.y);
            __syncwarp();
#pragma unroll
            for (int s = 0; s < 4; s++) ldsm_x4(afr[s], scr + (lr + 8 * (lm & 1)) * 144 + (2 * s + (lm >> 1)) * 16);
            {
                const uint32_t y[3] = {CJ(z1), CJ(z2), CJ(z3)}, yp[3] = {CJP(z1), CJP(z2), CJP(z3)};
#pragma unroll
                for (int tt = 0; tt < 2; tt++) {
                    const int rg = tt ? 0 : 2;
#pragma unroll
                    for (int i = 0; i < 2; i++) {
                        sts32(ws + rg * 1152 + (4 * i) * 144, cz[2 * tt + i]);
#pragma unroll
                        for (int j = 0; j < 3; j++) sts32(ws + rg * 1152 + (4 * i + 1 + j) * 144, hcm(cz[2 * tt + i], y[j], yp[j]));
                    }
                    tile(acc[tt], rg);
                }
            }
            if (tid >= 128 && tid < 416) M.wr[tid - 128] = wrv;
            if (wgi < 4) e1_store();
    if (warp == 15) {
        named_bar(9, 128);
        if (lane == 0) {
#pragma unroll 1
            for (int i = 0; i < 5; i++) {
                bulk_s2g((char*)&S->v[(size_t)b * 1152] + i * 4096, sb + OFF_MISC, i < 4 ? 4096 : 2048);
                if (i < 3) bulk_s2g((char*)&S->part[(size_t)b * 1152] + i * 4096, sb + OFF_MISC, i < 2 ? 4096 : 1024);
            }
            bulk_s2g(&S->rec[8 * b], sb + OFF_MISC, 32);
            asm volatile("cp.async.bulk.commit_group;" ::: "memory");
        }
        __syncwarp();
    }
            const cplx z258 = cmul(z256, z2), z512 = csq(z256), z768 = cmul(z512, z256);
            {
                const uint32_t a0 = CJ(z256), a0p = CJP(z256), a1 = CJ(z258), a1p = CJP(z258);
#pragma unroll
                for (int i = 0; i < 4; i++) { sts32(ws + 1152 + (2 * i) * 144, hcm(cz[i], a0, a0p)); sts32(ws + 1152 + (2 * i + 1) * 144, hcm(cz[i], a1, a1p)); }
                tile(acc[2], 1);
            }
            {
                const uint32_t a0 = CJ(z512), a0p = CJP(z512), a1 = CJ(z768), a1p = CJP(z768);
#pragma unroll
                for (int i = 0; i < 4; i++) { sts32(ws + 2304 + i * 144, hcm(cz[i], a0, a0p)); sts32(ws + 2304 + (4 + i) * 144, hcm(cz[i], a1, a1p)); }
                tile(acc[3], 2);
            }
            if (warp == 3) {
                if (lane == 15) pre = ld_rlx(S->hint);
            }
            const cplx z1024 = csq(z512);
            {
                const cplx zk[4] = {z1024, cmul(z1024, z256), csq(z768), cmul(z1024, z768)};
#pragma unroll
                for (int h = 0; h < 4; h++) {
                    const uint32_t a0 = CJ(zk[h]), a0p = CJP(zk[h]);
                    sts32(ws + (2 * h) * 144, hcm(cz[0], a0, a0p));
                    sts32(ws + (2 * h + 1) * 144, hcm(cz[2], a0, a0p));
                }
                tile(acc[4], 0);
            }
            const cplx z2048 = csq(z1024);
            float last = C.x * z2048.x - C.y * z2048.y;
#pragma unroll
            for (int o = 16; o; o >>= 1) last += __shfl_xor_sync(0xffffffffu, last, o);
            __syncwarp();
#pragma unroll
            for (int i = 0; i < 5; i++) *(float4*)(sm + (scr - sb) + i * 512 + lane * 16) = make_float4(acc[i][0], acc[i][1], acc[i][2], acc[i][3]);
            if (lane == 0) { const float inv = __uint_as_float(ex << 23); M.kinv[wgi][w] = inv; M.klast[wgi][w] = last * inv; }
        }
        if (tid == 111 && (int)(pre - HINT_N * wait_epoch(M)) >= 0) M.flag = 1u;
        named_bar(1 + wgi, 128);
        const uint32_t td = cb + XO_TD + 64 * 4, tf = cb + XO_TF - 32 * 4;
        if (tid == 111 && !M.flag) pre = ld_rlx(S->hint);
        const float4 ki = *(const float4*)M.kinv[wgi];
        auto fsum = [&](int off, uint32_t& r0, uint32_t& r1) {
            const unsigned char* p = sm + (cb - sb) + off;
            const float4 a = *(const float4*)p, b2 = *(const float4*)(p + KSCR), c = *(const float4*)(p + 2 * KSCR), d = *(const float4*)(p + 3 * KSCR);
            r0 = pack2(fmaf(a.y, ki.x, b2.y * ki.y) + fmaf(c.y, ki.z, d.y * ki.w), fmaf(a.x, ki.x, b2.x * ki.y) + fmaf(c.x, ki.z, d.x * ki.w));
            r1 = pack2(fmaf(a.w, ki.x, b2.w * ki.y) + fmaf(c.w, ki.z, d.w * ki.w), fmaf(a.z, ki.x, b2.z * ki.y) + fmaf(c.z, ki.z, d.z * ki.w));
        };
        uint32_t r[2], q[2];
        fsum(w * 512 + lane * 16, r[0], r[1]);
        fsum(2048 + w * 128 + lr * 16, q[0], q[1]);
        if (tid == 111) {
            if ((int)(pre - HINT_N * M.epoch) >= 0) M.flag = 1u;
            else pre = ld_rlx(S->hint);
        }
        __syncwarp();
        if (w < 2) {
            const uint32_t p = td + (16 * g + 8 * w + 2 * t) * 4;
#pragma unroll
            for (int h = 0; h < 2; h++) { sts16(p + h * 512, r[h] >> 16); sts32(p + h * 512 + 4, r[h]); sts16(p + h * 512 + 10, r[h]); }
        } else if (w == 2) {
            const uint32_t p = td + (256 + 16 * g + 4 * t) * 4;
#pragma unroll
            for (int h = 0; h < 2; h++) {
                const uint32_t k0 = r[h] >> 16;
                if (h || lane) { sts16(p + h * 512 - 4, k0); sts16(p + h * 512 + 2, k0); }
                sts16(p + h * 512, k0); sts32(p + h * 512 + 4, __byte_perm(r[h], 0, 0x3232)); sts32(p + h * 512 + 8, r[h]); sts16(p + h * 512 + 14, r[h]);
            }
        } else {
            const uint32_t p = tf + (64 + 32 * (t >> 1) + 2 * g + (t & 1)) * 4;
#pragma unroll
            for (int h = 0; h < 2; h++) {
                const uint32_t k0 = r[h] >> 16;
                sts16(p + h * 64 + 512, r[h]); sts16(p + h * 64 + 518, r[h]);
                if (h || lane) { sts16(p + h * 64 - 4, k0); sts16(p + h * 64 + 2, k0); }
            }
            if (lane == 0) {
                const uint32_t dd = __byte_perm(r[0], 0, 0x3232);
                sts16(td + 511 * 4, dd); sts32(td + 512 * 4, dd); sts32(td + 513 * 4, dd); sts32(td + 514 * 4, dd); sts16(td + 515 * 4 + 2, dd);
            }
        }
        if (lane < 8) {
            const uint32_t p = tf + 1024 + (64 + 16 * t + 2 * w + g) * 4;
#pragma unroll
            for (int h = 0; h < 2; h++) {
                const uint32_t k0 = q[h] >> 16;
                sts16(p + h * 32 + 512, q[h]); sts16(p + h * 32 + 518, q[h]);
                if (h || (tid & 127)) { sts16(p + h * 32 - 4, k0); sts16(p + h * 32 + 2, k0); }
            }
            if ((tid & 127) == 0) {
                const float4 kl4 = *(const float4*)M.klast[wgi];
                const uint32_t kl = f2bits((kl4.x + kl4.y) + (kl4.z + kl4.w)), dd = __byte_perm(q[0], 0, 0x3232);
                sts16(tf + 127 * 4, dd); sts16(tf + 128 * 4 + 2, dd); sts32(cb + XO_K1024, dd);
                sts16(tf + 1024 + 127 * 4, kl); sts16(tf + 1024 + 128 * 4 + 2, kl);
            }
        }
        __syncwarp();
    } else {
        const int i = tid - 512, idx = b >> 1;
        tag16 = (wait_epoch(M) % 65535u) + 1u;
        mod_tile(0);
        if (i == 0 && idx < 44) {
            PROXY_FENCE();
            mbar_expect(mb_wm + 8, 36864);
#pragma unroll
            for (int k = 0; k < 3; k++) tma2d(sb + OFF_WU + k * 12288, &tm_wm, 32 * (idx + 64), 192 * k, mb_wm + 8);
        }
        __syncwarp();
    }
    if (tid == 111) {
        epoch = wait_epoch(M);
#pragma unroll 1
        for (int it = 0; it < SPIN_MAX && (int)(pre - HINT_N * epoch) < 0; it++) pre = ld_rlx(S->hint);
        M.flag = 1u;
    }
    __syncwarp();
    const int ubp = (tid * 13108) >> 16, uloc = tid - 5 * ubp;
    const uint4* usrc = &S->xn[(size_t)b * 1280 + 2 * tid];
    uint4 ua = make_uint4(0, 0, 0, 0), uc = ua;
    uint32_t usa = 0, uca = 0;
    if (lane == 0) {
#pragma unroll 1
        for (int it = 0; it < (SPIN_MAX << 4) && !M.flag; it++) { }
    }
    __syncwarp();
    if (uloc < nch) {
 ua = ld_rlx4(usrc); uc = ld_rlx4(usrc + 1); usa = ld_rlx(&S->modw[cs + uloc]); uca = ld_rlx(&S->modw[D_ + cs + uloc]); }
    CBAR();
    epoch = M.epoch;
    tag16 = (epoch % 65535u) + 1u;
    {
        const int bp = ubp, loc = uloc;
        if (loc < nch) {
            const uint4* src = usrc;
            uint4 a = ua, c = uc;
#pragma unroll 1
            for (int it = 0; it < SPIN_MAX && (a.x == SENT || a.z == SENT || c.x == SENT || c.z == SENT || (usa >> 16) != tag16 || (uca >> 16) != tag16); it++) {
                a = ld_rlx4(src); c = ld_rlx4(src + 1); usa = ld_rlx(&S->modw[cs + loc]); uca = ld_rlx(&S->modw[D_ + cs + loc]);
            }
            const uint32_t sa = __byte_perm(usa, 0, 0x1010), ca = pack2(1.0f + lo2f(uca), 1.0f + lo2f(uca));
            unsigned char* up = sm + OFF_CH + loc * CHS + ((2 * bp) & 7) * ULBO + ((bp >> 2) + 9) * 16;
            *(uint4*)up = make_uint4(add2(mul2(~a.x, ca), sa), add2(mul2(~a.z, ca), sa), add2(mul2(~c.x, ca), sa), add2(mul2(~c.z, ca), sa));
            *(uint4*)(up + ULBO) = make_uint4(add2(mul2(~a.y, ca), sa), add2(mul2(~a.w, ca), sa), add2(mul2(~c.y, ca), sa), add2(mul2(~c.w, ca), sa));
        }
        publish_reset();
        const int i = tid & 127;
        unsigned char* cp = sm + OFF_CH + wgi * CHS;
        *(uint4*)(cp + XO_U8 - 1024 + (i >> 6) * 4096 + (i & 63) * 16) = make_uint4(0, 0, 0, 0);
        if (i < 72) { const int c = (i * 57) >> 9; *(uint4*)(cp + c * ULBO + (i - 9 * c) * 16) = make_uint4(0, 0, 0, 0); }
    }
    PROXY_FENCE();
    CBAR();
    if (w == 2 && lane == 0) {
        bulk_s2g((char*)&S->xn[(size_t)b * 1280] + wgi * 4096, sb + OFF_MISC, 4096);
        asm volatile("cp.async.bulk.commit_group;" ::: "memory");
    }
        if (tid == 416) {
            mbar_expect(mb_wg, nf * D_ * 2);
            tma2d(sb + OFF_WG, (b & 1) ? &tm_wg : &tm_wg32, f0, 0, mb_wg);
        }
    if (tid == 96 || tid == 224) tma2d(sb + OFF_WG + (1 + (tid >> 7)) * (nf * 384), (b & 1) ? &tm_wg : &tm_wg32, f0, 192 * (1 + (tid >> 7)), mb_wg);
    if (has_ch) {
        __syncwarp();
        conv_channel(sm, S, 2 * D_ + cs + wgi, epoch, w_down + (size_t)f0 * D_, (b & 1) ? nullptr : &tm_wu32, f0);
    } else {
        const int idx = b >> 1;
        if (idx < 44) mod_tile(1);
        if (tid == 512) {
            PROXY_FENCE();
            mbar_expect(mb_wu, 46080);
#pragma unroll 1
            for (int i = 0; i < 3; i++) {
                tma2d(sb + OFF_WU + i * 15360, &tm_wu, f0, 192 * i, mb_wu);
                const long long c0 = clock64();
                int it = 0;
                while (clock64() - c0 < 1200 && ++it < 4096) { }
            }
            wait_reset(S->cnt, epoch);
        }
        named_bar(5, 128);
    }
    {
    const int tid = fresh_tid(), warp = __shfl_sync(0xffffffffu, tid >> 5, 0), lane = tid & 31;
    const int g = lane >> 2, t = lane & 3, lr = lane & 7, lm = lane >> 3;
    uint32_t v3 = 0, v4 = 0, v5 = 0;
    auto load_consts = [&]() {
        if (tid < D_) { v3 = ld_rlx(&S->modw[3 * D_ + tid]); v4 = ld_rlx(&S->modw[4 * D_ + tid]); v5 = ld_rlx(&S->modw[5 * D_ + tid]); }
    };
    if (tid == 0) bulk_pf(w_down + (size_t)(f0 + 16) * D_, (nf - 16) * D_ * 2);
    uint32_t x1[2][4], wr2[2][2];
    if (warp < 18) {
        const char* vp = (const char*)S->v + ((size_t)b * D_ + 32 * warp + g) * 32 + t * 8;
        uint2 v[4];
#pragma unroll
        for (int i = 0; i < 4; i++) v[i] = ld_rlx2(vp + i * 256);
#pragma unroll
        for (int j = 0; j < 2; j++) {
            const uint32_t* wp = M.wr + 16 * warp + 8 * j + t;
            wr2[j][0] = (g == 0) ? wp[0] : 0u;
            wr2[j][1] = (g == 0) ? wp[4] : 0u;
            ldsm_x4(x1[j], sb + OFF_TILE + (lr + 8 * (lm & 1)) * (ROWP * 2) + (lm >> 1) * 16 + warp * 64 + j * 32);
        }
#pragma unroll 1
        for (int it = 0; it < SPIN_MAX && ((v3 >> 16) != tag16 || (v4 >> 16) != tag16 || (v5 >> 16) != tag16); it++) load_consts();
        ((unsigned short*)M.sb)[tid] = (unsigned short)v3;
        ((unsigned short*)M.cb1)[tid] = (unsigned short)f2bits(1.0f + lo2f(v4));
        ((unsigned short*)M.gb)[tid] = (unsigned short)v5;
#pragma unroll 1
        for (int it = 0; it < SPIN_MAX; it++) {
            bool bad = false;
#pragma unroll
            for (int i = 0; i < 4; i++) if (v[i].x == SENT) { v[i] = ld_rlx2(vp + i * 256); bad = true; }
            if (!bad) break;
        }
        __syncwarp();
        float c1[4] = {0.f, 0.f, 0.f, 0.f}, cl[4] = {0.f, 0.f, 0.f, 0.f}, chh[4] = {0.f, 0.f, 0.f, 0.f};
#pragma unroll
        for (int j = 0; j < 2; j++) {
            x1[j][0] = add2(x1[j][0], movm(~v[2 * j].x)); x1[j][1] = add2(x1[j][1], movm(~v[2 * j].y));
            x1[j][2] = add2(x1[j][2], movm(~v[2 * j + 1].x)); x1[j][3] = add2(x1[j][3], movm(~v[2 * j + 1].y));
            mma_bf16(c1, x1[j][0], x1[j][1], x1[j][2], x1[j][3], 0x3F803F80u, 0x3F803F80u);
            mma_bf16(cl, x1[j][0], x1[j][1], x1[j][2], x1[j][3], x1[j][0], x1[j][2]);
            mma_bf16(chh, x1[j][0], x1[j][1], x1[j][2], x1[j][3], x1[j][1], x1[j][3]);
        }
        float* pp = (float*)&M.part[warp][g];
        if (t == 0) { pp[0] = c1[0]; pp[16] = c1[2]; }
        if (t == (g >> 1)) { pp[1] = (g & 1) ? cl[1] : cl[0]; pp[17] = (g & 1) ? chh[3] : chh[2]; }
    }
    CBAR();
    if (warp < 18) {
        const int tok = lane & 15, hf = lane >> 4;
        uint32_t kc[2][2][2];
#pragma unroll
        for (int j = 0; j < 2; j++)
#pragma unroll
            for (int q = 0; q < 2; q++) { kc[j][q][0] = ((const uint32_t*)M.cb1)[16 * warp + 8 * j + 4 * q + t]; kc[j][q][1] = ((const uint32_t*)M.sb)[16 * warp + 8 * j + 4 * q + t]; }
        named_bar(13, 608);
        uint32_t st[2][3];
#pragma unroll
        for (int h = 0; h < 2; h++) { const uint4 q = M.st2[g + 8 * h]; st[h][0] = q.x; st[h][1] = q.y; st[h][2] = q.z; }
        float rc[4] = {0.f, 0.f, 0.f, 0.f};
        uint32_t h2[2][4];
#pragma unroll
        for (int j = 0; j < 2; j++) {
#pragma unroll
            for (int r = 0; r < 4; r++) {
                h2[j][r] = add2(mul2(norm2(x1[j][r], st[r & 1][0], st[r & 1][1], st[r & 1][2]), kc[j][r >> 1][0]), kc[j][r >> 1][1]);
            }
            mma_bf16(rc, h2[j][0], h2[j][1], h2[j][2], h2[j][3], wr2[j][0], wr2[j][1]);
        }
        if (t == 0) { M.rp[warp][g] = rc[0]; M.rp[warp][g + 8] = rc[2]; }
        if (warp == 0) {
            named_bar(12, 576);
            float r = M.rp[9 * hf][tok];
#pragma unroll
            for (int i = 1; i < 9; i++) r += M.rp[9 * hf + i][tok];
            r += __shfl_xor_sync(0xffffffffu, r, 16);
            const uint32_t rbits = f2bits(r);
            const uint32_t key = 0x80000000u | ((rbits ^ ((rbits & 0x8000u) ? 0xFFFFu : 0x8000u)) << 11) | (uint32_t)(2047 - (16 * b + tok));
            int rank = 0;
#pragma unroll
            for (int j = 1; j < 16; j++) rank += __shfl_xor_sync(0xffffffffu, key, j) > key;
            if (lane < 16) { M.skey[rank] = key; M.rank[rank] = tok; }
            __syncwarp();
            if (lane < 2) st_rlx4(&S->rec[8 * b + 4 * lane], *(const uint4*)&M.skey[4 * lane]);
        } else named_arrive(12, 576);
#pragma unroll
        for (int j = 0; j < 2; j++) {
            uint32_t o[4];
#pragma unroll
            for (int r = 0; r < 4; r++) o[r] = add2(x1[j][r], mul2(((const uint32_t*)M.gb)[16 * warp + 8 * j + 4 * (r >> 1) + t], h2[j][r]));
            const uint32_t to = (lr + 8 * (lm & 1)) * (ROWP * 2) + (lm >> 1) * 16 + warp * 64 + j * 32;
            stsm_x4(sb + OFF_H2T + to, h2[j][0], h2[j][1], h2[j][2], h2[j][3]);
            stsm_x4(sb + OFF_TILE + to, o[0], o[1], o[2], o[3]);
        }
    } else if (warp == 19) {
        const int tok = lane & 15, hf = lane >> 4;
        float2 s = M.part[9 * hf][tok];
#pragma unroll
        for (int i = 1; i < 9; i++) { const float2 q = M.part[9 * hf + i][tok]; s.x += q.x; s.y += q.y; }
        s.x += __shfl_xor_sync(0xffffffffu, s.x, 16); s.y += __shfl_xor_sync(0xffffffffu, s.y, 16);
        float meanb, rinv;
        ln_stats(s.x, s.y, meanb, rinv);
        const float rh = bfr(rinv);
        if (lane < 16) M.st2[tok] = make_uint4(pack2(meanb, meanb), pack2(rh, rh), pack2(rinv - rh, rinv - rh), 0u);
        __syncwarp();
        named_arrive(13, 608);
    } else if (lane < 9) {
        PROXY_FENCE();
        if (lane == 0) mbar_expect(mb_wd, nf * D_ * 2);
        tma2d(sb + OFF_WD + lane * 5120, (b & 1) ? &tm_wd : &tm_wd32, 64 * lane, f0, mb_wd);
    }
    CBAR();
    uint32_t wf[9][4], wd[2][3][4];
    const int fmt = warp >> 2, fsl = warp & 3;
    auto load_wf = [&]() {
        mbar_wait(mb_wg, 0);
        mbar_wait(mb_wu, 0);
        if (fmt < 4 || nf > 32) {
            const int half = lm & 1;
            const uint32_t base = (fmt == 4) ? ((half ? OFF_WU : OFF_WG) + 64)
                                             : ((fmt >> 1) * OFF_WU + (((2 * (fmt & 1) + half) ^ ((b & 1) ? 0 : (lr >> 1))) << 4));
            const uint32_t wa = sb + base + (144 * fsl + lr + 8 * (lm >> 1)) * (2 * nf);
#pragma unroll
            for (int ks = 0; ks < 9; ks++) ldsm_x4_t(wf[ks], wa + ks * (32 * nf));
        }
    mbar_wait(mb_wd, 0);
    {
#pragma unroll
        for (int i = 0; i < 2; i++) {
            const int mt = warp + 20 * i;
            const uint32_t wa = sb + OFF_WD + (mt >> 2) * 5120 + lr * 128 + (((2 * (mt & 3) + (lm & 1)) ^ lr) << 4);
#pragma unroll
            for (int ks = 0; ks < 3; ks++)
                if ((i == 0 || warp < 16) && (ks < 2 || nf > 32)) ldsm_x4_t(wd[i][ks], wa + ks * 2048 + ((ks < 2) ? (lm >> 1) * 1024 : 0));
        }
    }
    };
    if (warp >= 8) {
        if (warp < 16) {
            const int tk = M.rank[warp - 8];
            const uint32_t* hp = (const uint32_t*)(sm + OFF_H2T + tk * (ROWP * 2)) + lane;
            uint4* dst = &S->h2w[(size_t)(16 * b + tk) * 96 + lane];
#pragma unroll
            for (int j = 0; j < 3; j++) st_rlx4(dst + 32 * j, make_uint4(hp[96 * j], hp[96 * j + 32], hp[96 * j + 64], epoch));
        }
        load_wf();
    } else {
        const uint4* rp = (const uint4*)S->rec + tid;
        load_wf();
        uint4 rk = ld_rlx4(rp);
#pragma unroll 1
        for (int it = 0; it < SPIN_MAX && !rk.x; it++) rk = ld_rlx4(rp);
        __syncwarp();
        uint32_t mine = 0;
#pragma unroll
        for (int rnd = 0; rnd < 8; rnd++) {
            const uint32_t m = __reduce_max_sync(0xffffffffu, rk.x);
            if (rk.x == m) { rk.x = rk.y; rk.y = rk.z; rk.z = rk.w; rk.w = 0u; }
            if (lane == rnd) mine = m;
        }
        if (lane < 8) M.cand[8 * warp + lane] = mine;
    }
    CBAR();
    uint32_t selv = 0;
    if (warp < 12) {
        uint2 k = *(const uint2*)&M.cand[2 * lane];
#pragma unroll
        for (int rnd = 0; rnd < 8; rnd++) {
            const uint32_t m = __reduce_max_sync(0xffffffffu, k.x);
            if (k.x == m) { k.x = k.y; k.y = 0u; }
            if (lr == rnd) selv = m;
        }
        if (tid < 8) M.skey[tid] = selv;
    }
    const uint32_t seltok = 2047u - (selv & 2047u);
    const int fo = tid >> 3;
    const int fW = 9 * b + (fo >> 2), fcomp = fo & 3;
    const int fd = 16 * (fW >> 5) + ((fW >> 2) & 7) + 8 * (fcomp >> 1), fk = 2 * (fW & 3) + (fcomp & 1);
    const uint32_t fsel = __shfl_sync(0xffffffffu, selv, fk);
    uint32_t fx = 0, fv = 0;
    bf16(*h2s)[ROWP] = (bf16(*)[ROWP])(sm + OFF_H2S);
    if (warp < 12) {
        uint4 wv[2];
        const uint4* hp[2];
#pragma unroll
        for (int r = 0; r < 2; r++) {
            const int wi = warp + 12 * r, k = wi / 3, j = wi - 3 * k;
            hp[r] = &S->h2w[(size_t)__shfl_sync(0xffffffffu, seltok, k) * 96 + 32 * j + lane];
            wv[r] = ld_rlx4(hp[r]);
        }
        if (tid < 288 && (tid & 7) == 0) {
            const uint32_t ft = 2047u - (fsel & 2047u), pr = (ft & 15u) >> 1;
            fx = ((const unsigned short*)x)[(size_t)ft * D_ + fd];
            asm volatile("ld.relaxed.gpu.global.u16 %0, [%1];" : "=r"(fv)
                         : "l"((const unsigned short*)S->v + ((size_t)(ft >> 4) * D_ + fd) * 16 + ((pr & 3u) * 2 + (pr >> 2)) * 2 + (ft & 1u)) : "memory");
        }
#pragma unroll 1
        for (int it = 0; it < SPIN_MAX && (wv[0].w != epoch || wv[1].w != epoch); it++) { wv[0] = ld_rlx4(hp[0]); wv[1] = ld_rlx4(hp[1]); }
#pragma unroll
        for (int r = 0; r < 2; r++) {
            const int wi = warp + 12 * r, k = wi / 3, j = wi - 3 * k;
            uint32_t* dst = (uint32_t*)&h2s[k][0] + 96 * j + lane;
            dst[0] = wv[r].x; dst[32] = wv[r].y; dst[64] = wv[r].z;
        }
    }
    CBAR();
    float* ffr = (float*)(sm + OFF_FFR);
    if (fmt < 4 || nf > 32) {
        float acc[2][4] = {{0.f, 0.f, 0.f, 0.f}, {0.f, 0.f, 0.f, 0.f}};
        const uint32_t ha = sb + OFF_H2S + lr * (ROWP * 2) + (144 * fsl) * 2 + lm * 16;
#pragma unroll
        for (int k2 = 0; k2 < 5; k2++) {
            uint32_t hb[4];
            ldsm_x4(hb, ha + k2 * 64 - ((k2 == 4) ? (lm >> 1) * 32 : 0));
            mma_bf16(acc[0], wf[2 * k2][0], wf[2 * k2][1], wf[2 * k2][2], wf[2 * k2][3], hb[0], hb[1]);
            if (k2 < 4) mma_bf16(acc[1], wf[2 * k2 + 1][0], wf[2 * k2 + 1][1], wf[2 * k2 + 1][2], wf[2 * k2 + 1][3], hb[2], hb[3]);
        }
        float* o = ffr + ((fsl * 80 + 16 * fmt + g) * 8 + 2 * t);
        *(float2*)o = make_float2(acc[0][0] + acc[1][0], acc[0][1] + acc[1][1]);
        *(float2*)(o + 64) = make_float2(acc[0][2] + acc[1][2], acc[0][3] + acc[1][3]);
    }
    CBAR();
    bf16(*act)[56] = (bf16(*)[56])(sm + OFF_ACT);
    if (tid < 384) {
        const int f = tid >> 3, a = tid & 7;
        float v = 0.f;
        if (f < nf) {
            const int rg = (f < 32) ? f : f + 32, ru = (f < 32) ? f + 32 : f + 40;
            const float* pg = ffr + rg * 8 + a;
            const float* pu = ffr + ru * 8 + a;
            float gg = bfr((pg[0] + pg[640]) + (pg[1280] + pg[1920]));
            gg = bfr(silu(gg));
            const float uu = bfr((pu[0] + pu[640]) + (pu[1280] + pu[1920]));
            v = gg * uu;
        }
        act[a][f] = __ushort_as_bfloat16((unsigned short)f2bits(v));
    }
    CBAR();
    {
        uint32_t bq[3][2];
#pragma unroll
        for (int ks = 0; ks < 3; ks++) {
            bq[ks][0] = *(const uint32_t*)&act[g][16 * ks + 2 * t];
            bq[ks][1] = *(const uint32_t*)&act[g][16 * ks + 2 * t + 8];
        }
#pragma unroll
        for (int i = 0; i < 2; i++) {
            if (i == 0 || warp < 16) {
                float acc[4] = {0.f, 0.f, 0.f, 0.f};
#pragma unroll
                for (int ks = 0; ks < 3; ks++)
                    if (ks < 2 || nf > 32) mma_bf16(acc, wd[i][ks][0], wd[i][ks][1], wd[i][ks][2], wd[i][ks][3], bq[ks][0], bq[ks][1]);
                const int W = (warp + 20 * i) * 32 + lane, c = (W * 7282) >> 16;
                st_rlx2(&S->part[(c * G_ + b) * 9 + W - 9 * c], ~pack2(acc[0], acc[1]), ~pack2(acc[2], acc[3]));
            }
        }
    }
    if (warp >= 4) {
        const int tk = warp - 4;
        if (!__any_sync(0xffffffffu, 2047u - (M.skey[lr] & 2047u) == (uint32_t)(16 * b + tk))) {
            const uint4* src = (const uint4*)(sm + OFF_TILE + tk * (ROWP * 2));
            uint4* dst = (uint4*)(out + (size_t)(16 * b + tk) * D_);
            dst[lane] = src[lane]; dst[lane + 32] = src[lane + 32];
            if (lane < 8) dst[lane + 64] = src[lane + 64];
        }
    }
    float4* fin = (float4*)(sm + OFF_FIN);
    uint32_t rb = (fsel >> 11) & 0xFFFFu;
    rb ^= (rb & 0x8000u) ? 0x8000u : 0xFFFFu;
    const float rs = bfr(__fdividef(1.0f, 1.0f + __expf(-lo2f(rb))));
    const float fh2 = (tid < 288) ? __bfloat162float(h2s[fk][fd]) : 0.f, fgb = (tid < 288) ? __bfloat162float(M.gb[fd]) : 0.f;
    const float fx1 = bfr(lo2f(fx) + lo2f(~fv));
    if (tid < 576) {
        const uint2* src = &S->part[(size_t)b * 1152 + tid];
        uint2 a = ld_rlx2(src), c = ld_rlx2(src + 576);
#pragma unroll 1
        for (int it = 0; it < SPIN_MAX && (a.x == SENT || c.x == SENT); it++) {
            if (a.x == SENT) a = ld_rlx2(src);
            if (c.x == SENT) c = ld_rlx2(src + 576);
        }
        fin[tid] = make_float4(lo2f(~a.x) + lo2f(~c.x), hi2f(~a.x) + hi2f(~c.x), lo2f(~a.y) + lo2f(~c.y), hi2f(~a.y) + hi2f(~c.y));
    }
    CBAR();
    if (tid < 288) {
        const int part = tid & 7;
        const float* f = (const float*)fin + part * 36 + fo;
        float s = ((f[0] + f[288]) + (f[576] + f[864])) + ((f[1152] + f[1440]) + (f[1728] + f[2016]));
        s += __shfl_xor_sync(0xffffffffu, s, 1);
        s += __shfl_xor_sync(0xffffffffu, s, 2);
        s += __shfl_xor_sync(0xffffffffu, s, 4);
        const float upd = bfr(bfr(s) * rs);
        const float ov = fx1 + bfr(fgb * bfr(fh2 + upd));
        if (part == 0) out[(size_t)(2047u - (fsel & 2047u)) * D_ + fd] = __ushort_as_bfloat16((unsigned short)f2bits(ov));
    }
    if ((warp & 3) == 2 && lane == 0) asm volatile("cp.async.bulk.wait_group 0;" ::: "memory");
    }
}

typedef CUresult (*EncodeFn)(CUtensorMap*, CUtensorMapDataType, cuuint32_t, void*, const cuuint64_t*, const cuuint64_t*,
                             const cuuint32_t*, const cuuint32_t*, CUtensorMapInterleave, CUtensorMapSwizzle,
                             CUtensorMapL2promotion, CUtensorMapFloatOOBfill);

static void make_map(EncodeFn fn, CUtensorMap* m, const void* ptr, uint64_t cols, uint64_t rows, uint32_t bc, uint32_t br,
                     CUtensorMapSwizzle sw) {
    cuuint64_t dims[2] = {cols, rows};
    cuuint64_t strides[1] = {cols * 2};
    cuuint32_t box[2] = {bc, br};
    cuuint32_t es[2] = {1, 1};
    CUresult rc = fn(m, CU_TENSOR_MAP_DATA_TYPE_BFLOAT16, 2, (void*)ptr, dims, strides, box, es, CU_TENSOR_MAP_INTERLEAVE_NONE,
                     sw, CU_TENSOR_MAP_L2_PROMOTION_NONE, CU_TENSOR_MAP_FLOAT_OOB_FILL_NONE);
    (void)rc;
}

static void launch(void* const* d_in, const int* in_sizes, int n_in, void* d_out, int out_size) {
    static EncodeFn enc = nullptr;
    static CUtensorMap tmm, tmg, tmu, tmd, tmd32, tmg32, tmu32;
    static Scratch* sp = nullptr;
    static const void* cached[4] = {nullptr, nullptr, nullptr, nullptr};
    if (!enc) {
        cudaDriverEntryPointQueryResult qr;
        void* fn = nullptr;
        cudaGetDriverEntryPoint("cuTensorMapEncodeTiled", &fn, cudaEnableDefault, &qr);
        enc = (EncodeFn)fn;
        cudaFuncSetAttribute(mega_kernel, cudaFuncAttributeMaxDynamicSharedMemorySize, SMEM_TOTAL);
        cudaGetSymbolAddress((void**)&sp, g_s);
    }
    if (cached[0] != d_in[13] || cached[1] != d_in[9] || cached[2] != d_in[10] || cached[3] != d_in[11]) {
        make_map(enc, &tmm, d_in[13], 6 * D_, D_, 32, 192, CU_TENSOR_MAP_SWIZZLE_64B);
        make_map(enc, &tmg, d_in[9], F_, D_, 40, 192, CU_TENSOR_MAP_SWIZZLE_NONE);
        make_map(enc, &tmu, d_in[10], F_, D_, 40, 192, CU_TENSOR_MAP_SWIZZLE_NONE);
        make_map(enc, &tmg32, d_in[9], F_, D_, 32, 192, CU_TENSOR_MAP_SWIZZLE_64B);
        make_map(enc, &tmu32, d_in[10], F_, D_, 32, 192, CU_TENSOR_MAP_SWIZZLE_64B);
        make_map(enc, &tmd, d_in[11], D_, F_, 64, 40, CU_TENSOR_MAP_SWIZZLE_128B);
        make_map(enc, &tmd32, d_in[11], D_, F_, 64, 32, CU_TENSOR_MAP_SWIZZLE_128B);
        cached[3] = d_in[11];
        cached[0] = d_in[13]; cached[1] = d_in[9]; cached[2] = d_in[10];
    }
    mega_kernel<<<G_, NTHR, SMEM_TOTAL>>>((const bf16*)d_in[0], (const bf16*)d_in[1], (const bf16*)d_in[2], (const bf16*)d_in[3],
                                          (const bf16*)d_in[4], (const bf16*)d_in[5], (const bf16*)d_in[12], sp, (const bf16*)d_in[6],
                                          (const bf16*)d_in[8], (const bf16*)d_in[11], (bf16*)d_out, tmm, tmg, tmu, tmd, tmd32, tmg32, tmu32);
}

}

extern "C" void kernel_launch(void* const* d_in, const int* in_sizes, int n_in, void* d_out, int out_size) {
    static int mode = -1;
    if (mode < 0) mode = v5::fits() ? 1 : 0;
    if (mode) v5::launch(d_in, in_sizes, n_in, d_out, out_size);
    else v4::launch(d_in, in_sizes, n_in, d_out, out_size);
}
```

```cpp
#include <cuda_runtime.h>
#include <cuda.h>
#include <cuda_bf16.h>
#include <cuda_fp16.h>
#include <stdint.h>

namespace v5 {

#define L_ 2048
#define D_ 576
#define N_ 128
#define F_ 4608
#define G_ 120
#define NCL 15
#define NTHR 768
#define SPIN_MAX (1 << 18)

typedef __nv_bfloat16 bf16;

struct Scratch {
    float4 acc1[L_ + 8];
    float4 acc2[L_];
    uint4 h2c[136 * 72];
    float4 acc3[72 * 32];
    float4 rs[33 * 8];
    unsigned int gb[320];
};
static_assert(136 * 72 + 72 * 32 + 33 * 8 == 103 * G_, "16 B units cleared early in a launch (h2c, acc3, rs)");
__device__ __align__(1024) Scratch g_s;

#define OFF_WG 0
#define OFF_WU 46080
#define KSCR 3456
#define OFF_WM0 69120
#define OFF_STG OFF_WM0
#define OFF_MG2 86400
#define OFF_CH 92160
#define CHS 18688
#define UP 3808
#define UB 192
#define XO_TF 1216
#define XO_U8 2016
#define XO_U16 3328
#define XO_ZA 1232
#define XO_ZB 2016
#define XO_ZC 2800
#define XO_ZD 3328
#define XO_TD 16000
#define XO_K1024 18624
#define XO_DSK 18628
#define XO_KLAST 18656
#define XO_MBU 18672
#define OFF_X 185600
#define XG 672
#define XI(i) (((i) >> 1) * 5520 + ((i) & 1) * 2752)
#define XN(n) ((((n) >> 1) & 3) * XG + (2 * ((n) >> 3) + ((n) & 1)) * 80)
#define OFF_V 207616
#define VP 528
#define OFF_EK (OFF_V + 512)
#define OFF_WM2 OFF_V
#define OFF_MG1 (OFF_V + 17280)
#define OFF_SC (OFF_V + 19840)
#define OFF_C1 (OFF_V + 20640)
#define OFF_MISC 228736
#define OFF_WD OFF_CH
#define OFF_H2T (OFF_CH + 46080)
#define OFF_OUT (OFF_CH + 66560)
#define ROWP 584
#define OFF_H2S 0
#define OFF_FFR 9344
#define OFF_ACT 19584
#define OFF_RS 20480

enum { MB_WM2, MB_MG1, MB_MG2, MB_KEY, MB_V, MB_RS, MB_WG, MB_WU, MB_WD, MB_KEY2, MB_EK, MB_RS2, MB_C2, MB_CW, MB_KD, MB_OUT, MB_C1, MB_N };

struct Misc {
    union {
        __align__(16) uint4 box[11 * 16];
        struct { unsigned int cand[128], key[256], cand2[128], sel[8]; };
    };
    __align__(16) uint4 c2[20];
    __align__(16) unsigned int fin[12];
    unsigned int ga[8], wr[20];
    float cws[2];
    unsigned long long mbar[MB_N];
};
#define SMEM_TOTAL (OFF_MISC + (int)sizeof(Misc))
static_assert(SMEM_TOTAL <= 232448, "smem");

__device__ __forceinline__ float lo2f(uint32_t w) { return __uint_as_float(w << 16); }
__device__ __forceinline__ float hi2f(uint32_t w) { return __uint_as_float(w & 0xFFFF0000u); }
__device__ __forceinline__ uint32_t pack2(float lo, float hi) { uint32_t r; asm("cvt.rn.bf16x2.f32 %0, %1, %2;" : "=r"(r) : "f"(hi), "f"(lo)); return r; }
__device__ __forceinline__ float bfr(float x) { return __uint_as_float(pack2(0.f, x)); }
__device__ __forceinline__ uint32_t f2bits(float x) { return pack2(x, 0.f); }
__device__ __forceinline__ uint32_t packh(float lo, float hi) { uint32_t r; asm("cvt.rn.f16x2.f32 %0, %1, %2;" : "=r"(r) : "f"(hi), "f"(lo)); return r; }
__device__ __forceinline__ float frcp(float x) { float r; asm("rcp.approx.ftz.f32 %0, %1;" : "=f"(r) : "f"(x)); return r; }
__device__ __forceinline__ float fsqrt(float x) { float r; asm("sqrt.approx.f32 %0, %1;" : "=f"(r) : "f"(x)); return r; }
__device__ __forceinline__ float fex2(float x) { float r; asm("ex2.approx.ftz.f32 %0, %1;" : "=f"(r) : "f"(x)); return r; }
__device__ __forceinline__ float silu(float x) { return __fdividef(x, 1.0f + __expf(-x)); }
__device__ __forceinline__ uint32_t add2(uint32_t a, uint32_t b) { uint32_t r; asm("add.rn.bf16x2 %0, %1, %2;" : "=r"(r) : "r"(a), "r"(b)); return r; }
__device__ __forceinline__ uint32_t sub2(uint32_t a, uint32_t b) { uint32_t r; asm("sub.rn.bf16x2 %0, %1, %2;" : "=r"(r) : "r"(a), "r"(b)); return r; }
__device__ __forceinline__ uint32_t mul2(uint32_t a, uint32_t b) { uint32_t r; asm("mul.rn.bf16x2 %0, %1, %2;" : "=r"(r) : "r"(a), "r"(b)); return r; }
__device__ __forceinline__ uint32_t fma2(uint32_t a, uint32_t b, uint32_t c) { uint32_t r; asm("fma.rn.bf16x2 %0, %1, %2, %3;" : "=r"(r) : "r"(a), "r"(b), "r"(c)); return r; }
__device__ __forceinline__ uint32_t norm2(uint32_t x, uint32_t m, uint32_t rh, uint32_t rl) { const uint32_t d = sub2(x, m); return fma2(d, rh, mul2(d, rl)); }

__device__ __forceinline__ void mma_bf16(float* c, uint32_t a0, uint32_t a1, uint32_t a2, uint32_t a3, uint32_t b0, uint32_t b1) {
    asm volatile("mma.sync.aligned.m16n8k16.row.col.f32.bf16.bf16.f32 {%0,%1,%2,%3}, {%4,%5,%6,%7}, {%8,%9}, {%0,%1,%2,%3};\n"
                 : "+f"(c[0]), "+f"(c[1]), "+f"(c[2]), "+f"(c[3]) : "r"(a0), "r"(a1), "r"(a2), "r"(a3), "r"(b0), "r"(b1));
}
__device__ __forceinline__ void mma_f16(float* c, const uint32_t* a, uint32_t b0, uint32_t b1) {
    asm volatile("mma.sync.aligned.m16n8k16.row.col.f32.f16.f16.f32 {%0,%1,%2,%3}, {%4,%5,%6,%7}, {%8,%9}, {%0,%1,%2,%3};\n"
                 : "+f"(c[0]), "+f"(c[1]), "+f"(c[2]), "+f"(c[3]) : "r"(a[0]), "r"(a[1]), "r"(a[2]), "r"(a[3]), "r"(b0), "r"(b1));
}
__device__ __forceinline__ void ldsm_x4(uint32_t* r, uint32_t addr) {
    asm volatile("ldmatrix.sync.aligned.m8n8.x4.shared.b16 {%0,%1,%2,%3}, [%4];" : "=r"(r[0]), "=r"(r[1]), "=r"(r[2]), "=r"(r[3]) : "r"(addr) : "memory");
}
__device__ __forceinline__ void ldsm_x4_t(uint32_t* r, uint32_t addr) {
    asm volatile("ldmatrix.sync.aligned.m8n8.x4.trans.shared.b16 {%0,%1,%2,%3}, [%4];" : "=r"(r[0]), "=r"(r[1]), "=r"(r[2]), "=r"(r[3]) : "r"(addr) : "memory");
}
__device__ __forceinline__ void stsm_x4(uint32_t addr, uint32_t r0, uint32_t r1, uint32_t r2, uint32_t r3) {
    asm volatile("stmatrix.sync.aligned.m8n8.x4.shared.b16 [%0], {%1,%2,%3,%4};" ::"r"(addr), "r"(r0), "r"(r1), "r"(r2), "r"(r3) : "memory");
}
__device__ __forceinline__ void stsm_x4_t(uint32_t addr, uint32_t r0, uint32_t r1, uint32_t r2, uint32_t r3) {
    asm volatile("stmatrix.sync.aligned.m8n8.x4.trans.shared.b16 [%0], {%1,%2,%3,%4};" ::"r"(addr), "r"(r0), "r"(r1), "r"(r2), "r"(r3) : "memory");
}
__device__ __forceinline__ uint32_t movm(uint32_t a) { uint32_t r; asm volatile("movmatrix.sync.aligned.m8n8.trans.b16 %0, %1;" : "=r"(r) : "r"(a)); return r; }
__device__ __forceinline__ uint32_t lds32(uint32_t a) { uint32_t v; asm volatile("ld.shared.u32 %0, [%1];" : "=r"(v) : "r"(a)); return v; }
__device__ __forceinline__ void sts32(uint32_t a, uint32_t v) { asm volatile("st.shared.u32 [%0], %1;" ::"r"(a), "r"(v) : "memory"); }
__device__ __forceinline__ void sts16(uint32_t a, uint32_t v) { asm volatile("st.shared.u16 [%0], %1;" ::"r"(a), "h"((unsigned short)v) : "memory"); }
__device__ __forceinline__ void named_bar(int id, int n) { asm volatile("bar.sync %0, %1;" ::"r"(id), "r"(n) : "memory"); }
__device__ __forceinline__ void named_arrive(int id, int n) { asm volatile("bar.arrive %0, %1;" ::"r"(id), "r"(n) : "memory"); }
#define CBAR() asm volatile("bar.sync 0, 640;" ::: "memory")
#define PROXY_FENCE() asm volatile("fence.proxy.async.shared::cta;" ::: "memory")

#define D4(d, o) "+f"(d[o]), "+f"(d[o + 1]), "+f"(d[o + 2]), "+f"(d[o + 3])
__device__ __forceinline__ void wg32(float* d, uint32_t a0, uint32_t a1, uint32_t a2, uint32_t a3, uint64_t desc) {
    asm volatile("wgmma.mma_async.sync.aligned.m64n32k16.f32.bf16.bf16 {%0,%1,%2,%3,%4,%5,%6,%7,%8,%9,%10,%11,%12,%13,%14,%15}, {%16,%17,%18,%19}, %20, 1, 1, 1, 0;"
                 : D4(d, 0), D4(d, 4), D4(d, 8), D4(d, 12) : "r"(a0), "r"(a1), "r"(a2), "r"(a3), "l"(desc));
}
__device__ __forceinline__ void wg48(float* d, uint32_t a0, uint32_t a1, uint32_t a2, uint32_t a3, uint64_t desc) {
    asm volatile("wgmma.mma_async.sync.aligned.m64n48k16.f32.bf16.bf16 {%0,%1,%2,%3,%4,%5,%6,%7,%8,%9,%10,%11,%12,%13,%14,%15,%16,%17,%18,%19,%20,%21,%22,%23}, {%24,%25,%26,%27}, %28, 1, 1, 1, 0;"
                 : D4(d, 0), D4(d, 4), D4(d, 8), D4(d, 12), D4(d, 16), D4(d, 20) : "r"(a0), "r"(a1), "r"(a2), "r"(a3), "l"(desc));
}
__device__ __forceinline__ void wg64(float* d, uint32_t a0, uint32_t a1, uint32_t a2, uint32_t a3, uint64_t desc) {
    asm volatile("wgmma.mma_async.sync.aligned.m64n64k16.f32.bf16.bf16 {%0,%1,%2,%3,%4,%5,%6,%7,%8,%9,%10,%11,%12,%13,%14,%15,%16,%17,%18,%19,%20,%21,%22,%23,%24,%25,%26,%27,%28,%29,%30,%31}, {%32,%33,%34,%35}, %36, 1, 1, 1, 0;"
                 : D4(d, 0), D4(d, 4), D4(d, 8), D4(d, 12), D4(d, 16), D4(d, 20), D4(d, 24), D4(d, 28) : "r"(a0), "r"(a1), "r"(a2), "r"(a3), "l"(desc));
}
#define O4(d, o) "=f"(d[o]), "=f"(d[o + 1]), "=f"(d[o + 2]), "=f"(d[o + 3])
__device__ __forceinline__ void wg32z(float* d, uint32_t a0, uint32_t a1, uint32_t a2, uint32_t a3, uint64_t desc) {
    asm volatile("wgmma.mma_async.sync.aligned.m64n32k16.f32.bf16.bf16 {%0,%1,%2,%3,%4,%5,%6,%7,%8,%9,%10,%11,%12,%13,%14,%15}, {%16,%17,%18,%19}, %20, 0, 1, 1, 0;"
                 : O4(d, 0), O4(d, 4), O4(d, 8), O4(d, 12) : "r"(a0), "r"(a1), "r"(a2), "r"(a3), "l"(desc));
}
__device__ __forceinline__ void wg48z(float* d, uint32_t a0, uint32_t a1, uint32_t a2, uint32_t a3, uint64_t desc) {
    asm volatile("wgmma.mma_async.sync.aligned.m64n48k16.f32.bf16.bf16 {%0,%1,%2,%3,%4,%5,%6,%7,%8,%9,%10,%11,%12,%13,%14,%15,%16,%17,%18,%19,%20,%21,%22,%23}, {%24,%25,%26,%27}, %28, 0, 1, 1, 0;"
                 : O4(d, 0), O4(d, 4), O4(d, 8), O4(d, 12), O4(d, 16), O4(d, 20) : "r"(a0), "r"(a1), "r"(a2), "r"(a3), "l"(desc));
}
__device__ __forceinline__ void wg56(float* d, uint32_t a0, uint32_t a1, uint32_t a2, uint32_t a3, uint64_t desc) {
    asm volatile("wgmma.mma_async.sync.aligned.m64n56k16.f32.bf16.bf16 {%0,%1,%2,%3,%4,%5,%6,%7,%8,%9,%10,%11,%12,%13,%14,%15,%16,%17,%18,%19,%20,%21,%22,%23,%24,%25,%26,%27}, {%28,%29,%30,%31}, %32, 1, 1, 1, 0;"
                 : D4(d, 0), D4(d, 4), D4(d, 8), D4(d, 12), D4(d, 16), D4(d, 20), D4(d, 24) : "r"(a0), "r"(a1), "r"(a2), "r"(a3), "l"(desc));
}
__device__ __forceinline__ void wg64z(float* d, uint32_t a0, uint32_t a1, uint32_t a2, uint32_t a3, uint64_t desc) {
    asm volatile("wgmma.mma_async.sync.aligned.m64n64k16.f32.bf16.bf16 {%0,%1,%2,%3,%4,%5,%6,%7,%8,%9,%10,%11,%12,%13,%14,%15,%16,%17,%18,%19,%20,%21,%22,%23,%24,%25,%26,%27,%28,%29,%30,%31}, {%32,%33,%34,%35}, %36, 0, 1, 1, 0;"
                 : O4(d, 0), O4(d, 4), O4(d, 8), O4(d, 12), O4(d, 16), O4(d, 20), O4(d, 24), O4(d, 28) : "r"(a0), "r"(a1), "r"(a2), "r"(a3), "l"(desc));
}
#define WG_FENCE() asm volatile("wgmma.fence.sync.aligned;" ::: "memory")
#define WG_COMMIT() asm volatile("wgmma.commit_group.sync.aligned;" ::: "memory")
#define WG_WAIT(n) asm volatile("wgmma.wait_group.sync.aligned " #n ";" ::: "memory")
#define TQ(p, k) p[2 * (k) + 1], p[2 * (k) + 2], p[2 * (k)], p[2 * (k) + 1]

__device__ __forceinline__ uint4 ld_nc4(const void* p) { uint4 v; asm volatile("ld.global.nc.v4.u32 {%0,%1,%2,%3}, [%4];" : "=r"(v.x), "=r"(v.y), "=r"(v.z), "=r"(v.w) : "l"(p)); return v; }
__device__ __forceinline__ uint2 ld_nc2(const void* p) { uint2 v; asm volatile("ld.global.nc.v2.u32 {%0,%1}, [%2];" : "=r"(v.x), "=r"(v.y) : "l"(p)); return v; }
__device__ __forceinline__ unsigned short ld_nc16(const void* p) { unsigned short v; asm volatile("ld.global.nc.u16 %0, [%1];" : "=h"(v) : "l"(p)); return v; }
__device__ __forceinline__ uint32_t ld_nc(const void* p) { uint32_t v; asm volatile("ld.global.nc.u32 %0, [%1];" : "=r"(v) : "l"(p)); return v; }
__device__ __forceinline__ uint32_t ld_rlx(const unsigned int* p) { uint32_t v; asm volatile("ld.relaxed.gpu.global.u32 %0, [%1];" : "=r"(v) : "l"(p) : "memory"); return v; }
__device__ __forceinline__ uint2 ld_rlx2(const void* p) { uint2 v; asm volatile("ld.relaxed.gpu.global.v2.u32 {%0,%1}, [%2];" : "=r"(v.x), "=r"(v.y) : "l"(p) : "memory"); return v; }
__device__ __forceinline__ uint4 ld_rlx4(const void* p) { uint4 v; asm volatile("ld.relaxed.gpu.global.v4.u32 {%0,%1,%2,%3}, [%4];" : "=r"(v.x), "=r"(v.y), "=r"(v.z), "=r"(v.w) : "l"(p) : "memory"); return v; }
__device__ __forceinline__ void st_rlx(unsigned int* p, uint32_t v) { asm volatile("st.relaxed.gpu.global.u32 [%0], %1;" ::"l"(p), "r"(v) : "memory"); }
__device__ __forceinline__ void st_rlx2(void* p, uint32_t a, uint32_t b) { asm volatile("st.relaxed.gpu.global.v2.u32 [%0], {%1,%2};" ::"l"(p), "r"(a), "r"(b) : "memory"); }
__device__ __forceinline__ void st_rlx4(void* p, uint4 v) { asm volatile("st.relaxed.gpu.global.v4.u32 [%0], {%1,%2,%3,%4};" ::"l"(p), "r"(v.x), "r"(v.y), "r"(v.z), "r"(v.w) : "memory"); }
__device__ __forceinline__ void red_inc(unsigned int* p) { asm volatile("red.relaxed.gpu.global.add.u32 [%0], 1;" ::"l"(p) : "memory"); }

__device__ __forceinline__ void mbar_init(uint32_t a, int cnt) { asm volatile("mbarrier.init.shared::cta.b64 [%0], %1;" ::"r"(a), "r"(cnt) : "memory"); }
__device__ __forceinline__ void mbar_expect(uint32_t a, uint32_t bytes) { asm volatile("mbarrier.arrive.expect_tx.shared::cta.b64 _, [%0], %1;" ::"r"(a), "r"(bytes) : "memory"); }
__device__ __forceinline__ void mbar_wait(uint32_t a, uint32_t parity) {
    uint32_t ok = 0;
    int it = 0;
    do {
        asm volatile("{\n.reg .pred p;\nmbarrier.try_wait.parity.shared::cta.b64 p, [%1], %2;\nselp.u32 %0, 1, 0, p;\n}" : "=r"(ok) : "r"(a), "r"(parity) : "memory");
    } while (!ok && ++it < SPIN_MAX);
}
__device__ __forceinline__ bool mbar_test(uint32_t a, uint32_t parity) {
    uint32_t ok;
    asm volatile("{\n.reg .pred p;\nmbarrier.test_wait.parity.shared::cta.b64 p, [%1], %2;\nselp.u32 %0, 1, 0, p;\n}" : "=r"(ok) : "r"(a), "r"(parity) : "memory");
    return __all_sync(0xffffffffu, ok);
}
__device__ __forceinline__ void tma2d(uint32_t dst, const CUtensorMap* tm, int c0, int c1, uint32_t mbar) {
    asm volatile("cp.async.bulk.tensor.2d.shared::cluster.global.mbarrier::complete_tx::bytes [%0], [%1, {%3, %4}], [%2];"
                 ::"r"(dst), "l"(tm), "r"(mbar), "r"(c0), "r"(c1) : "memory");
}
__device__ __forceinline__ void bulk_s2g(void* dst, uint32_t src, uint32_t bytes) {
    asm volatile("cp.async.bulk.global.shared::cta.bulk_group [%0], [%1], %2;" ::"l"(dst), "r"(src), "r"(bytes) : "memory");
}
__device__ __forceinline__ uint32_t ld_acq(const unsigned int* p) { uint32_t v; asm volatile("ld.acquire.gpu.global.u32 %0, [%1];" : "=r"(v) : "l"(p) : "memory"); return v; }
__device__ __forceinline__ void bulk_pf(const void* src, uint32_t bytes) { asm volatile("cp.async.bulk.prefetch.L2.global [%0], %1;" ::"l"(src), "r"(bytes) : "memory"); }

struct cplx { float x, y; };
__device__ __forceinline__ cplx cmul(cplx a, cplx b) { cplx r; r.x = a.x * b.x - a.y * b.y; r.y = a.x * b.y + a.y * b.x; return r; }
__device__ __forceinline__ cplx csq(cplx a) { cplx r; r.x = a.x * a.x - a.y * a.y; r.y = 2.0f * a.x * a.y; return r; }
__device__ __forceinline__ uint32_t hcm(uint32_t x, uint32_t y, uint32_t yp) {
    const __half2 X = *(const __half2*)&x, Y = *(const __half2*)&y, YP = *(const __half2*)&yp;
    const __half2 r = __hfma2(__high2half2(X), YP, __hmul2(__low2half2(X), Y));
    return *(const uint32_t*)&r;
}
__device__ __forceinline__ uint32_t hcn(uint32_t x, uint32_t y, uint32_t yq) {
    const __half2 X = *(const __half2*)&x, Y = *(const __half2*)&y, YQ = *(const __half2*)&yq;
    const __half2 r = __hfma2(__hneg2(__high2half2(X)), YQ, __hmul2(__low2half2(X), Y));
    return *(const uint32_t*)&r;
}
__device__ __forceinline__ float2 hsum4(uint32_t a, uint32_t b, uint32_t c, uint32_t d) {
    return __half22float2(__hadd2(__hadd2(*(const __half2*)&a, *(const __half2*)&b), __hadd2(*(const __half2*)&c, *(const __half2*)&d)));
}
__device__ __forceinline__ uint32_t amax2(uint32_t a, uint32_t b) { uint32_t r; asm("max.xorsign.abs.bf16x2 %0, %1, %2;" : "=r"(r) : "r"(a), "r"(b)); return r; }
__device__ __forceinline__ void ln_stats(float s1, float s2, float& meanb, float& rinv) {
    const float mean = s1 * (1.0f / D_);
    const float den = bfr(fsqrt(bfr(bfr(fmaxf(fmaf(-mean, mean, s2 * (1.0f / D_)), 0.f)) + 1e-5f)));
    meanb = bfr(mean);
    rinv = frcp(den);
}

__device__ __forceinline__ int fresh_tid() { int v; asm volatile("mov.u32 %0, %tid.x;" : "=r"(v)); return v - 128; }
__device__ __forceinline__ void mma_k8(float* c, uint32_t a0, uint32_t a1, uint32_t b0) {
    asm volatile("mma.sync.aligned.m16n8k8.row.col.f32.bf16.bf16.f32 {%0,%1,%2,%3}, {%4,%5}, {%6}, {%0,%1,%2,%3};\n"
                 : "+f"(c[0]), "+f"(c[1]), "+f"(c[2]), "+f"(c[3]) : "r"(a0), "r"(a1), "r"(b0));
}
__device__ __forceinline__ void ldsm_x2(uint32_t* r, uint32_t addr) {
    asm volatile("ldmatrix.sync.aligned.m8n8.x2.shared.b16 {%0,%1}, [%2];" : "=r"(r[0]), "=r"(r[1]) : "r"(addr) : "memory");
}
__device__ __forceinline__ void ldsm_x2_t(uint32_t* r, uint32_t addr) {
    asm volatile("ldmatrix.sync.aligned.m8n8.x2.trans.shared.b16 {%0,%1}, [%2];" : "=r"(r[0]), "=r"(r[1]) : "r"(addr) : "memory");
}
__device__ __forceinline__ void stsm_x2(uint32_t addr, uint32_t r0, uint32_t r1) {
    asm volatile("stmatrix.sync.aligned.m8n8.x2.shared.b16 [%0], {%1,%2};" ::"r"(addr), "r"(r0), "r"(r1) : "memory");
}
__device__ __forceinline__ uint4 lds128(uint32_t a) { uint4 v; asm volatile("ld.shared.v4.u32 {%0,%1,%2,%3}, [%4];" : "=r"(v.x), "=r"(v.y), "=r"(v.z), "=r"(v.w) : "r"(a) : "memory"); return v; }
__device__ __forceinline__ uint32_t mapa(uint32_t a, uint32_t r) { uint32_t o; asm("mapa.shared::cluster.u32 %0, %1, %2;" : "=r"(o) : "r"(a), "r"(r)); return o; }
__device__ __forceinline__ void sta4(uint32_t dst, uint4 v, uint32_t mb) {
    asm volatile("st.async.weak.shared::cluster.mbarrier::complete_tx::bytes.v4.b32 [%0], {%1,%2,%3,%4}, [%5];" ::"r"(dst), "r"(v.x), "r"(v.y), "r"(v.z), "r"(v.w), "r"(mb) : "memory");
}
__device__ __forceinline__ void sta2(uint32_t dst, uint32_t a, uint32_t b, uint32_t mb) {
    asm volatile("st.async.weak.shared::cluster.mbarrier::complete_tx::bytes.v2.b32 [%0], {%1,%2}, [%3];" ::"r"(dst), "r"(a), "r"(b), "r"(mb) : "memory");
}
__device__ __forceinline__ void mbar_arrive(uint32_t a) { asm volatile("mbarrier.arrive.shared::cta.b64 _, [%0];" ::"r"(a) : "memory"); }
__device__ __forceinline__ void red4(float4* p, float a, float b, float c) {
    asm volatile("red.relaxed.gpu.global.add.v4.f32 [%0], {%1,%2,%3,%4};" ::"l"(p), "f"(a), "f"(b), "f"(c), "f"(1.0f) : "memory");
}
__device__ __forceinline__ void red4p(bool on, float4* p, float a, float b, float c) {
    asm volatile("{\n.reg .pred q;\nsetp.ne.u32 q, %5, 0;\n@q red.relaxed.gpu.global.add.v4.f32 [%0], {%1,%2,%3,%4};\n}" ::"l"(p), "f"(a), "f"(b), "f"(c), "f"(1.0f), "r"((uint32_t)on) : "memory");
}
__device__ __forceinline__ float4 atom4(float4* p, float a, float b, float c, float d) {
    float4 v;
    asm volatile("atom.relaxed.gpu.global.add.v4.f32 {%0,%1,%2,%3}, [%4], {%5,%6,%7,%8};" : "=f"(v.x), "=f"(v.y), "=f"(v.z), "=f"(v.w) : "l"(p), "f"(a), "f"(b), "f"(c), "f"(d) : "memory");
    return v;
}
__device__ __forceinline__ uint2 lds64(uint32_t a) { uint2 v; asm volatile("ld.shared.v2.u32 {%0,%1}, [%2];" : "=r"(v.x), "=r"(v.y) : "r"(a) : "memory"); return v; }
__device__ __forceinline__ float4 ld_rlx4f(const float4* p) { float4 v; asm volatile("ld.relaxed.gpu.global.v4.f32 {%0,%1,%2,%3}, [%4];" : "=f"(v.x), "=f"(v.y), "=f"(v.z), "=f"(v.w) : "l"(p) : "memory"); return v; }
__device__ __forceinline__ void tma5d_st(const CUtensorMap* tm, int c0, int c4, uint32_t src) {
    asm volatile("cp.async.bulk.tensor.5d.global.shared::cta.bulk_group [%0, {%2, %4, %4, %4, %3}], [%1];" ::"l"(tm), "r"(src), "r"(c0), "r"(c4), "r"(0) : "memory");
}
__device__ __forceinline__ void tma2d_pf(const CUtensorMap* tm, int c0, int c1) {
    asm volatile("cp.async.bulk.prefetch.tensor.2d.L2.global [%0, {%1, %2}];" ::"l"(tm), "r"(c0), "r"(c1) : "memory");
}
__device__ __forceinline__ void pace(int clk) {
    const long long c0 = clock64();
    int it = 0;
    while (clock64() - c0 < clk && ++it < 4096) { }
}
__device__ __forceinline__ uint32_t sign2(uint32_t a) { uint32_t r; asm("prmt.b32 %0, %1, 0, 0xBB99;" : "=r"(r) : "r"(a)); return r; }
#define MB(i) (sb + OFF_MISC + (uint32_t)offsetof(Misc, mbar) + 8 * (i))
__device__ __forceinline__ uint32_t box_tap(int i) {
    const int f = (i * 205) >> 13, l = i - 40 * f - 6 - ((0x35C36 >> (4 * f)) & 15);
    const unsigned wd = (0x16824 >> (4 * f)) & 15, one = f == 4 ? 0xFFFFu : 0x3F80u;
    return ((unsigned)l <= wd ? one : 0u) | ((unsigned)(l - 1) <= wd ? one << 16 : 0u);
}
#define UF(u) ((u) < 4 ? (u) + 5 : (u) == 4 ? 13 : (u) < 10 ? (u) - 5 : (u) - 1)
__device__ __forceinline__ void conv_channel(unsigned char* sm, uint32_t rank, uint32_t fixa, uint32_t fixv) {
    Misc& M = *(Misc*)(sm + OFF_MISC);
    const uint32_t sb = (uint32_t)__cvta_generic_to_shared(sm);
    const int tid = fresh_tid(), lane = tid & 31, g = lane >> 2, t = lane & 3, lr = lane & 7, lm = lane >> 3;
    const int warp_ = __shfl_sync(0xffffffffu, tid >> 5, 0), wgi = warp_ >> 2, w = warp_ & 3;
    const uint32_t cb = sb + OFF_CH + wgi * CHS;
    float D[32];
    const uint32_t dlo = ((cb & 0x3FFFF) >> 4) | ((UP >> 4) << 16);
#define DS(o, z, bl) (((uint64_t)(128 >> 4) << 32) | (uint64_t)(dlo + (o) / 16 + (((z) & 1) ? 0 : UP / 8) - ((z) >> 1) * (bl)))
    {
        const uint32_t pf = cb + XO_TF + (w >> 1) * UP + (8 + 16 * (w & 1) + g - 2 * t) * 4;
        uint32_t p[13], q[9];
        named_bar(1 + wgi, 128);
        if (fixa) sts16(fixa, fixv);
#pragma unroll
        for (int s = 0; s < 13; s++) p[s] = lds32(pf + s * 32);
        {
            const uint32_t a8 = cb + UB + t * UP + g * 16 + w * 128, b8 = cb + XO_U8 + lm * UP + lr * 16 + w * 128;
            const uint32_t a16 = cb + UB + (2 * (lr & 1) + (lm & 1)) * UP + ((lr >> 1) + 2 * (lm & 2)) * 16 + w * 128;
            const uint32_t b16 = cb + XO_U16 + (2 * (w & 1) + (lm >> 1)) * UP + (lane & 15) * 16 + (w >> 1) * 256;
            uint32_t r[3][4];
            mbar_wait(cb + XO_MBU, 0);
            ldsm_x4_t(r[0], a8);
            ldsm_x4_t(r[1], a16);
            if (w < 2) ldsm_x4_t(r[2], a8 + 512);
            stsm_x4(b8, r[0][0], r[0][1], r[0][2], r[0][3]);
            stsm_x4(b16, r[1][0], r[1][1], r[1][2], r[1][3]);
            if (w < 2) stsm_x4(b8 + 512, r[2][0], r[2][1], r[2][2], r[2][3]);
        }
        PROXY_FENCE();
        named_bar(1 + wgi, 128);
        {
            float Z8[24], Z16[16];
            uint32_t z8[12];
            WG_FENCE();
#pragma unroll
            for (int e = 0; e < 6; e++) {
                if (e == 0) wg48z(Z8, TQ(p, e), DS(XO_U8, e, 8));
                else wg48(Z8, TQ(p, e), DS(XO_U8, e, 8));
            }
            WG_COMMIT();
            WG_WAIT(0);
            asm volatile("setmaxnreg.inc.sync.aligned.u32 88;");
#pragma unroll
            for (int s = 0; s < 9; s++) q[s] = lds32(pf + 2 * UP + s * 32);
#pragma unroll
            for (int i = 0; i < 12; i++) asm volatile("cvt.rn.bf16x2.f32 %0, %1, %2;" : "=r"(z8[i]) : "f"(Z8[2 * i + 1]), "f"(Z8[2 * i]));
            WG_FENCE();
#pragma unroll
            for (int e = 0; e < 4; e++) {
                if (e == 0) wg32z(Z16, TQ(q, e), DS(XO_U16, e, 16));
                else wg32(Z16, TQ(q, e), DS(XO_U16, e, 16));
            }
            WG_COMMIT();
            WG_WAIT(0);
            named_bar(1 + wgi, 128);
            const uint32_t za = cb + ((w >> 1) ? XO_ZB : XO_ZA) + t * UP + (4 * (w & 1) + (g & 3) + 8 * (g >> 2)) * 16;
#pragma unroll
            for (int i = 0; i < 3; i++) stsm_x4(za + i * 256, z8[4 * i], z8[4 * i + 1], z8[4 * i + 2], z8[4 * i + 3]);
            const uint32_t zc = cb + ((w >> 1) ? XO_ZD : XO_ZC) + (2 * (lr & 1) + (lm >> 1)) * UP + (((lane & 15) >> 1) + 8 * (w & 1)) * 16;
#pragma unroll
            for (int ob = 0; ob < 2; ob++) stsm_x4(zc + ob * 256, pack2(Z16[8 * ob], Z16[8 * ob + 1]), pack2(Z16[8 * ob + 2], Z16[8 * ob + 3]), pack2(Z16[8 * ob + 4], Z16[8 * ob + 5]), pack2(Z16[8 * ob + 6], Z16[8 * ob + 7]));
        }
    }
    PROXY_FENCE();
    {
        const uint32_t pa = cb + XO_TD + (40 + 8 * w + g - 2 * t) * 4, pq = sb + OFF_MISC + (8 * w - 18 + g - 2 * t) * 4;
        uint32_t q[3][8];
        const uint32_t k2 = lds32(cb + XO_K1024);
        auto ld = [&](int u) {
            uint32_t* d = q[u % 3];
            const int f = UF(u);
            if (f >= 5) {
#pragma unroll
                for (int i = 0; i < 8; i++) d[i] = (f == 13 && i > 4) ? 0u : lds32(pa + (f - 5) * 256 + i * 32);
            } else {
                const int lo = f == 2, hi = f == 2 ? 3 : (f == 1 || f == 4) ? 1 : 2;
#pragma unroll
                for (int i = 0; i < 8; i++) {
                    if (f < 3) d[i] = 0u;
                    if (i >= lo && i <= hi + 3) {
                        asm volatile("{\n.reg .pred p;\nsetp.le.u32 p, %2, %3;\n@p ld.shared.u32 %0, [%1];\n}" : "+r"(d[i]) : "r"(pq + f * 160 + i * 32), "r"(w + i - 3 - lo), "r"(hi - lo));
                        if (f == 4) asm volatile("and.b32 %0, %0, %1;" : "+r"(d[i]) : "r"(k2));
                    }
                }
            }
        };
        auto go = [&](int u) {
            const int f = UF(u);
            WG_FENCE();
#pragma unroll
            for (int z = 0; z < 2; z++) {
                const uint32_t* a = q[u % 3] + 2 * z;
#define Q4 a[1], a[5], a[0], a[4]
                if (f == 5 && z == 0) wg64z(D, Q4, DS(UB, 0, 2));
                else if (f < 2) wg48(D + 8, Q4, DS(f ? XO_ZB : XO_ZA, z, 0));
                else if (f < 5) wg32(D + 16, Q4, DS(f == 2 ? XO_ZC : f == 3 ? XO_ZD : UB, z, 0));
                else if (f < 9) wg64(D, Q4, DS(UB, 2 * (f - 5) + z, 2));
                else if (f == 13) wg48(D + 8, Q4, DS(UB, z, 0));
                else wg56(D + 4, Q4, DS(UB + 128, 2 * (f - 5) + z, 2));
            }
            WG_COMMIT();
        };
#define RD_(o) _Pragma("unroll") for (int i = o; i < 32; i++) { float y_; asm volatile("mov.b32 %0, %1;" : "=f"(y_) : "f"(D[i])); D[i] = y_; }
        ld(0); ld(1); go(0); ld(2); go(1);
        named_bar(1 + wgi, 128);
#pragma unroll
        for (int u = 2; u < 14; u++) {
            WG_WAIT(1);
            if (u < 13) ld(u + 1);
            if (u == 4 || u == 7 || u == 10) { WG_WAIT(0); RD_(u == 4 ? 8 : u == 7 ? 16 : 4); }
            go(u);
        }
    }
    {
        const int tid = fresh_tid(), lane = tid & 31, lr = lane & 7, lm = lane >> 3;
        uint32_t u[2][4];
        const uint32_t ua = cb + UB + w * UP + lm * 256 + lr * 16;
        ldsm_x4_t(u[0], ua); ldsm_x4_t(u[1], ua + 128);
        const uint32_t dk2 = __byte_perm(lds32(cb + XO_DSK), 0, (rank & 1) ? 0x3232 : 0x1010);
#pragma unroll
        for (int i = 0; i < 8; i++) u[i >> 2][i & 3] = mul2(u[i >> 2][i & 3], dk2);
        mbar_wait(MB(MB_C2), 0);
        const uint32_t ga2 = M.ga[wgi];
        const int src = (lane & 28) | ((lane + 3) & 3);
        WG_WAIT(0);
        float s[8];
#pragma unroll
        for (int j = 0; j < 8; j++) s[j] = __shfl_sync(0xffffffffu, (lane & 3) < 3 ? D[4 * j + 3] : j ? D[4 * j - 1] : 0.f, src);
#pragma unroll
        for (int h = 0; h < 2; h++) {
            const uint32_t rb = mapa(sb, w + 4 * h);
#pragma unroll
            for (int j = 0; j < 4; j++) u[h][j] = mul2(ga2, add2(pack2(D[8 * j + 4 * h] + s[2 * j + h], D[8 * j + 4 * h + 1] + D[8 * j + 4 * h + 2]), u[h][j]));
            sta4(rb + OFF_V + (8 * wgi + rank) * VP + lane * 16, make_uint4(u[h][0], u[h][1], u[h][2], u[h][3]), rb + (MB(MB_V) - sb));
        }
    }
}
#define M2W 4
#define WS 0x3210
#define WMS(p) if (warp == 7) { if (p == 0) CL_WAIT(); if (lane == 0) { _Pragma("unroll") for (int i = 2; i < 6; i++) if (((WS >> (4 * (i - 2))) & 15) == p) tma2d(sb + (i == 5 ? OFF_WM0 + 11520 : OFF_WM2 + (i - 2) * 5760), &tm_wm, i * D_ + 40 * cl, 72 * rk, MB(MB_WM2)); } __syncwarp(); }
#define PQT 10
#define PQD 400
#define L2P 2
#define L2M 2
#define PDE 100
#define WMD 400
#define CWP 200
#define CWD 3000
#define ROW(key) (((~(key) << 2) & 0xE0u) | ((~(key) >> 6) & 24u) | ((~(key) >> 11) & 6u) | ((~(key) >> 8) & 1u))
#define RKT (((rk & 4) << 6) | ((rk & 3) << 3))
#define MINE(key) ((~(key) & 0x8C0u) == (uint32_t)(RKT << 3))
#define CE(a, b) { const uint32_t hi_ = max(a, b); b = min(a, b); a = hi_; }
#define POP(k, m) if (k.x == m) { k.x = k.y; k.y = k.z; k.z = k.w; k.w = 0u; }
#define CGT(c, a, b, n) asm volatile("{\n.reg .pred p;\nsetp.gt.u32 p, %1, %2;\n@p add.u32 %0, %0, " #n ";\n}" : "+r"(c) : "r"(a), "r"(b))
#define CL_ARRIVE() asm volatile("barrier.cluster.arrive.relaxed.aligned;" ::: "memory")
#define CL_WAIT() asm volatile("barrier.cluster.wait.aligned;" ::: "memory")
__global__ void __cluster_dims__(8, 1, 1) __launch_bounds__(NTHR, 1)
clus_kernel(const bf16* __restrict__ x, const bf16* __restrict__ logAr, const bf16* __restrict__ Aim, const bf16* __restrict__ Cr, const bf16* __restrict__ Ci,
            const bf16* __restrict__ logdt, const bf16* __restrict__ c_in, Scratch* __restrict__ S, const bf16* __restrict__ Dskip,
            const bf16* __restrict__ w_r, const bf16* __restrict__ w_mod, bf16* __restrict__ out,
            const __grid_constant__ CUtensorMap tm_wm, const __grid_constant__ CUtensorMap tm_wg,
            const __grid_constant__ CUtensorMap tm_wu, const __grid_constant__ CUtensorMap tm_wd, const __grid_constant__ CUtensorMap tm_out) {
    extern __shared__ __align__(1024) unsigned char sm[];
    Misc& M = *(Misc*)(sm + OFF_MISC);
    const uint32_t sb = (uint32_t)__cvta_generic_to_shared(sm);
    const int tid = threadIdx.x < 128 ? threadIdx.x + 640 : threadIdx.x - 128, warp = __shfl_sync(0xffffffffu, tid >> 5, 0), lane = tid & 31;
    const int g = lane >> 2, t = lane & 3, lr = lane & 7, lm = lane >> 3;
    const int wgi = warp >> 2, w = warp & 3;
    const int b = blockIdx.x, cl = b >> 3, rk = b & 7;
    auto mod_ld = [&](uint32_t (*a)[4], uint32_t s0, uint32_t s1, int i) {
        const uint32_t wa = sb + ((lm & 1) ? s1 : s0) + (lr + 8 * (lm >> 1)) * 80 + i * 16;
#pragma unroll
        for (int ks = 0; ks < 4; ks++) ldsm_x4_t(a[ks], wa + ks * 1280);
        ldsm_x2_t(a[4], wa + 5120);
    };
    auto mod_mma2 = [&](float* d, float* e, uint32_t (*a)[4], uint32_t (*c)[4], const uint32_t* bs) {
        mma_k8(d, a[4][0], a[4][1], bs[8]); mma_k8(e, c[4][0], c[4][1], bs[8]);
#pragma unroll
        for (int ks = 0; ks < 4; ks++) {
            mma_bf16(d, a[ks][0], a[ks][1], a[ks][2], a[ks][3], bs[2 * ks], bs[2 * ks + 1]);
            mma_bf16(e, c[ks][0], c[ks][1], c[ks][2], c[ks][3], bs[2 * ks], bs[2 * ks + 1]);
        }
    };
    auto mod_st = [&](const float* d, uint32_t dst, int mb) {
#pragma unroll
        for (int h = 0; h < 2; h++) {
            const uint32_t rb = mapa(sb, t + 4 * h);
            sta2(rb + dst + g * 8, __float_as_uint(d[0]), __float_as_uint(d[2]), rb + (MB(mb) - sb));
        }
    };
    auto gsum = [&](uint32_t a, int pitch) {
        float4 s = make_float4(0.f, 0.f, 0.f, 0.f);
#pragma unroll
        for (int i = 0; i < 8; i++) { const float4 q = *(const float4*)(sm + a + i * pitch); s.x += q.x; s.y += q.y; s.z += q.z; s.w += q.w; }
        return make_uint2(pack2(s.x, s.z), pack2(s.y, s.w));
    };
    auto one_plus = [&](uint32_t v) { return pack2(1.0f + lo2f(v), 1.0f + hi2f(v)); };
    auto mkc1 = [&]() {
        const int lane = fresh_tid() & 31;
        const uint2 v = gsum(OFF_MG1 + 16 * min(lane, 19), 320);
        const uint32_t c1 = one_plus(v.x);
        if (lane < 20) *(uint4*)(sm + OFF_C1 + 16 * lane) = make_uint4(__byte_perm(c1, 0, 0x1010), __byte_perm(v.y, 0, 0x1010), __byte_perm(c1, 0, 0x3232), __byte_perm(v.y, 0, 0x3232));
        __syncwarp();
        named_arrive(10, 160);
    };
    if (wgi == 5) {
        CL_ARRIVE();
        const uint32_t c_a = ld_nc((const uint32_t*)c_in + 36 * rk + lane), c_b = ld_nc((const uint32_t*)c_in + 36 * rk + 32 + t);
        {
            pace(WMD);
            const char* wp = (const char*)(w_mod + (72 * rk + 18 * w) * (6 * D_) + 40 * cl);
#pragma unroll
            for (int i = 0; i < 3; i++) {
                const uint32_t c = lane + 32 * i, row = (c * 205) >> 10;
                const char* p = wp + (row * (12 * D_ - 80) + 16 * c);
                if (c < 90) {
                    asm volatile("cp.async.cg.shared.global [%0], [%1], 16;" ::"r"(sb + OFF_WM0 + 1440 * w + 16 * c), "l"(p) : "memory");
                    asm volatile("cp.async.cg.shared.global [%0], [%1], 16;" ::"r"(sb + OFF_WM0 + 5760 + 1440 * w + 16 * c), "l"(p + 2 * D_) : "memory");
                }
            }
            if (w == 3 && lane < 20)
                asm volatile("cp.async.ca.shared.global [%0], [%1], 4, %2;" ::"r"(sb + OFF_MISC + (uint32_t)offsetof(Misc, c2) + 12 + 16 * lane), "l"((const uint32_t*)w_r + min(20 * cl + lane, D_ / 2 - 1)),
                             "r"(20 * cl + lane < D_ / 2 ? 4 : 0) : "memory");
            asm volatile("cp.async.commit_group;" ::: "memory");
        }
        {
            uint32_t bs[9], a[5][4], c[5][4];
            float d[4] = {0.f, 0.f, 0.f, 0.f}, e[4] = {0.f, 0.f, 0.f, 0.f};
            const uint32_t sc = pack2(silu(lo2f(c_a)), silu(hi2f(c_a)));
            bs[8] = pack2(silu(lo2f(c_b)), silu(hi2f(c_b)));
            if (w == 2) { sts32(sb + OFF_SC + 4 * lane, sc); sts32(sb + OFF_SC + 128 + 4 * t, bs[8]); }
#pragma unroll
            for (int ks = 0; ks < 8; ks++) bs[ks] = __shfl_sync(0xffffffffu, sc, 4 * ks + t);
            CL_WAIT();
            asm volatile("cp.async.wait_group 0;" ::: "memory");
            named_bar(10, 128);
            mod_ld(a, OFF_WM0 + 5760, OFF_WM0, w);
            mod_ld(c, OFF_WM0 + 5760, OFF_WM0, 4);
            mod_mma2(d, e, a, c, bs);
            mod_st(d, OFF_MG1 + rk * 320 + 64 * w, MB_MG1);
            if (w == 1) mod_st(e, OFF_MG1 + rk * 320 + 256, MB_MG1);
        }
        {
            const int n0 = 8 * w + 2 * (rk & 1), n1 = 8 * w + ((n0 + 4 + t) & 7);
            const float4* ap = &S->acc1[256 * rk + 8 * (n0 + t) + g];
            const float4* aq = &S->acc1[256 * rk + 8 * n1 + g];
            named_bar(9, 640);
            float4 pa = ld_rlx4f(ap), pb = ld_rlx4f(aq);
            uint32_t xq[2][5][4];
            uint2 cc[5];
            const uint32_t xa = sb + OFF_X + XI(2 * lm + (lr & 1)) + XN(n0 + (lr >> 1)), xb = sb + OFF_X + XI(2 * lm + (lr & 1)) + XN(8 * w + ((n0 + 4 + (lr >> 1)) & 7));
            const uint32_t ua = mapa(sb, g) + OFF_CH;
#pragma unroll
            for (int j = 0; j < 5; j++) ldsm_x4_t(xq[0][j], xa + 16 * j);
#pragma unroll 1
            for (int it = 0; it < SPIN_MAX && (pa.w != (float)NCL || pb.w != (float)NCL); it++) {
                pa = ld_rlx4f(ap); pb = ld_rlx4f(aq);
            }
            __syncwarp();
            float m0, r0, m1, r1;
            ln_stats(pa.x, pa.y, m0, r0);
            ln_stats(pb.x, pb.y, m1, r1);
            const uint32_t rh = pack2(r0, r1), rl = pack2(r0 - lo2f(rh), r1 - hi2f(rh));
            const uint32_t stage = sb + OFF_STG + w * 512;
            stsm_x4_t(stage + lane * 16, pack2(m0, m1), rh, rl, rl);
            __syncwarp();
            named_bar(10, 160);
            uint4 st[2][3];
#pragma unroll
            for (int q = 0; q < 2; q++)
#pragma unroll
                for (int i = 0; i < 3; i++) st[q][i] = lds128(stage + 128 * i + (2 * t + q) * 16);
#pragma unroll
            for (int j = 0; j < 5; j++) cc[j] = *(const uint2*)(sm + OFF_C1 + 64 * j + 8 * g);
            ldsm_x4_t(xq[1][0], xb);
            const uint32_t ub = ua + (rk & 3) * UP + UB + (8 * w + 8 * (rk >> 2)) * 16, u0 = ub + (n0 + t) * 16, u1 = ub + n1 * 16;
#pragma unroll
            for (int j = 0; j < 5; j++) {
                if (j >= 2 && cl == 14) break;
                if (j < 4) ldsm_x4_t(xq[1][j + 1], xb + 16 * (j + 1));
#pragma unroll
                for (int q = 0; q < 2; q++) {
                    const uint4 sm_ = st[q][0], sh = st[q][1], sl = st[q][2];
                    const uint32_t v0 = add2(mul2(norm2(xq[q][j][0], sm_.x, sh.x, sl.x), cc[j].x), cc[j].y), v1 = add2(mul2(norm2(xq[q][j][1], sm_.y, sh.y, sl.y), cc[j].x), cc[j].y);
                    const uint32_t v2 = add2(mul2(norm2(xq[q][j][2], sm_.z, sh.z, sl.z), cc[j].x), cc[j].y), v3 = add2(mul2(norm2(xq[q][j][3], sm_.w, sh.w, sl.w), cc[j].x), cc[j].y);
                    asm volatile("{\n.reg .pred p;\nsetp.ne.u32 p, %6, %7;\n"
                                 "@p st.async.weak.shared::cluster.mbarrier::complete_tx::bytes.v4.b32 [%0], {%1,%2,%3,%4}, [%5];\n"
                                 "@!p st.shared.v4.b32 [%0], {%1,%2,%3,%4};\n}"
                                 ::"r"((q ? u1 : u0) + j * CHS), "r"(v0), "r"(v1), "r"(v2), "r"(v3), "r"(ua + j * CHS + XO_MBU), "r"(g), "r"(rk) : "memory");
                }
                __syncwarp();
                if (lane == 0) mbar_arrive(sb + OFF_CH + XO_MBU + j * CHS);
            }
        }
        asm volatile("setmaxnreg.dec.sync.aligned.u32 40;");
        {
        int cl;
        asm volatile("mov.u32 %0, %clusterid.x;" : "=r"(cl));
        const int w = __shfl_sync(0xffffffffu, (fresh_tid() >> 5) & 3, 0);
        uint32_t gz = 0;
        if (w) named_arrive(11, 128); else named_bar(11, 128);
        if (w == 0) {
            const int lane = fresh_tid() & 31;
            mbar_wait(MB(MB_KD), 0);
            PROXY_FENCE();
            if (lane == 0) {
                tma2d(sb + OFF_WU + 15360, &tm_wu, 40 * b, 192, MB(MB_WU));
                tma2d_pf(&tm_wu, 40 * b, 384);
                mbar_wait(MB(MB_C2), 0);
                PROXY_FENCE();
                tma2d(sb + OFF_WU + 2 * 15360, &tm_wu, 40 * b, 384, MB(MB_WU));
#pragma unroll 1
                for (int i = 0; i < 9; i++) { pace(PDE); tma2d_pf(&tm_wd, 64 * i, 40 * b); }
                mbar_wait(MB(MB_WU), 0);
            }
            __syncwarp();
        } else if (w == 2) {
            if ((fresh_tid() & 31) == 0) {
                float4 v;
                int it = 0;
                pace(CWD);
                for (;;) { v = ld_rlx4f(&S->acc1[L_]); if (++it >= SPIN_MAX || (v.z == (float)G_ && v.w == (float)NCL)) break; pace(CWP); }
                M.cws[0] = v.x; M.cws[1] = v.y;
                mbar_arrive(MB(MB_CW));
            }
        } else if (w == 3) {
            const int lane = fresh_tid() & 31, l20 = min(lane, 19);
            mbar_wait(MB(MB_MG2), 0);
            const uint2 v = gsum(OFF_MG2 + 16 * l20, 640), u = gsum(OFF_MG2 + 320 + 16 * l20, 640);
            const uint32_t wr = lane < 20 ? M.c2[lane].w : 0u, cb1 = one_plus(v.x), cw = mul2(cb1, wr);
            if (lane < 20) {
                M.c2[lane] = make_uint4(cb1, v.y, u.x, cw);
                M.wr[lane] = wr;
                unsigned e;
                asm volatile("mov.u32 %0, %cluster_ctarank;" : "=r"(e));
                if ((lane & 3) == (e >> 1)) M.ga[lane >> 2] = __byte_perm(u.y, 0, (e & 1) ? 0x3232 : 0x1010);
            }
            __syncwarp();
            if (lane == 0) mbar_arrive(MB(MB_C2));
            if (rk == 0) {
                float a = lo2f(cw) + hi2f(cw), s = lo2f(v.y) * lo2f(wr) + hi2f(v.y) * hi2f(wr);
#pragma unroll
                for (int o = 16; o; o >>= 1) { a += __shfl_xor_sync(0xffffffffu, a, o); s += __shfl_xor_sync(0xffffffffu, s, o); }
                if (lane == 0) red4(&S->acc1[L_], a, s, 0.f);
                __syncwarp();
                if (lane < 20) st_rlx(&S->gb[20 * cl + lane], u.x);
                gz = ld_rlx(&S->gb[20 * cl + l20]) ^ u.x;
            }
        }
        {
        const int lane = fresh_tid() & 31, t = lane & 3, lr = lane & 7, lm = lane >> 3;
        uint32_t aw[5];
        __syncwarp();
        mbar_wait(MB(MB_C2), 0);
#pragma unroll
        for (int j = 0; j < 5; j++) aw[j] = M.wr[4 * j + t];
        const int ph = w >> 1, lst = 16 * ph + 2 * rk + (w & 1);
        const uint32_t rb = mapa(sb, lr);
        named_bar(6, 640);
        uint4 k = *(const uint4*)&M.key[128 * (w & 1) + 4 * lane];
        CE(k.x, k.y); CE(k.z, k.w); CE(k.x, k.z); CE(k.y, k.w); CE(k.y, k.z);
        uint32_t m[4];
#pragma unroll 1
        for (int q = 0; q <= ph; q++) {
#pragma unroll
            for (int rnd = 0; rnd < 4; rnd++) {
                m[rnd] = __reduce_max_sync(0xffffffffu, k.x);
                POP(k, m[rnd]);
            }
        }
        if (lane < 8) sta4(rb + OFF_MISC + (uint32_t)offsetof(Misc, cand) + lst * 16, make_uint4(m[0], m[1], m[2], m[3]), rb + (MB(MB_KEY2) - sb));
        const uint32_t mine = (t & 2) ? ((t & 1) ? m[3] : m[2]) : ((t & 1) ? m[1] : m[0]);
        const uint32_t ra = sb + OFF_H2T + ROW(mine) * 80;
        uint32_t bq[6];
        float rr[4] = {0.f, 0.f, 0.f, 0.f};
        ldsm_x4(bq, ra + 16 * lm); ldsm_x2(bq + 4, ra + 64);
        mma_bf16(rr, aw[0], aw[0], aw[1], aw[1], bq[0], bq[1]); mma_bf16(rr, aw[2], aw[2], aw[3], aw[3], bq[2], bq[3]); mma_k8(rr, aw[4], aw[4], bq[4]);
        float4* p = &S->rs[8 * lst];
        if (lane < 2) red4(p + lane, rr[0], __uint_as_float(gz), rr[1]);
        float4 e0 = ld_rlx4f(p), e1 = ld_rlx4f(p + 1);
        uint32_t sl = 0;
        if (w == 1) {
            mbar_wait(MB(MB_KEY2), 0);
            k = *(const uint4*)&M.cand[4 * lane];
            named_bar(14, 64);
#pragma unroll
            for (int s = 0; s < 8; s++) {
                const uint32_t v = M.sel[s] & ~1u;
                if (k.x == v) sl |= 8 + s;
                if (k.y == v) sl |= (8 + s) << 8;
                if (k.z == v) sl |= (8 + s) << 16;
                if (k.w == v) sl |= (8 + s) << 24;
            }
        }
        if (w == 0) {
            named_bar(8, 64);
            if (lane == 0) {
                PROXY_FENCE();
                tma5d_st(&tm_out, 40 * cl, RKT, sb + OFF_OUT);
                asm volatile("cp.async.bulk.commit_group;" ::: "memory");
            }
            __syncwarp();
        }
#pragma unroll 1
        for (int it = 0; it < SPIN_MAX && (e0.w != (float)NCL || e1.w != (float)NCL); it++) {
            e0 = ld_rlx4f(p); e1 = ld_rlx4f(p + 1);
        }
        {
            const uint32_t r0 = pack2(e0.x, e0.z), r1 = pack2(e1.x, e1.z);
            const uint32_t o0 = r0 ^ (sign2(r0) | 0x80008000u), o1 = r1 ^ (sign2(r1) | 0x80008000u);
            if (lane < 8) sta4(rb + OFF_EK + lst * VP, make_uint4((o0 << 16) | (m[0] & 0x3FFFu), (o0 & 0xFFFF0000u) | (m[1] & 0x3FFFu), (o1 << 16) | (m[2] & 0x3FFFu), (o1 & 0xFFFF0000u) | (m[3] & 0x3FFFu)),
                               rb + (MB(MB_EK) - sb));
        }
        if (w == 0) {
            if (lane == 0) {
                asm volatile("cp.async.bulk.wait_group 0;" ::: "memory");
                asm volatile("fence.acq_rel.gpu;" ::: "memory");
                mbar_arrive(MB(MB_OUT));
            }
        } else if (w == 1) {
            const uint32_t found = __reduce_add_sync(0xffffffffu, __popc(sl & 0x08080808u));
            mbar_wait(MB(MB_EK), 0);
            if (b == 0 && lane == 0) st_rlx4(&S->acc1[L_], make_uint4(0, 0, 0, 0));
            if (lane < 16 || cl == 14) st_rlx4(&S->acc2[256 * rk + 16 * cl + lane], make_uint4(0, 0, 0, 0));
            k = lds128(sb + OFF_EK + lane * VP);
            const bool s0 = sl & 8u, s1 = sl & 0x800u, s2 = sl & 0x80000u, s3 = sl & 0x8000000u;
            if (s0) M.fin[sl & 7u] = k.x;
            if (s1) M.fin[(sl >> 8) & 7u] = k.y;
            if (s2) M.fin[(sl >> 16) & 7u] = k.z;
            if (s3) M.fin[(sl >> 24) & 7u] = k.w;
            const uint32_t lo = min(min(s0 ? k.x : ~0u, s1 ? k.y : ~0u), min(s2 ? k.z : ~0u, s3 ? k.w : ~0u));
            const uint32_t hi = max(max(s0 ? 0u : k.x, s1 ? 0u : k.y), max(s2 ? 0u : k.z, s3 ? 0u : k.w));
            const uint32_t hi2 = __reduce_max_sync(0xffffffffu, hi), lo2 = __reduce_min_sync(0xffffffffu, lo);
            bool redo = found != 8u;
            if (hi2 > lo2) {
                const uint32_t h = hi2 | 0xFFFFu, l = lo2 & 0xFFFF0000u;
                const uint32_t n = __reduce_add_sync(0xffffffffu, ((s0 ? k.x <= h : (k.x >= l) << 8) + (s1 ? k.y <= h : (k.y >= l) << 8)) + ((s2 ? k.z <= h : (k.z >= l) << 8) + (s3 ? k.w <= h : (k.w >= l) << 8)));
                redo = redo || (h >> 16) - (l >> 16) > 1u || ((n & 255u) > 1u && n >= 512u) || (n & 255u) + (n >> 8) > 9u;
            }
            if (redo) {
                CE(k.x, k.y); CE(k.z, k.w); CE(k.x, k.z); CE(k.y, k.w); CE(k.y, k.z);
                __syncwarp();
#pragma unroll 1
                for (int rnd = 0; rnd < 8; rnd++) {
                    const uint32_t m8 = __reduce_max_sync(0xffffffffu, k.x);
                    POP(k, m8);
                    if (lane == 0) M.fin[rnd] = m8;
                }
            }
            if (lane == 0) M.fin[8] = redo;
            __syncwarp();
            named_arrive(12, 672);
        }
        }
        }
    } else {
    if (warp != 19) CL_ARRIVE();
    const int chn = 40 * cl + 8 * wgi + rk;
    const bool has_ch = chn < D_;
    const uint32_t cb = sb + OFF_CH + wgi * CHS;
    auto ldx = [&]() {
    if (warp < 16) {
        const char* xp = (const char*)(x + (512 * (warp >> 2) + 64 * (warp & 3) + RKT) * D_ + 40 * cl);
        const uint32_t dst = sb + OFF_X + XN(2 * warp) + XI(lm) + 16 * lr;
        xp += lm * (2 * D_) + 16 * lr;
#pragma unroll
        for (int i = 0; i < 4; i++)
            if (lr < 5) asm volatile("cp.async.cg.shared.global [%0], [%1], 16, %2;" ::"r"(dst + XI(4 * (i & 1)) + 80 * (i >> 1)), "l"(xp + ((i & 1) * 4 + (i >> 1) * 32) * (2 * D_)),
                                     "r"((cl < 14 || lr < 2) ? 16 : 0) : "memory");
    }
    };
    unsigned short r_ldt = 0, r_lar = 0, r_aim = 0;
    uint2 r_cr, r_ci;
    {
        const int n = min(chn, D_ - 1) * N_ + 4 * lane;
        r_ldt = ld_nc16((const unsigned short*)logdt + min(chn, D_ - 1));
        r_lar = ld_nc16((const unsigned short*)logAr + n + w);
        r_aim = ld_nc16((const unsigned short*)Aim + n + w);
        r_cr = ld_nc2(Cr + n);
        r_ci = ld_nc2(Ci + n);
    }
    if (warp == 19) {
        if (lane == 0) asm volatile("prefetch.tensormap [%0];" ::"l"(&tm_wm) : "memory");
        const uint32_t lo = 90u | (10u << 8) | (20u << 16) | (2u << 24), hi = (cl == 14 ? 32u : 80u) | ((rk < 4 ? 40u : 32u) << 8) | (180u << 16) | (180u << 24);
        const uint32_t tx = lane < 8 ? (((lane & 4 ? hi : lo) >> (8 * (lane & 3))) & 255u) : lane == 8 ? 180u : lane < 11 ? 2u : lane == 11 ? (hi >> 8) & 255u : 14u;
        if (lane == 0) {
#pragma unroll
            for (int i = 0; i < MB_N; i++) mbar_init(MB(i), i == MB_KD ? 20 : 1);
#pragma unroll
            for (int i = 0; i < 5; i++) mbar_init(sb + OFF_CH + XO_MBU + i * CHS, 5);
        }
        __syncwarp();
        if (lane < 17) mbar_expect(lane < MB_C2 ? MB(lane) : sb + OFF_CH + XO_MBU + (lane - MB_C2) * CHS, tx << 8);
        asm volatile("fence.mbarrier_init.release.cluster;" ::: "memory");
        __syncwarp();
        CL_ARRIVE();
    }
    ldx();
    auto rst = [&]() {
        if (warp == 18) {
            const int lane = fresh_tid() & 31;
            uint4* rp = S->h2c + 103 * b + lane;
#pragma unroll
            for (int i = 0; i < 4; i++) if (i < 3 || lane < 7) st_rlx4(rp + 32 * i, make_uint4(0, 0, 0, 0));
            uint32_t z = 0x3F800000u;
#pragma unroll
            for (int i = 0; i < 4; i++) if (i < 3 || lane < 7) z |= ld_rlx((const unsigned int*)(rp + 32 * i));
            if (lane == 0) asm volatile("red.relaxed.gpu.global.add.f32 [%0], %1;" ::"l"(&S->acc1[L_].z), "f"(__uint_as_float(z)) : "memory");
            __syncwarp();
        }
    };
    if ((tid & 127) == 32) asm volatile("cp.async.ca.shared.global [%0], [%1], 4;" ::"r"(cb + XO_DSK), "l"((const uint32_t*)Dskip + (min(chn, D_ - 1) >> 1)) : "memory");
    asm volatile("cp.async.commit_group;" ::: "memory");
    auto mod2 = [&]() {
        if (wgi == M2W) {
            const int lane = fresh_tid() & 31, t = lane & 3;
            const uint32_t wa = sb + ((lane & 7) + ((lane >> 1) & 8)) * 80, p0 = wa + ((lane & 8) ? OFF_WM2 + 5760 : OFF_WM2 + 11520), p1 = wa + ((lane & 8) ? OFF_WM2 : OFF_WM0 + 11520);
            auto ld = [&](uint32_t (*a)[4], uint32_t p) {
#pragma unroll
                for (int ks = 0; ks < 4; ks++) ldsm_x4_t(a[ks], p + ks * 1280);
                ldsm_x2_t(a[4], p + 5120);
            };
            const uint32_t rb = mapa(sb, t), rd = mapa(sb, 4) - mapa(sb, 0), dst = rb + OFF_MG2 + rk * 640 + (lane >> 2) * 8;
            auto st = [&](const float* d, uint32_t o) {
                sta2(dst + o, __float_as_uint(d[0]), __float_as_uint(d[2]), rb + (MB(MB_MG2) - sb));
                sta2(dst + rd + o, __float_as_uint(d[0]), __float_as_uint(d[2]), rb + rd + (MB(MB_MG2) - sb));
            };
            uint32_t bs[9], a[5][4], c[5][4];
            float d[4] = {0.f, 0.f, 0.f, 0.f}, e[4] = {0.f, 0.f, 0.f, 0.f};
            mbar_wait(MB(MB_MG1), 0);
#pragma unroll
            for (int ks = 0; ks < 9; ks++) bs[ks] = lds32(sb + OFF_SC + 16 * ks + 4 * t);
            mbar_wait(MB(MB_WM2), 0);
            __syncwarp();
            ld(a, p0 + 16 * w);
            ld(c, p1 + 16 * w);
            {
                float h[6][4];
#pragma unroll
                for (int i = 0; i < 24; i++) h[i >> 2][i & 3] = 0.f;
                mma_k8(h[0], a[4][0], a[4][1], bs[8]); mma_k8(h[3], c[4][0], c[4][1], bs[8]);
#pragma unroll
                for (int ks = 0; ks < 4; ks++) {
                    mma_bf16(h[(ks + 1) % 3], a[ks][0], a[ks][1], a[ks][2], a[ks][3], bs[2 * ks], bs[2 * ks + 1]);
                    mma_bf16(h[3 + (ks + 1) % 3], c[ks][0], c[ks][1], c[ks][2], c[ks][3], bs[2 * ks], bs[2 * ks + 1]);
                }
                d[0] = h[0][0] + h[1][0] + h[2][0]; d[2] = h[0][2] + h[1][2] + h[2][2];
                e[0] = h[3][0] + h[4][0] + h[5][0]; e[2] = h[3][2] + h[4][2] + h[5][2];
                ld(a, ((w & 1) ? p1 : p0) + 64);
                st(d, 64 * w);
                st(e, 320 + 64 * w);
#pragma unroll
                for (int i = 0; i < 20; i++) h[i >> 2][i & 3] = 0.f;
                mma_k8(h[4], a[4][0], a[4][1], bs[8]);
#pragma unroll
                for (int ks = 0; ks < 4; ks++) mma_bf16(h[ks], a[ks][0], a[ks][1], a[ks][2], a[ks][3], bs[2 * ks], bs[2 * ks + 1]);
                d[0] = (h[0][0] + h[1][0]) + (h[2][0] + h[3][0]) + h[4][0]; d[2] = (h[0][2] + h[1][2]) + (h[2][2] + h[3][2]) + h[4][2];
            }
            if (w < 2) st(d, 320 * w + 256);
            __syncwarp();
        }
    };
    auto ln1 = [&]() {
        if (warp < 16) {
            uint32_t a[10];
            const uint32_t xa = sb + OFF_X + XN(2 * warp) + (lm & 1) * 80 + XI(lr) + (lm >> 1) * 16;
            asm volatile("cp.async.wait_group 0;" ::: "memory");
            __syncwarp();
            ldsm_x4(a, xa); ldsm_x4(a + 4, xa + 32); ldsm_x2(a + 8, xa + 64);
            named_arrive(9, 640);
            float c1[4] = {0.f, 0.f, 0.f, 0.f}, c2[4] = {0.f, 0.f, 0.f, 0.f}, c3[4] = {0.f, 0.f, 0.f, 0.f};
#pragma unroll
            for (int j = 0; j < 2; j++) {
                mma_bf16(c1, a[4 * j], a[4 * j + 1], a[4 * j + 2], a[4 * j + 3], 0x3F803F80u, 0x3F803F80u);
                mma_bf16(c2, a[4 * j], a[4 * j + 1], a[4 * j + 2], a[4 * j + 3], a[4 * j], a[4 * j + 2]);
                mma_bf16(c3, a[4 * j], a[4 * j + 1], a[4 * j + 2], a[4 * j + 3], a[4 * j + 1], a[4 * j + 3]);
            }
            mma_k8(c1, a[8], a[9], 0x3F803F80u); mma_k8(c2, a[8], a[9], a[8]); mma_k8(c3, a[8], a[9], a[9]);
            float4* p = &S->acc1[256 * rk + 16 * warp + g];
            red4p(t == (g >> 1), p, c1[0], (g & 1) ? c2[1] : c2[0], 0.f);
            red4p(t == (g >> 1), p + 8, c1[2], (g & 1) ? c3[3] : c3[2], 0.f);
        }
    };
    {
        unsigned char* cp = sm + OFF_CH + wgi * CHS + lane * 16;
        const uint4 z = make_uint4(0, 0, 0, 0);
        *(uint4*)(cp + w * UP + XO_TF) = z;
        *(uint4*)(cp + w * UP + (lane < 16 ? XO_U8 - 256 : XO_U16 - 512)) = z;
        if (lane < 16) *(uint4*)(cp + (lane < 8 ? w * UP + UB - 128 : XO_TD + (4 * w + (lane < 12 ? -8 : 145 - 12)) * 16)) = z;
    }
    if (tid < 200) ((uint32_t*)M.box)[tid] = box_tap(tid);
    const uint32_t scr = sb + warp * KSCR, ws = scr + lane * 4;
    uint32_t fixa = 0, fixv = 0;
    {
        uint32_t zr;
        asm volatile("ld.volatile.shared.u32 %0, [%1];" : "=r"(zr) : "r"(cb + XO_TF + w * UP + lane * 16) : "memory");
        const float p_ldt = __uint_as_float(r_ldt * 65536u + zr), p_lar = __uint_as_float(r_lar * 65536u + zr), p_aim = __uint_as_float(r_aim * 65536u + zr);
        const float p_cr = __uint_as_float((uint32_t)((((uint64_t)r_cr.y << 32) | r_cr.x) >> (16 * w)) * 65536u + zr), p_ci = __uint_as_float((uint32_t)((((uint64_t)r_ci.y << 32) | r_ci.x) >> (16 * w)) * 65536u + zr);
        float acc[5][4];
        uint32_t afr[4][4], cz[4], cq[4], bb[2][8];
        const uint32_t ba = scr + lr * 144 + lm * 16;
        auto tld = [&](int i) {
            __syncwarp();
            ldsm_x4(bb[i & 1], ba + ((i + 2) % 3) * 1152);
            ldsm_x4(bb[i & 1] + 4, ba + ((i + 2) % 3) * 1152 + 64);
        };
        auto tmm = [&](int i) {
            float* c = acc[i];
            c[0] = c[1] = c[2] = c[3] = 0.f;
#pragma unroll
            for (int s = 0; s < 4; s++) mma_f16(c, afr[s], bb[i & 1][2 * s], bb[i & 1][2 * s + 1]);
        };
#define TA(i) if (i == 1) tmm(0); WMS(i); tld(i); tmm(i);
#define PH(z) packh((z).x, (z).y)
        const float dt = bfr(expf(p_ldt));
        const float al = -bfr(expf(p_lar)) * dt * 1.4426950408889634f;
        const float th = p_aim * dt;
        const float th_ = th * 0.15915494309189535f;
        const float tl_ = fmaf(th, 0.15915494309189535f, -th_) + th * 6.4206382e-9f;
        auto anchor = [&](float s) {
            float f = th_ * s;
            f -= rintf(f);
            f = fmaf(tl_, s, f) * 6.283185307179586f;
            const float e = fex2(al * s);
            return cplx{e * __cosf(f), e * __sinf(f)};
        };
        const uint32_t cm = amax2(amax2(r_cr.x, r_cr.y), amax2(r_ci.x, r_ci.y));
        const uint32_t ex = __reduce_max_sync(0xffffffffu, __float_as_uint(fmaxf(fabsf(lo2f(cm)), fabsf(__uint_as_float(cm))))) & 0x7F800000u;
        const float scl = __uint_as_float(0x7F000000u - ex), inv = (dt + dt) * __uint_as_float(ex);
        const cplx C = cplx{p_cr * scl, p_ci * scl};
        const cplx z1 = anchor(1.f), z16 = anchor(16.f), z256 = anchor(256.f);
        {
            const cplx z32 = csq(z16), z48 = cmul(z32, z16), z64 = csq(z32), z128 = csq(z64), z192 = cmul(z128, z64);
            const uint32_t y[3] = {packh(z16.x, z16.y), packh(z32.x, z32.y), packh(z48.x, z48.y)};
            const uint32_t yp[3] = {packh(-z16.y, z16.x), packh(-z32.y, z32.x), packh(-z48.y, z48.x)};
            const uint32_t xx[3] = {packh(z64.x, z64.y), packh(z128.x, z128.y), packh(z192.x, z192.y)};
            sts32(ws, 0x00003C00u);
#pragma unroll
            for (int j = 0; j < 3; j++) sts32(ws + (1 + j) * 144, y[j]);
#pragma unroll
            for (int i = 0; i < 3; i++) {
                sts32(ws + (4 + 4 * i) * 144, xx[i]);
#pragma unroll
                for (int j = 0; j < 3; j++) sts32(ws + (5 + 4 * i + j) * 144, hcm(xx[i], y[j], yp[j]));
            }
        }
        ln1();
        WMS(0);
        const cplx z2 = csq(z1);
        {
            const cplx z3 = cmul(z2, z1), z4 = csq(z2), z8 = csq(z4);
            const cplx c4 = cmul(C, z4), c8 = cmul(C, z8), c12 = cmul(c8, z4);
            cz[0] = packh(C.x, -C.y); cz[1] = packh(c4.x, -c4.y); cz[2] = packh(c8.x, -c8.y); cz[3] = packh(c12.x, -c12.y);
            cq[0] = packh(C.y, C.x); cq[1] = packh(c4.y, c4.x); cq[2] = packh(c8.y, c8.x); cq[3] = packh(c12.y, c12.x);
            __syncwarp();
#pragma unroll
            for (int s = 0; s < 4; s++) ldsm_x4(afr[s], scr + (lr + 8 * (lm & 1)) * 144 + (lm >> 1) * 16 + 32 * s);
            const uint32_t y[3] = {PH(z1), PH(z2), PH(z3)};
#pragma unroll
            for (int tt = 0; tt < 2; tt++) {
                const int rg = tt ? 0 : 2;
#pragma unroll
                for (int i = 0; i < 2; i++) {
                    sts32(ws + rg * 1152 + (4 * i) * 144, cz[2 * tt + i]);
#pragma unroll
                    for (int j = 0; j < 3; j++) sts32(ws + rg * 1152 + (4 * i + 1 + j) * 144, hcn(y[j], cz[2 * tt + i], cq[2 * tt + i]));
                }
                if (tt == 0) tld(0);
            }
            TA(1)
        }
        const cplx z258 = cmul(z256, z2), z512 = csq(z256), z768 = cmul(z512, z256);
        {
            const uint32_t a0 = PH(z256), a1 = PH(z258);
#pragma unroll
            for (int i = 0; i < 4; i++) { sts32(ws + 1152 + (2 * i) * 144, hcn(a0, cz[i], cq[i])); sts32(ws + 1152 + (2 * i + 1) * 144, hcn(a1, cz[i], cq[i])); }
            TA(2)
        }
        {
            const uint32_t a0 = PH(z512), a1 = PH(z768);
#pragma unroll
            for (int i = 0; i < 4; i++) { sts32(ws + 2304 + i * 144, hcn(a0, cz[i], cq[i])); sts32(ws + 2304 + (4 + i) * 144, hcn(a1, cz[i], cq[i])); }
            TA(3)
        }
        const cplx z1024 = csq(z512);
        {
            const cplx zk[4] = {z1024, cmul(z1024, z256), csq(z768), cmul(z1024, z768)};
#pragma unroll
            for (int h = 0; h < 4; h++) {
                const uint32_t a0 = PH(zk[h]);
                sts32(ws + (2 * h) * 144, hcn(a0, cz[0], cq[0]));
                sts32(ws + (2 * h + 1) * 144, hcn(a0, cz[2], cq[2]));
            }
            tld(4);
            tmm(4);
        }
        const cplx z2048 = csq(z1024);
        const uint32_t last = __reduce_add_sync(0xffffffffu, __float_as_uint(fmaf(-C.y, z2048.y, fmaf(C.x, z2048.x, 12.f))));
        __syncwarp();
#pragma unroll
        for (int i = 0; i < 5; i++) *(uint2*)(sm + (scr - sb) + i * 256 + ((lane * 8) ^ (i == 1 ? 64 : 0))) = make_uint2(packh(acc[i][1], acc[i][0]), packh(acc[i][3], acc[i][2]));
        if (lane == 0) sts32(cb + XO_KLAST + 4 * w, last);
        asm volatile("cp.async.wait_group 0;" ::: "memory");
        if (warp != 7) CL_WAIT();
        named_bar(1 + wgi, 128);
        if (warp == 16) { mbar_wait(MB(MB_MG1), 0); mkc1(); }
        const uint32_t td = cb + XO_TD + 64 * 4, tf = cb + XO_TF - 32 * 4;
        auto fsum = [&](int off, uint32_t& r0, uint32_t& r1) {
            const unsigned char* p = sm + wgi * (4 * KSCR) + off;
            const uint2 a = *(const uint2*)p, b2 = *(const uint2*)(p + KSCR), c = *(const uint2*)(p + 2 * KSCR), d = *(const uint2*)(p + 3 * KSCR);
            const float2 u = hsum4(a.x, b2.x, c.x, d.x), v = hsum4(a.y, b2.y, c.y, d.y);
            r0 = pack2(u.x * inv, u.y * inv);
            r1 = pack2(v.x * inv, v.y * inv);
        };
        const int role = (w + wgi) & 3;
        const int fo = role ? (role + 1) * 256 + lane * 8 : (((g & 1) * 320) ^ (lm * 32)) + t * 8;
        uint32_t r[2];
        fsum(fo, r[0], r[1]);
        if (role == 0) {
            uint32_t q[2], v[4];
            fsum(fo + 128, q[0], q[1]);
            const uint32_t c[4] = {r[0], q[0], r[1], q[1]};
#pragma unroll
            for (int i = 0; i < 4; i++) v[i] = __shfl_sync(0xffffffffu, c[i], (lane + 31) & 31);
            if (lane == 0) mbar_arrive(MB(MB_KD));
#pragma unroll
            for (int i = 0; i < 4; i++) *(uint2*)(sm + (td - sb) + lane * 8 + i * 256) = make_uint2(__byte_perm(c[i], lane ? v[i] : i ? v[i - 1] : 0u, 0x5432), c[i]);
            if (lane == 0) { fixa = td + 256 * 4 + 2; fixv = v[3]; }
        } else if (role == 1) {
            const uint32_t v0 = __shfl_sync(0xffffffffu, r[0], (lane + 1) & 31), v1 = __shfl_sync(0xffffffffu, r[1], (lane + 1) & 31);
            if (lane == 0) mbar_arrive(MB(MB_KD));
#pragma unroll
            for (int h = 0; h < 2; h++) {
                const uint32_t dd = __byte_perm(r[h], 0, 0x3232);
                *(uint4*)(sm + (td - sb) + 1024 + lane * 16 + h * 512) = make_uint4(dd, dd, r[h], __byte_perm((h || lane == 31) ? v1 : v0, r[h], 0x5432));
            }
        } else {
            __syncwarp();
            if (lane == 0) mbar_arrive(MB(MB_KD));
            const uint32_t p = role == 2 ? tf + (64 + 32 * (t >> 1) + 2 * g + (t & 1)) * 4 : tf + 2 * UP + (64 + 16 * t + g) * 4, p1 = p + (role == 2 ? 64 : 32);
            const uint32_t k0 = r[0] >> 16, k1 = r[1] >> 16;
            sts16(p + UP, r[0]); sts16(p + UP + 6, r[0]); sts16(p1 + UP, r[1]); sts16(p1 + UP + 6, r[1]);
            sts16(p1 - 4, k1); sts16(p1 + 2, k1);
            const uint32_t dd = __byte_perm(r[0], 0, 0x3232);
            if (lane) { sts16(p - 4, k0); sts16(p + 2, k0); }
            else if (role == 2) {
                *(uint4*)(sm + (td - sb) + 512 * 4) = make_uint4(dd, dd, dd, r[0] & 0xFFFF0000u);
                fixa = td + 511 * 4; fixv = k0;
            } else {
                const uint4 kl4 = *(const uint4*)(sm + (cb - sb) + XO_KLAST);
                const uint32_t kl = f2bits((float)(int)(kl4.x + kl4.y + kl4.z + kl4.w - 128u * 0x41400000u) * 9.5367431640625e-7f * inv);
                sts16(tf + 127 * 4, dd); sts16(tf + 128 * 4 + 2, dd); sts32(cb + XO_K1024, dd);
                sts16(tf + 2 * UP + 127 * 4, kl); sts16(tf + 2 * UP + 128 * 4 + 2, kl);
            }
        }
        __syncwarp();
        rst();
        mod2();
        if (wgi == 3) {
            mbar_wait(MB(MB_KD), 0);
            mbar_wait(MB(MB_WM2), 0);
            PROXY_FENCE();
            if (lane == 0) tma2d(sb + w * 15360, w < 3 ? &tm_wg : &tm_wu, 40 * b, w < 3 ? 192 * w : 0, w < 3 ? MB(MB_WG) : MB(MB_WU));
            __syncwarp();
        }
    }
    if (has_ch) {
        conv_channel(sm, rk, fixa, fixv);
    } else {
        asm volatile("setmaxnreg.inc.sync.aligned.u32 88;");
        mbar_wait(MB(MB_WG), 0);
        mbar_wait(MB(MB_C2), 0);
    }
    {
    const int tid = fresh_tid(), warp = __shfl_sync(0xffffffffu, tid >> 5, 0), lane = tid & 31;
    const int g = lane >> 2, t = lane & 3, lr = lane & 7, lm = lane >> 3;
    __syncwarp();
    if (lane == 0) mbar_arrive(MB(MB_KD));
    uint32_t x1[10];
    uint32_t wf[9][4], wd[2][3][4];
    const int fmt = warp >> 2, fsl = warp & 3;
    auto ldwf = [&]() {
        const int half = lm & 1;
        const uint32_t base = (fmt == 4) ? ((half ? OFF_WU : OFF_WG) + 64) : ((fmt >> 1) * OFF_WU + ((2 * (fmt & 1) + half) << 4));
        const uint32_t wa = sb + base + (144 * fsl + lr + 8 * (lm >> 1)) * 80;
#pragma unroll
        for (int ks = 0; ks < 9; ks++) ldsm_x4_t(wf[ks], wa + ks * 1280);
    };
    if (warp < 16) {
        uint32_t bw[5], v[10];
#pragma unroll
        for (int j = 0; j < 5; j++) bw[j] = (g & 1) ? M.c2[4 * j + t].w : 0x3F803F80u;
        const uint32_t xa = sb + OFF_X + XI(warp >> 1) + (2 * (warp & 1) + (lm & 1)) * XG + lr * 80 + (lm >> 1) * 16;
        const uint32_t va = sb + OFF_V + (8 * (lm >> 1) + lr) * VP + 32 * warp + 16 * (lm & 1);
        ldsm_x4(x1, xa); ldsm_x4(x1 + 4, xa + 32); ldsm_x2(x1 + 8, xa + 64);
        mbar_wait(MB(MB_V), 0);
        ldsm_x4_t(v, va); ldsm_x4_t(v + 4, va + 16 * VP); ldsm_x2_t(v + 8, va + 32 * VP);
#pragma unroll
        for (int i = 0; i < 10; i++) x1[i] = add2(x1[i], (i >= 4 && cl == 14) ? 0u : v[i]);
        float c1[4] = {0.f, 0.f, 0.f, 0.f}, c2[4] = {0.f, 0.f, 0.f, 0.f}, c3[4] = {0.f, 0.f, 0.f, 0.f};
#pragma unroll
        for (int j = 0; j < 2; j++) {
            mma_bf16(c1, x1[4 * j], x1[4 * j + 1], x1[4 * j + 2], x1[4 * j + 3], bw[2 * j], bw[2 * j + 1]);
            mma_bf16(c2, x1[4 * j], x1[4 * j + 1], x1[4 * j + 2], x1[4 * j + 3], x1[4 * j], x1[4 * j + 2]);
            mma_bf16(c3, x1[4 * j], x1[4 * j + 1], x1[4 * j + 2], x1[4 * j + 3], x1[4 * j + 1], x1[4 * j + 3]);
        }
        mma_k8(c1, x1[8], x1[9], bw[4]); mma_k8(c2, x1[8], x1[9], x1[8]); mma_k8(c3, x1[8], x1[9], x1[9]);
        if (t == (g >> 1)) {
            float4* p = &S->acc2[256 * rk + 16 * warp + g];
            red4(p, c1[0], (g & 1) ? c2[1] : c2[0], c1[1]);
            red4(p + 8, c1[2], (g & 1) ? c3[3] : c3[2], c1[3]);
        }
        __syncwarp();
    }
    if (warp >= 16) { mbar_wait(MB(MB_WG), 0); mbar_wait(MB(MB_WU), 0); ldwf(); }
    if (warp >= 17) {
        if (warp == 17) mbar_wait(MB(MB_KD), 1);
        else named_bar(7, 96);
        PROXY_FENCE();
        if (lane < 3) tma2d(sb + OFF_WD + (3 * (warp - 17) + lane) * 5120, &tm_wd, 64 * (3 * (warp - 17) + lane), 40 * b, MB(MB_WD));
        __syncwarp();
    }
    uint32_t h2[10];
    uint32_t ta = sb + OFF_H2T + (16 * warp + (lane & 15)) * 80 + (lane >> 4) * 16;
    if (warp < 16) {
        const float4* ap = &S->acc2[256 * rk + 32 * (warp >> 1) + lane];
        if (warp < 8) { mbar_wait(MB(MB_WG), 0); ldwf(); }
        float4 s = ld_rlx4f(ap);
        uint2 kc[5];
#pragma unroll
        for (int j = 0; j < 5; j++) kc[j] = *(const uint2*)&M.c2[4 * j + t];
        mbar_wait(MB(MB_CW), 0);
        const float cw = M.cws[0], sbw = M.cws[1];
        uint32_t tk0 = (2047 - (((lane & 6) << 8) + ((lane & 24) << 3) + ((lane & 1) << 5) + RKT + (warp >> 1))) << 3;
        uint32_t ka = sb + OFF_MISC + (uint32_t)offsetof(Misc, key) + (32 * (warp >> 1) + lane) * 4;
        uint32_t rb = mapa(sb, 4 * (warp & 1) + t), cd = rb + OFF_MISC + (uint32_t)offsetof(Misc, cand2) + (8 * rk + (warp >> 1)) * 8;
        const int pj = lane >= 5, pc = lane - 5 * pj;
        uint4* dst = &S->h2c[(2 * (8 * rk + (warp >> 1)) + pj) * 72 + 5 * cl + pc];
        uint32_t pa = sb + OFF_H2T + 32 * (warp >> 1) * 80 + 16 * pc;
        asm volatile("" : "+r"(tk0), "+r"(ta), "+r"(ka), "+r"(rb), "+r"(cd), "+r"(pa), "+l"(dst));
        mbar_wait(MB(MB_KD), 1);
#pragma unroll 1
        for (int it = 0; it < SPIN_MAX && s.w != (float)NCL; it++) {
            if (s.w < (float)PQT) { const uint32_t c0 = clock(); for (int k = 0; k < 1024 && (uint32_t)clock() - c0 < PQD; k++) { } }
            s = ld_rlx4f(ap);
        }
        __syncwarp();
        if (warp == 0) named_arrive(7, 96);
        float meanb, rinv;
        ln_stats(s.x, s.y, meanb, rinv);
        const uint32_t rbits = __float_as_uint(fmaf(fmaf(-meanb, cw, s.z), rinv, sbw));
        const uint32_t key = ((rbits ^ (((int)rbits >> 31) | 0x80000000u)) & 0xFFFFC000u) | tk0;
        const uint32_t m0 = __reduce_max_sync(0xffffffffu, key);
        const uint32_t mr = pack2(meanb, rinv), rl = f2bits(rinv - hi2f(mr));
        const uint32_t m1 = __reduce_max_sync(0xffffffffu, key == m0 ? 0u : key);
        uint32_t st[2][2];
#pragma unroll
        for (int h = 0; h < 2; h++) { st[h][0] = __shfl_sync(0xffffffffu, mr, 16 * (warp & 1) + 8 * h + g); st[h][1] = __shfl_sync(0xffffffffu, rl, 16 * (warp & 1) + 8 * h + g); }
        if (lane < 4) sta2(cd, m0, m1 | 1u, rb + (MB(MB_KEY) - sb));
        sts32(ka, key);
        const int pr = __ffs(__ballot_sync(0xffffffffu, key == m0) | 0x80000000u) - 1, pr1 = __ffs(__ballot_sync(0xffffffffu, key == m1) | 0x80000000u) - 1;
#pragma unroll
        for (int i = 0; i < 10; i++)
            h2[i] = add2(mul2(norm2(x1[i], __byte_perm(st[i & 1][0], 0, 0x1010), __byte_perm(st[i & 1][0], 0, 0x3232), __byte_perm(st[i & 1][1], 0, 0x1010)), kc[i >> 1].x), kc[i >> 1].y);
        stsm_x4(ta, h2[0], h2[1], h2[2], h2[3]); stsm_x4(ta + 32, h2[4], h2[5], h2[6], h2[7]); stsm_x2(ta + 64, h2[8], h2[9]);
        __syncwarp();
        const int row = pj ? pr1 : pr;
        if (lane < 10 && (row >> 4) == (warp & 1) && pc < (cl < 14 ? 5 : 2)) {
            const uint4 a = lds128(pa + 80 * row);
            st_rlx4(dst, make_uint4(~a.x, ~a.y, ~a.z, ~a.w));
        }
        __syncwarp();
        named_arrive(6, 640);
        if (warp >= 8) { mbar_wait(MB(MB_WU), 0); ldwf(); }
    }
    auto outt = [&]() {
        if (warp < 16) {
            uint32_t o[10];
            if ((warp == cl || (warp == 15 && cl == 0)) && lane < 16) st_rlx4(&S->acc1[256 * rk + 16 * warp + lane], make_uint4(0, 0, 0, 0));
#pragma unroll
            for (int i = 0; i < 10; i++) o[i] = add2(x1[i], mul2(M.c2[4 * (i >> 1) + t].z, h2[i]));
            stsm_x4(ta + (OFF_OUT - OFF_H2T), o[0], o[1], o[2], o[3]); stsm_x4(ta + (OFF_OUT - OFF_H2T) + 32, o[4], o[5], o[6], o[7]); stsm_x2(ta + (OFF_OUT - OFF_H2T) + 64, o[8], o[9]);
        }
    };
    outt();
    uint4 gv = make_uint4(1, 1, 1, 1);
    const uint4* gp;
    uint32_t gdst;
    {
        const int gi = 32 * warp + lane, kk = (gi * 911) >> 16, seg = gi - 72 * kk;
        uint32_t ca = sb + OFF_MISC + (uint32_t)offsetof(Misc, cand2), sa = ca + 512 + 4 * (kk & 7);
        gp = &S->h2c[seg];
        gdst = sb + OFF_H2S + kk * (ROWP * 2) + seg * 16;
        asm volatile("" : "+r"(sa), "+r"(gdst), "+l"(gp));
        mbar_wait(MB(MB_KEY), 0);
        if (warp < 16) {
            const uint4 o = lds128(ca + 16 * lane), a = lds128(ca + 32 * warp), c = lds128(ca + 32 * warp + 16);
            const uint32_t mx = max(o.x, o.z), hd[4] = {a.x, a.z, c.x, c.z}, sc[4] = {a.y, a.w, c.y, c.w};
            uint32_t n[4];
#pragma unroll
            for (int q = 0; q < 4; q++) n[q] = __popc(__ballot_sync(0xffffffffu, mx > hd[q]));
            auto rank = [&](uint32_t k) {
                return (__popc(__ballot_sync(0xffffffffu, o.x > k)) + __popc(__ballot_sync(0xffffffffu, o.y > k))) + (__popc(__ballot_sync(0xffffffffu, o.z > k)) + __popc(__ballot_sync(0xffffffffu, o.w > k)));
            };
#pragma unroll
            for (int q = 0; q < 4; q++) {
                if (n[q] < 8) {
                    const uint32_t r0 = rank(hd[q]), r1 = rank(sc[q]);
                    if (r0 < 8) sts32(ca + 512 + 4 * r0, hd[q]);
                    if (r1 < 8) sts32(ca + 512 + 4 * r1, sc[q]);
                }
            }
        }
        named_bar(13, 640);
        if (warp < 18) {
            const uint32_t key = lds32(sa);
            gp += (((~key >> 2) & 0x3Eu) | ((~key >> 5) & 0x40u) | (key & 1u)) * 72;
            gv = ld_rlx4(gp);
        } else if (warp == 18) named_arrive(14, 64);
        else named_arrive(8, 64);
    }
    uint32_t wda = sb + OFF_WD + fmt * 5120 + lr * 128 + (((2 * fsl + (lm & 1)) ^ lr) << 4), wda2 = wda + (lm >> 1) * 1024;
    uint32_t ha = sb + OFF_H2S + lr * (ROWP * 2) + (144 * fsl) * 2 + lm * 16, fo = sb + OFF_FFR + ((fsl * 80 + 16 * fmt + g) * 8 + 2 * t) * 4;
    asm volatile("" : "+r"(ha), "+r"(fo));
    auto ldwd = [&]() {
#pragma unroll
        for (int i = 0; i < 2; i++)
#pragma unroll
            for (int ks = 0; ks < 3; ks++)
                if (i == 0 || warp < 16) ldsm_x4_t(wd[i][ks], ((ks < 2) ? wda2 : wda) + ks * 2048 + i * 5 * 5120);
    };
    mbar_wait(MB(MB_WD), 0);
    ldwd();
#pragma unroll 1
    for (int it = 0; it < SPIN_MAX && gv.x == 0u; it++) {
        gv = ld_rlx4(gp);
    }
    if (warp < 18) asm volatile("st.shared.v4.u32 [%0], {%1,%2,%3,%4};" ::"r"(gdst), "r"(~gv.x), "r"(~gv.y), "r"(~gv.z), "r"(~gv.w) : "memory");
    CBAR();
    float* ffr = (float*)(sm + OFF_FFR);
    auto ffn1 = [&]() {
        float acc[2][4] = {{0.f, 0.f, 0.f, 0.f}, {0.f, 0.f, 0.f, 0.f}};
#pragma unroll
        for (int k2 = 0; k2 < 5; k2++) {
            uint32_t hb[4];
            if (k2 < 4) ldsm_x4(hb, ha + k2 * 64); else ldsm_x2(hb, ha + 256);
            mma_bf16(acc[0], wf[2 * k2][0], wf[2 * k2][1], wf[2 * k2][2], wf[2 * k2][3], hb[0], hb[1]);
            if (k2 < 4) mma_bf16(acc[1], wf[2 * k2 + 1][0], wf[2 * k2 + 1][1], wf[2 * k2 + 1][2], wf[2 * k2 + 1][3], hb[2], hb[3]);
        }
        asm volatile("st.shared.v2.f32 [%0], {%1,%2};" ::"r"(fo), "f"(acc[0][0] + acc[1][0]), "f"(acc[0][1] + acc[1][1]) : "memory");
        asm volatile("st.shared.v2.f32 [%0+256], {%1,%2};" ::"r"(fo), "f"(acc[0][2] + acc[1][2]), "f"(acc[0][3] + acc[1][3]) : "memory");
    };
    ffn1();
    bf16(*act)[56] = (bf16(*)[56])(sm + OFF_ACT);
    auto gate = [&]() {
        if (warp < 12) {
            const int f = 4 * warp + lm, a = lr;
            float v = 0.f;
            if (warp < 10) {
                const float* pg = ffr + 32 * warp + (warp < 8 ? 0 : 256) + lane;
                const float* pu = pg + (warp < 8 ? 256 : 64);
                float gg = bfr((pg[0] + pg[640]) + (pg[1280] + pg[1920]));
                gg = bfr(silu(gg));
                const float uu = bfr((pu[0] + pu[640]) + (pu[1280] + pu[1920]));
                v = gg * uu;
            }
            act[a][f] = __ushort_as_bfloat16((unsigned short)f2bits(v));
        }
    };
    CBAR();
    gate();
    CBAR();
    auto ffn2 = [&](uint32_t buf, int mb) {
        uint32_t bq[3][2];
#pragma unroll
        for (int ks = 0; ks < 3; ks++) {
            bq[ks][0] = *(const uint32_t*)&act[g][16 * ks + 2 * t];
            bq[ks][1] = *(const uint32_t*)&act[g][16 * ks + 2 * t + 8];
        }
#pragma unroll
        for (int i = 0; i < 2; i++) {
            if (i == 0 || warp < 16) {
                float acc[4] = {0.f, 0.f, 0.f, 0.f};
#pragma unroll
                for (int ks = 0; ks < 3; ks++) mma_bf16(acc, wd[i][ks][0], wd[i][ks][1], wd[i][ks][2], wd[i][ks][3], bq[ks][0], bq[ks][1]);
                const int d = i ? 4 + (warp >> 2) : (warp * 13) >> 6, slot = i ? (warp & 3) : warp - 5 * d;
                const uint32_t rb = mapa(sb, d);
                sta2(rb + buf + (rk * 5 + slot) * 640 + lm * 160 + lr * 8, movm(pack2(acc[0], acc[1])), movm(pack2(acc[2], acc[3])), rb + (MB(mb) - sb));
            }
        }
    };
    ffn2(OFF_RS, MB_RS);
    named_bar(12, 672);
    const uint32_t redo = M.fin[8];
    if (redo) {
        const int gi = fresh_tid(), kk = (gi * 911) >> 16, seg = gi - 72 * kk;
        if (warp < 8) {
            const uint32_t key = M.fin[warp];
            if (MINE(key) && lane < (cl < 14 ? 5 : 2)) {
                const uint4 a = lds128(sb + OFF_H2T + ROW(key) * 80 + 16 * lane);
                st_rlx4(&S->h2c[(128 + warp) * 72 + 5 * cl + lane], make_uint4(~a.x, ~a.y, ~a.z, ~a.w));
            }
            __syncwarp();
        }
        if (warp < 18) {
            uint4 gv = make_uint4(0, 0, 0, 0);
#pragma unroll 1
            for (int it = 0; it < SPIN_MAX && gv.x == 0u; it++) gv = ld_rlx4(&S->h2c[128 * 72 + gi]);
            *(uint4*)(sm + OFF_H2S + kk * (ROWP * 2) + seg * 16) = make_uint4(~gv.x, ~gv.y, ~gv.z, ~gv.w);
        }
        CBAR();
        ffn1();
        CBAR();
        gate();
        CBAR();
        ffn2(OFF_RS + 80, MB_RS2);
        mbar_wait(MB(MB_RS2), 0);
    }
    {
        const int lane = fresh_tid() & 31;
        const int fP = min(warp < 8 ? 20 * cl + lane : 8 * (rk < 4 ? 5 * rk : 4 * rk + 4) + 4 * (warp - 8) + (lane & 3), D_ / 2);
        const uint32_t fgb = ld_rlx(&S->gb[fP]);
        const int ftok = warp < 8 ? warp : lane >> 2;
        const uint32_t fkey = M.fin[ftok];
        const bool fon = warp < 8 ? (MINE(fkey) && lane < 20 && fP < D_ / 2) : warp < (rk < 4 ? 18 : 16)
            ;
        const float rs = __fdividef(1.0f, 1.0f + __expf(-hi2f(fkey ^ (((int)~fkey >> 31) | 0x80000000u))));
        const uint32_t hv = lds32(sb + OFF_H2S + ftok * (ROWP * 2) + 4 * fP);
        float s0 = 0.f, s1 = 0.f, s2 = 1.0f, s3 = 0.f;
        if (warp >= 8) {
            if (fon) {
                mbar_wait(MB(MB_RS), 0);
                const uint32_t p = sb + OFF_RS + redo * 80 + ((warp - 8) >> 1) * 640 + (lane >> 3) * 160 + (lane & 7) * 8 + 4 * (warp & 1);
                uint32_t v[8];
#pragma unroll
                for (int i = 0; i < 8; i++) v[i] = lds32(p + i * 3200);
                s0 = ((lo2f(v[0]) + lo2f(v[1])) + (lo2f(v[2]) + lo2f(v[3]))) + ((lo2f(v[4]) + lo2f(v[5])) + (lo2f(v[6]) + lo2f(v[7])));
                s1 = ((hi2f(v[0]) + hi2f(v[1])) + (hi2f(v[2]) + hi2f(v[3]))) + ((hi2f(v[4]) + hi2f(v[5])) + (hi2f(v[6]) + hi2f(v[7])));
            }
        } else if (fon) {
            const uint32_t row = ROW(fkey);
            const unsigned short* vp = (const unsigned short*)(sm + OFF_V + 2 * lane * VP) + row;
            const uint32_t xv = add2(lds32(sb + OFF_X + XI(row >> 5) + ((row >> 3) & 3) * XG + (row & 7) * 80 + 4 * lane), (uint32_t)vp[0] | ((uint32_t)vp[VP / 2] << 16));
            s2 = (float)(((xv & 0xFFFFu) << 5) | 1u); s3 = (float)(xv >> 16);
            mbar_wait(MB(MB_OUT), 0);
        }
        if (fon) {
            const float4 o = atom4(&S->acc3[(fP >> 2) * 32 + 4 * ftok + (fP & 3)], s0, s1, s2, s3);
            const uint32_t z = __float_as_uint((o.z + s2) + 8388608.f), zh = __float_as_uint((o.w + s3) + 8388608.f);
            if (z & 16u) {
                const uint32_t xv = __byte_perm(z >> 5, zh, 0x5410);
                *(uint32_t*)(out + ((~fkey >> 3) & 2047u) * D_ + 2 * fP) = add2(xv, mul2(fgb, add2(hv, mul2(pack2(o.x + s0, o.y + s1), pack2(rs, rs)))));
            }
        }
    }
    }
    }
}

typedef CUresult (*EncodeFn)(CUtensorMap*, CUtensorMapDataType, cuuint32_t, void*, const cuuint64_t*, const cuuint64_t*,
                             const cuuint32_t*, const cuuint32_t*, CUtensorMapInterleave, CUtensorMapSwizzle,
                             CUtensorMapL2promotion, CUtensorMapFloatOOBfill);

static void make_map(EncodeFn fn, CUtensorMap* m, const void* ptr, uint64_t cols, uint64_t rows, uint32_t bc, uint32_t br,
                     CUtensorMapSwizzle sw, int five) {
    cuuint64_t dims[5] = {cols, rows, 4, 4, 288};
    cuuint64_t strides[4] = {cols * 2 * (five ? 32 : 1), cols * 2 * 512, cols * 2 * 64, cols * 2};
    cuuint32_t box[5] = {bc, br, 4, 4, 8};
    cuuint32_t es[5] = {1, 1, 1, 1, 1};
    CUresult rc = fn(m, CU_TENSOR_MAP_DATA_TYPE_BFLOAT16, five ? 5 : 2, (void*)ptr, dims, strides, box, es, CU_TENSOR_MAP_INTERLEAVE_NONE,
                     sw, (CUtensorMapL2promotion)(five || sw ? 0 : br == 72 ? L2M : L2P), CU_TENSOR_MAP_FLOAT_OOB_FILL_NONE);
    (void)rc;
}

static void launch(void* const* d_in, const int* in_sizes, int n_in, void* d_out, int out_size) {
    static EncodeFn enc = nullptr;
    static CUtensorMap tmm, tmg, tmu, tmd, tmo;
    static Scratch* sp = nullptr;
    static const void* cached[6] = {nullptr, nullptr, nullptr, nullptr, nullptr, nullptr};
    if (!enc) {
        cudaDriverEntryPointQueryResult qr;
        void* fn = nullptr;
        cudaGetDriverEntryPoint("cuTensorMapEncodeTiled", &fn, cudaEnableDefault, &qr);
        enc = (EncodeFn)fn;
        cudaFuncSetAttribute(clus_kernel, cudaFuncAttributeMaxDynamicSharedMemorySize, SMEM_TOTAL);
        cudaGetSymbolAddress((void**)&sp, g_s);
    }
    if (cached[0] != d_in[13] || cached[1] != d_in[9] || cached[2] != d_in[10] || cached[3] != d_in[11] || cached[4] != d_in[0] || cached[5] != d_out) {
        make_map(enc, &tmo, d_out, D_, 2, 40, 2, CU_TENSOR_MAP_SWIZZLE_NONE, 1);
        make_map(enc, &tmm, d_in[13], 6 * D_, D_, 40, 72, CU_TENSOR_MAP_SWIZZLE_NONE, 0);
        make_map(enc, &tmg, d_in[9], F_, D_, 40, 192, CU_TENSOR_MAP_SWIZZLE_NONE, 0);
        make_map(enc, &tmu, d_in[10], F_, D_, 40, 192, CU_TENSOR_MAP_SWIZZLE_NONE, 0);
        make_map(enc, &tmd, d_in[11], D_, F_, 64, 40, CU_TENSOR_MAP_SWIZZLE_128B, 0);
        cached[0] = d_in[13]; cached[1] = d_in[9]; cached[2] = d_in[10]; cached[3] = d_in[11]; cached[4] = d_in[0]; cached[5] = d_out;
    }
    clus_kernel<<<G_, NTHR, SMEM_TOTAL>>>((const bf16*)d_in[0], (const bf16*)d_in[1], (const bf16*)d_in[2], (const bf16*)d_in[3], (const bf16*)d_in[4],
                                          (const bf16*)d_in[5], (const bf16*)d_in[12], sp, (const bf16*)d_in[6], (const bf16*)d_in[8], (const bf16*)d_in[13],
                                          (bf16*)d_out, tmm, tmg, tmu, tmd, tmo);
}


static bool fits() {
    cudaFuncSetAttribute(clus_kernel, cudaFuncAttributeMaxDynamicSharedMemorySize, SMEM_TOTAL);
    cudaLaunchConfig_t cfg = {};
    cudaLaunchAttribute at;
    at.id = cudaLaunchAttributeClusterDimension;
    at.val.clusterDim.x = 8; at.val.clusterDim.y = 1; at.val.clusterDim.z = 1;
    cfg.gridDim = dim3(G_); cfg.blockDim = dim3(NTHR); cfg.dynamicSmemBytes = SMEM_TOTAL; cfg.attrs = &at; cfg.numAttrs = 1;
    int n = 0;
    const bool ok = cudaOccupancyMaxActiveClusters(&n, clus_kernel, &cfg) == cudaSuccess && n >= NCL;
    cudaGetLastError();
    return ok;
}
}
#undef L_
#undef D_
#undef N_
#undef F_
#undef G_
#undef NCL
#undef NTHR
#undef SPIN_MAX
#undef OFF_WG
#undef OFF_WU
#undef KSCR
#undef OFF_WM0
#undef OFF_STG
#undef OFF_MG2
#undef OFF_CH
#undef CHS
#undef UP
#undef UB
#undef XO_TF
#undef XO_U8
#undef XO_U16
#undef XO_ZA
#undef XO_ZB
#undef XO_ZC
#undef XO_ZD
#undef XO_TD
#undef XO_K1024
#undef XO_DSK
#undef XO_KLAST
#undef XO_MBU
#undef OFF_X
#undef XG
#undef XI
#undef XN
#undef OFF_V
#undef VP
#undef OFF_EK
#undef OFF_WM2
#undef OFF_MG1
#undef OFF_SC
#undef OFF_C1
#undef OFF_MISC
#undef OFF_WD
#undef OFF_H2T
#undef OFF_OUT
#undef ROWP
#undef OFF_H2S
#undef OFF_FFR
#undef OFF_ACT
#undef OFF_RS
#undef SMEM_TOTAL
#undef CBAR
#undef PROXY_FENCE
#undef D4
#undef O4
#undef WG_FENCE
#undef WG_COMMIT
#undef WG_WAIT
#undef TQ
#undef MB
#undef UF
#undef DS
#undef Q4
#undef RD_
#undef M2W
#undef WS
#undef WMS
#undef PQT
#undef PQD
#undef L2P
#undef L2M
#undef PDE
#undef WMD
#undef CWP
#undef CWD
#undef ROW
#undef RKT
#undef MINE
#undef CE
#undef POP
#undef CGT
#undef CL_ARRIVE
#undef CL_WAIT
#undef TA
#undef PH

namespace v4 {

#define L_ 2048
#define D_ 576
#define N_ 128
#define F_ 4608
#define G_ 128
#define NTHR 640
#define SPIN_MAX (1 << 18)
#define SENT 0u
#define HINT_N 182u

typedef __nv_bfloat16 bf16;

struct Scratch {
    uint4 xn[G_ * G_ * 10];
    uint4 v[G_ * D_ * 2];
    uint2 part[G_ * G_ * 9];
    uint4 h2w[L_ * 96];
    unsigned int rec[G_ * 8];
    unsigned int modw[6 * D_];
    unsigned int ticket[64];
    unsigned int cnt[64];
    unsigned int hint[64];
};
__device__ __align__(1024) Scratch g_s;

#define OFF_WG 0
#define OFF_WU 46080
#define OFF_CH 92160
#define CHS 20784
#define ULBO 656
#define XO_U8 6272
#define XO_U16 10368
#define XO_ZA 5248
#define XO_ZB 8448
#define XO_ZC 11648
#define XO_ZD 13824
#define XO_TD 16000
#define XO_TF 18624
#define XO_K1024 20672
#define KSCR 3456
#define OFF_TILE 196096
#define ROWP 584
#define OFF_MISC 214784
#define OFF_WD OFF_CH
#define OFF_H2T (OFF_CH + 3 * CHS)
#define OFF_H2S (OFF_H2T + 18688)
#define OFF_FFR (OFF_H2S + 9344)
#define OFF_FIN OFF_FFR
#define OFF_ACT (OFF_FFR + 10240)

struct Misc {
    __align__(16) uint4 sent[256];
    __align__(16) uint4 box[11 * 14];
    union {
        struct {
            __align__(16) float2 part[18][16];
            float rp[18][16];
        };
        struct {
            __align__(16) unsigned short st1[3][16];
            __align__(16) float p1[16][4], p2[16][4];
        };
    };
    __align__(16) bf16 cb1[D_], sb[D_], gb[D_];
    __align__(16) bf16 sc[D_];
    __align__(16) unsigned int cand[64], skey[16];
    __align__(16) float kinv[5][4], klast[5][4];
    unsigned int pk[4][8];
    __align__(16) uint4 st2[16];
    unsigned int wr[D_ / 2];
    float modx[32];
    unsigned int rank[16];
    volatile unsigned int flag;
    unsigned int e1cnt;
    unsigned long long mbar[5];
    unsigned int epoch;
};
#define SMEM_TOTAL (OFF_MISC + (int)sizeof(Misc))
static_assert(SMEM_TOTAL <= 232448, "smem");

__device__ __forceinline__ float lo2f(uint32_t w) { return __uint_as_float(w << 16); }
__device__ __forceinline__ float hi2f(uint32_t w) { return __uint_as_float(w & 0xFFFF0000u); }
__device__ __forceinline__ uint32_t pack2(float lo, float hi) { uint32_t r; asm("cvt.rn.bf16x2.f32 %0, %1, %2;" : "=r"(r) : "f"(hi), "f"(lo)); return r; }
__device__ __forceinline__ float bfr(float x) { return __uint_as_float(pack2(0.f, x)); }
__device__ __forceinline__ uint32_t f2bits(float x) { return pack2(x, 0.f); }
__device__ __forceinline__ uint32_t packh(float lo, float hi) { uint32_t r; asm("cvt.rn.f16x2.f32 %0, %1, %2;" : "=r"(r) : "f"(hi), "f"(lo)); return r; }
__device__ __forceinline__ float frcp(float x) { float r; asm("rcp.approx.ftz.f32 %0, %1;" : "=f"(r) : "f"(x)); return r; }
__device__ __forceinline__ float fsqrt(float x) { float r; asm("sqrt.approx.f32 %0, %1;" : "=f"(r) : "f"(x)); return r; }
__device__ __forceinline__ float fex2(float x) { float r; asm("ex2.approx.ftz.f32 %0, %1;" : "=f"(r) : "f"(x)); return r; }
__device__ __forceinline__ float silu(float x) { return __fdividef(x, 1.0f + __expf(-x)); }
__device__ __forceinline__ uint32_t add2(uint32_t a, uint32_t b) { uint32_t r; asm("add.rn.bf16x2 %0, %1, %2;" : "=r"(r) : "r"(a), "r"(b)); return r; }
__device__ __forceinline__ uint32_t sub2(uint32_t a, uint32_t b) { uint32_t r; asm("sub.rn.bf16x2 %0, %1, %2;" : "=r"(r) : "r"(a), "r"(b)); return r; }
__device__ __forceinline__ uint32_t mul2(uint32_t a, uint32_t b) { uint32_t r; asm("mul.rn.bf16x2 %0, %1, %2;" : "=r"(r) : "r"(a), "r"(b)); return r; }
__device__ __forceinline__ uint32_t fma2(uint32_t a, uint32_t b, uint32_t c) { uint32_t r; asm("fma.rn.bf16x2 %0, %1, %2, %3;" : "=r"(r) : "r"(a), "r"(b), "r"(c)); return r; }
__device__ __forceinline__ uint32_t norm2(uint32_t x, uint32_t m, uint32_t rh, uint32_t rl) { const uint32_t d = sub2(x, m); return fma2(d, rh, mul2(d, rl)); }

__device__ __forceinline__ void mma_bf16(float* c, uint32_t a0, uint32_t a1, uint32_t a2, uint32_t a3, uint32_t b0, uint32_t b1) {
    asm volatile("mma.sync.aligned.m16n8k16.row.col.f32.bf16.bf16.f32 {%0,%1,%2,%3}, {%4,%5,%6,%7}, {%8,%9}, {%0,%1,%2,%3};\n"
                 : "+f"(c[0]), "+f"(c[1]), "+f"(c[2]), "+f"(c[3]) : "r"(a0), "r"(a1), "r"(a2), "r"(a3), "r"(b0), "r"(b1));
}
__device__ __forceinline__ void mma_f16(float* c, const uint32_t* a, uint32_t b0, uint32_t b1) {
    asm volatile("mma.sync.aligned.m16n8k16.row.col.f32.f16.f16.f32 {%0,%1,%2,%3}, {%4,%5,%6,%7}, {%8,%9}, {%0,%1,%2,%3};\n"
                 : "+f"(c[0]), "+f"(c[1]), "+f"(c[2]), "+f"(c[3]) : "r"(a[0]), "r"(a[1]), "r"(a[2]), "r"(a[3]), "r"(b0), "r"(b1));
}
__device__ __forceinline__ void ldsm_x4(uint32_t* r, uint32_t addr) {
    asm volatile("ldmatrix.sync.aligned.m8n8.x4.shared.b16 {%0,%1,%2,%3}, [%4];" : "=r"(r[0]), "=r"(r[1]), "=r"(r[2]), "=r"(r[3]) : "r"(addr) : "memory");
}
__device__ __forceinline__ void ldsm_x4_t(uint32_t* r, uint32_t addr) {
    asm volatile("ldmatrix.sync.aligned.m8n8.x4.trans.shared.b16 {%0,%1,%2,%3}, [%4];" : "=r"(r[0]), "=r"(r[1]), "=r"(r[2]), "=r"(r[3]) : "r"(addr) : "memory");
}
__device__ __forceinline__ void stsm_x4(uint32_t addr, uint32_t r0, uint32_t r1, uint32_t r2, uint32_t r3) {
    asm volatile("stmatrix.sync.aligned.m8n8.x4.shared.b16 [%0], {%1,%2,%3,%4};" ::"r"(addr), "r"(r0), "r"(r1), "r"(r2), "r"(r3) : "memory");
}
__device__ __forceinline__ void stsm_x4_t(uint32_t addr, uint32_t r0, uint32_t r1, uint32_t r2, uint32_t r3) {
    asm volatile("stmatrix.sync.aligned.m8n8.x4.trans.shared.b16 [%0], {%1,%2,%3,%4};" ::"r"(addr), "r"(r0), "r"(r1), "r"(r2), "r"(r3) : "memory");
}
__device__ __forceinline__ uint32_t movm(uint32_t a) { uint32_t r; asm volatile("movmatrix.sync.aligned.m8n8.trans.b16 %0, %1;" : "=r"(r) : "r"(a)); return r; }
__device__ __forceinline__ uint32_t lds32(uint32_t a) { uint32_t v; asm volatile("ld.shared.u32 %0, [%1];" : "=r"(v) : "r"(a)); return v; }
__device__ __forceinline__ void sts32(uint32_t a, uint32_t v) { asm volatile("st.shared.u32 [%0], %1;" ::"r"(a), "r"(v) : "memory"); }
__device__ __forceinline__ void sts16(uint32_t a, uint32_t v) { asm volatile("st.shared.u16 [%0], %1;" ::"r"(a), "h"((unsigned short)v) : "memory"); }
__device__ __forceinline__ void named_bar(int id, int n) { asm volatile("bar.sync %0, %1;" ::"r"(id), "r"(n) : "memory"); }
__device__ __forceinline__ void named_arrive(int id, int n) { asm volatile("bar.arrive %0, %1;" ::"r"(id), "r"(n) : "memory"); }
#define CBAR() asm volatile("bar.sync 0, 640;" ::: "memory")
#define PROXY_FENCE() asm volatile("fence.proxy.async.shared::cta;" ::: "memory")

#define D4(d, o) "+f"(d[o]), "+f"(d[o + 1]), "+f"(d[o + 2]), "+f"(d[o + 3])
__device__ __forceinline__ void wg32(float* d, uint32_t a0, uint32_t a1, uint32_t a2, uint32_t a3, uint64_t desc) {
    asm volatile("wgmma.mma_async.sync.aligned.m64n32k16.f32.bf16.bf16 {%0,%1,%2,%3,%4,%5,%6,%7,%8,%9,%10,%11,%12,%13,%14,%15}, {%16,%17,%18,%19}, %20, 1, 1, 1, 0;"
                 : D4(d, 0), D4(d, 4), D4(d, 8), D4(d, 12) : "r"(a0), "r"(a1), "r"(a2), "r"(a3), "l"(desc));
}
__device__ __forceinline__ void wg48(float* d, uint32_t a0, uint32_t a1, uint32_t a2, uint32_t a3, uint64_t desc) {
    asm volatile("wgmma.mma_async.sync.aligned.m64n48k16.f32.bf16.bf16 {%0,%1,%2,%3,%4,%5,%6,%7,%8,%9,%10,%11,%12,%13,%14,%15,%16,%17,%18,%19,%20,%21,%22,%23}, {%24,%25,%26,%27}, %28, 1, 1, 1, 0;"
                 : D4(d, 0), D4(d, 4), D4(d, 8), D4(d, 12), D4(d, 16), D4(d, 20) : "r"(a0), "r"(a1), "r"(a2), "r"(a3), "l"(desc));
}
#define O4(d, o) "=f"(d[o]), "=f"(d[o + 1]), "=f"(d[o + 2]), "=f"(d[o + 3])
__device__ __forceinline__ void wg32z(float* d, uint32_t a0, uint32_t a1, uint32_t a2, uint32_t a3, uint64_t desc) {
    asm volatile("wgmma.mma_async.sync.aligned.m64n32k16.f32.bf16.bf16 {%0,%1,%2,%3,%4,%5,%6,%7,%8,%9,%10,%11,%12,%13,%14,%15}, {%16,%17,%18,%19}, %20, 0, 1, 1, 0;"
                 : O4(d, 0), O4(d, 4), O4(d, 8), O4(d, 12) : "r"(a0), "r"(a1), "r"(a2), "r"(a3), "l"(desc));
}
__device__ __forceinline__ void wg48z(float* d, uint32_t a0, uint32_t a1, uint32_t a2, uint32_t a3, uint64_t desc) {
    asm volatile("wgmma.mma_async.sync.aligned.m64n48k16.f32.bf16.bf16 {%0,%1,%2,%3,%4,%5,%6,%7,%8,%9,%10,%11,%12,%13,%14,%15,%16,%17,%18,%19,%20,%21,%22,%23}, {%24,%25,%26,%27}, %28, 0, 1, 1, 0;"
                 : O4(d, 0), O4(d, 4), O4(d, 8), O4(d, 12), O4(d, 16), O4(d, 20) : "r"(a0), "r"(a1), "r"(a2), "r"(a3), "l"(desc));
}
#define WG_FENCE() asm volatile("wgmma.fence.sync.aligned;" ::: "memory")
#define WG_COMMIT() asm volatile("wgmma.commit_group.sync.aligned;" ::: "memory")
#define WG_WAIT(n) asm volatile("wgmma.wait_group.sync.aligned " #n ";" ::: "memory")
#define TQ(p, k) p[2 * (k) + 1], p[2 * (k) + 2], p[2 * (k)], p[2 * (k) + 1]

__device__ __forceinline__ uint4 ld_nc4(const void* p) { uint4 v; asm volatile("ld.global.nc.v4.u32 {%0,%1,%2,%3}, [%4];" : "=r"(v.x), "=r"(v.y), "=r"(v.z), "=r"(v.w) : "l"(p)); return v; }
__device__ __forceinline__ unsigned short ld_nc16(const void* p) { unsigned short v; asm volatile("ld.global.nc.u16 %0, [%1];" : "=h"(v) : "l"(p)); return v; }
__device__ __forceinline__ uint32_t ld_nc(const void* p) { uint32_t v; asm volatile("ld.global.nc.u32 %0, [%1];" : "=r"(v) : "l"(p)); return v; }
__device__ __forceinline__ uint32_t ld_rlx(const unsigned int* p) { uint32_t v; asm volatile("ld.relaxed.gpu.global.u32 %0, [%1];" : "=r"(v) : "l"(p) : "memory"); return v; }
__device__ __forceinline__ uint2 ld_rlx2(const void* p) { uint2 v; asm volatile("ld.relaxed.gpu.global.v2.u32 {%0,%1}, [%2];" : "=r"(v.x), "=r"(v.y) : "l"(p) : "memory"); return v; }
__device__ __forceinline__ uint4 ld_rlx4(const void* p) { uint4 v; asm volatile("ld.relaxed.gpu.global.v4.u32 {%0,%1,%2,%3}, [%4];" : "=r"(v.x), "=r"(v.y), "=r"(v.z), "=r"(v.w) : "l"(p) : "memory"); return v; }
__device__ __forceinline__ void st_rlx(unsigned int* p, uint32_t v) { asm volatile("st.relaxed.gpu.global.u32 [%0], %1;" ::"l"(p), "r"(v) : "memory"); }
__device__ __forceinline__ void st_rlx2(void* p, uint32_t a, uint32_t b) { asm volatile("st.relaxed.gpu.global.v2.u32 [%0], {%1,%2};" ::"l"(p), "r"(a), "r"(b) : "memory"); }
__device__ __forceinline__ void st_rlx4(void* p, uint4 v) { asm volatile("st.relaxed.gpu.global.v4.u32 [%0], {%1,%2,%3,%4};" ::"l"(p), "r"(v.x), "r"(v.y), "r"(v.z), "r"(v.w) : "memory"); }
__device__ __forceinline__ void red_inc(unsigned int* p) { asm volatile("red.relaxed.gpu.global.add.u32 [%0], 1;" ::"l"(p) : "memory"); }

__device__ __forceinline__ void mbar_init(uint32_t a, int cnt) { asm volatile("mbarrier.init.shared::cta.b64 [%0], %1;" ::"r"(a), "r"(cnt) : "memory"); }
__device__ __forceinline__ void mbar_expect(uint32_t a, uint32_t bytes) { asm volatile("mbarrier.arrive.expect_tx.shared::cta.b64 _, [%0], %1;" ::"r"(a), "r"(bytes) : "memory"); }
__device__ __forceinline__ void mbar_wait(uint32_t a, uint32_t parity) {
    uint32_t ok = 0;
    int it = 0;
    do {
        asm volatile("{\n.reg .pred p;\nmbarrier.try_wait.parity.shared::cta.b64 p, [%1], %2;\nselp.u32 %0, 1, 0, p;\n}" : "=r"(ok) : "r"(a), "r"(parity) : "memory");
    } while (!ok && ++it < SPIN_MAX);
}
__device__ __forceinline__ void tma2d(uint32_t dst, const CUtensorMap* tm, int c0, int c1, uint32_t mbar) {
    asm volatile("cp.async.bulk.tensor.2d.shared::cluster.global.mbarrier::complete_tx::bytes [%0], [%1, {%3, %4}], [%2];"
                 ::"r"(dst), "l"(tm), "r"(mbar), "r"(c0), "r"(c1) : "memory");
}
__device__ __forceinline__ void bulk_s2g(void* dst, uint32_t src, uint32_t bytes) {
    asm volatile("cp.async.bulk.global.shared::cta.bulk_group [%0], [%1], %2;" ::"l"(dst), "r"(src), "r"(bytes) : "memory");
}
__device__ __forceinline__ uint32_t ld_acq(const unsigned int* p) { uint32_t v; asm volatile("ld.acquire.gpu.global.u32 %0, [%1];" : "=r"(v) : "l"(p) : "memory"); return v; }
__device__ __forceinline__ void bulk_pf(const void* src, uint32_t bytes) { asm volatile("cp.async.bulk.prefetch.L2.global [%0], %1;" ::"l"(src), "r"(bytes) : "memory"); }

__device__ __forceinline__ uint32_t wait_epoch(Misc& M) {
    uint32_t e = 0;
#pragma unroll 1
    for (int it = 0; it < (SPIN_MAX << 4) && e == 0; it++) e = *(volatile unsigned int*)&M.epoch;
    return e;
}
__device__ __forceinline__ void wait_reset(const unsigned int* ctr, uint32_t epoch) {
#pragma unroll 1
    for (int it = 0; it < SPIN_MAX; it++)
        if ((int)(ld_acq(ctr) - G_ * epoch) >= 0) break;
}
struct cplx { float x, y; };
__device__ __forceinline__ cplx cmul(cplx a, cplx b) { cplx r; r.x = a.x * b.x - a.y * b.y; r.y = a.x * b.y + a.y * b.x; return r; }
__device__ __forceinline__ cplx csq(cplx a) { cplx r; r.x = a.x * a.x - a.y * a.y; r.y = 2.0f * a.x * a.y; return r; }
__device__ __forceinline__ uint32_t hcm(uint32_t x, uint32_t y, uint32_t yp) {
    const __half2 X = *(const __half2*)&x, Y = *(const __half2*)&y, YP = *(const __half2*)&yp;
    const __half2 r = __hfma2(__high2half2(X), YP, __hmul2(__low2half2(X), Y));
    return *(const uint32_t*)&r;
}
__device__ __forceinline__ void ln_stats(float s1, float s2, float& meanb, float& rinv) {
    const float mean = s1 * (1.0f / D_);
    const float den = bfr(fsqrt(bfr(bfr(fmaxf(fmaf(-mean, mean, s2 * (1.0f / D_)), 0.f)) + 1e-5f)));
    meanb = bfr(mean);
    rinv = frcp(den);
}

__device__ __forceinline__ int fresh_tid() { int v; asm volatile("mov.u32 %0, %tid.x;" : "=r"(v)); return v; }
__device__ __forceinline__ void conv_channel(unsigned char* sm, Scratch* S, uint32_t gidx, uint32_t epoch, const void* pf_src,
                                             const CUtensorMap* tmu, int f0) {
    Misc& M = *(Misc*)(sm + OFF_MISC);
    const uint32_t sb = (uint32_t)__cvta_generic_to_shared(sm);
    const int tid = fresh_tid(), lane = tid & 31, g = lane >> 2, t = lane & 3, lr = lane & 7, lm = lane >> 3;
    const int warp_ = __shfl_sync(0xffffffffu, tid >> 5, 0), wgi = warp_ >> 2, w = warp_ & 3;
    const uint32_t cb = sb + OFF_CH + wgi * CHS, tag16 = (epoch % 65535u) + 1u;
    float D[16];
    uint32_t gaw, rcnt = 0;
    {
        {
            const uint32_t a8 = cb + lr * ULBO + (lm + 9) * 16 + w * 64, b8 = cb + XO_U8 + lm * 128 + lr * 16 + w * 512;
            const uint32_t a16 = cb + (((2 * lr) & 7) + (lm & 1)) * ULBO + (9 + (lr >> 2) + (lm & 2)) * 16 + w * 64;
            const uint32_t b16 = cb + XO_U16 + (lm & 1) * 512 + lr * 16 + (lm >> 1) * 128 + (w >> 1) * 1024 + (w & 1) * 256;
            uint32_t r[3][4];
            ldsm_x4_t(r[0], a8);
            ldsm_x4_t(r[1], a16);
            if (w < 2) ldsm_x4_t(r[2], a8 + 256);
            stsm_x4(b8, r[0][0], r[0][1], r[0][2], r[0][3]);
            stsm_x4(b16, r[1][0], r[1][1], r[1][2], r[1][3]);
            if (w < 2) stsm_x4(b8 + 2048, r[2][0], r[2][1], r[2][2], r[2][3]);
        }
        PROXY_FENCE();
        named_bar(1 + wgi, 128);
        {
            float Z8[24], Z16[16];
            const uint32_t pf = cb + XO_TF + (w >> 1) * 512 + (8 + 16 * (w & 1) + g - 2 * t) * 4;
            uint32_t p[13], q[9], z16[8];
#pragma unroll
            for (int s = 0; s < 9; s++) q[s] = lds32(pf + 1024 + s * 32);
            const uint32_t d8 = ((((cb + XO_U8) & 0x3FFFF) >> 4) | ((128 >> 4) << 16));
#define DZ(o) (((uint64_t)(512 >> 4) << 32) | (uint64_t)(d8 + (o)))
            WG_FENCE();
#pragma unroll
            for (int e = 0; e < 4; e++) {
                if (e == 0) wg32z(Z16, TQ(q, e), DZ(256 + 16));
                else wg32(Z16, TQ(q, e), DZ(256 - (e >> 1) * 64 + (1 - (e & 1)) * 16));
            }
            WG_COMMIT();
#pragma unroll
            for (int s = 0; s < 13; s++) p[s] = lds32(pf + s * 32);
            WG_WAIT(0);
#pragma unroll
            for (int i = 0; i < 8; i++) z16[i] = pack2(Z16[2 * i], Z16[2 * i + 1]);
            WG_FENCE();
#pragma unroll
            for (int e = 0; e < 6; e++) {
                if (e == 0) wg48z(Z8, TQ(p, e), DZ(16));
                else wg48(Z8, TQ(p, e), DZ(-(e >> 1) * 32 + (1 - (e & 1)) * 16));
            }
            WG_COMMIT();
            WG_WAIT(0);
            named_bar(1 + wgi, 128);
            const uint32_t za = cb + ((w >> 1) ? XO_ZB : XO_ZA) + lr * 400 + (1 + 2 * (w & 1) + (lm & 1) + 4 * (lm >> 1)) * 16;
#pragma unroll
            for (int i = 0; i < 3; i++)
                stsm_x4(za + i * 128, pack2(Z8[8 * i], Z8[8 * i + 1]), pack2(Z8[8 * i + 2], Z8[8 * i + 3]), pack2(Z8[8 * i + 4], Z8[8 * i + 5]), pack2(Z8[8 * i + 6], Z8[8 * i + 7]));
            const int Cz = 2 * (16 * (w & 1) + 8 * (lm & 1) + lr) + (lm >> 1);
            const uint32_t zc = cb + ((w >> 1) ? XO_ZD : XO_ZC) + (Cz & 7) * 272 + (1 + (Cz >> 3)) * 16;
#pragma unroll
            for (int ob = 0; ob < 2; ob++) stsm_x4(zc + ob * 128, z16[4 * ob], z16[4 * ob + 1], z16[4 * ob + 2], z16[4 * ob + 3]);
            if (lane < 8) *(uint4*)(sm + (cb - sb) + ((w < 2) ? (XO_ZA + w * 3200 + lane * 400) : (XO_ZC + (w - 2) * 2176 + lane * 272))) = make_uint4(0, 0, 0, 0);
        }
        gaw = ld_rlx(&S->modw[gidx]);
        if (tmu && wgi >= 2 && (tid & 127) == 96) {
            const uint32_t mbu = sb + OFF_MISC + (uint32_t)offsetof(Misc, mbar) + 24;
            if (wgi == 2) mbar_expect(mbu, 36864);
            tma2d(sb + OFF_WU + (wgi - 2) * 12288, tmu, f0, 192 * (wgi - 2), mbu);
        }
        __syncwarp();
        if ((tid & 127) == 64) rcnt = ld_rlx(S->cnt);
        {
#pragma unroll
            for (int i = 0; i < 16; i++) D[i] = 0.f;
            uint32_t pa = cb + XO_TD + (8 + 16 * w + g - 2 * t) * 4;
            uint32_t dlo = (((cb + 9 * 16) & 0x3FFFF) >> 4) | ((ULBO >> 4) << 16);
#define DS(o) (((uint64_t)(128 >> 4) << 32) | (uint64_t)(dlo + (o)))
#define KST (2 * (ULBO / 16))
            uint32_t pA[9], pB[9];
#pragma unroll
            for (int s = 0; s < 9; s++) pA[s] = lds32(pa + s * 32);
#pragma unroll 1
            for (int j = 0; j < 4; j++) {
                WG_FENCE();
#pragma unroll
                for (int q = 0; q < 4; q++) wg32(D, TQ(pA, q), DS((3 - q) * KST));
                WG_COMMIT();
                WG_WAIT(1);
#pragma unroll
                for (int s = 0; s < 9; s++) pB[s] = lds32(pa + 256 + s * 32);
                WG_FENCE();
#pragma unroll
                for (int q = 0; q < 4; q++) wg32(D, TQ(pB, q), DS((3 - q) * KST - 1));
                WG_COMMIT();
                WG_WAIT(1);
#pragma unroll
                for (int s = 0; s < 9; s++) pA[s] = lds32(pa + 512 + s * 32);
                dlo -= 2; pa += 512;
            }
            pB[1] = lds32(pa + 256 + 32); pB[2] = lds32(pa + 256 + 64);
            WG_FENCE();
#pragma unroll
            for (int q = 0; q < 4; q++) wg32(D, TQ(pA, q), DS((3 - q) * KST));
            wg32(D, pB[1], pB[2], pA[8], pB[1], DS(3 * KST - 1));
            WG_COMMIT();
        }
        if (tid == 128) bulk_pf(pf_src, 16 * D_ * 2);
        if ((tid & 127) == 64) {
#pragma unroll 1
            for (int it = 0; it < SPIN_MAX && (int)(rcnt - G_ * epoch) < 0; it++) rcnt = ld_rlx(S->cnt);
        }
    }
    {
        named_bar(1 + wgi, 128);
        {
            const uint4* pq = M.box + (6 + g - 2 * t);
#define QM(q) (q).x, (q).y, (q).z, (q).w
            uint32_t bA[2][6], bB[2][6], bC[3][4], bD[2][4], bU[2][4];
            const uint32_t k2 = lds32(cb + XO_K1024);
            uint32_t ofs[3];
#pragma unroll
            for (int d = 0; d < 3; d++) ofs[d] = cb + ((w - d) < 0 ? 0 : 16) + (lr + 8 * (lm >> 1)) * 16;
#define COL(d) (2 * ((w - (d)) & 3) + (lm & 1))
            WG_WAIT(0);
            uint4 m[4];
#pragma unroll
            for (int d = 0; d < 2; d++) {
                const uint32_t a = XO_ZA + COL(d) * 400 + ofs[d];
                ldsm_x4(bA[d], a); ldsm_x4(bB[d], a + 3200);
                uint32_t r[4];
                ldsm_x4(r, a + 256 + (lm >> 1) * (3200 - 128));
                bA[d][4] = r[0]; bA[d][5] = r[1]; bB[d][4] = r[2]; bB[d][5] = r[3];
            }
#pragma unroll
            for (int i = 0; i < 4; i++) m[i] = pq[14 * i];
#pragma unroll
            for (int d = 0; d < 2; d++)
#pragma unroll
                for (int c = 0; c < 3; c++) mma_bf16(D + 4 + 4 * c, QM(m[d]), bA[d][2 * c], bA[d][2 * c + 1]);
#pragma unroll
            for (int d = 0; d < 3; d++) ldsm_x4(bC[d], XO_ZC + COL(d) * 272 + ofs[d]);
#pragma unroll
            for (int d = 0; d < 2; d++)
#pragma unroll
                for (int c = 0; c < 3; c++) mma_bf16(D + 4 + 4 * c, QM(m[2 + d]), bB[d][2 * c], bB[d][2 * c + 1]);
#pragma unroll
            for (int i = 0; i < 3; i++) m[i] = pq[14 * (4 + i)];
#pragma unroll
            for (int d = 0; d < 2; d++) { ldsm_x4(bD[d], XO_ZD + COL(d) * 272 + ofs[d]); ldsm_x4(bU[d], COL(d) * ULBO + 128 + ofs[d]); }
#pragma unroll
            for (int d = 0; d < 3; d++)
#pragma unroll
                for (int c = 0; c < 2; c++) mma_bf16(D + 8 + 4 * c, QM(m[d]), bC[d][2 * c], bC[d][2 * c + 1]);
#pragma unroll
            for (int i = 0; i < 4; i++) m[i] = pq[14 * (7 + i)];
#pragma unroll
            for (int d = 0; d < 2; d++)
#pragma unroll
                for (int c = 0; c < 2; c++) mma_bf16(D + 8 + 4 * c, QM(m[d]), bD[d][2 * c], bD[d][2 * c + 1]);
#pragma unroll
            for (int d = 0; d < 2; d++) {
                m[2 + d].x &= k2; m[2 + d].y &= k2; m[2 + d].z &= k2; m[2 + d].w &= k2;
#pragma unroll
                for (int c = 0; c < 2; c++) mma_bf16(D + 8 + 4 * c, QM(m[2 + d]), bU[d][2 * c], bU[d][2 * c + 1]);
            }
        }
        {
#pragma unroll 1
            for (int it = 0; it < SPIN_MAX && (gaw >> 16) != tag16; it++) gaw = ld_rlx(&S->modw[gidx]);
            const uint32_t ga2 = __byte_perm(gaw, 0, 0x1010), dk2 = M.pk[3][wgi];
            const uint32_t ua = cb + (2 * w + (lm & 1)) * ULBO + (9 + lr + 8 * (lm >> 1)) * 16;
            const uint32_t ya = cb + XO_TD + w * 1024;
            const uint32_t sa = ya + (lr + 8 * (lm >> 1)) * 32 + (((lm & 1) ^ ((lane >> 2) & 1)) << 4);
#pragma unroll
            for (int cc = 0; cc < 2; cc++) {
                uint32_t u[4], v[4];
                ldsm_x4_t(u, ua + cc * 256);
#pragma unroll
                for (int m = 0; m < 4; m++) {
                    const int c = 2 * cc + (m >> 1), h = m & 1;
                    v[m] = ~mul2(ga2, add2(pack2(D[4 * c + 2 * h], D[4 * c + 2 * h + 1]), mul2(u[m], dk2)));
                }
                stsm_x4_t(sa + cc * 512, v[0], v[1], v[2], v[3]);
            }
            __syncwarp();
            const int sw = (lane >> 3) & 1;
            const uint32_t vo = (uint32_t)(((4 * (lane >> 1) + w) * D_ + gidx - 2 * D_) * 32 + (lane & 1) * 16);
            const unsigned char* yp = sm + (ya - sb) + (lane >> 1) * 32 + (lane & 1) * 8;
#pragma unroll
            for (int i = 0; i < 2; i++) {
                const uint2 A = *(const uint2*)(yp + i * 512 + (sw << 4)), B = *(const uint2*)(yp + i * 512 + ((sw ^ 1) << 4));
                st_rlx4((char*)S->v + vo + i * (64 * D_ * 32), make_uint4(A.x, B.x, A.y, B.y));
            }
        }
    }
}

__global__ void __launch_bounds__(NTHR, 1)
mega_kernel(const bf16* __restrict__ x, const bf16* __restrict__ logAr, const bf16* __restrict__ Aim,
            const bf16* __restrict__ Cr, const bf16* __restrict__ Ci, const bf16* __restrict__ logdt, const bf16* __restrict__ c_in,
            Scratch* __restrict__ S, const bf16* __restrict__ Dskip, const bf16* __restrict__ w_r, const bf16* __restrict__ w_down,
            bf16* __restrict__ out,
            const __grid_constant__ CUtensorMap tm_wm, const __grid_constant__ CUtensorMap tm_wg, const __grid_constant__ CUtensorMap tm_wu,
            const __grid_constant__ CUtensorMap tm_wd, const __grid_constant__ CUtensorMap tm_wd32,
            const __grid_constant__ CUtensorMap tm_wg32, const __grid_constant__ CUtensorMap tm_wu32) {
    extern __shared__ __align__(1024) unsigned char sm[];
    Misc& M = *(Misc*)(sm + OFF_MISC);
    const uint32_t sb = (uint32_t)__cvta_generic_to_shared(sm);
    const int tid = threadIdx.x, warp = __shfl_sync(0xffffffffu, tid >> 5, 0), lane = tid & 31;
    const int g = lane >> 2, t = lane & 3, lr = lane & 7, lm = lane >> 3;
    const int wgi = warp >> 2, w = warp & 3;
    const int b = blockIdx.x;
    const int nch = 5 - (b & 1), cs = 9 * (b >> 1) + 5 * (b & 1);
    const int f0 = 72 * (b >> 1) + 32 * (b & 1), nf = 32 + 8 * (b & 1);
    const bool has_ch = wgi < nch;
    const uint32_t mb0 = sb + OFF_MISC + offsetof(Misc, mbar), mb_wm = mb0, mb_wg = mb0 + 16, mb_wu = mb0 + 24, mb_wd = mb0 + 32;
    const uint32_t cb = sb + OFF_CH + wgi * CHS;

    if (wgi == 3) {
        M.sent[tid - 384] = make_uint4(SENT, SENT, SENT, SENT);
        M.sent[tid - 256] = make_uint4(SENT, SENT, SENT, SENT);
        if (tid == 384) {
            M.epoch = 0u; M.flag = 0u; M.e1cnt = 0u;
#pragma unroll
            for (int i = 0; i < 5; i++) mbar_init(mb0 + 8 * i, 1);
        }
        PROXY_FENCE();
        __syncwarp();
        if (warp == 12) { named_arrive(8, 160); if (b & 1) named_arrive(14, 64); }
        if (warp != 15) named_arrive(9, 128);
    }
    unsigned short r_ldt = 0, r_lar = 0, r_aim = 0, r_cr = 0, r_ci = 0;
    if (has_ch) {
        const int d = cs + wgi, n = d * N_ + (tid & 127);
        r_ldt = ld_nc16((const unsigned short*)logdt + d);
        r_lar = ld_nc16((const unsigned short*)logAr + n);
        r_aim = ld_nc16((const unsigned short*)Aim + n);
        r_cr = ld_nc16((const unsigned short*)Cr + n);
        r_ci = ld_nc16((const unsigned short*)Ci + n);
    } else {
        const unsigned short* cp = (const unsigned short*)c_in + (tid - 512);
        r_ldt = ld_nc16(cp); r_lar = ld_nc16(cp + 128); r_aim = ld_nc16(cp + 256); r_cr = ld_nc16(cp + 384);
        if (tid < 576) r_ci = ld_nc16(cp + 512);
    }
    uint4 xr[9];
    if (wgi == 4) {
        const uint4* p = (const uint4*)(x + (size_t)16 * b * D_) + (tid - 512);
#pragma unroll
        for (int i = 0; i < 9; i++) xr[i] = ld_nc4(p + 128 * i);
    }
    uint32_t wrv = 0;
    if (tid >= 128 && tid < 416) wrv = ld_nc((const uint32_t*)w_r + (tid - 128));
    if (warp == 2 && lane < nch) M.pk[3][lane] = (uint32_t)ld_nc16((const unsigned short*)Dskip + cs + lane) * 0x10001u;
    if (tid == 384) {
        const unsigned int tk = atomicAdd(S->ticket, 1u);
        *(volatile unsigned int*)&M.epoch = (tk >> 7) + 1u;
    }
    if (has_ch) {
        for (int i = tid & 127; i < 296; i += 128) *(uint4*)(sm + OFF_CH + wgi * CHS + XO_TD + i * 16) = make_uint4(0, 0, 0, 0);
    }
    if (tid < 154) {
        const int idx = (tid * 4682) >> 16, dl = tid - 14 * idx - 6;
        const int a = (0x44332221100ull >> (4 * idx)) & 7, d = (0x10102101010ull >> (4 * idx)) & 3;
        const int lo = (0x35c36 >> (4 * a)) & 15, wd = (0x16824 >> (4 * a)) & 15;
        const uint32_t one = (a == 4) ? 0xFFFFu : 0x3F80u;
        auto mk = [&](int l) { return (((unsigned)(l - lo) <= (unsigned)wd) ? one : 0u) | (((unsigned)(l - 1 - lo) <= (unsigned)wd) ? (one << 16) : 0u); };
        const int l0 = 16 * d + dl;
        M.box[tid] = make_uint4(mk(l0), mk(l0 + 8), mk(l0 - 8), mk(l0));
    }
    uint32_t xo[6];
#pragma unroll
    for (int i = 0; i < 6; i++) {
        const int ch = 16 * (warp + 16 * (i >> 1)) + 8 * (i & 1) + g;
        const int pr = (ch * 7282) >> 16, rm = ch - 9 * pr, hi = rm >= 5;
        xo[i] = (uint32_t)((((2 * pr + hi) * G_ + b) * 5 + rm - 5 * hi) * 32 + t * 8);
    }
    auto e1_store = [&]() {
        named_bar(11, 640);
        uint32_t mm[2], rhh[2], rll[2];
#pragma unroll
        for (int h = 0; h < 2; h++) {
            mm[h] = ((const uint32_t*)M.st1[0])[t + 4 * h]; rhh[h] = ((const uint32_t*)M.st1[1])[t + 4 * h]; rll[h] = ((const uint32_t*)M.st1[2])[t + 4 * h];
        }
        const uint32_t ta = sb + OFF_TILE + (lr + 8 * (lm & 1)) * (ROWP * 2) + (lm >> 1) * 16 + warp * 32;
#pragma unroll
        for (int i = 0; i < 3; i++) {
            if (i < 2 || warp < 4) {
                uint32_t r[4];
                ldsm_x4_t(r, ta + i * 512);
#pragma unroll
                for (int h = 0; h < 2; h++)
                    st_rlx2((char*)S->xn + xo[2 * i + h], ~norm2(r[2 * h], mm[0], rhh[0], rll[0]), ~norm2(r[2 * h + 1], mm[1], rhh[1], rll[1]));
            }
        }
        __syncwarp();
        if (lane == 0 && atomicAdd(&M.e1cnt, 1u) == 15u) red_inc(S->hint);
    };
    const float p_ldt = lo2f(r_ldt), p_lar = lo2f(r_lar), p_aim = lo2f(r_aim), p_cr = lo2f(r_cr), p_ci = lo2f(r_ci);
    cplx z1 = {0.f, 0.f}, z16 = z1, z256 = z1, C = z1;
    const uint32_t scr = cb + w * KSCR, ws = scr + lane * 4;
    float acc[5][4];
    uint32_t afr[4][4], cz[4];
    cplx z2 = {0.f, 0.f};
    const uint32_t ba = scr + lr * 144 + lm * 16;
    auto tile = [&](float* c, int rg) {
        __syncwarp();
        c[0] = c[1] = c[2] = c[3] = 0.f;
        uint32_t bb[2][4];
        ldsm_x4(bb[0], ba + rg * 1152);
        ldsm_x4(bb[1], ba + rg * 1152 + 64);
        mma_f16(c, afr[0], bb[0][0], bb[0][1]);
        mma_f16(c, afr[1], bb[0][2], bb[0][3]);
        mma_f16(c, afr[2], bb[1][0], bb[1][1]);
        mma_f16(c, afr[3], bb[1][2], bb[1][3]);
    };
#define CJ(z) packh((z).x, -(z).y)
#define CJP(z) packh((z).y, (z).x)
    uint32_t ex = 0;
    if (has_ch) {
        const float dt = bfr(expf(p_ldt));
        const float al = -bfr(expf(p_lar)) * dt * 1.4426950408889634f;
        const float th = p_aim * dt;
        const float th_ = th * 0.15915494309189535f;
        const float tl_ = fmaf(th, 0.15915494309189535f, -th_) + th * 6.4206382e-9f;
        auto anchor = [&](float s) {
            float f = th_ * s;
            f -= rintf(f);
            f = fmaf(tl_, s, f) * 6.283185307179586f;
            const float e = fex2(al * s);
            return cplx{e * __cosf(f), e * __sinf(f)};
        };
        const float cx = p_cr * dt * 2.0f, cy = p_ci * dt * 2.0f;
        ex = __reduce_max_sync(0xffffffffu, __float_as_uint(fmaxf(fabsf(cx), fabsf(cy)))) >> 23;
        const float scl = __uint_as_float((254u - ex) << 23);
        C = cplx{cx * scl, cy * scl};
        z1 = anchor(1.f); z16 = anchor(16.f); z256 = anchor(256.f);
            {
                const cplx z32 = csq(z16), z48 = cmul(z32, z16), z64 = csq(z32), z128 = csq(z64), z192 = cmul(z128, z64);
                const uint32_t y[3] = {packh(z16.x, z16.y), packh(z32.x, z32.y), packh(z48.x, z48.y)};
                const uint32_t yp[3] = {packh(-z16.y, z16.x), packh(-z32.y, z32.x), packh(-z48.y, z48.x)};
                const uint32_t xx[3] = {packh(z64.x, z64.y), packh(z128.x, z128.y), packh(z192.x, z192.y)};
                sts32(ws, 0x00003C00u);
#pragma unroll
                for (int j = 0; j < 3; j++) sts32(ws + (1 + j) * 144, y[j]);
#pragma unroll
                for (int i = 0; i < 3; i++) {
                    sts32(ws + (4 + 4 * i) * 144, xx[i]);
#pragma unroll
                    for (int j = 0; j < 3; j++) sts32(ws + (5 + 4 * i + j) * 144, hcm(xx[i], y[j], yp[j]));
                }
            }
    }
    if (wgi == 4) {
        if (!has_ch) {
            const int i = tid - 512;
            ((unsigned short*)M.sc)[i] = (unsigned short)f2bits(silu(lo2f(r_ldt)));
            ((unsigned short*)M.sc)[i + 128] = (unsigned short)f2bits(silu(lo2f(r_lar)));
            ((unsigned short*)M.sc)[i + 256] = (unsigned short)f2bits(silu(lo2f(r_aim)));
            ((unsigned short*)M.sc)[i + 384] = (unsigned short)f2bits(silu(lo2f(r_cr)));
            if (i < 64) ((unsigned short*)M.sc)[i + 512] = (unsigned short)f2bits(silu(lo2f(r_ci)));
            if (warp == 16) {
                named_bar(14, 64);
                if (lane == 0) {
                    mbar_expect(mb_wm, 36864);
#pragma unroll
                    for (int k = 0; k < 3; k++) tma2d(sb + OFF_WU + k * 12288, &tm_wm, 32 * (b >> 1), 192 * k, mb_wm);
                }
                __syncwarp();
            }
        }
#pragma unroll
        for (int i = 0; i < 9; i++) {
            const int c = tid - 512 + 128 * i, rr = (c * 911) >> 16;
            *(uint4*)(sm + OFF_TILE + rr * (ROWP * 2 - 1152) + c * 16) = xr[i];
        }
        named_bar(8, 160);
        {
            float c1[4] = {0.f, 0.f, 0.f, 0.f}, cl[4] = {0.f, 0.f, 0.f, 0.f}, chh[4] = {0.f, 0.f, 0.f, 0.f};
            const uint32_t a0 = sb + OFF_TILE + (lane & 15) * (ROWP * 2) + (lane >> 4) * 16 + w * 288;
            uint32_t a[9][4];
#pragma unroll
            for (int ks = 0; ks < 9; ks++) ldsm_x4(a[ks], a0 + ks * 32);
#pragma unroll
            for (int ks = 0; ks < 9; ks++) {
                mma_bf16(c1, a[ks][0], a[ks][1], a[ks][2], a[ks][3], 0x3F803F80u, 0x3F803F80u);
                mma_bf16(cl, a[ks][0], a[ks][1], a[ks][2], a[ks][3], a[ks][0], a[ks][2]);
                mma_bf16(chh, a[ks][0], a[ks][1], a[ks][2], a[ks][3], a[ks][1], a[ks][3]);
            }
            if (t == 0) { M.p1[g][w] = c1[0]; M.p1[g + 8][w] = c1[2]; }
            if (t == (g >> 1)) { M.p2[g][w] = (g & 1) ? cl[1] : cl[0]; M.p2[g + 8][w] = (g & 1) ? chh[3] : chh[2]; }
        }
        named_bar(5, 128);
        if (warp == 16) {
            const float4 q1 = *(const float4*)M.p1[lane & 15], q2 = *(const float4*)M.p2[lane & 15];
            float meanb, rinv;
            ln_stats((q1.x + q1.y) + (q1.z + q1.w), (q2.x + q2.y) + (q2.z + q2.w), meanb, rinv);
            const float rh = bfr(rinv);
            if (lane < 16) { M.st1[0][lane] = (unsigned short)f2bits(meanb); M.st1[1][lane] = (unsigned short)f2bits(rh); M.st1[2][lane] = (unsigned short)f2bits(rinv - rh); }
        }
        __syncwarp();
        named_arrive(11, 640);
    }
    auto publish_reset = [&]() {
        if (tid == 480) {
            asm volatile("cp.async.bulk.wait_group 0;" ::: "memory");
            asm volatile("fence.proxy.async;" ::: "memory");
            red_inc(S->cnt);
        }
    };
    uint32_t epoch = 0, tag16 = 0, pre = 0;
    auto mod_tile = [&](int rd) {
        const uint32_t* s2 = (const uint32_t*)M.sc + 144 * (w >> 1) + t;
        uint32_t bb[18][2];
#pragma unroll
        for (int ks = 0; ks < 18; ks++) { bb[ks][0] = (g == 0) ? s2[8 * ks] : 0u; bb[ks][1] = (g == 0) ? s2[8 * ks + 4] : 0u; }
        float acc[2][4] = {{0.f, 0.f, 0.f, 0.f}, {0.f, 0.f, 0.f, 0.f}};
        const int row = lr + 8 * (lm >> 1);
        const uint32_t wa = sb + OFF_WU + (288 * (w >> 1) + row) * 64 + ((((2 * (w & 1) + (lm & 1)) ^ (row >> 1)) & 3) << 4);
        mbar_wait(mb_wm + 8 * rd, 0);
        if (rd == 0)
#pragma unroll
        for (int kb = 0; kb < 2; kb++) {
            uint32_t a[9][4];
#pragma unroll
            for (int ks = 0; ks < 9; ks++) ldsm_x4_t(a[ks], wa + (9 * kb + ks) * 1024);
#pragma unroll
            for (int ks = 0; ks < 9; ks++) mma_bf16(acc[ks & 1], a[ks][0], a[ks][1], a[ks][2], a[ks][3], bb[9 * kb + ks][0], bb[9 * kb + ks][1]);
        }
        const float v0 = acc[0][0] + acc[1][0], v1 = acc[0][2] + acc[1][2];
        float* mx = M.modx + 16 * (w & 1) + g;
        if (w >= 2 && t == 0) { mx[0] = v0; mx[8] = v1; }
        named_bar(5, 128);
        if (w < 2 && t == 0) {
            unsigned int* mp = &S->modw[32 * ((b >> 1) + 64 * rd) + 16 * w + g];
            st_rlx(mp, f2bits(v0 + mx[0]) | (tag16 << 16));
            st_rlx(mp + 8, f2bits(v1 + mx[8]) | (tag16 << 16));
        }
        if (rd == 0 && w < 2 && b < 108) {
            named_bar(7, 64);
            if (tid == 512) red_inc(S->hint);
        }
    };
    if (has_ch) {
        {
            z2 = csq(z1);
            const cplx z3 = cmul(z2, z1), z4 = csq(z2), z8 = csq(z4);
            const cplx c4 = cmul(C, z4), c8 = cmul(C, z8), c12 = cmul(c8, z4);
            cz[0] = packh(C.x, -C.y); cz[1] = packh(c4.x, -c4.y); cz[2] = packh(c8.x, -c8.y); cz[3] = packh(c12.x, -c12.y);
            __syncwarp();
#pragma unroll
            for (int s = 0; s < 4; s++) ldsm_x4(afr[s], scr + (lr + 8 * (lm & 1)) * 144 + (2 * s + (lm >> 1)) * 16);
            {
                const uint32_t y[3] = {CJ(z1), CJ(z2), CJ(z3)}, yp[3] = {CJP(z1), CJP(z2), CJP(z3)};
#pragma unroll
                for (int tt = 0; tt < 2; tt++) {
                    const int rg = tt ? 0 : 2;
#pragma unroll
                    for (int i = 0; i < 2; i++) {
                        sts32(ws + rg * 1152 + (4 * i) * 144, cz[2 * tt + i]);
#pragma unroll
                        for (int j = 0; j < 3; j++) sts32(ws + rg * 1152 + (4 * i + 1 + j) * 144, hcm(cz[2 * tt + i], y[j], yp[j]));
                    }
                    tile(acc[tt], rg);
                }
            }
            if (tid >= 128 && tid < 416) M.wr[tid - 128] = wrv;
            if (wgi < 4) e1_store();
    if (warp == 15) {
        named_bar(9, 128);
        if (lane == 0) {
#pragma unroll 1
            for (int i = 0; i < 5; i++) {
                bulk_s2g((char*)&S->v[(size_t)b * 1152] + i * 4096, sb + OFF_MISC, i < 4 ? 4096 : 2048);
                if (i < 3) bulk_s2g((char*)&S->part[(size_t)b * 1152] + i * 4096, sb + OFF_MISC, i < 2 ? 4096 : 1024);
            }
            bulk_s2g(&S->rec[8 * b], sb + OFF_MISC, 32);
            asm volatile("cp.async.bulk.commit_group;" ::: "memory");
        }
        __syncwarp();
    }
            const cplx z258 = cmul(z256, z2), z512 = csq(z256), z768 = cmul(z512, z256);
            {
                const uint32_t a0 = CJ(z256), a0p = CJP(z256), a1 = CJ(z258), a1p = CJP(z258);
#pragma unroll
                for (int i = 0; i < 4; i++) { sts32(ws + 1152 + (2 * i) * 144, hcm(cz[i], a0, a0p)); sts32(ws + 1152 + (2 * i + 1) * 144, hcm(cz[i], a1, a1p)); }
                tile(acc[2], 1);
            }
            {
                const uint32_t a0 = CJ(z512), a0p = CJP(z512), a1 = CJ(z768), a1p = CJP(z768);
#pragma unroll
                for (int i = 0; i < 4; i++) { sts32(ws + 2304 + i * 144, hcm(cz[i], a0, a0p)); sts32(ws + 2304 + (4 + i) * 144, hcm(cz[i], a1, a1p)); }
                tile(acc[3], 2);
            }
            if (warp == 3) {
                if (lane == 15) pre = ld_rlx(S->hint);
            }
            const cplx z1024 = csq(z512);
            {
                const cplx zk[4] = {z1024, cmul(z1024, z256), csq(z768), cmul(z1024, z768)};
#pragma unroll
                for (int h = 0; h < 4; h++) {
                    const uint32_t a0 = CJ(zk[h]), a0p = CJP(zk[h]);
                    sts32(ws + (2 * h) * 144, hcm(cz[0], a0, a0p));
                    sts32(ws + (2 * h + 1) * 144, hcm(cz[2], a0, a0p));
                }
                tile(acc[4], 0);
            }
            const cplx z2048 = csq(z1024);
            float last = C.x * z2048.x - C.y * z2048.y;
#pragma unroll
            for (int o = 16; o; o >>= 1) last += __shfl_xor_sync(0xffffffffu, last, o);
            __syncwarp();
#pragma unroll
            for (int i = 0; i < 5; i++) *(float4*)(sm + (scr - sb) + i * 512 + lane * 16) = make_float4(acc[i][0], acc[i][1], acc[i][2], acc[i][3]);
            if (lane == 0) { const float inv = __uint_as_float(ex << 23); M.kinv[wgi][w] = inv; M.klast[wgi][w] = last * inv; }
        }
        if (tid == 111 && (int)(pre - HINT_N * wait_epoch(M)) >= 0) M.flag = 1u;
        named_bar(1 + wgi, 128);
        const uint32_t td = cb + XO_TD + 64 * 4, tf = cb + XO_TF - 32 * 4;
        if (tid == 111 && !M.flag) pre = ld_rlx(S->hint);
        const float4 ki = *(const float4*)M.kinv[wgi];
        auto fsum = [&](int off, uint32_t& r0, uint32_t& r1) {
            const unsigned char* p = sm + (cb - sb) + off;
            const float4 a = *(const float4*)p, b2 = *(const float4*)(p + KSCR), c = *(const float4*)(p + 2 * KSCR), d = *(const float4*)(p + 3 * KSCR);
            r0 = pack2(fmaf(a.y, ki.x, b2.y * ki.y) + fmaf(c.y, ki.z, d.y * ki.w), fmaf(a.x, ki.x, b2.x * ki.y) + fmaf(c.x, ki.z, d.x * ki.w));
            r1 = pack2(fmaf(a.w, ki.x, b2.w * ki.y) + fmaf(c.w, ki.z, d.w * ki.w), fmaf(a.z, ki.x, b2.z * ki.y) + fmaf(c.z, ki.z, d.z * ki.w));
        };
        uint32_t r[2], q[2];
        fsum(w * 512 + lane * 16, r[0], r[1]);
        fsum(2048 + w * 128 + lr * 16, q[0], q[1]);
        if (tid == 111) {
            if ((int)(pre - HINT_N * M.epoch) >= 0) M.flag = 1u;
            else pre = ld_rlx(S->hint);
        }
        __syncwarp();
        if (w < 2) {
            const uint32_t p = td + (16 * g + 8 * w + 2 * t) * 4;
#pragma unroll
            for (int h = 0; h < 2; h++) { sts16(p + h * 512, r[h] >> 16); sts32(p + h * 512 + 4, r[h]); sts16(p + h * 512 + 10, r[h]); }
        } else if (w == 2) {
            const uint32_t p = td + (256 + 16 * g + 4 * t) * 4;
#pragma unroll
            for (int h = 0; h < 2; h++) {
                const uint32_t k0 = r[h] >> 16;
                if (h || lane) { sts16(p + h * 512 - 4, k0); sts16(p + h * 512 + 2, k0); }
                sts16(p + h * 512, k0); sts32(p + h * 512 + 4, __byte_perm(r[h], 0, 0x3232)); sts32(p + h * 512 + 8, r[h]); sts16(p + h * 512 + 14, r[h]);
            }
        } else {
            const uint32_t p = tf + (64 + 32 * (t >> 1) + 2 * g + (t & 1)) * 4;
#pragma unroll
            for (int h = 0; h < 2; h++) {
                const uint32_t k0 = r[h] >> 16;
                sts16(p + h * 64 + 512, r[h]); sts16(p + h * 64 + 518, r[h]);
                if (h || lane) { sts16(p + h * 64 - 4, k0); sts16(p + h * 64 + 2, k0); }
            }
            if (lane == 0) {
                const uint32_t dd = __byte_perm(r[0], 0, 0x3232);
                sts16(td + 511 * 4, dd); sts32(td + 512 * 4, dd); sts32(td + 513 * 4, dd); sts32(td + 514 * 4, dd); sts16(td + 515 * 4 + 2, dd);
            }
        }
        if (lane < 8) {
            const uint32_t p = tf + 1024 + (64 + 16 * t + 2 * w + g) * 4;
#pragma unroll
            for (int h = 0; h < 2; h++) {
                const uint32_t k0 = q[h] >> 16;
                sts16(p + h * 32 + 512, q[h]); sts16(p + h * 32 + 518, q[h]);
                if (h || (tid & 127)) { sts16(p + h * 32 - 4, k0); sts16(p + h * 32 + 2, k0); }
            }
            if ((tid & 127) == 0) {
                const float4 kl4 = *(const float4*)M.klast[wgi];
                const uint32_t kl = f2bits((kl4.x + kl4.y) + (kl4.z + kl4.w)), dd = __byte_perm(q[0], 0, 0x3232);
                sts16(tf + 127 * 4, dd); sts16(tf + 128 * 4 + 2, dd); sts32(cb + XO_K1024, dd);
                sts16(tf + 1024 + 127 * 4, kl); sts16(tf + 1024 + 128 * 4 + 2, kl);
            }
        }
        __syncwarp();
    } else {
        const int i = tid - 512, idx = b >> 1;
        tag16 = (wait_epoch(M) % 65535u) + 1u;
        mod_tile(0);
        if (i == 0 && idx < 44) {
            PROXY_FENCE();
            mbar_expect(mb_wm + 8, 36864);
#pragma unroll
            for (int k = 0; k < 3; k++) tma2d(sb + OFF_WU + k * 12288, &tm_wm, 32 * (idx + 64), 192 * k, mb_wm + 8);
        }
        __syncwarp();
    }
    if (tid == 111) {
        epoch = wait_epoch(M);
#pragma unroll 1
        for (int it = 0; it < SPIN_MAX && (int)(pre - HINT_N * epoch) < 0; it++) pre = ld_rlx(S->hint);
        M.flag = 1u;
    }
    __syncwarp();
    const int ubp = (tid * 13108) >> 16, uloc = tid - 5 * ubp;
    const uint4* usrc = &S->xn[(size_t)b * 1280 + 2 * tid];
    uint4 ua = make_uint4(0, 0, 0, 0), uc = ua;
    uint32_t usa = 0, uca = 0;
    if (lane == 0) {
#pragma unroll 1
        for (int it = 0; it < (SPIN_MAX << 4) && !M.flag; it++) { }
    }
    __syncwarp();
    if (uloc < nch) {
 ua = ld_rlx4(usrc); uc = ld_rlx4(usrc + 1); usa = ld_rlx(&S->modw[cs + uloc]); uca = ld_rlx(&S->modw[D_ + cs + uloc]); }
    CBAR();
    epoch = M.epoch;
    tag16 = (epoch % 65535u) + 1u;
    {
        const int bp = ubp, loc = uloc;
        if (loc < nch) {
            const uint4* src = usrc;
            uint4 a = ua, c = uc;
#pragma unroll 1
            for (int it = 0; it < SPIN_MAX && (a.x == SENT || a.z == SENT || c.x == SENT || c.z == SENT || (usa >> 16) != tag16 || (uca >> 16) != tag16); it++) {
                a = ld_rlx4(src); c = ld_rlx4(src + 1); usa = ld_rlx(&S->modw[cs + loc]); uca = ld_rlx(&S->modw[D_ + cs + loc]);
            }
            const uint32_t sa = __byte_perm(usa, 0, 0x1010), ca = pack2(1.0f + lo2f(uca), 1.0f + lo2f(uca));
            unsigned char* up = sm + OFF_CH + loc * CHS + ((2 * bp) & 7) * ULBO + ((bp >> 2) + 9) * 16;
            *(uint4*)up = make_uint4(add2(mul2(~a.x, ca), sa), add2(mul2(~a.z, ca), sa), add2(mul2(~c.x, ca), sa), add2(mul2(~c.z, ca), sa));
            *(uint4*)(up + ULBO) = make_uint4(add2(mul2(~a.y, ca), sa), add2(mul2(~a.w, ca), sa), add2(mul2(~c.y, ca), sa), add2(mul2(~c.w, ca), sa));
        }
        publish_reset();
        const int i = tid & 127;
        unsigned char* cp = sm + OFF_CH + wgi * CHS;
        *(uint4*)(cp + XO_U8 - 1024 + (i >> 6) * 4096 + (i & 63) * 16) = make_uint4(0, 0, 0, 0);
        if (i < 72) { const int c = (i * 57) >> 9; *(uint4*)(cp + c * ULBO + (i - 9 * c) * 16) = make_uint4(0, 0, 0, 0); }
    }
    PROXY_FENCE();
    CBAR();
    if (w == 2 && lane == 0) {
        bulk_s2g((char*)&S->xn[(size_t)b * 1280] + wgi * 4096, sb + OFF_MISC, 4096);
        asm volatile("cp.async.bulk.commit_group;" ::: "memory");
    }
        if (tid == 416) {
            mbar_expect(mb_wg, nf * D_ * 2);
            tma2d(sb + OFF_WG, (b & 1) ? &tm_wg : &tm_wg32, f0, 0, mb_wg);
        }
    if (tid == 96 || tid == 224) tma2d(sb + OFF_WG + (1 + (tid >> 7)) * (nf * 384), (b & 1) ? &tm_wg : &tm_wg32, f0, 192 * (1 + (tid >> 7)), mb_wg);
    if (has_ch) {
        __syncwarp();
        conv_channel(sm, S, 2 * D_ + cs + wgi, epoch, w_down + (size_t)f0 * D_, (b & 1) ? nullptr : &tm_wu32, f0);
    } else {
        const int idx = b >> 1;
        if (idx < 44) mod_tile(1);
        if (tid == 512) {
            PROXY_FENCE();
            mbar_expect(mb_wu, 46080);
#pragma unroll 1
            for (int i = 0; i < 3; i++) {
                tma2d(sb + OFF_WU + i * 15360, &tm_wu, f0, 192 * i, mb_wu);
                const long long c0 = clock64();
                int it = 0;
                while (clock64() - c0 < 1200 && ++it < 4096) { }
            }
            wait_reset(S->cnt, epoch);
        }
        named_bar(5, 128);
    }
    {
    const int tid = fresh_tid(), warp = __shfl_sync(0xffffffffu, tid >> 5, 0), lane = tid & 31;
    const int g = lane >> 2, t = lane & 3, lr = lane & 7, lm = lane >> 3;
    uint32_t v3 = 0, v4 = 0, v5 = 0;
    auto load_consts = [&]() {
        if (tid < D_) { v3 = ld_rlx(&S->modw[3 * D_ + tid]); v4 = ld_rlx(&S->modw[4 * D_ + tid]); v5 = ld_rlx(&S->modw[5 * D_ + tid]); }
    };
    if (tid == 0) bulk_pf(w_down + (size_t)(f0 + 16) * D_, (nf - 16) * D_ * 2);
    uint32_t x1[2][4], wr2[2][2];
    if (warp < 18) {
        const char* vp = (const char*)S->v + ((size_t)b * D_ + 32 * warp + g) * 32 + t * 8;
        uint2 v[4];
#pragma unroll
        for (int i = 0; i < 4; i++) v[i] = ld_rlx2(vp + i * 256);
#pragma unroll
        for (int j = 0; j < 2; j++) {
            const uint32_t* wp = M.wr + 16 * warp + 8 * j + t;
            wr2[j][0] = (g == 0) ? wp[0] : 0u;
            wr2[j][1] = (g == 0) ? wp[4] : 0u;
            ldsm_x4(x1[j], sb + OFF_TILE + (lr + 8 * (lm & 1)) * (ROWP * 2) + (lm >> 1) * 16 + warp * 64 + j * 32);
        }
#pragma unroll 1
        for (int it = 0; it < SPIN_MAX && ((v3 >> 16) != tag16 || (v4 >> 16) != tag16 || (v5 >> 16) != tag16); it++) load_consts();
        ((unsigned short*)M.sb)[tid] = (unsigned short)v3;
        ((unsigned short*)M.cb1)[tid] = (unsigned short)f2bits(1.0f + lo2f(v4));
        ((unsigned short*)M.gb)[tid] = (unsigned short)v5;
#pragma unroll 1
        for (int it = 0; it < SPIN_MAX; it++) {
            bool bad = false;
#pragma unroll
            for (int i = 0; i < 4; i++) if (v[i].x == SENT) { v[i] = ld_rlx2(vp + i * 256); bad = true; }
            if (!bad) break;
        }
        __syncwarp();
        float c1[4] = {0.f, 0.f, 0.f, 0.f}, cl[4] = {0.f, 0.f, 0.f, 0.f}, chh[4] = {0.f, 0.f, 0.f, 0.f};
#pragma unroll
        for (int j = 0; j < 2; j++) {
            x1[j][0] = add2(x1[j][0], movm(~v[2 * j].x)); x1[j][1] = add2(x1[j][1], movm(~v[2 * j].y));
            x1[j][2] = add2(x1[j][2], movm(~v[2 * j + 1].x)); x1[j][3] = add2(x1[j][3], movm(~v[2 * j + 1].y));
            mma_bf16(c1, x1[j][0], x1[j][1], x1[j][2], x1[j][3], 0x3F803F80u, 0x3F803F80u);
            mma_bf16(cl, x1[j][0], x1[j][1], x1[j][2], x1[j][3], x1[j][0], x1[j][2]);
            mma_bf16(chh, x1[j][0], x1[j][1], x1[j][2], x1[j][3], x1[j][1], x1[j][3]);
        }
        float* pp = (float*)&M.part[warp][g];
        if (t == 0) { pp[0] = c1[0]; pp[16] = c1[2]; }
        if (t == (g >> 1)) { pp[1] = (g & 1) ? cl[1] : cl[0]; pp[17] = (g & 1) ? chh[3] : chh[2]; }
    }
    CBAR();
    if (warp < 18) {
        const int tok = lane & 15, hf = lane >> 4;
        uint32_t kc[2][2][2];
#pragma unroll
        for (int j = 0; j < 2; j++)
#pragma unroll
            for (int q = 0; q < 2; q++) { kc[j][q][0] = ((const uint32_t*)M.cb1)[16 * warp + 8 * j + 4 * q + t]; kc[j][q][1] = ((const uint32_t*)M.sb)[16 * warp + 8 * j + 4 * q + t]; }
        named_bar(13, 608);
        uint32_t st[2][3];
#pragma unroll
        for (int h = 0; h < 2; h++) { const uint4 q = M.st2[g + 8 * h]; st[h][0] = q.x; st[h][1] = q.y; st[h][2] = q.z; }
        float rc[4] = {0.f, 0.f, 0.f, 0.f};
        uint32_t h2[2][4];
#pragma unroll
        for (int j = 0; j < 2; j++) {
#pragma unroll
            for (int r = 0; r < 4; r++) {
                h2[j][r] = add2(mul2(norm2(x1[j][r], st[r & 1][0], st[r & 1][1], st[r & 1][2]), kc[j][r >> 1][0]), kc[j][r >> 1][1]);
            }
            mma_bf16(rc, h2[j][0], h2[j][1], h2[j][2], h2[j][3], wr2[j][0], wr2[j][1]);
        }
        if (t == 0) { M.rp[warp][g] = rc[0]; M.rp[warp][g + 8] = rc[2]; }
        if (warp == 0) {
            named_bar(12, 576);
            float r = M.rp[9 * hf][tok];
#pragma unroll
            for (int i = 1; i < 9; i++) r += M.rp[9 * hf + i][tok];
            r += __shfl_xor_sync(0xffffffffu, r, 16);
            const uint32_t rbits = f2bits(r);
            const uint32_t key = 0x80000000u | ((rbits ^ ((rbits & 0x8000u) ? 0xFFFFu : 0x8000u)) << 11) | (uint32_t)(2047 - (16 * b + tok));
            int rank = 0;
#pragma unroll
            for (int j = 1; j < 16; j++) rank += __shfl_xor_sync(0xffffffffu, key, j) > key;
            if (lane < 16) { M.skey[rank] = key; M.rank[rank] = tok; }
            __syncwarp();
            if (lane < 2) st_rlx4(&S->rec[8 * b + 4 * lane], *(const uint4*)&M.skey[4 * lane]);
        } else named_arrive(12, 576);
#pragma unroll
        for (int j = 0; j < 2; j++) {
            uint32_t o[4];
#pragma unroll
            for (int r = 0; r < 4; r++) o[r] = add2(x1[j][r], mul2(((const uint32_t*)M.gb)[16 * warp + 8 * j + 4 * (r >> 1) + t], h2[j][r]));
            const uint32_t to = (lr + 8 * (lm & 1)) * (ROWP * 2) + (lm >> 1) * 16 + warp * 64 + j * 32;
            stsm_x4(sb + OFF_H2T + to, h2[j][0], h2[j][1], h2[j][2], h2[j][3]);
            stsm_x4(sb + OFF_TILE + to, o[0], o[1], o[2], o[3]);
        }
    } else if (warp == 19) {
        const int tok = lane & 15, hf = lane >> 4;
        float2 s = M.part[9 * hf][tok];
#pragma unroll
        for (int i = 1; i < 9; i++) { const float2 q = M.part[9 * hf + i][tok]; s.x += q.x; s.y += q.y; }
        s.x += __shfl_xor_sync(0xffffffffu, s.x, 16); s.y += __shfl_xor_sync(0xffffffffu, s.y, 16);
        float meanb, rinv;
        ln_stats(s.x, s.y, meanb, rinv);
        const float rh = bfr(rinv);
        if (lane < 16) M.st2[tok] = make_uint4(pack2(meanb, meanb), pack2(rh, rh), pack2(rinv - rh, rinv - rh), 0u);
        __syncwarp();
        named_arrive(13, 608);
    } else if (lane < 9) {
        PROXY_FENCE();
        if (lane == 0) mbar_expect(mb_wd, nf * D_ * 2);
        tma2d(sb + OFF_WD + lane * 5120, (b & 1) ? &tm_wd : &tm_wd32, 64 * lane, f0, mb_wd);
    }
    CBAR();
    uint32_t wf[9][4], wd[2][3][4];
    const int fmt = warp >> 2, fsl = warp & 3;
    auto load_wf = [&]() {
        mbar_wait(mb_wg, 0);
        mbar_wait(mb_wu, 0);
        if (fmt < 4 || nf > 32) {
            const int half = lm & 1;
            const uint32_t base = (fmt == 4) ? ((half ? OFF_WU : OFF_WG) + 64)
                                             : ((fmt >> 1) * OFF_WU + (((2 * (fmt & 1) + half) ^ ((b & 1) ? 0 : (lr >> 1))) << 4));
            const uint32_t wa = sb + base + (144 * fsl + lr + 8 * (lm >> 1)) * (2 * nf);
#pragma unroll
            for (int ks = 0; ks < 9; ks++) ldsm_x4_t(wf[ks], wa + ks * (32 * nf));
        }
    mbar_wait(mb_wd, 0);
    {
#pragma unroll
        for (int i = 0; i < 2; i++) {
            const int mt = warp + 20 * i;
            const uint32_t wa = sb + OFF_WD + (mt >> 2) * 5120 + lr * 128 + (((2 * (mt & 3) + (lm & 1)) ^ lr) << 4);
#pragma unroll
            for (int ks = 0; ks < 3; ks++)
                if ((i == 0 || warp < 16) && (ks < 2 || nf > 32)) ldsm_x4_t(wd[i][ks], wa + ks * 2048 + ((ks < 2) ? (lm >> 1) * 1024 : 0));
        }
    }
    };
    if (warp >= 8) {
        if (warp < 16) {
            const int tk = M.rank[warp - 8];
            const uint32_t* hp = (const uint32_t*)(sm + OFF_H2T + tk * (ROWP * 2)) + lane;
            uint4* dst = &S->h2w[(size_t)(16 * b + tk) * 96 + lane];
#pragma unroll
            for (int j = 0; j < 3; j++) st_rlx4(dst + 32 * j, make_uint4(hp[96 * j], hp[96 * j + 32], hp[96 * j + 64], epoch));
        }
        load_wf();
    } else {
        const uint4* rp = (const uint4*)S->rec + tid;
        load_wf();
        uint4 rk = ld_rlx4(rp);
#pragma unroll 1
        for (int it = 0; it < SPIN_MAX && !rk.x; it++) rk = ld_rlx4(rp);
        __syncwarp();
        uint32_t mine = 0;
#pragma unroll
        for (int rnd = 0; rnd < 8; rnd++) {
            const uint32_t m = __reduce_max_sync(0xffffffffu, rk.x);
            if (rk.x == m) { rk.x = rk.y; rk.y = rk.z; rk.z = rk.w; rk.w = 0u; }
            if (lane == rnd) mine = m;
        }
        if (lane < 8) M.cand[8 * warp + lane] = mine;
    }
    CBAR();
    uint32_t selv = 0;
    if (warp < 12) {
        uint2 k = *(const uint2*)&M.cand[2 * lane];
#pragma unroll
        for (int rnd = 0; rnd < 8; rnd++) {
            const uint32_t m = __reduce_max_sync(0xffffffffu, k.x);
            if (k.x == m) { k.x = k.y; k.y = 0u; }
            if (lr == rnd) selv = m;
        }
        if (tid < 8) M.skey[tid] = selv;
    }
    const uint32_t seltok = 2047u - (selv & 2047u);
    const int fo = tid >> 3;
    const int fW = 9 * b + (fo >> 2), fcomp = fo & 3;
    const int fd = 16 * (fW >> 5) + ((fW >> 2) & 7) + 8 * (fcomp >> 1), fk = 2 * (fW & 3) + (fcomp & 1);
    const uint32_t fsel = __shfl_sync(0xffffffffu, selv, fk);
    uint32_t fx = 0, fv = 0;
    bf16(*h2s)[ROWP] = (bf16(*)[ROWP])(sm + OFF_H2S);
    if (warp < 12) {
        uint4 wv[2];
        const uint4* hp[2];
#pragma unroll
        for (int r = 0; r < 2; r++) {
            const int wi = warp + 12 * r, k = wi / 3, j = wi - 3 * k;
            hp[r] = &S->h2w[(size_t)__shfl_sync(0xffffffffu, seltok, k) * 96 + 32 * j + lane];
            wv[r] = ld_rlx4(hp[r]);
        }
        if (tid < 288 && (tid & 7) == 0) {
            const uint32_t ft = 2047u - (fsel & 2047u), pr = (ft & 15u) >> 1;
            fx = ((const unsigned short*)x)[(size_t)ft * D_ + fd];
            asm volatile("ld.relaxed.gpu.global.u16 %0, [%1];" : "=r"(fv)
                         : "l"((const unsigned short*)S->v + ((size_t)(ft >> 4) * D_ + fd) * 16 + ((pr & 3u) * 2 + (pr >> 2)) * 2 + (ft & 1u)) : "memory");
        }
#pragma unroll 1
        for (int it = 0; it < SPIN_MAX && (wv[0].w != epoch || wv[1].w != epoch); it++) { wv[0] = ld_rlx4(hp[0]); wv[1] = ld_rlx4(hp[1]); }
#pragma unroll
        for (int r = 0; r < 2; r++) {
            const int wi = warp + 12 * r, k = wi / 3, j = wi - 3 * k;
            uint32_t* dst = (uint32_t*)&h2s[k][0] + 96 * j + lane;
            dst[0] = wv[r].x; dst[32] = wv[r].y; dst[64] = wv[r].z;
        }
    }
    CBAR();
    float* ffr = (float*)(sm + OFF_FFR);
    if (fmt < 4 || nf > 32) {
        float acc[2][4] = {{0.f, 0.f, 0.f, 0.f}, {0.f, 0.f, 0.f, 0.f}};
        const uint32_t ha = sb + OFF_H2S + lr * (ROWP * 2) + (144 * fsl) * 2 + lm * 16;
#pragma unroll
        for (int k2 = 0; k2 < 5; k2++) {
            uint32_t hb[4];
            ldsm_x4(hb, ha + k2 * 64 - ((k2 == 4) ? (lm >> 1) * 32 : 0));
            mma_bf16(acc[0], wf[2 * k2][0], wf[2 * k2][1], wf[2 * k2][2], wf[2 * k2][3], hb[0], hb[1]);
            if (k2 < 4) mma_bf16(acc[1], wf[2 * k2 + 1][0], wf[2 * k2 + 1][1], wf[2 * k2 + 1][2], wf[2 * k2 + 1][3], hb[2], hb[3]);
        }
        float* o = ffr + ((fsl * 80 + 16 * fmt + g) * 8 + 2 * t);
        *(float2*)o = make_float2(acc[0][0] + acc[1][0], acc[0][1] + acc[1][1]);
        *(float2*)(o + 64) = make_float2(acc[0][2] + acc[1][2], acc[0][3] + acc[1][3]);
    }
    CBAR();
    bf16(*act)[56] = (bf16(*)[56])(sm + OFF_ACT);
    if (tid < 384) {
        const int f = tid >> 3, a = tid & 7;
        float v = 0.f;
        if (f < nf) {
            const int rg = (f < 32) ? f : f + 32, ru = (f < 32) ? f + 32 : f + 40;
            const float* pg = ffr + rg * 8 + a;
            const float* pu = ffr + ru * 8 + a;
            float gg = bfr((pg[0] + pg[640]) + (pg[1280] + pg[1920]));
            gg = bfr(silu(gg));
            const float uu = bfr((pu[0] + pu[640]) + (pu[1280] + pu[1920]));
            v = gg * uu;
        }
        act[a][f] = __ushort_as_bfloat16((unsigned short)f2bits(v));
    }
    CBAR();
    {
        uint32_t bq[3][2];
#pragma unroll
        for (int ks = 0; ks < 3; ks++) {
            bq[ks][0] = *(const uint32_t*)&act[g][16 * ks + 2 * t];
            bq[ks][1] = *(const uint32_t*)&act[g][16 * ks + 2 * t + 8];
        }
#pragma unroll
        for (int i = 0; i < 2; i++) {
            if (i == 0 || warp < 16) {
                float acc[4] = {0.f, 0.f, 0.f, 0.f};
#pragma unroll
                for (int ks = 0; ks < 3; ks++)
                    if (ks < 2 || nf > 32) mma_bf16(acc, wd[i][ks][0], wd[i][ks][1], wd[i][ks][2], wd[i][ks][3], bq[ks][0], bq[ks][1]);
                const int W = (warp + 20 * i) * 32 + lane, c = (W * 7282) >> 16;
                st_rlx2(&S->part[(c * G_ + b) * 9 + W - 9 * c], ~pack2(acc[0], acc[1]), ~pack2(acc[2], acc[3]));
            }
        }
    }
    if (warp >= 4) {
        const int tk = warp - 4;
        if (!__any_sync(0xffffffffu, 2047u - (M.skey[lr] & 2047u) == (uint32_t)(16 * b + tk))) {
            const uint4* src = (const uint4*)(sm + OFF_TILE + tk * (ROWP * 2));
            uint4* dst = (uint4*)(out + (size_t)(16 * b + tk) * D_);
            dst[lane] = src[lane]; dst[lane + 32] = src[lane + 32];
            if (lane < 8) dst[lane + 64] = src[lane + 64];
        }
    }
    float4* fin = (float4*)(sm + OFF_FIN);
    uint32_t rb = (fsel >> 11) & 0xFFFFu;
    rb ^= (rb & 0x8000u) ? 0x8000u : 0xFFFFu;
    const float rs = bfr(__fdividef(1.0f, 1.0f + __expf(-lo2f(rb))));
    const float fh2 = (tid < 288) ? __bfloat162float(h2s[fk][fd]) : 0.f, fgb = (tid < 288) ? __bfloat162float(M.gb[fd]) : 0.f;
    const float fx1 = bfr(lo2f(fx) + lo2f(~fv));
    if (tid < 576) {
        const uint2* src = &S->part[(size_t)b * 1152 + tid];
        uint2 a = ld_rlx2(src), c = ld_rlx2(src + 576);
#pragma unroll 1
        for (int it = 0; it < SPIN_MAX && (a.x == SENT || c.x == SENT); it++) {
            if (a.x == SENT) a = ld_rlx2(src);
            if (c.x == SENT) c = ld_rlx2(src + 576);
        }
        fin[tid] = make_float4(lo2f(~a.x) + lo2f(~c.x), hi2f(~a.x) + hi2f(~c.x), lo2f(~a.y) + lo2f(~c.y), hi2f(~a.y) + hi2f(~c.y));
    }
    CBAR();
    if (tid < 288) {
        const int part = tid & 7;
        const float* f = (const float*)fin + part * 36 + fo;
        float s = ((f[0] + f[288]) + (f[576] + f[864])) + ((f[1152] + f[1440]) + (f[1728] + f[2016]));
        s += __shfl_xor_sync(0xffffffffu, s, 1);
        s += __shfl_xor_sync(0xffffffffu, s, 2);
        s += __shfl_xor_sync(0xffffffffu, s, 4);
        const float upd = bfr(bfr(s) * rs);
        const float ov = fx1 + bfr(fgb * bfr(fh2 + upd));
        if (part == 0) out[(size_t)(2047u - (fsel & 2047u)) * D_ + fd] = __ushort_as_bfloat16((unsigned short)f2bits(ov));
    }
    if ((warp & 3) == 2 && lane == 0) asm volatile("cp.async.bulk.wait_group 0;" ::: "memory");
    }
}

typedef CUresult (*EncodeFn)(CUtensorMap*, CUtensorMapDataType, cuuint32_t, void*, const cuuint64_t*, const cuuint64_t*,
                             const cuuint32_t*, const cuuint32_t*, CUtensorMapInterleave, CUtensorMapSwizzle,
                             CUtensorMapL2promotion, CUtensorMapFloatOOBfill);

static void make_map(EncodeFn fn, CUtensorMap* m, const void* ptr, uint64_t cols, uint64_t rows, uint32_t bc, uint32_t br,
                     CUtensorMapSwizzle sw) {
    cuuint64_t dims[2] = {cols, rows};
    cuuint64_t strides[1] = {cols * 2};
    cuuint32_t box[2] = {bc, br};
    cuuint32_t es[2] = {1, 1};
    CUresult rc = fn(m, CU_TENSOR_MAP_DATA_TYPE_BFLOAT16, 2, (void*)ptr, dims, strides, box, es, CU_TENSOR_MAP_INTERLEAVE_NONE,
                     sw, CU_TENSOR_MAP_L2_PROMOTION_NONE, CU_TENSOR_MAP_FLOAT_OOB_FILL_NONE);
    (void)rc;
}

static void launch(void* const* d_in, const int* in_sizes, int n_in, void* d_out, int out_size) {
    static EncodeFn enc = nullptr;
    static CUtensorMap tmm, tmg, tmu, tmd, tmd32, tmg32, tmu32;
    static Scratch* sp = nullptr;
    static const void* cached[4] = {nullptr, nullptr, nullptr, nullptr};
    if (!enc) {
        cudaDriverEntryPointQueryResult qr;
        void* fn = nullptr;
        cudaGetDriverEntryPoint("cuTensorMapEncodeTiled", &fn, cudaEnableDefault, &qr);
        enc = (EncodeFn)fn;
        cudaFuncSetAttribute(mega_kernel, cudaFuncAttributeMaxDynamicSharedMemorySize, SMEM_TOTAL);
        cudaGetSymbolAddress((void**)&sp, g_s);
    }
    if (cached[0] != d_in[13] || cached[1] != d_in[9] || cached[2] != d_in[10] || cached[3] != d_in[11]) {
        make_map(enc, &tmm, d_in[13], 6 * D_, D_, 32, 192, CU_TENSOR_MAP_SWIZZLE_64B);
        make_map(enc, &tmg, d_in[9], F_, D_, 40, 192, CU_TENSOR_MAP_SWIZZLE_NONE);
        make_map(enc, &tmu, d_in[10], F_, D_, 40, 192, CU_TENSOR_MAP_SWIZZLE_NONE);
        make_map(enc, &tmg32, d_in[9], F_, D_, 32, 192, CU_TENSOR_MAP_SWIZZLE_64B);
        make_map(enc, &tmu32, d_in[10], F_, D_, 32, 192, CU_TENSOR_MAP_SWIZZLE_64B);
        make_map(enc, &tmd, d_in[11], D_, F_, 64, 40, CU_TENSOR_MAP_SWIZZLE_128B);
        make_map(enc, &tmd32, d_in[11], D_, F_, 64, 32, CU_TENSOR_MAP_SWIZZLE_128B);
        cached[3] = d_in[11];
        cached[0] = d_in[13]; cached[1] = d_in[9]; cached[2] = d_in[10];
    }
    mega_kernel<<<G_, NTHR, SMEM_TOTAL>>>((const bf16*)d_in[0], (const bf16*)d_in[1], (const bf16*)d_in[2], (const bf16*)d_in[3],
                                          (const bf16*)d_in[4], (const bf16*)d_in[5], (const bf16*)d_in[12], sp, (const bf16*)d_in[6],
                                          (const bf16*)d_in[8], (const bf16*)d_in[11], (bf16*)d_out, tmm, tmg, tmu, tmd, tmd32, tmg32, tmu32);
}

}

extern "C" void kernel_launch(void* const* d_in, const int* in_sizes, int n_in, void* d_out, int out_size) {
    static int mode = -1;
    if (mode < 0) mode = v5::fits() ? 1 : 0;
    if (mode) v5::launch(d_in, in_sizes, n_in, d_out, out_size);
    else v4::launch(d_in, in_sizes, n_in, d_out, out_size);
}
```

```cpp
#include <cuda_runtime.h>
#include <cuda.h>
#include <cuda_bf16.h>
#include <cuda_fp16.h>
#include <stdint.h>

namespace v5 {

#define L_ 2048
#define D_ 576
#define N_ 128
#define F_ 4608
#define G_ 120
#define NCL 15
#define NTHR 768
#define SPIN_MAX (1 << 18)

typedef __nv_bfloat16 bf16;

struct Scratch {
    float4 acc1[L_ + 8];
    float4 acc2[L_];
    uint4 h2c[137 * 72];
    float4 rs[39 * 8];
    float4 acc3[2 * 72 * 32 + 96];
};
#define NRS 124
static_assert(137 * 72 + 2 * 72 * 32 + 39 * 8 + 96 == 124 * G_, "16 B units cleared early in a launch (h2c, acc3, rs)");
__device__ __align__(1024) Scratch g_s;

#define OFF_WG 0
#define OFF_WU 46080
#define KSCR 3456
#define OFF_WM0 69120
#define OFF_STG OFF_WM0
#define OFF_MG2 86400
#define OFF_CH 92160
#define CHS 18688
#define UP 3808
#define UB 192
#define XO_TF 1216
#define XO_U8 2016
#define XO_U16 3328
#define XO_ZA 1232
#define XO_ZB 2016
#define XO_ZC 2800
#define XO_ZD 3328
#define XO_TD 16000
#define XO_K1024 18624
#define XO_DSK 18628
#define XO_KLAST 18656
#define XO_MBU 18672
#define OFF_X 185600
#define XG 672
#define XI(i) (((i) >> 1) * 5520 + ((i) & 1) * 2752)
#define XN(n) ((((n) >> 1) & 3) * XG + (2 * ((n) >> 3) + ((n) & 1)) * 80)
#define OFF_V 207616
#define VP 528
#define OFF_EK (OFF_V + 512)
#define OFF_WM2 OFF_V
#define OFF_MG1 (OFF_V + 17280)
#define OFF_SC (OFF_V + 19840)
#define OFF_C1 (OFF_V + 20640)
#define OFF_MISC 228736
#define OFF_WD OFF_CH
#define OFF_H2T (OFF_CH + 46080)
#define OFF_OUT (OFF_CH + 66560)
#define OFF_GB (OFF_CH + 87040)
#define ROWP 584
#define OFF_H2S 0
#define OFF_FFR 9344
#define OFF_ACT 19584
#define OFF_RS 20480

enum { MB_WM2, MB_MG1, MB_MG2, MB_KEY, MB_V, MB_RS, MB_WG, MB_WU, MB_WD, MB_KEY2, MB_EK, MB_RS2, MB_C2, MB_CW, MB_KD, MB_CD, MB_OUT, MB_FIN, MB_N };

struct Misc {
    union {
        __align__(16) uint4 box[11 * 16];
        struct { unsigned int cand[128], key[256], cand2[128], sel[8], selo[8]; };
    };
    __align__(16) uint4 c2[20];
    __align__(16) unsigned int fin[12];
    unsigned int ga[8], wr[20];
    float cws[2];
    unsigned long long mbar[MB_N];
};
#define SMEM_TOTAL (OFF_MISC + (int)sizeof(Misc))
static_assert(SMEM_TOTAL <= 232448, "smem");

__device__ __forceinline__ float lo2f(uint32_t w) { return __uint_as_float(w << 16); }
__device__ __forceinline__ float hi2f(uint32_t w) { return __uint_as_float(w & 0xFFFF0000u); }
__device__ __forceinline__ uint32_t pack2(float lo, float hi) { uint32_t r; asm("cvt.rn.bf16x2.f32 %0, %1, %2;" : "=r"(r) : "f"(hi), "f"(lo)); return r; }
__device__ __forceinline__ float bfr(float x) { return __uint_as_float(pack2(0.f, x)); }
__device__ __forceinline__ uint32_t f2bits(float x) { return pack2(x, 0.f); }
__device__ __forceinline__ uint32_t packh(float lo, float hi) { uint32_t r; asm("cvt.rn.f16x2.f32 %0, %1, %2;" : "=r"(r) : "f"(hi), "f"(lo)); return r; }
__device__ __forceinline__ float frcp(float x) { float r; asm("rcp.approx.ftz.f32 %0, %1;" : "=f"(r) : "f"(x)); return r; }
__device__ __forceinline__ float fsqrt(float x) { float r; asm("sqrt.approx.ftz.f32 %0, %1;" : "=f"(r) : "f"(x)); return r; }
__device__ __forceinline__ float fex2(float x) { float r; asm("ex2.approx.ftz.f32 %0, %1;" : "=f"(r) : "f"(x)); return r; }
__device__ __forceinline__ float sigm(float x) { return frcp(1.0f + fex2(x * -1.4426950408889634f)); }
__device__ __forceinline__ float silu(float x) { return x * sigm(x); }
__device__ __forceinline__ uint32_t add2(uint32_t a, uint32_t b) { uint32_t r; asm("add.rn.bf16x2 %0, %1, %2;" : "=r"(r) : "r"(a), "r"(b)); return r; }
__device__ __forceinline__ uint32_t sub2(uint32_t a, uint32_t b) { uint32_t r; asm("sub.rn.bf16x2 %0, %1, %2;" : "=r"(r) : "r"(a), "r"(b)); return r; }
__device__ __forceinline__ uint32_t mul2(uint32_t a, uint32_t b) { uint32_t r; asm("mul.rn.bf16x2 %0, %1, %2;" : "=r"(r) : "r"(a), "r"(b)); return r; }
__device__ __forceinline__ uint32_t fma2(uint32_t a, uint32_t b, uint32_t c) { uint32_t r; asm("fma.rn.bf16x2 %0, %1, %2, %3;" : "=r"(r) : "r"(a), "r"(b), "r"(c)); return r; }
__device__ __forceinline__ uint32_t norm2(uint32_t x, uint32_t m, uint32_t rh, uint32_t rl) { const uint32_t d = sub2(x, m); return fma2(d, rh, mul2(d, rl)); }

__device__ __forceinline__ void mma_bf16(float* c, uint32_t a0, uint32_t a1, uint32_t a2, uint32_t a3, uint32_t b0, uint32_t b1) {
    asm volatile("mma.sync.aligned.m16n8k16.row.col.f32.bf16.bf16.f32 {%0,%1,%2,%3}, {%4,%5,%6,%7}, {%8,%9}, {%0,%1,%2,%3};\n"
                 : "+f"(c[0]), "+f"(c[1]), "+f"(c[2]), "+f"(c[3]) : "r"(a0), "r"(a1), "r"(a2), "r"(a3), "r"(b0), "r"(b1));
}
__device__ __forceinline__ void mma_f16(float* c, const uint32_t* a, uint32_t b0, uint32_t b1) {
    asm volatile("mma.sync.aligned.m16n8k16.row.col.f32.f16.f16.f32 {%0,%1,%2,%3}, {%4,%5,%6,%7}, {%8,%9}, {%0,%1,%2,%3};\n"
                 : "+f"(c[0]), "+f"(c[1]), "+f"(c[2]), "+f"(c[3]) : "r"(a[0]), "r"(a[1]), "r"(a[2]), "r"(a[3]), "r"(b0), "r"(b1));
}
__device__ __forceinline__ void ldsm_x4(uint32_t* r, uint32_t addr) {
    asm volatile("ldmatrix.sync.aligned.m8n8.x4.shared.b16 {%0,%1,%2,%3}, [%4];" : "=r"(r[0]), "=r"(r[1]), "=r"(r[2]), "=r"(r[3]) : "r"(addr) : "memory");
}
__device__ __forceinline__ void ldsm_x4_t(uint32_t* r, uint32_t addr) {
    asm volatile("ldmatrix.sync.aligned.m8n8.x4.trans.shared.b16 {%0,%1,%2,%3}, [%4];" : "=r"(r[0]), "=r"(r[1]), "=r"(r[2]), "=r"(r[3]) : "r"(addr) : "memory");
}
__device__ __forceinline__ void stsm_x4(uint32_t addr, uint32_t r0, uint32_t r1, uint32_t r2, uint32_t r3) {
    asm volatile("stmatrix.sync.aligned.m8n8.x4.shared.b16 [%0], {%1,%2,%3,%4};" ::"r"(addr), "r"(r0), "r"(r1), "r"(r2), "r"(r3) : "memory");
}
__device__ __forceinline__ void stsm_x4_t(uint32_t addr, uint32_t r0, uint32_t r1, uint32_t r2, uint32_t r3) {
    asm volatile("stmatrix.sync.aligned.m8n8.x4.trans.shared.b16 [%0], {%1,%2,%3,%4};" ::"r"(addr), "r"(r0), "r"(r1), "r"(r2), "r"(r3) : "memory");
}
__device__ __forceinline__ uint32_t movm(uint32_t a) { uint32_t r; asm volatile("movmatrix.sync.aligned.m8n8.trans.b16 %0, %1;" : "=r"(r) : "r"(a)); return r; }
__device__ __forceinline__ uint32_t lds32(uint32_t a) { uint32_t v; asm volatile("ld.shared.u32 %0, [%1];" : "=r"(v) : "r"(a)); return v; }
__device__ __forceinline__ void sts32(uint32_t a, uint32_t v) { asm volatile("st.shared.u32 [%0], %1;" ::"r"(a), "r"(v) : "memory"); }
__device__ __forceinline__ void sts16(uint32_t a, uint32_t v) { asm volatile("st.shared.u16 [%0], %1;" ::"r"(a), "h"((unsigned short)v) : "memory"); }
__device__ __forceinline__ void named_bar(int id, int n) { asm volatile("bar.sync %0, %1;" ::"r"(id), "r"(n) : "memory"); }
__device__ __forceinline__ void named_arrive(int id, int n) { asm volatile("bar.arrive %0, %1;" ::"r"(id), "r"(n) : "memory"); }
#define CBAR() asm volatile("bar.sync 0, 640;" ::: "memory")
#define RBAR() asm volatile("bar.sync 0;" ::: "memory")
#define PROXY_FENCE() asm volatile("fence.proxy.async.shared::cta;" ::: "memory")

#define D4(d, o) "+f"(d[o]), "+f"(d[o + 1]), "+f"(d[o + 2]), "+f"(d[o + 3])
__device__ __forceinline__ void wg32(float* d, uint32_t a0, uint32_t a1, uint32_t a2, uint32_t a3, uint64_t desc) {
    asm volatile("wgmma.mma_async.sync.aligned.m64n32k16.f32.bf16.bf16 {%0,%1,%2,%3,%4,%5,%6,%7,%8,%9,%10,%11,%12,%13,%14,%15}, {%16,%17,%18,%19}, %20, 1, 1, 1, 0;"
                 : D4(d, 0), D4(d, 4), D4(d, 8), D4(d, 12) : "r"(a0), "r"(a1), "r"(a2), "r"(a3), "l"(desc));
}
__device__ __forceinline__ void wg48(float* d, uint32_t a0, uint32_t a1, uint32_t a2, uint32_t a3, uint64_t desc) {
    asm volatile("wgmma.mma_async.sync.aligned.m64n48k16.f32.bf16.bf16 {%0,%1,%2,%3,%4,%5,%6,%7,%8,%9,%10,%11,%12,%13,%14,%15,%16,%17,%18,%19,%20,%21,%22,%23}, {%24,%25,%26,%27}, %28, 1, 1, 1, 0;"
                 : D4(d, 0), D4(d, 4), D4(d, 8), D4(d, 12), D4(d, 16), D4(d, 20) : "r"(a0), "r"(a1), "r"(a2), "r"(a3), "l"(desc));
}
__device__ __forceinline__ void wg64(float* d, uint32_t a0, uint32_t a1, uint32_t a2, uint32_t a3, uint64_t desc) {
    asm volatile("wgmma.mma_async.sync.aligned.m64n64k16.f32.bf16.bf16 {%0,%1,%2,%3,%4,%5,%6,%7,%8,%9,%10,%11,%12,%13,%14,%15,%16,%17,%18,%19,%20,%21,%22,%23,%24,%25,%26,%27,%28,%29,%30,%31}, {%32,%33,%34,%35}, %36, 1, 1, 1, 0;"
                 : D4(d, 0), D4(d, 4), D4(d, 8), D4(d, 12), D4(d, 16), D4(d, 20), D4(d, 24), D4(d, 28) : "r"(a0), "r"(a1), "r"(a2), "r"(a3), "l"(desc));
}
#define O4(d, o) "=f"(d[o]), "=f"(d[o + 1]), "=f"(d[o + 2]), "=f"(d[o + 3])
__device__ __forceinline__ void wg32z(float* d, uint32_t a0, uint32_t a1, uint32_t a2, uint32_t a3, uint64_t desc) {
    asm volatile("wgmma.mma_async.sync.aligned.m64n32k16.f32.bf16.bf16 {%0,%1,%2,%3,%4,%5,%6,%7,%8,%9,%10,%11,%12,%13,%14,%15}, {%16,%17,%18,%19}, %20, 0, 1, 1, 0;"
                 : O4(d, 0), O4(d, 4), O4(d, 8), O4(d, 12) : "r"(a0), "r"(a1), "r"(a2), "r"(a3), "l"(desc));
}
__device__ __forceinline__ void wg48z(float* d, uint32_t a0, uint32_t a1, uint32_t a2, uint32_t a3, uint64_t desc) {
    asm volatile("wgmma.mma_async.sync.aligned.m64n48k16.f32.bf16.bf16 {%0,%1,%2,%3,%4,%5,%6,%7,%8,%9,%10,%11,%12,%13,%14,%15,%16,%17,%18,%19,%20,%21,%22,%23}, {%24,%25,%26,%27}, %28, 0, 1, 1, 0;"
                 : O4(d, 0), O4(d, 4), O4(d, 8), O4(d, 12), O4(d, 16), O4(d, 20) : "r"(a0), "r"(a1), "r"(a2), "r"(a3), "l"(desc));
}
__device__ __forceinline__ void wg56(float* d, uint32_t a0, uint32_t a1, uint32_t a2, uint32_t a3, uint64_t desc) {
    asm volatile("wgmma.mma_async.sync.aligned.m64n56k16.f32.bf16.bf16 {%0,%1,%2,%3,%4,%5,%6,%7,%8,%9,%10,%11,%12,%13,%14,%15,%16,%17,%18,%19,%20,%21,%22,%23,%24,%25,%26,%27}, {%28,%29,%30,%31}, %32, 1, 1, 1, 0;"
                 : D4(d, 0), D4(d, 4), D4(d, 8), D4(d, 12), D4(d, 16), D4(d, 20), D4(d, 24) : "r"(a0), "r"(a1), "r"(a2), "r"(a3), "l"(desc));
}
__device__ __forceinline__ void wg64z(float* d, uint32_t a0, uint32_t a1, uint32_t a2, uint32_t a3, uint64_t desc) {
    asm volatile("wgmma.mma_async.sync.aligned.m64n64k16.f32.bf16.bf16 {%0,%1,%2,%3,%4,%5,%6,%7,%8,%9,%10,%11,%12,%13,%14,%15,%16,%17,%18,%19,%20,%21,%22,%23,%24,%25,%26,%27,%28,%29,%30,%31}, {%32,%33,%34,%35}, %36, 0, 1, 1, 0;"
                 : O4(d, 0), O4(d, 4), O4(d, 8), O4(d, 12), O4(d, 16), O4(d, 20), O4(d, 24), O4(d, 28) : "r"(a0), "r"(a1), "r"(a2), "r"(a3), "l"(desc));
}
#define WG_FENCE() asm volatile("wgmma.fence.sync.aligned;" ::: "memory")
#define WG_COMMIT() asm volatile("wgmma.commit_group.sync.aligned;" ::: "memory")
#define WG_WAIT(n) asm volatile("wgmma.wait_group.sync.aligned " #n ";" ::: "memory")
#define TQ(p, k) p[2 * (k) + 1], p[2 * (k) + 2], p[2 * (k)], p[2 * (k) + 1]

__device__ __forceinline__ uint4 ld_nc4(const void* p) { uint4 v; asm volatile("ld.global.nc.v4.u32 {%0,%1,%2,%3}, [%4];" : "=r"(v.x), "=r"(v.y), "=r"(v.z), "=r"(v.w) : "l"(p)); return v; }
__device__ __forceinline__ uint2 ld_nc2(const void* p) { uint2 v; asm volatile("ld.global.nc.v2.u32 {%0,%1}, [%2];" : "=r"(v.x), "=r"(v.y) : "l"(p)); return v; }
__device__ __forceinline__ unsigned short ld_nc16(const void* p) { unsigned short v; asm volatile("ld.global.nc.u16 %0, [%1];" : "=h"(v) : "l"(p)); return v; }
__device__ __forceinline__ uint32_t ld_nc(const void* p) { uint32_t v; asm volatile("ld.global.nc.u32 %0, [%1];" : "=r"(v) : "l"(p)); return v; }
__device__ __forceinline__ uint32_t ld_rlx(const unsigned int* p) { uint32_t v; asm volatile("ld.relaxed.gpu.global.u32 %0, [%1];" : "=r"(v) : "l"(p) : "memory"); return v; }
__device__ __forceinline__ uint2 ld_rlx2(const void* p) { uint2 v; asm volatile("ld.relaxed.gpu.global.v2.u32 {%0,%1}, [%2];" : "=r"(v.x), "=r"(v.y) : "l"(p) : "memory"); return v; }
__device__ __forceinline__ uint4 ld_rlx4(const void* p) { uint4 v; asm volatile("ld.relaxed.gpu.global.v4.u32 {%0,%1,%2,%3}, [%4];" : "=r"(v.x), "=r"(v.y), "=r"(v.z), "=r"(v.w) : "l"(p) : "memory"); return v; }
__device__ __forceinline__ void st_rlx(unsigned int* p, uint32_t v) { asm volatile("st.relaxed.gpu.global.u32 [%0], %1;" ::"l"(p), "r"(v) : "memory"); }
__device__ __forceinline__ void st_rlx2(void* p, uint32_t a, uint32_t b) { asm volatile("st.relaxed.gpu.global.v2.u32 [%0], {%1,%2};" ::"l"(p), "r"(a), "r"(b) : "memory"); }
__device__ __forceinline__ void st_rlx4(void* p, uint4 v) { asm volatile("st.relaxed.gpu.global.v4.u32 [%0], {%1,%2,%3,%4};" ::"l"(p), "r"(v.x), "r"(v.y), "r"(v.z), "r"(v.w) : "memory"); }
__device__ __forceinline__ void red_inc(unsigned int* p) { asm volatile("red.relaxed.gpu.global.add.u32 [%0], 1;" ::"l"(p) : "memory"); }

__device__ __forceinline__ void mbar_init(uint32_t a, int cnt) { asm volatile("mbarrier.init.shared::cta.b64 [%0], %1;" ::"r"(a), "r"(cnt) : "memory"); }
__device__ __forceinline__ void mbar_expect(uint32_t a, uint32_t bytes) { asm volatile("mbarrier.arrive.expect_tx.shared::cta.b64 _, [%0], %1;" ::"r"(a), "r"(bytes) : "memory"); }
__device__ __forceinline__ void mbar_wait(uint32_t a, uint32_t parity) {
    uint32_t ok;
    int it = 0;
    do {
        ++it;
        asm volatile("{\n.reg .pred p;\nmbarrier.try_wait.parity.shared::cta.b64 p, [%1], %2;\nselp.u32 %0, 1, 0, p;\n}" : "=r"(ok) : "r"(a), "r"(parity) : "memory");
    } while (!ok & (it < SPIN_MAX));
}
__device__ __forceinline__ bool mbar_test(uint32_t a, uint32_t parity) {
    uint32_t ok;
    asm volatile("{\n.reg .pred p;\nmbarrier.test_wait.parity.shared::cta.b64 p, [%1], %2;\nselp.u32 %0, 1, 0, p;\n}" : "=r"(ok) : "r"(a), "r"(parity) : "memory");
    return __all_sync(0xffffffffu, ok);
}
__device__ __forceinline__ void tma2d(uint32_t dst, const CUtensorMap* tm, int c0, int c1, uint32_t mbar) {
    asm volatile("cp.async.bulk.tensor.2d.shared::cluster.global.mbarrier::complete_tx::bytes [%0], [%1, {%3, %4}], [%2];"
                 ::"r"(dst), "l"(tm), "r"(mbar), "r"(c0), "r"(c1) : "memory");
}
__device__ __forceinline__ void bulk_s2g(void* dst, uint32_t src, uint32_t bytes) {
    asm volatile("cp.async.bulk.global.shared::cta.bulk_group [%0], [%1], %2;" ::"l"(dst), "r"(src), "r"(bytes) : "memory");
}
__device__ __forceinline__ uint32_t ld_acq(const unsigned int* p) { uint32_t v; asm volatile("ld.acquire.gpu.global.u32 %0, [%1];" : "=r"(v) : "l"(p) : "memory"); return v; }
__device__ __forceinline__ void bulk_pf(const void* src, uint32_t bytes) { asm volatile("cp.async.bulk.prefetch.L2.global [%0], %1;" ::"l"(src), "r"(bytes) : "memory"); }

struct cplx { float x, y; };
__device__ __forceinline__ cplx cmul(cplx a, cplx b) { cplx r; r.x = a.x * b.x - a.y * b.y; r.y = a.x * b.y + a.y * b.x; return r; }
__device__ __forceinline__ cplx csq(cplx a) { cplx r; r.x = a.x * a.x - a.y * a.y; r.y = 2.0f * a.x * a.y; return r; }
__device__ __forceinline__ uint32_t hcm(uint32_t x, uint32_t y, uint32_t yp) {
    const __half2 X = *(const __half2*)&x, Y = *(const __half2*)&y, YP = *(const __half2*)&yp;
    const __half2 r = __hfma2(__high2half2(X), YP, __hmul2(__low2half2(X), Y));
    return *(const uint32_t*)&r;
}
__device__ __forceinline__ uint32_t hcn(uint32_t x, uint32_t y, uint32_t yq) {
    const __half2 X = *(const __half2*)&x, Y = *(const __half2*)&y, YQ = *(const __half2*)&yq;
    const __half2 r = __hfma2(__hneg2(__high2half2(X)), YQ, __hmul2(__low2half2(X), Y));
    return *(const uint32_t*)&r;
}
__device__ __forceinline__ float2 hsum4(uint32_t a, uint32_t b, uint32_t c, uint32_t d) {
    return __half22float2(__hadd2(__hadd2(*(const __half2*)&a, *(const __half2*)&b), __hadd2(*(const __half2*)&c, *(const __half2*)&d)));
}
__device__ __forceinline__ uint32_t amax2(uint32_t a, uint32_t b) { uint32_t r; asm("max.xorsign.abs.bf16x2 %0, %1, %2;" : "=r"(r) : "r"(a), "r"(b)); return r; }
__device__ __forceinline__ void ln_stats(float s1, float s2, float& meanb, float& rinv) {
    const float mean = s1 * (1.0f / D_);
    const float den = bfr(fsqrt(bfr(bfr(fmaxf(fmaf(-mean, mean, s2 * (1.0f / D_)), 0.f)) + 1e-5f)));
    meanb = bfr(mean);
    rinv = frcp(den);
}

__device__ __forceinline__ int fresh_tid() { int v; asm volatile("mov.u32 %0, %tid.x;" : "=r"(v)); return v - 128; }
__device__ __forceinline__ void mma_k8(float* c, uint32_t a0, uint32_t a1, uint32_t b0) {
    asm volatile("mma.sync.aligned.m16n8k8.row.col.f32.bf16.bf16.f32 {%0,%1,%2,%3}, {%4,%5}, {%6}, {%0,%1,%2,%3};\n"
                 : "+f"(c[0]), "+f"(c[1]), "+f"(c[2]), "+f"(c[3]) : "r"(a0), "r"(a1), "r"(b0));
}
__device__ __forceinline__ void ldsm_x2(uint32_t* r, uint32_t addr) {
    asm volatile("ldmatrix.sync.aligned.m8n8.x2.shared.b16 {%0,%1}, [%2];" : "=r"(r[0]), "=r"(r[1]) : "r"(addr) : "memory");
}
__device__ __forceinline__ void ldsm_x2_t(uint32_t* r, uint32_t addr) {
    asm volatile("ldmatrix.sync.aligned.m8n8.x2.trans.shared.b16 {%0,%1}, [%2];" : "=r"(r[0]), "=r"(r[1]) : "r"(addr) : "memory");
}
__device__ __forceinline__ void stsm_x2(uint32_t addr, uint32_t r0, uint32_t r1) {
    asm volatile("stmatrix.sync.aligned.m8n8.x2.shared.b16 [%0], {%1,%2};" ::"r"(addr), "r"(r0), "r"(r1) : "memory");
}
__device__ __forceinline__ uint4 lds128(uint32_t a) { uint4 v; asm volatile("ld.shared.v4.u32 {%0,%1,%2,%3}, [%4];" : "=r"(v.x), "=r"(v.y), "=r"(v.z), "=r"(v.w) : "r"(a) : "memory"); return v; }
__device__ __forceinline__ uint32_t mapa(uint32_t a, uint32_t r) { uint32_t o; asm("mapa.shared::cluster.u32 %0, %1, %2;" : "=r"(o) : "r"(a), "r"(r)); return o; }
__device__ __forceinline__ void sta4(uint32_t dst, uint4 v, uint32_t mb) {
    asm volatile("st.async.weak.shared::cluster.mbarrier::complete_tx::bytes.v4.b32 [%0], {%1,%2,%3,%4}, [%5];" ::"r"(dst), "r"(v.x), "r"(v.y), "r"(v.z), "r"(v.w), "r"(mb) : "memory");
}
__device__ __forceinline__ void sta2(uint32_t dst, uint32_t a, uint32_t b, uint32_t mb) {
    asm volatile("st.async.weak.shared::cluster.mbarrier::complete_tx::bytes.v2.b32 [%0], {%1,%2}, [%3];" ::"r"(dst), "r"(a), "r"(b), "r"(mb) : "memory");
}
__device__ __forceinline__ void mbar_arrive(uint32_t a) { asm volatile("mbarrier.arrive.shared::cta.b64 _, [%0];" ::"r"(a) : "memory"); }
__device__ __forceinline__ void red4(float4* p, float a, float b, float c) {
    asm volatile("red.relaxed.gpu.global.add.v4.f32 [%0], {%1,%2,%3,%4};" ::"l"(p), "f"(a), "f"(b), "f"(c), "f"(1.0f) : "memory");
}
__device__ __forceinline__ void red4p(bool on, float4* p, float a, float b, float c) {
    asm volatile("{\n.reg .pred q;\nsetp.ne.u32 q, %5, 0;\n@q red.relaxed.gpu.global.add.v4.f32 [%0], {%1,%2,%3,%4};\n}" ::"l"(p), "f"(a), "f"(b), "f"(c), "f"(1.0f), "r"((uint32_t)on) : "memory");
}
__device__ __forceinline__ float4 atom4(float4* p, float a, float b, float c, float d) {
    float4 v;
    asm volatile("atom.relaxed.gpu.global.add.v4.f32 {%0,%1,%2,%3}, [%4], {%5,%6,%7,%8};" : "=f"(v.x), "=f"(v.y), "=f"(v.z), "=f"(v.w) : "l"(p), "f"(a), "f"(b), "f"(c), "f"(d) : "memory");
    return v;
}
__device__ __forceinline__ uint2 lds64(uint32_t a) { uint2 v; asm volatile("ld.shared.v2.u32 {%0,%1}, [%2];" : "=r"(v.x), "=r"(v.y) : "r"(a) : "memory"); return v; }
__device__ __forceinline__ float4 ld_rlx4f(const float4* p) { float4 v; asm volatile("ld.relaxed.gpu.global.v4.f32 {%0,%1,%2,%3}, [%4];" : "=f"(v.x), "=f"(v.y), "=f"(v.z), "=f"(v.w) : "l"(p) : "memory"); return v; }
__device__ __forceinline__ void tma5d_st(const CUtensorMap* tm, int c0, int c4, uint32_t src) {
    asm volatile("cp.async.bulk.tensor.5d.global.shared::cta.bulk_group [%0, {%2, %4, %4, %4, %3}], [%1];" ::"l"(tm), "r"(src), "r"(c0), "r"(c4), "r"(0) : "memory");
}
__device__ __forceinline__ void tma2d_pf(const CUtensorMap* tm, int c0, int c1) {
    asm volatile("cp.async.bulk.prefetch.tensor.2d.L2.global [%0, {%1, %2}];" ::"l"(tm), "r"(c0), "r"(c1) : "memory");
}
__device__ __forceinline__ void pace(int clk) {
    const long long c0 = clock64();
    int it = 0;
    while (clock64() - c0 < clk && ++it < 4096) { }
}
__device__ __forceinline__ uint32_t sign2(uint32_t a) { uint32_t r; asm("prmt.b32 %0, %1, 0, 0xBB99;" : "=r"(r) : "r"(a)); return r; }
#define MB(i) (sb + OFF_MISC + (uint32_t)offsetof(Misc, mbar) + 8 * (i))
__device__ __forceinline__ uint32_t box_tap(int i) {
    const int f = (i * 205) >> 13, l = i - 40 * f - 6 - ((0x35C36 >> (4 * f)) & 15);
    const unsigned wd = (0x16824 >> (4 * f)) & 15, one = f == 4 ? 0xFFFFu : 0x3F80u;
    return ((unsigned)l <= wd ? one : 0u) | ((unsigned)(l - 1) <= wd ? one << 16 : 0u);
}
#define UF(u) ((u) < 4 ? (u) + 5 : (u) == 4 ? 13 : (u) < 10 ? (u) - 5 : (u) - 1)
template <class F>
__device__ __forceinline__ void conv_channel(unsigned char* sm, uint32_t rank, uint32_t fixa, uint32_t fixv, F& late) {
    Misc& M = *(Misc*)(sm + OFF_MISC);
    const uint32_t sb = (uint32_t)__cvta_generic_to_shared(sm);
    const int tid = fresh_tid(), lane = tid & 31, g = lane >> 2, t = lane & 3, lr = lane & 7, lm = lane >> 3;
    const int warp_ = __shfl_sync(0xffffffffu, tid >> 5, 0), wgi = warp_ >> 2, w = warp_ & 3;
    const uint32_t cb = sb + OFF_CH + wgi * CHS;
    float D[32];
    const uint32_t dlo = ((cb & 0x3FFFF) >> 4) | ((UP >> 4) << 16);
#define DS(o, z, bl) (((uint64_t)(128 >> 4) << 32) | (uint64_t)(dlo + (o) / 16 + (((z) & 1) ? 0 : UP / 8) - ((z) >> 1) * (bl)))
    const uint32_t pf = cb + XO_TF + (w >> 1) * UP + (8 + 16 * (w & 1) + g - 2 * t) * 4;
    uint32_t p[13], r9[9];
    named_bar(1 + wgi, 128);
    if (fixa) sts16(fixa, fixv);
#pragma unroll
    for (int s = 0; s < 13; s++) p[s] = lds32(pf + s * 32);
    {
        const uint32_t a8 = cb + UB + t * UP + g * 16 + w * 128, b8 = cb + XO_U8 + lm * UP + lr * 16 + w * 128;
        const uint32_t a16 = cb + UB + (2 * (lr & 1) + (lm & 1)) * UP + ((lr >> 1) + 2 * (lm & 2)) * 16 + w * 128;
        const uint32_t b16 = cb + XO_U16 + (2 * (w & 1) + (lm >> 1)) * UP + (lane & 15) * 16 + (w >> 1) * 256;
        uint32_t r[3][4];
        mbar_wait(cb + XO_MBU, 0);
        ldsm_x4_t(r[0], a8);
        ldsm_x4_t(r[1], a16);
        if (w < 2) ldsm_x4_t(r[2], a8 + 512);
        stsm_x4(b8, r[0][0], r[0][1], r[0][2], r[0][3]);
        stsm_x4(b16, r[1][0], r[1][1], r[1][2], r[1][3]);
        if (w < 2) stsm_x4(b8 + 512, r[2][0], r[2][1], r[2][2], r[2][3]);
    }
    PROXY_FENCE();
    named_bar(1 + wgi, 128);
    const uint32_t pa = cb + XO_TD + (40 + 8 * w + g - 2 * t) * 4, pq = sb + OFF_MISC + (8 * w - 18 + g - 2 * t) * 4;
    uint32_t q[3][8], k2;
    auto ld = [&](int u) {
        uint32_t* d = q[u % 3];
        const int f = UF(u);
        if (f >= 5) {
#pragma unroll
            for (int i = 0; i < 8; i++) d[i] = (f == 13 && i > 4) ? 0u : lds32(pa + (f - 5) * 256 + i * 32);
        } else {
            const int lo = f == 2, hi = f == 2 ? 3 : (f == 1 || f == 4) ? 1 : 2;
#pragma unroll
            for (int i = 0; i < 8; i++) {
                if (f < 3) d[i] = 0u;
                if (i >= lo && i <= hi + 3) {
                    asm volatile("{\n.reg .pred p;\nsetp.le.u32 p, %2, %3;\n@p ld.shared.u32 %0, [%1];\n}" : "+r"(d[i]) : "r"(pq + f * 160 + i * 32), "r"(w + i - 3 - lo), "r"(hi - lo));
                    if (f == 4) asm volatile("and.b32 %0, %0, %1;" : "+r"(d[i]) : "r"(k2));
                }
            }
        }
    };
    auto go = [&](int u) {
        const int f = UF(u);
        WG_FENCE();
#pragma unroll
        for (int z = 0; z < 2; z++) {
            const uint32_t* a = q[u % 3] + 2 * z;
#define Q4 a[1], a[5], a[0], a[4]
            if (f == 5 && z == 0) wg64z(D, Q4, DS(UB, 0, 2));
            else if (f < 2) wg48(D + 8, Q4, DS(f ? XO_ZB : XO_ZA, z, 0));
            else if (f < 5) wg32(D + 16, Q4, DS(f == 2 ? XO_ZC : f == 3 ? XO_ZD : UB, z, 0));
            else if (f < 9) wg64(D, Q4, DS(UB, 2 * (f - 5) + z, 2));
            else if (f == 13) wg48(D + 8, Q4, DS(UB, z, 0));
            else wg56(D + 4, Q4, DS(UB + 128, 2 * (f - 5) + z, 2));
        }
        WG_COMMIT();
    };
    {
        float Z8[24], Z16[16];
        uint32_t z8[12], z16[8];
        const uint32_t za = cb + ((w >> 1) ? XO_ZB : XO_ZA) + t * UP + (4 * (w & 1) + (g & 3) + 8 * (g >> 2)) * 16;
        const uint32_t zc = cb + ((w >> 1) ? XO_ZD : XO_ZC) + (2 * (lr & 1) + (lm >> 1)) * UP + (((lane & 15) >> 1) + 8 * (w & 1)) * 16;
        WG_FENCE();
#pragma unroll
        for (int e = 0; e < 6; e++) {
            if (e == 0) wg48z(Z8, TQ(p, e), DS(XO_U8, e, 8));
            else wg48(Z8, TQ(p, e), DS(XO_U8, e, 8));
        }
        WG_COMMIT();
        late();
        WG_WAIT(0);
        asm volatile("setmaxnreg.inc.sync.aligned.u32 88;");
#pragma unroll
        for (int s = 0; s < 9; s++) r9[s] = lds32(pf + 2 * UP + s * 32);
#pragma unroll
        for (int i = 0; i < 12; i++) asm volatile("cvt.rn.bf16x2.f32 %0, %1, %2;" : "=r"(z8[i]) : "f"(Z8[2 * i + 1]), "f"(Z8[2 * i]));
        WG_FENCE();
#pragma unroll
        for (int e = 0; e < 4; e++) {
            if (e == 0) wg32z(Z16, TQ(r9, e), DS(XO_U16, e, 16));
            else wg32(Z16, TQ(r9, e), DS(XO_U16, e, 16));
        }
        WG_COMMIT();
        WG_WAIT(0);
#pragma unroll
        for (int i = 0; i < 8; i++) asm volatile("cvt.rn.bf16x2.f32 %0, %1, %2;" : "=r"(z16[i]) : "f"(Z16[2 * i + 1]), "f"(Z16[2 * i]));
        named_bar(1 + wgi, 128);
#pragma unroll
        for (int i = 0; i < 3; i++) stsm_x4(za + i * 256, z8[4 * i], z8[4 * i + 1], z8[4 * i + 2], z8[4 * i + 3]);
#pragma unroll
        for (int ob = 0; ob < 2; ob++) stsm_x4(zc + ob * 256, z16[4 * ob], z16[4 * ob + 1], z16[4 * ob + 2], z16[4 * ob + 3]);
    }
    {
#define RD_(o) _Pragma("unroll") for (int i = o; i < 32; i++) { float y_; asm volatile("mov.b32 %0, %1;" : "=f"(y_) : "f"(D[i])); D[i] = y_; }
        ld(0); ld(1);
        go(0);
        ld(2);
        go(1);
        k2 = lds32(cb + XO_K1024);
#pragma unroll
        for (int u = 2; u < 14; u++) {
            WG_WAIT(1);
            if (u < 13) ld(u + 1);
            if (u == 4 || u == 7 || u == 10) { WG_WAIT(0); RD_(u == 4 ? 8 : u == 7 ? 16 : 4); }
            go(u);
            if (u == 3) { PROXY_FENCE(); named_bar(1 + wgi, 128); }
        }
    }
    {
        const int tid = fresh_tid(), lane = tid & 31, lr = lane & 7, lm = lane >> 3;
        uint32_t u[2][4];
        const uint32_t ua = cb + UB + w * UP + lm * 256 + lr * 16;
        ldsm_x4_t(u[0], ua); ldsm_x4_t(u[1], ua + 128);
        const uint32_t dk2 = __byte_perm(lds32(cb + XO_DSK), 0, (rank & 1) ? 0x3232 : 0x1010);
#pragma unroll
        for (int i = 0; i < 8; i++) u[i >> 2][i & 3] = mul2(u[i >> 2][i & 3], dk2);
        mbar_wait(MB(MB_C2), 0);
        const uint32_t ga2 = M.ga[wgi];
        const int src = (lane & 28) | ((lane + 3) & 3);
        WG_WAIT(0);
        float s[8];
#pragma unroll
        for (int j = 0; j < 8; j++) s[j] = __shfl_sync(0xffffffffu, (lane & 3) < 3 ? D[4 * j + 3] : j ? D[4 * j - 1] : 0.f, src);
#pragma unroll
        for (int h = 0; h < 2; h++) {
            const uint32_t rb = mapa(sb, w + 4 * h);
#pragma unroll
            for (int j = 0; j < 4; j++) u[h][j] = mul2(ga2, add2(pack2(D[8 * j + 4 * h] + s[2 * j + h], D[8 * j + 4 * h + 1] + D[8 * j + 4 * h + 2]), u[h][j]));
            sta4(rb + OFF_V + (8 * wgi + rank) * VP + lane * 16, make_uint4(u[h][0], u[h][1], u[h][2], u[h][3]), rb + (MB(MB_V) - sb));
        }
    }
}
#define M2W 4
#define WS 0x3210
#define WMS(p) if (warp == 7) { if (p == 0) CL_WAIT(); if (lane == 0) { _Pragma("unroll") for (int i = 2; i < 6; i++) if (((WS >> (4 * (i - 2))) & 15) == p) tma2d(sb + (i == 5 ? OFF_WM0 + 11520 : OFF_WM2 + (i - 2) * 5760), &tm_wm, i * D_ + 40 * cl, 72 * rk, MB(MB_WM2)); } __syncwarp(); }
#define PQT 10
#define PQD 400
#define L2P 2
#define L2M 2
#define PDE 100
#define WMD 400
#define CWP 200
#define CWD 3000
#define ROW(key) (((~(key) << 2) & 0xE0u) | ((~(key) >> 6) & 24u) | ((~(key) >> 11) & 6u) | ((~(key) >> 8) & 1u))
#define RKT (((rk & 4) << 6) | ((rk & 3) << 3))
#define MINE(key) ((~(key) & 0x8C0u) == (uint32_t)(RKT << 3))
#define CE(a, b) { const uint32_t hi_ = max(a, b); b = min(a, b); a = hi_; }
#define POP(k, m) if (k.x == m) { k.x = k.y; k.y = k.z; k.z = k.w; k.w = 0u; }
#define CGT(c, a, b, n) asm volatile("{\n.reg .pred p;\nsetp.gt.u32 p, %1, %2;\n@p add.u32 %0, %0, " #n ";\n}" : "+r"(c) : "r"(a), "r"(b))
#define CL_ARRIVE() asm volatile("barrier.cluster.arrive.relaxed.aligned;" ::: "memory")
#define CL_WAIT() asm volatile("barrier.cluster.wait.aligned;" ::: "memory")
__global__ void __cluster_dims__(8, 1, 1) __launch_bounds__(NTHR, 1)
clus_kernel(const bf16* __restrict__ x, const bf16* __restrict__ logAr, const bf16* __restrict__ Aim, const bf16* __restrict__ Cr, const bf16* __restrict__ Ci,
            const bf16* __restrict__ logdt, const bf16* __restrict__ c_in, Scratch* __restrict__ S, const bf16* __restrict__ Dskip,
            const bf16* __restrict__ w_r, const bf16* __restrict__ w_mod, bf16* __restrict__ out,
            const __grid_constant__ CUtensorMap tm_wm, const __grid_constant__ CUtensorMap tm_wg,
            const __grid_constant__ CUtensorMap tm_wu, const __grid_constant__ CUtensorMap tm_wd, const __grid_constant__ CUtensorMap tm_out) {
    extern __shared__ __align__(1024) unsigned char sm[];
    Misc& M = *(Misc*)(sm + OFF_MISC);
    const uint32_t sb = (uint32_t)__cvta_generic_to_shared(sm);
    const int tid = threadIdx.x < 128 ? threadIdx.x + 640 : threadIdx.x - 128, warp = __shfl_sync(0xffffffffu, tid >> 5, 0), lane = tid & 31;
    const int g = lane >> 2, t = lane & 3, lr = lane & 7, lm = lane >> 3;
    const int wgi = warp >> 2, w = warp & 3;
    const int b = blockIdx.x, cl = b >> 3, rk = b & 7;
    auto mod_ld = [&](uint32_t (*a)[4], uint32_t s0, uint32_t s1, int i) {
        const uint32_t wa = sb + ((lm & 1) ? s1 : s0) + (lr + 8 * (lm >> 1)) * 80 + i * 16;
#pragma unroll
        for (int ks = 0; ks < 4; ks++) ldsm_x4_t(a[ks], wa + ks * 1280);
        ldsm_x2_t(a[4], wa + 5120);
    };
    auto mod_mma2 = [&](float* d, float* e, uint32_t (*a)[4], uint32_t (*c)[4], const uint32_t* bs) {
        mma_k8(d, a[4][0], a[4][1], bs[8]); mma_k8(e, c[4][0], c[4][1], bs[8]);
#pragma unroll
        for (int ks = 0; ks < 4; ks++) {
            mma_bf16(d, a[ks][0], a[ks][1], a[ks][2], a[ks][3], bs[2 * ks], bs[2 * ks + 1]);
            mma_bf16(e, c[ks][0], c[ks][1], c[ks][2], c[ks][3], bs[2 * ks], bs[2 * ks + 1]);
        }
    };
    auto mod_st = [&](const float* d, uint32_t dst, int mb) {
#pragma unroll
        for (int h = 0; h < 2; h++) {
            const uint32_t rb = mapa(sb, t + 4 * h);
            sta2(rb + dst + g * 8, __float_as_uint(d[0]), __float_as_uint(d[2]), rb + (MB(mb) - sb));
        }
    };
    auto gsum = [&](uint32_t a, int pitch) {
        float4 s = make_float4(0.f, 0.f, 0.f, 0.f);
#pragma unroll
        for (int i = 0; i < 8; i++) { const float4 q = *(const float4*)(sm + a + i * pitch); s.x += q.x; s.y += q.y; s.z += q.z; s.w += q.w; }
        return make_uint2(pack2(s.x, s.z), pack2(s.y, s.w));
    };
    auto one_plus = [&](uint32_t v) { return pack2(1.0f + lo2f(v), 1.0f + hi2f(v)); };
    auto mkc1 = [&]() {
        const int lane = fresh_tid() & 31;
        const uint2 v = gsum(OFF_MG1 + 16 * min(lane, 19), 320);
        const uint32_t c1 = one_plus(v.x);
        if (lane < 20) *(uint4*)(sm + OFF_C1 + 16 * lane) = make_uint4(__byte_perm(c1, 0, 0x1010), __byte_perm(v.y, 0, 0x1010), __byte_perm(c1, 0, 0x3232), __byte_perm(v.y, 0, 0x3232));
        __syncwarp();
        named_arrive(10, 160);
    };
    if (wgi == 5) {
        CL_ARRIVE();
        const uint32_t c_a = ld_nc((const uint32_t*)c_in + 36 * rk + lane), c_b = ld_nc((const uint32_t*)c_in + 36 * rk + 32 + t);
        {
            pace(WMD);
            const char* wp = (const char*)(w_mod + (72 * rk + 18 * w) * (6 * D_) + 40 * cl);
#pragma unroll
            for (int i = 0; i < 3; i++) {
                const uint32_t c = lane + 32 * i, row = (c * 205) >> 10;
                const char* p = wp + (row * (12 * D_ - 80) + 16 * c);
                if (c < 90) {
                    asm volatile("cp.async.cg.shared.global [%0], [%1], 16;" ::"r"(sb + OFF_WM0 + 1440 * w + 16 * c), "l"(p) : "memory");
                    asm volatile("cp.async.cg.shared.global [%0], [%1], 16;" ::"r"(sb + OFF_WM0 + 5760 + 1440 * w + 16 * c), "l"(p + 2 * D_) : "memory");
                }
            }
            if (w == 3 && lane < 20)
                asm volatile("cp.async.ca.shared.global [%0], [%1], 4, %2;" ::"r"(sb + OFF_MISC + (uint32_t)offsetof(Misc, c2) + 12 + 16 * lane), "l"((const uint32_t*)w_r + min(20 * cl + lane, D_ / 2 - 1)),
                             "r"(20 * cl + lane < D_ / 2 ? 4 : 0) : "memory");
            asm volatile("cp.async.commit_group;" ::: "memory");
        }
        {
            uint32_t bs[9], a[5][4], c[5][4];
            float d[4] = {0.f, 0.f, 0.f, 0.f}, e[4] = {0.f, 0.f, 0.f, 0.f};
            const uint32_t sc = pack2(silu(lo2f(c_a)), silu(hi2f(c_a)));
            bs[8] = pack2(silu(lo2f(c_b)), silu(hi2f(c_b)));
            if (w == 2) { sts32(sb + OFF_SC + 4 * lane, sc); sts32(sb + OFF_SC + 128 + 4 * t, bs[8]); }
#pragma unroll
            for (int ks = 0; ks < 8; ks++) bs[ks] = __shfl_sync(0xffffffffu, sc, 4 * ks + t);
            CL_WAIT();
            asm volatile("cp.async.wait_group 0;" ::: "memory");
            named_bar(10, 128);
            mod_ld(a, OFF_WM0 + 5760, OFF_WM0, w);
            mod_ld(c, OFF_WM0 + 5760, OFF_WM0, 4);
            mod_mma2(d, e, a, c, bs);
            mod_st(d, OFF_MG1 + rk * 320 + 64 * w, MB_MG1);
            if (w == 1) mod_st(e, OFF_MG1 + rk * 320 + 256, MB_MG1);
        }
        {
            const int n0 = 8 * w + 2 * (rk & 1), n1 = 8 * w + ((n0 + 4 + t) & 7);
            const float4* ap = &S->acc1[256 * rk + 8 * (n0 + t) + g];
            const float4* aq = &S->acc1[256 * rk + 8 * n1 + g];
            named_bar(9, 640);
            float4 pa = ld_rlx4f(ap), pb = ld_rlx4f(aq);
            uint32_t xq[2][5][4];
            uint2 cc[5];
            const uint32_t xa = sb + OFF_X + XI(2 * lm + (lr & 1)) + XN(n0 + (lr >> 1)), xb = sb + OFF_X + XI(2 * lm + (lr & 1)) + XN(8 * w + ((n0 + 4 + (lr >> 1)) & 7));
            const uint32_t ua = mapa(sb, g) + OFF_CH;
#pragma unroll
            for (int j = 0; j < 5; j++) ldsm_x4_t(xq[0][j], xa + 16 * j);
#pragma unroll 1
            for (int it = 0; it < SPIN_MAX && (pa.w != (float)NCL || pb.w != (float)NCL); it++) {
                pa = ld_rlx4f(ap); pb = ld_rlx4f(aq);
            }
            __syncwarp();
            float m0, r0, m1, r1;
            ln_stats(pa.x, pa.y, m0, r0);
            ln_stats(pb.x, pb.y, m1, r1);
            const uint32_t rh = pack2(r0, r1), rl = pack2(r0 - lo2f(rh), r1 - hi2f(rh));
            const uint32_t stage = sb + OFF_STG + w * 512;
            stsm_x4_t(stage + lane * 16, pack2(m0, m1), rh, rl, rl);
            __syncwarp();
            named_bar(10, 160);
            uint4 st[2][3];
#pragma unroll
            for (int q = 0; q < 2; q++)
#pragma unroll
                for (int i = 0; i < 3; i++) st[q][i] = lds128(stage + 128 * i + (2 * t + q) * 16);
#pragma unroll
            for (int j = 0; j < 5; j++) cc[j] = *(const uint2*)(sm + OFF_C1 + 64 * j + 8 * g);
            ldsm_x4_t(xq[1][0], xb);
            const uint32_t ub = ua + (rk & 3) * UP + UB + (8 * w + 8 * (rk >> 2)) * 16, u0 = ub + (n0 + t) * 16, u1 = ub + n1 * 16;
#pragma unroll
            for (int j = 0; j < 5; j++) {
                if (j >= 2 && cl == 14) break;
                if (j < 4) ldsm_x4_t(xq[1][j + 1], xb + 16 * (j + 1));
#pragma unroll
                for (int q = 0; q < 2; q++) {
                    const uint4 sm_ = st[q][0], sh = st[q][1], sl = st[q][2];
                    const uint32_t v0 = add2(mul2(norm2(xq[q][j][0], sm_.x, sh.x, sl.x), cc[j].x), cc[j].y), v1 = add2(mul2(norm2(xq[q][j][1], sm_.y, sh.y, sl.y), cc[j].x), cc[j].y);
                    const uint32_t v2 = add2(mul2(norm2(xq[q][j][2], sm_.z, sh.z, sl.z), cc[j].x), cc[j].y), v3 = add2(mul2(norm2(xq[q][j][3], sm_.w, sh.w, sl.w), cc[j].x), cc[j].y);
                    asm volatile("{\n.reg .pred p;\nsetp.ne.u32 p, %6, %7;\n"
                                 "@p st.async.weak.shared::cluster.mbarrier::complete_tx::bytes.v4.b32 [%0], {%1,%2,%3,%4}, [%5];\n"
                                 "@!p st.shared.v4.b32 [%0], {%1,%2,%3,%4};\n}"
                                 ::"r"((q ? u1 : u0) + j * CHS), "r"(v0), "r"(v1), "r"(v2), "r"(v3), "r"(ua + j * CHS + XO_MBU), "r"(g), "r"(rk) : "memory");
                }
                __syncwarp();
                if (lane == 0) mbar_arrive(sb + OFF_CH + XO_MBU + j * CHS);
            }
        }
        asm volatile("setmaxnreg.dec.sync.aligned.u32 40;");
        {
        int cl;
        asm volatile("mov.u32 %0, %clusterid.x;" : "=r"(cl));
        const int w = __shfl_sync(0xffffffffu, (fresh_tid() >> 5) & 3, 0);
        if (w) named_arrive(11, 128); else named_bar(11, 128);
        if (w == 0) {
            const int lane = fresh_tid() & 31;
            mbar_wait(MB(MB_KD), 0);
            PROXY_FENCE();
            if (lane == 0) {
                tma2d(sb + OFF_WU + 15360, &tm_wu, 40 * b, 192, MB(MB_WU));
                tma2d_pf(&tm_wu, 40 * b, 384);
                mbar_wait(MB(MB_C2), 0);
                PROXY_FENCE();
                tma2d(sb + OFF_WU + 2 * 15360, &tm_wu, 40 * b, 384, MB(MB_WU));
#pragma unroll 1
                for (int i = 0; i < 9; i++) { pace(PDE); tma2d_pf(&tm_wd, 64 * i, 40 * b); }
                mbar_wait(MB(MB_WU), 0);
            }
            __syncwarp();
        } else if (w == 2) {
            if ((fresh_tid() & 31) == 0) {
                float4 v;
                int it = 0;
                pace(CWD);
                for (;;) { v = ld_rlx4f(&S->acc1[L_]); if (++it >= SPIN_MAX || (v.z == (float)G_ && v.w == (float)NCL)) break; pace(CWP); }
                M.cws[0] = v.x; M.cws[1] = v.y;
                mbar_arrive(MB(MB_CW));
            }
            __syncwarp();
            mbar_wait(MB(MB_C2), 0);
            const int lane = fresh_tid() & 31;
            if (rk == 0 && lane < (cl < 14 ? 5 : 2)) st_rlx4(&S->h2c[136 * 72 + 5 * cl + lane], make_uint4(~M.c2[4 * lane].z, ~M.c2[4 * lane + 1].z, ~M.c2[4 * lane + 2].z, ~M.c2[4 * lane + 3].z));
        } else if (w == 3) {
            const int lane = fresh_tid() & 31, l20 = min(lane, 19);
            mbar_wait(MB(MB_MG2), 0);
            const uint2 v = gsum(OFF_MG2 + 16 * l20, 640), u = gsum(OFF_MG2 + 320 + 16 * l20, 640);
            const uint32_t wr = lane < 20 ? M.c2[lane].w : 0u, cb1 = one_plus(v.x), cw = mul2(cb1, wr);
            if (lane < 20) {
                M.c2[lane] = make_uint4(cb1, v.y, u.x, cw);
                M.wr[lane] = wr;
                unsigned e;
                asm volatile("mov.u32 %0, %cluster_ctarank;" : "=r"(e));
                if ((lane & 3) == (e >> 1)) M.ga[lane >> 2] = __byte_perm(u.y, 0, (e & 1) ? 0x3232 : 0x1010);
            }
            __syncwarp();
            if (lane == 0) mbar_arrive(MB(MB_C2));
            if (rk == 0) {
                float a = lo2f(cw) + hi2f(cw), s = lo2f(v.y) * lo2f(wr) + hi2f(v.y) * hi2f(wr);
#pragma unroll
                for (int o = 16; o; o >>= 1) { a += __shfl_xor_sync(0xffffffffu, a, o); s += __shfl_xor_sync(0xffffffffu, s, o); }
                if (lane == 0) red4(&S->acc1[L_], a, s, 0.f);
            }
        }
        {
        const int lane = fresh_tid() & 31, t = lane & 3, lr = lane & 7, lm = lane >> 3;
        uint32_t aw[5];
        __syncwarp();
        mbar_wait(MB(MB_C2), 0);
#pragma unroll
        for (int j = 0; j < 5; j++) aw[j] = M.wr[4 * j + t];
        const int ph = w >> 1, lst = 16 * ph + 2 * rk + (w & 1);
        const uint32_t rb = mapa(sb, lr);
        named_bar(6, 640);
        uint4 k = *(const uint4*)&M.key[128 * (w & 1) + 4 * lane];
        CE(k.x, k.y); CE(k.z, k.w); CE(k.x, k.z); CE(k.y, k.w); CE(k.y, k.z);
        uint32_t m[4];
#pragma unroll 1
        for (int q = 0; q <= ph; q++) {
#pragma unroll
            for (int rnd = 0; rnd < 4; rnd++) {
                m[rnd] = __reduce_max_sync(0xffffffffu, k.x);
                POP(k, m[rnd]);
            }
        }
        if (lane < 8) sta4(rb + OFF_MISC + (uint32_t)offsetof(Misc, cand) + lst * 16, make_uint4(m[0], m[1], m[2], m[3]), rb + (MB(MB_KEY2) - sb));
        const uint32_t mine = (t & 2) ? ((t & 1) ? m[3] : m[2]) : ((t & 1) ? m[1] : m[0]);
        const uint32_t ra = sb + OFF_H2T + ROW(mine) * 80;
        uint32_t bq[6];
        float rr[4] = {0.f, 0.f, 0.f, 0.f};
        ldsm_x4(bq, ra + 16 * lm); ldsm_x2(bq + 4, ra + 64);
        mma_bf16(rr, aw[0], aw[0], aw[1], aw[1], bq[0], bq[1]); mma_bf16(rr, aw[2], aw[2], aw[3], aw[3], bq[2], bq[3]); mma_k8(rr, aw[4], aw[4], bq[4]);
        float4* p = &S->rs[8 * lst];
        if (lane < 2) red4(p + lane, rr[0], 0.f, rr[1]);
        float4 e0 = ld_rlx4f(p), e1 = ld_rlx4f(p + 1);
        uint32_t sl = 0;
        if (w == 1) {
            mbar_wait(MB(MB_KEY2), 0);
            k = *(const uint4*)&M.cand[4 * lane];
            named_bar(14, 64);
#pragma unroll
            for (int s = 0; s < 8; s++) {
                const uint32_t v = M.sel[s] & ~1u;
                if (k.x == v) sl |= 8 + s;
                if (k.y == v) sl |= (8 + s) << 8;
                if (k.z == v) sl |= (8 + s) << 16;
                if (k.w == v) sl |= (8 + s) << 24;
            }
        }
        if (w == 0) {
            named_bar(8, 64);
            if (lane == 0) {
                PROXY_FENCE();
                tma5d_st(&tm_out, 40 * cl, RKT, sb + OFF_OUT);
                asm volatile("cp.async.bulk.commit_group;" ::: "memory");
            }
            __syncwarp();
        }
#pragma unroll 1
        for (int it = 0; it < SPIN_MAX && (e0.w != (float)NCL || e1.w != (float)NCL); it++) {
            e0 = ld_rlx4f(p); e1 = ld_rlx4f(p + 1);
        }
        {
            const uint32_t r0 = pack2(e0.x, e0.z), r1 = pack2(e1.x, e1.z);
            const uint32_t o0 = r0 ^ (sign2(r0) | 0x80008000u), o1 = r1 ^ (sign2(r1) | 0x80008000u);
            if (lane < 8) sta4(rb + OFF_EK + lst * VP, make_uint4((o0 << 16) | (m[0] & 0x3FFFu), (o0 & 0xFFFF0000u) | (m[1] & 0x3FFFu), (o1 << 16) | (m[2] & 0x3FFFu), (o1 & 0xFFFF0000u) | (m[3] & 0x3FFFu)),
                               rb + (MB(MB_EK) - sb));
        }
        if (w == 0) {
            if (lane == 0) {
                asm volatile("cp.async.bulk.wait_group 0;" ::: "memory");
                asm volatile("fence.acq_rel.gpu;" ::: "memory");
                mbar_arrive(MB(MB_OUT));
            }
        } else if (w == 1) {
            const uint32_t found = __reduce_add_sync(0xffffffffu, __popc(sl & 0x08080808u));
            mbar_wait(MB(MB_EK), 0);
            if (b == 0 && lane == 0) st_rlx4(&S->acc1[L_], make_uint4(0, 0, 0, 0));
            if (lane < 16 || cl == 14) st_rlx4(&S->acc2[256 * rk + 16 * cl + lane], make_uint4(0, 0, 0, 0));
            k = lds128(sb + OFF_EK + lane * VP);
            const bool s0 = sl & 8u, s1 = sl & 0x800u, s2 = sl & 0x80000u, s3 = sl & 0x8000000u;
            if (s0) M.fin[sl & 7u] = k.x;
            if (s1) M.fin[(sl >> 8) & 7u] = k.y;
            if (s2) M.fin[(sl >> 16) & 7u] = k.z;
            if (s3) M.fin[(sl >> 24) & 7u] = k.w;
            const uint32_t lo = min(min(s0 ? k.x : ~0u, s1 ? k.y : ~0u), min(s2 ? k.z : ~0u, s3 ? k.w : ~0u));
            const uint32_t hi = max(max(s0 ? 0u : k.x, s1 ? 0u : k.y), max(s2 ? 0u : k.z, s3 ? 0u : k.w));
            const uint32_t hi2 = __reduce_max_sync(0xffffffffu, hi), lo2 = __reduce_min_sync(0xffffffffu, lo);
            bool redo = found != 8u;
            if (hi2 > lo2) {
                const uint32_t h = hi2 | 0xFFFFu, l = lo2 & 0xFFFF0000u;
                const uint32_t n = __reduce_add_sync(0xffffffffu, ((s0 ? k.x <= h : (k.x >= l) << 8) + (s1 ? k.y <= h : (k.y >= l) << 8)) + ((s2 ? k.z <= h : (k.z >= l) << 8) + (s3 ? k.w <= h : (k.w >= l) << 8)));
                redo = redo || (h >> 16) - (l >> 16) > 1u || ((n & 255u) > 1u && n >= 512u) || (n & 255u) + (n >> 8) > 9u;
            }
            if (redo) {
                CE(k.x, k.y); CE(k.z, k.w); CE(k.x, k.z); CE(k.y, k.w); CE(k.y, k.z);
                __syncwarp();
#pragma unroll 1
                for (int rnd = 0; rnd < 8; rnd++) {
                    const uint32_t m8 = __reduce_max_sync(0xffffffffu, k.x);
                    POP(k, m8);
                    if (lane == 0) M.fin[rnd] = m8;
                }
            }
            if (lane == 0) M.fin[8] = redo;
            __syncwarp();
            if (lane == 0) mbar_arrive(MB(MB_FIN));
        }
        }
        }
    } else {
    if (warp != 19) CL_ARRIVE();
    const int chn = 40 * cl + 8 * wgi + rk;
    const bool has_ch = chn < D_;
    const uint32_t cb = sb + OFF_CH + wgi * CHS;
    auto ldx = [&]() {
    if (warp < 16) {
        const char* xp = (const char*)(x + (512 * (warp >> 2) + 64 * (warp & 3) + RKT) * D_ + 40 * cl);
        const uint32_t dst = sb + OFF_X + XN(2 * warp) + XI(lm) + 16 * lr;
        xp += lm * (2 * D_) + 16 * lr;
#pragma unroll
        for (int i = 0; i < 4; i++)
            if (lr < 5) asm volatile("cp.async.cg.shared.global [%0], [%1], 16, %2;" ::"r"(dst + XI(4 * (i & 1)) + 80 * (i >> 1)), "l"(xp + ((i & 1) * 4 + (i >> 1) * 32) * (2 * D_)),
                                     "r"((cl < 14 || lr < 2) ? 16 : 0) : "memory");
    }
    };
    unsigned short r_ldt = 0, r_lar = 0, r_aim = 0;
    uint2 r_cr, r_ci;
    {
        const int n = min(chn, D_ - 1) * N_ + 4 * lane;
        r_ldt = ld_nc16((const unsigned short*)logdt + min(chn, D_ - 1));
        r_lar = ld_nc16((const unsigned short*)logAr + n + w);
        r_aim = ld_nc16((const unsigned short*)Aim + n + w);
        r_cr = ld_nc2(Cr + n);
        r_ci = ld_nc2(Ci + n);
    }
    if (warp == 19) {
        if (lane == 0) asm volatile("prefetch.tensormap [%0];" ::"l"(&tm_wm) : "memory");
        const uint32_t lo = 90u | (10u << 8) | (20u << 16) | (2u << 24), hi = (cl == 14 ? 32u : 80u) | ((rk < 4 ? 40u : 32u) << 8) | (180u << 16) | (180u << 24);
        const uint32_t tx = lane < 8 ? (((lane & 4 ? hi : lo) >> (8 * (lane & 3))) & 255u) : lane == 8 ? 180u : lane < 11 ? 2u : lane == 11 ? (hi >> 8) & 255u : 14u;
        if (lane == 0) {
#pragma unroll
            for (int i = 0; i < MB_N; i++) mbar_init(MB(i), i == MB_KD || i == MB_CD ? 20 : 1);
#pragma unroll
            for (int i = 0; i < 5; i++) mbar_init(sb + OFF_CH + XO_MBU + i * CHS, 5);
        }
        __syncwarp();
        if (lane < 17) mbar_expect(lane < MB_C2 ? MB(lane) : sb + OFF_CH + XO_MBU + (lane - MB_C2) * CHS, tx << 8);
        asm volatile("fence.mbarrier_init.release.cluster;" ::: "memory");
        __syncwarp();
        CL_ARRIVE();
    }
    ldx();
    uint32_t rz[4] = {0u, 0u, 0u, 0u};
    auto rst2 = [&]() {
        if (fresh_tid() == 576) asm volatile("red.relaxed.gpu.global.add.f32 [%0], %1;" ::"l"(&S->acc1[L_].z), "f"(__uint_as_float(0x3F800000u | rz[0] | rz[1] | rz[2] | rz[3])) : "memory");
        __syncwarp();
    };
    auto rst = [&]() {
        if (warp == 18) {
            const int lane = fresh_tid() & 31;
            uint4* rp = S->h2c + NRS * b + lane;
#pragma unroll
            for (int i = 0; i < 4; i++) if (i < 3 || lane < NRS - 96) st_rlx4(rp + 32 * i, make_uint4(0, 0, 0, 0));
#pragma unroll
            for (int i = 0; i < 4; i++) asm volatile("atom.relaxed.gpu.global.or.b32 %0, [%1], 0;" : "=r"(rz[i]) : "l"((unsigned int*)(rp + (i < 3 || lane < NRS - 96 ? 32 * i : 0)) + (i & 1)) : "memory");
        }
    };
    if ((tid & 127) == 32) asm volatile("cp.async.ca.shared.global [%0], [%1], 4;" ::"r"(cb + XO_DSK), "l"((const uint32_t*)Dskip + (min(chn, D_ - 1) >> 1)) : "memory");
    asm volatile("cp.async.commit_group;" ::: "memory");
    auto mod2 = [&]() {
        if (wgi == M2W) {
            const int lane = fresh_tid() & 31, t = lane & 3;
            const uint32_t wa = sb + ((lane & 7) + ((lane >> 1) & 8)) * 80, p0 = wa + ((lane & 8) ? OFF_WM2 + 5760 : OFF_WM2 + 11520), p1 = wa + ((lane & 8) ? OFF_WM2 : OFF_WM0 + 11520);
            auto ld = [&](uint32_t (*a)[4], uint32_t p) {
#pragma unroll
                for (int ks = 0; ks < 4; ks++) ldsm_x4_t(a[ks], p + ks * 1280);
                ldsm_x2_t(a[4], p + 5120);
            };
            const uint32_t rb = mapa(sb, t), rd = mapa(sb, 4) - mapa(sb, 0), dst = rb + OFF_MG2 + rk * 640 + (lane >> 2) * 8;
            auto st = [&](const float* d, uint32_t o) {
                sta2(dst + o, __float_as_uint(d[0]), __float_as_uint(d[2]), rb + (MB(MB_MG2) - sb));
                sta2(dst + rd + o, __float_as_uint(d[0]), __float_as_uint(d[2]), rb + rd + (MB(MB_MG2) - sb));
            };
            uint32_t bs[9], a[5][4], c[5][4];
            float d[4] = {0.f, 0.f, 0.f, 0.f}, e[4] = {0.f, 0.f, 0.f, 0.f};
            mbar_wait(MB(MB_MG1), 0);
#pragma unroll
            for (int ks = 0; ks < 9; ks++) bs[ks] = lds32(sb + OFF_SC + 16 * ks + 4 * t);
            mbar_wait(MB(MB_WM2), 0);
            __syncwarp();
            ld(a, p0 + 16 * w);
            ld(c, p1 + 16 * w);
            {
                float h[6][4];
#pragma unroll
                for (int i = 0; i < 24; i++) h[i >> 2][i & 3] = 0.f;
                mma_k8(h[0], a[4][0], a[4][1], bs[8]); mma_k8(h[3], c[4][0], c[4][1], bs[8]);
#pragma unroll
                for (int ks = 0; ks < 4; ks++) {
                    mma_bf16(h[(ks + 1) % 3], a[ks][0], a[ks][1], a[ks][2], a[ks][3], bs[2 * ks], bs[2 * ks + 1]);
                    mma_bf16(h[3 + (ks + 1) % 3], c[ks][0], c[ks][1], c[ks][2], c[ks][3], bs[2 * ks], bs[2 * ks + 1]);
                }
                d[0] = h[0][0] + h[1][0] + h[2][0]; d[2] = h[0][2] + h[1][2] + h[2][2];
                e[0] = h[3][0] + h[4][0] + h[5][0]; e[2] = h[3][2] + h[4][2] + h[5][2];
                ld(a, ((w & 1) ? p1 : p0) + 64);
                st(d, 64 * w);
                st(e, 320 + 64 * w);
#pragma unroll
                for (int i = 0; i < 20; i++) h[i >> 2][i & 3] = 0.f;
                mma_k8(h[4], a[4][0], a[4][1], bs[8]);
#pragma unroll
                for (int ks = 0; ks < 4; ks++) mma_bf16(h[ks], a[ks][0], a[ks][1], a[ks][2], a[ks][3], bs[2 * ks], bs[2 * ks + 1]);
                d[0] = (h[0][0] + h[1][0]) + (h[2][0] + h[3][0]) + h[4][0]; d[2] = (h[0][2] + h[1][2]) + (h[2][2] + h[3][2]) + h[4][2];
            }
            if (w < 2) st(d, 320 * w + 256);
            __syncwarp();
        }
    };
    auto ln1 = [&]() {
        if (warp < 16) {
            uint32_t a[10];
            const uint32_t xa = sb + OFF_X + XN(2 * warp) + (lm & 1) * 80 + XI(lr) + (lm >> 1) * 16;
            asm volatile("cp.async.wait_group 0;" ::: "memory");
            __syncwarp();
            ldsm_x4(a, xa); ldsm_x4(a + 4, xa + 32); ldsm_x2(a + 8, xa + 64);
            named_arrive(9, 640);
            float c1[4] = {0.f, 0.f, 0.f, 0.f}, c2[4] = {0.f, 0.f, 0.f, 0.f}, c3[4] = {0.f, 0.f, 0.f, 0.f};
#pragma unroll
            for (int j = 0; j < 2; j++) {
                mma_bf16(c1, a[4 * j], a[4 * j + 1], a[4 * j + 2], a[4 * j + 3], 0x3F803F80u, 0x3F803F80u);
                mma_bf16(c2, a[4 * j], a[4 * j + 1], a[4 * j + 2], a[4 * j + 3], a[4 * j], a[4 * j + 2]);
                mma_bf16(c3, a[4 * j], a[4 * j + 1], a[4 * j + 2], a[4 * j + 3], a[4 * j + 1], a[4 * j + 3]);
            }
            mma_k8(c1, a[8], a[9], 0x3F803F80u); mma_k8(c2, a[8], a[9], a[8]); mma_k8(c3, a[8], a[9], a[9]);
            float4* p = &S->acc1[256 * rk + 16 * warp + g];
            red4p(t == (g >> 1), p, c1[0], (g & 1) ? c2[1] : c2[0], 0.f);
            red4p(t == (g >> 1), p + 8, c1[2], (g & 1) ? c3[3] : c3[2], 0.f);
        }
    };
    {
        unsigned char* cp = sm + OFF_CH + wgi * CHS + lane * 16;
        const uint4 z = make_uint4(0, 0, 0, 0);
        *(uint4*)(cp + w * UP + XO_TF) = z;
        *(uint4*)(cp + w * UP + (lane < 16 ? XO_U8 - 256 : XO_U16 - 512)) = z;
        if (lane < 16) *(uint4*)(cp + (lane < 8 ? w * UP + UB - 128 : XO_TD + (4 * w + (lane < 12 ? -8 : 145 - 12)) * 16)) = z;
    }
    if (tid < 200) ((uint32_t*)M.box)[tid] = box_tap(tid);
    const uint32_t scr = sb + warp * KSCR, ws = scr + lane * 4;
    uint32_t fixa = 0, fixv = 0;
    {
        uint32_t zr;
        asm volatile("ld.volatile.shared.u32 %0, [%1];" : "=r"(zr) : "r"(cb + XO_TF + w * UP + lane * 16) : "memory");
        const float p_ldt = __uint_as_float(r_ldt * 65536u + zr), p_lar = __uint_as_float(r_lar * 65536u + zr), p_aim = __uint_as_float(r_aim * 65536u + zr);
        const float p_cr = __uint_as_float((uint32_t)((((uint64_t)r_cr.y << 32) | r_cr.x) >> (16 * w)) * 65536u + zr), p_ci = __uint_as_float((uint32_t)((((uint64_t)r_ci.y << 32) | r_ci.x) >> (16 * w)) * 65536u + zr);
        float acc[5][4];
        uint32_t afr[4][4], cz[4], cq[4], bb[2][8];
        const uint32_t ba = scr + lr * 144 + lm * 16;
        auto tld = [&](int i) {
            __syncwarp();
            ldsm_x4(bb[i & 1], ba + ((i + 2) % 3) * 1152);
            ldsm_x4(bb[i & 1] + 4, ba + ((i + 2) % 3) * 1152 + 64);
        };
        auto tmm = [&](int i) {
            float* c = acc[i];
            c[0] = c[1] = c[2] = c[3] = 0.f;
#pragma unroll
            for (int s = 0; s < 4; s++) mma_f16(c, afr[s], bb[i & 1][2 * s], bb[i & 1][2 * s + 1]);
        };
#define TA(i) if (i == 1) tmm(0); WMS(i); tld(i); tmm(i);
#define PH(z) packh((z).x, (z).y)
        const float dt = bfr(expf(p_ldt));
        const float al = -bfr(expf(p_lar)) * dt * 1.4426950408889634f;
        const float th = p_aim * dt;
        const float th_ = th * 0.15915494309189535f;
        const float tl_ = fmaf(th, 0.15915494309189535f, -th_) + th * 6.4206382e-9f;
        auto anchor = [&](float s) {
            float f = th_ * s;
            f -= rintf(f);
            f = fmaf(tl_, s, f) * 6.283185307179586f;
            const float e = fex2(al * s);
            return cplx{e * __cosf(f), e * __sinf(f)};
        };
        const uint32_t cm = amax2(amax2(r_cr.x, r_cr.y), amax2(r_ci.x, r_ci.y));
        const uint32_t ex = __reduce_max_sync(0xffffffffu, __float_as_uint(fmaxf(fabsf(lo2f(cm)), fabsf(__uint_as_float(cm))))) & 0x7F800000u;
        const float scl = __uint_as_float(0x7F000000u - ex), inv = (dt + dt) * __uint_as_float(ex);
        const cplx C = cplx{p_cr * scl, p_ci * scl};
        const cplx z1 = anchor(1.f), z16 = anchor(16.f), z256 = anchor(256.f);
        {
            const cplx z32 = csq(z16), z48 = cmul(z32, z16), z64 = csq(z32), z128 = csq(z64), z192 = cmul(z128, z64);
            const uint32_t y[3] = {packh(z16.x, z16.y), packh(z32.x, z32.y), packh(z48.x, z48.y)};
            const uint32_t yp[3] = {packh(-z16.y, z16.x), packh(-z32.y, z32.x), packh(-z48.y, z48.x)};
            const uint32_t xx[3] = {packh(z64.x, z64.y), packh(z128.x, z128.y), packh(z192.x, z192.y)};
            sts32(ws, 0x00003C00u);
#pragma unroll
            for (int j = 0; j < 3; j++) sts32(ws + (1 + j) * 144, y[j]);
#pragma unroll
            for (int i = 0; i < 3; i++) {
                sts32(ws + (4 + 4 * i) * 144, xx[i]);
#pragma unroll
                for (int j = 0; j < 3; j++) sts32(ws + (5 + 4 * i + j) * 144, hcm(xx[i], y[j], yp[j]));
            }
        }
        ln1();
        WMS(0);
        const cplx z2 = csq(z1);
        {
            const cplx z3 = cmul(z2, z1), z4 = csq(z2), z8 = csq(z4);
            const cplx c4 = cmul(C, z4), c8 = cmul(C, z8), c12 = cmul(c8, z4);
            cz[0] = packh(C.x, -C.y); cz[1] = packh(c4.x, -c4.y); cz[2] = packh(c8.x, -c8.y); cz[3] = packh(c12.x, -c12.y);
            cq[0] = packh(C.y, C.x); cq[1] = packh(c4.y, c4.x); cq[2] = packh(c8.y, c8.x); cq[3] = packh(c12.y, c12.x);
            __syncwarp();
#pragma unroll
            for (int s = 0; s < 4; s++) ldsm_x4(afr[s], scr + (lr + 8 * (lm & 1)) * 144 + (lm >> 1) * 16 + 32 * s);
            const uint32_t y[3] = {PH(z1), PH(z2), PH(z3)};
#pragma unroll
            for (int tt = 0; tt < 2; tt++) {
                const int rg = tt ? 0 : 2;
#pragma unroll
                for (int i = 0; i < 2; i++) {
                    sts32(ws + rg * 1152 + (4 * i) * 144, cz[2 * tt + i]);
#pragma unroll
                    for (int j = 0; j < 3; j++) sts32(ws + rg * 1152 + (4 * i + 1 + j) * 144, hcn(y[j], cz[2 * tt + i], cq[2 * tt + i]));
                }
                if (tt == 0) tld(0);
            }
            TA(1)
        }
        const cplx z258 = cmul(z256, z2), z512 = csq(z256), z768 = cmul(z512, z256);
        {
            const uint32_t a0 = PH(z256), a1 = PH(z258);
#pragma unroll
            for (int i = 0; i < 4; i++) { sts32(ws + 1152 + (2 * i) * 144, hcn(a0, cz[i], cq[i])); sts32(ws + 1152 + (2 * i + 1) * 144, hcn(a1, cz[i], cq[i])); }
            TA(2)
        }
        {
            const uint32_t a0 = PH(z512), a1 = PH(z768);
#pragma unroll
            for (int i = 0; i < 4; i++) { sts32(ws + 2304 + i * 144, hcn(a0, cz[i], cq[i])); sts32(ws + 2304 + (4 + i) * 144, hcn(a1, cz[i], cq[i])); }
            TA(3)
        }
        const cplx z1024 = csq(z512);
        {
            const cplx zk[4] = {z1024, cmul(z1024, z256), csq(z768), cmul(z1024, z768)};
#pragma unroll
            for (int h = 0; h < 4; h++) {
                const uint32_t a0 = PH(zk[h]);
                sts32(ws + (2 * h) * 144, hcn(a0, cz[0], cq[0]));
                sts32(ws + (2 * h + 1) * 144, hcn(a0, cz[2], cq[2]));
            }
            tld(4);
            tmm(4);
        }
        const cplx z2048 = csq(z1024);
        const uint32_t last = __reduce_add_sync(0xffffffffu, __float_as_uint(fmaf(-C.y, z2048.y, fmaf(C.x, z2048.x, 12.f))));
        __syncwarp();
#pragma unroll
        for (int i = 0; i < 5; i++) *(uint2*)(sm + (scr - sb) + i * 256 + ((lane * 8) ^ (i == 1 ? 64 : 0))) = make_uint2(packh(acc[i][1], acc[i][0]), packh(acc[i][3], acc[i][2]));
        if (lane == 0) sts32(cb + XO_KLAST + 4 * w, last);
        asm volatile("cp.async.wait_group 0;" ::: "memory");
        if (warp != 7) CL_WAIT();
        named_bar(1 + wgi, 128);
        if (warp == 16) { mbar_wait(MB(MB_MG1), 0); mkc1(); }
        const uint32_t td = cb + XO_TD + 64 * 4, tf = cb + XO_TF - 32 * 4;
        auto fsum = [&](int off, uint32_t& r0, uint32_t& r1) {
            const unsigned char* p = sm + wgi * (4 * KSCR) + off;
            const uint2 a = *(const uint2*)p, b2 = *(const uint2*)(p + KSCR), c = *(const uint2*)(p + 2 * KSCR), d = *(const uint2*)(p + 3 * KSCR);
            const float2 u = hsum4(a.x, b2.x, c.x, d.x), v = hsum4(a.y, b2.y, c.y, d.y);
            r0 = pack2(u.x * inv, u.y * inv);
            r1 = pack2(v.x * inv, v.y * inv);
        };
        const int role = (w + wgi) & 3;
        const int fo = role ? (role + 1) * 256 + lane * 8 : (((g & 1) * 320) ^ (lm * 32)) + t * 8;
        uint32_t r[2];
        fsum(fo, r[0], r[1]);
        if (role == 0) {
            uint32_t q[2], v[4];
            fsum(fo + 128, q[0], q[1]);
            const uint32_t c[4] = {r[0], q[0], r[1], q[1]};
#pragma unroll
            for (int i = 0; i < 4; i++) v[i] = __shfl_sync(0xffffffffu, c[i], (lane + 31) & 31);
            if (lane == 0) mbar_arrive(MB(MB_KD));
#pragma unroll
            for (int i = 0; i < 4; i++) *(uint2*)(sm + (td - sb) + lane * 8 + i * 256) = make_uint2(__byte_perm(c[i], lane ? v[i] : i ? v[i - 1] : 0u, 0x5432), c[i]);
            if (lane == 0) { fixa = td + 256 * 4 + 2; fixv = v[3]; }
        } else if (role == 1) {
            const uint32_t v0 = __shfl_sync(0xffffffffu, r[0], (lane + 1) & 31), v1 = __shfl_sync(0xffffffffu, r[1], (lane + 1) & 31);
            if (lane == 0) mbar_arrive(MB(MB_KD));
#pragma unroll
            for (int h = 0; h < 2; h++) {
                const uint32_t dd = __byte_perm(r[h], 0, 0x3232);
                *(uint4*)(sm + (td - sb) + 1024 + lane * 16 + h * 512) = make_uint4(dd, dd, r[h], __byte_perm((h || lane == 31) ? v1 : v0, r[h], 0x5432));
            }
        } else {
            __syncwarp();
            if (lane == 0) mbar_arrive(MB(MB_KD));
            const uint32_t p = role == 2 ? tf + (64 + 32 * (t >> 1) + 2 * g + (t & 1)) * 4 : tf + 2 * UP + (64 + 16 * t + g) * 4, p1 = p + (role == 2 ? 64 : 32);
            const uint32_t k0 = r[0] >> 16, k1 = r[1] >> 16;
            sts16(p + UP, r[0]); sts16(p + UP + 6, r[0]); sts16(p1 + UP, r[1]); sts16(p1 + UP + 6, r[1]);
            sts16(p1 - 4, k1); sts16(p1 + 2, k1);
            const uint32_t dd = __byte_perm(r[0], 0, 0x3232);
            if (lane) { sts16(p - 4, k0); sts16(p + 2, k0); }
            else if (role == 2) {
                *(uint4*)(sm + (td - sb) + 512 * 4) = make_uint4(dd, dd, dd, r[0] & 0xFFFF0000u);
                fixa = td + 511 * 4; fixv = k0;
            } else {
                const uint4 kl4 = *(const uint4*)(sm + (cb - sb) + XO_KLAST);
                const uint32_t kl = f2bits((float)(int)(kl4.x + kl4.y + kl4.z + kl4.w - 128u * 0x41400000u) * 9.5367431640625e-7f * inv);
                sts16(tf + 127 * 4, dd); sts16(tf + 128 * 4 + 2, dd); sts32(cb + XO_K1024, dd);
                sts16(tf + 2 * UP + 127 * 4, kl); sts16(tf + 2 * UP + 128 * 4 + 2, kl);
            }
        }
        __syncwarp();
        rst();
        mod2();
        if (wgi == 3) {
            mbar_wait(MB(MB_KD), 0);
            mbar_wait(MB(MB_WM2), 0);
            PROXY_FENCE();
            if (lane == 0) tma2d(sb + w * 15360, w < 3 ? &tm_wg : &tm_wu, 40 * b, w < 3 ? 192 * w : 0, w < 3 ? MB(MB_WG) : MB(MB_WU));
            __syncwarp();
        }
    }
    if (has_ch) {
        conv_channel(sm, rk, fixa, fixv, rst2);
    } else {
        rst2();
        asm volatile("setmaxnreg.inc.sync.aligned.u32 88;");
        mbar_wait(MB(MB_WG), 0);
        mbar_wait(MB(MB_C2), 0);
    }
    {
    const int tid = fresh_tid(), warp = __shfl_sync(0xffffffffu, tid >> 5, 0), lane = tid & 31;
    const int g = lane >> 2, t = lane & 3, lr = lane & 7, lm = lane >> 3;
    __syncwarp();
    if (lane == 0) mbar_arrive(MB(MB_CD));
    uint32_t x1[10];
    uint32_t wf[9][4], wd[2][3][4];
    const int fmt = warp >> 2, fsl = warp & 3;
    auto ldwf = [&]() {
        const int half = lm & 1;
        const uint32_t base = (fmt == 4) ? ((half ? OFF_WU : OFF_WG) + 64) : ((fmt >> 1) * OFF_WU + ((2 * (fmt & 1) + half) << 4));
        const uint32_t wa = sb + base + (144 * fsl + lr + 8 * (lm >> 1)) * 80;
#pragma unroll
        for (int ks = 0; ks < 9; ks++) ldsm_x4_t(wf[ks], wa + ks * 1280);
    };
    if (warp < 16) {
        uint32_t bw[5], v[10];
#pragma unroll
        for (int j = 0; j < 5; j++) bw[j] = (g & 1) ? M.c2[4 * j + t].w : 0x3F803F80u;
        const uint32_t xa = sb + OFF_X + XI(warp >> 1) + (2 * (warp & 1) + (lm & 1)) * XG + lr * 80 + (lm >> 1) * 16;
        uint32_t va = sb + OFF_V + (8 * (lm >> 1) + lr) * VP + 32 * warp + 16 * (lm & 1);
        uint32_t vb = cl == 14 ? xa + 32 : va + 16 * VP, vc = cl == 14 ? xa + 32 : va + 32 * VP;
        float4* p = &S->acc2[256 * rk + 16 * warp + g];
        asm volatile("" : "+r"(va), "+r"(vb), "+r"(vc), "+l"(p));
        ldsm_x4(x1, xa); ldsm_x4(x1 + 4, xa + 32); ldsm_x2(x1 + 8, xa + 64);
        mbar_wait(MB(MB_V), 0);
        ldsm_x4_t(v, va); ldsm_x4_t(v + 4, vb); ldsm_x2_t(v + 8, vc);
#pragma unroll
        for (int i = 0; i < 10; i++) x1[i] = add2(x1[i], v[i]);
        float c1[4] = {0.f, 0.f, 0.f, 0.f}, c2[4] = {0.f, 0.f, 0.f, 0.f}, c3[4] = {0.f, 0.f, 0.f, 0.f};
#pragma unroll
        for (int j = 0; j < 2; j++) {
            mma_bf16(c1, x1[4 * j], x1[4 * j + 1], x1[4 * j + 2], x1[4 * j + 3], bw[2 * j], bw[2 * j + 1]);
            mma_bf16(c2, x1[4 * j], x1[4 * j + 1], x1[4 * j + 2], x1[4 * j + 3], x1[4 * j], x1[4 * j + 2]);
            mma_bf16(c3, x1[4 * j], x1[4 * j + 1], x1[4 * j + 2], x1[4 * j + 3], x1[4 * j + 1], x1[4 * j + 3]);
        }
        mma_k8(c1, x1[8], x1[9], bw[4]); mma_k8(c2, x1[8], x1[9], x1[8]); mma_k8(c3, x1[8], x1[9], x1[9]);
        if (t == (g >> 1)) {
            red4(p, c1[0], (g & 1) ? c2[1] : c2[0], c1[1]);
            red4(p + 8, c1[2], (g & 1) ? c3[3] : c3[2], c1[3]);
        }
        __syncwarp();
    }
    if (warp >= 16) { mbar_wait(MB(MB_WG), 0); mbar_wait(MB(MB_WU), 0); ldwf(); }
    if (warp >= 17) {
        if (warp == 17) mbar_wait(MB(MB_CD), 0);
        else named_bar(7, 96);
        PROXY_FENCE();
        if (lane < 3) tma2d(sb + OFF_WD + (3 * (warp - 17) + lane) * 5120, &tm_wd, 64 * (3 * (warp - 17) + lane), 40 * b, MB(MB_WD));
        __syncwarp();
    }
    uint32_t h2[10];
    uint32_t ta = sb + OFF_H2T + (16 * warp + (lane & 15)) * 80 + (lane >> 4) * 16;
    if (warp < 16) {
        const float4* ap = &S->acc2[256 * rk + 32 * (warp >> 1) + lane];
        if (warp < 8) { mbar_wait(MB(MB_WG), 0); ldwf(); }
        float4 s = ld_rlx4f(ap);
        uint2 kc[5];
#pragma unroll
        for (int j = 0; j < 5; j++) kc[j] = *(const uint2*)&M.c2[4 * j + t];
        mbar_wait(MB(MB_CW), 0);
        const float cw = M.cws[0], sbw = M.cws[1];
        uint32_t tk0 = (2047 - (((lane & 6) << 8) + ((lane & 24) << 3) + ((lane & 1) << 5) + RKT + (warp >> 1))) << 3;
        uint32_t ka = sb + OFF_MISC + (uint32_t)offsetof(Misc, key) + (32 * (warp >> 1) + lane) * 4;
        uint32_t rb = mapa(sb, 4 * (warp & 1) + t), cd = rb + OFF_MISC + (uint32_t)offsetof(Misc, cand2) + (8 * rk + (warp >> 1)) * 8;
        const int pj = lane >= 5, pc = lane - 5 * pj;
        uint4* dst = &S->h2c[(2 * (8 * rk + (warp >> 1)) + pj) * 72 + 5 * cl + pc];
        uint32_t pa = sb + OFF_H2T + 32 * (warp >> 1) * 80 + 16 * pc;
        asm volatile("" : "+r"(tk0), "+r"(ta), "+r"(ka), "+r"(rb), "+r"(cd), "+r"(pa), "+l"(dst));
        mbar_wait(MB(MB_CD), 0);
#pragma unroll 1
        for (int it = 0; it < SPIN_MAX && s.w != (float)NCL; it++) {
            if (s.w < (float)PQT) { const uint32_t c0 = clock(); for (int k = 0; k < 1024 && (uint32_t)clock() - c0 < PQD; k++) { } }
            s = ld_rlx4f(ap);
        }
        __syncwarp();
        float meanb, rinv;
        ln_stats(s.x, s.y, meanb, rinv);
        const uint32_t rbits = __float_as_uint(fmaf(fmaf(-meanb, cw, s.z), rinv, sbw));
        const uint32_t key = ((rbits ^ (((int)rbits >> 31) | 0x80000000u)) & 0xFFFFC000u) | tk0;
        const uint32_t m0 = __reduce_max_sync(0xffffffffu, key);
        const uint32_t mr = pack2(meanb, rinv), rl = f2bits(rinv - hi2f(mr));
        const uint32_t m1 = __reduce_max_sync(0xffffffffu, key == m0 ? 0u : key);
        uint32_t st[2][2];
#pragma unroll
        for (int h = 0; h < 2; h++) { st[h][0] = __shfl_sync(0xffffffffu, mr, 16 * (warp & 1) + 8 * h + g); st[h][1] = __shfl_sync(0xffffffffu, rl, 16 * (warp & 1) + 8 * h + g); }
        if (lane < 4) sta2(cd, m0, m1 | 1u, rb + (MB(MB_KEY) - sb));
        sts32(ka, key);
        const int pr = __ffs(__ballot_sync(0xffffffffu, key == m0) | 0x80000000u) - 1, pr1 = __ffs(__ballot_sync(0xffffffffu, key == m1) | 0x80000000u) - 1;
#pragma unroll
        for (int i = 0; i < 10; i++)
            h2[i] = add2(mul2(norm2(x1[i], __byte_perm(st[i & 1][0], 0, 0x1010), __byte_perm(st[i & 1][0], 0, 0x3232), __byte_perm(st[i & 1][1], 0, 0x1010)), kc[i >> 1].x), kc[i >> 1].y);
        stsm_x4(ta, h2[0], h2[1], h2[2], h2[3]); stsm_x4(ta + 32, h2[4], h2[5], h2[6], h2[7]); stsm_x2(ta + 64, h2[8], h2[9]);
        __syncwarp();
        const int row = pj ? pr1 : pr;
        if (lane < 10 && (row >> 4) == (warp & 1) && pc < (cl < 14 ? 5 : 2)) {
            const uint4 a = lds128(pa + 80 * row);
            st_rlx4(dst, make_uint4(~a.x, ~a.y, ~a.z, ~a.w));
        }
        __syncwarp();
        named_arrive(6, 640);
        if (warp == 0) named_arrive(7, 96);
        if (warp >= 8) { mbar_wait(MB(MB_WU), 0); ldwf(); }
    }
    auto outt = [&]() {
        if (warp < 16) {
            uint32_t o[10];
            if ((warp == cl || (warp == 15 && cl == 0)) && lane < 16) st_rlx4(&S->acc1[256 * rk + 16 * warp + lane], make_uint4(0, 0, 0, 0));
#pragma unroll
            for (int i = 0; i < 10; i++) o[i] = add2(x1[i], mul2(M.c2[4 * (i >> 1) + t].z, h2[i]));
            stsm_x4(ta + (OFF_OUT - OFF_H2T), o[0], o[1], o[2], o[3]); stsm_x4(ta + (OFF_OUT - OFF_H2T) + 32, o[4], o[5], o[6], o[7]); stsm_x2(ta + (OFF_OUT - OFF_H2T) + 64, o[8], o[9]);
        }
    };
    outt();
    uint4 gv = make_uint4(1, 1, 1, 1);
    const unsigned char* gp;
    uint32_t gdst;
    uint32_t wda = sb + OFF_WD + fmt * 5120 + lr * 128 + (((2 * fsl + (lm & 1)) ^ lr) << 4) + (lm >> 1) * 1024;
    uint32_t ha = sb + OFF_H2S + lr * (ROWP * 2) + (144 * fsl) * 2 + lm * 16, fo = sb + OFF_FFR + (fsl * 80 + 16 * fmt) * 32 + 8 * lane;
    uint32_t pg = sb + OFF_FFR + (32 * warp + (warp < 8 ? 0 : 256) + lane) * 4, pu = pg + (warp < 8 ? 1024 : 256);
    uint32_t pv = sb + OFF_ACT + lr * 112 + (4 * warp + lm) * 2, pa = sb + OFF_ACT + lr * 112 + lm * 16;
    uint32_t rd[2], rm[2];
#pragma unroll
    for (int j = 0; j < 2; j++) {
        const int d = j ? 4 + (warp >> 2) : (warp * 13) >> 6, slot = j ? (warp & 3) : warp - 5 * d;
        const uint32_t rb = mapa(sb, d);
        rd[j] = rb + OFF_RS + (rk * 5 + slot) * 640 + lm * 160 + lr * 8;
        rm[j] = rb + (MB(MB_RS) - sb);
    }
    {
        const int gi = 32 * warp + lane, kk = (gi * 911) >> 16, seg = gi - 72 * kk;
        uint32_t ca = sb + OFF_MISC + (uint32_t)offsetof(Misc, cand2), sa = ca + 544 + 4 * (kk & 7);
        gp = (const unsigned char*)&S->h2c[seg];
        gdst = sb + OFF_H2S + kk * (ROWP * 2) + seg * 16;
        if (warp == 18) {
            gp = (const unsigned char*)&S->h2c[136 * 72 + min(2 * (rk < 4 ? 5 * rk : 4 * rk + 4) + lane, 71)];
            gdst = sb + OFF_GB + 16 * lane;
            if (lane < 10) gv = ld_rlx4(gp);
        }
        asm volatile("" : "+r"(sa), "+r"(gdst), "+l"(gp));
        asm volatile("" : "+r"(wda), "+r"(ha), "+r"(fo), "+r"(pg), "+r"(pu), "+r"(pv), "+r"(pa), "+r"(rd[0]), "+r"(rd[1]), "+r"(rm[0]), "+r"(rm[1]));
        mbar_wait(MB(MB_KEY), 0);
        if (warp < 16) {
            const uint4 o = lds128(ca + 16 * lane);
            uint32_t hd[4], sc[4];
#pragma unroll
            for (int q = 0; q < 4; q++) { const uint2 a = lds64(ca + 8 * warp + 128 * q); hd[q] = a.x; sc[q] = a.y; }
            const uint32_t mx = max(o.x, o.z);
            uint32_t n[4];
#pragma unroll
            for (int q = 0; q < 4; q++) n[q] = __popc(__ballot_sync(0xffffffffu, mx > hd[q]));
            auto rank = [&](uint32_t k) {
                return (__popc(__ballot_sync(0xffffffffu, o.x > k)) + __popc(__ballot_sync(0xffffffffu, o.y > k))) + (__popc(__ballot_sync(0xffffffffu, o.z > k)) + __popc(__ballot_sync(0xffffffffu, o.w > k)));
            };
#pragma unroll
            for (int q = 0; q < 4; q++) {
                if (n[q] < 8) {
                    const uint32_t r0 = rank(hd[q]), r1 = rank(sc[q]);
                    if (r0 < 8) { sts32(ca + 544 + 4 * r0, (2 * warp + 32 * q) * 1152); sts32(ca + 512 + 4 * r0, hd[q]); }
                    if (r1 < 8) { sts32(ca + 544 + 4 * r1, (2 * warp + 32 * q + 1) * 1152); sts32(ca + 512 + 4 * r1, sc[q]); }
                }
            }
        }
        named_bar(13, 640);
        if (warp < 18) {
            gp += lds32(sa);
            gv = ld_rlx4(gp);
        } else if (warp == 18) named_arrive(14, 64);
        else named_arrive(8, 64);
    }
    auto ldwd = [&]() {
#pragma unroll
        for (int i = 0; i < 2; i++)
#pragma unroll
            for (int ks = 0; ks < 3; ks++)
                if (i == 0 || warp < 16) {
                    if (ks == 2) ldsm_x2_t(wd[i][ks], wda + ks * 2048 + i * 5 * 5120);
                    else ldsm_x4_t(wd[i][ks], wda + ks * 2048 + i * 5 * 5120);
                }
    };
#pragma unroll 1
    for (int it = 0; it < SPIN_MAX && gv.x == 0u; it++) {
        gv = ld_rlx4(gp);
    }
    asm volatile("st.shared.v4.u32 [%0], {%1,%2,%3,%4};" ::"r"(gdst), "r"(~gv.x), "r"(~gv.y), "r"(~gv.z), "r"(~gv.w) : "memory");
    CBAR();
    auto ffn1 = [&]() {
        float acc[2][4] = {{0.f, 0.f, 0.f, 0.f}, {0.f, 0.f, 0.f, 0.f}};
        uint32_t hb[5][4];
#pragma unroll
        for (int k2 = 0; k2 < 5; k2++) if (k2 < 4) ldsm_x4(hb[k2], ha + k2 * 64); else ldsm_x2(hb[k2], ha + 256);
#pragma unroll
        for (int k2 = 0; k2 < 5; k2++) {
            mma_bf16(acc[0], wf[2 * k2][0], wf[2 * k2][1], wf[2 * k2][2], wf[2 * k2][3], hb[k2][0], hb[k2][1]);
            if (k2 < 4) mma_bf16(acc[1], wf[2 * k2 + 1][0], wf[2 * k2 + 1][1], wf[2 * k2 + 1][2], wf[2 * k2 + 1][3], hb[k2][2], hb[k2][3]);
        }
        asm volatile("st.shared.v2.f32 [%0], {%1,%2};" ::"r"(fo), "f"(acc[0][0] + acc[1][0]), "f"(acc[0][1] + acc[1][1]) : "memory");
        asm volatile("st.shared.v2.f32 [%0+256], {%1,%2};" ::"r"(fo), "f"(acc[0][2] + acc[1][2]), "f"(acc[0][3] + acc[1][3]) : "memory");
    };
    ffn1();
    auto gate = [&]() {
        if (warp < 10) {
            float a[8];
#pragma unroll
            for (int i = 0; i < 8; i++) a[i] = __uint_as_float(lds32((i & 4 ? pu : pg) + (i & 3) * 2560));
            float gg = bfr((a[0] + a[1]) + (a[2] + a[3]));
            gg = bfr(silu(gg));
            const float uu = bfr((a[4] + a[5]) + (a[6] + a[7]));
            sts16(pv, f2bits(gg * uu));
        }
    };
    if (warp < 10) { CBAR(); gate(); }
    else named_arrive(0, 640);
    mbar_wait(MB(MB_WD), 0);
    ldwd();
    named_bar(12, 640);
    auto ffn2 = [&](int pass) {
        uint32_t bq[6];
        ldsm_x4(bq, pa); ldsm_x2(bq + 4, pa + 64);
        float acc[2][4] = {{0.f, 0.f, 0.f, 0.f}, {0.f, 0.f, 0.f, 0.f}};
        uint32_t r[2][2];
#pragma unroll
        for (int ks = 0; ks < 3; ks++)
#pragma unroll
            for (int i = 0; i < 2; i++) {
                if (ks == 2) mma_k8(acc[i], wd[i][ks][0], wd[i][ks][1], bq[4]);
                else mma_bf16(acc[i], wd[i][ks][0], wd[i][ks][1], wd[i][ks][2], wd[i][ks][3], bq[2 * ks], bq[2 * ks + 1]);
            }
#pragma unroll
        for (int i = 0; i < 2; i++) { r[i][0] = movm(pack2(acc[i][0], acc[i][1])); r[i][1] = movm(pack2(acc[i][2], acc[i][3])); }
#pragma unroll
        for (int j = 0; j < 2; j++)
            if (j == 0 || warp < 16) sta2(rd[j] + 80 * pass, r[j][0], r[j][1], rm[j] + pass * 8 * (MB_RS2 - MB_RS));
    };
    ffn2(0);
    auto fin = [&](int pass) {
        const int lane = fresh_tid() & 31;
        const int fP = min(warp < 8 ? 20 * cl + lane : 8 * (rk < 4 ? 5 * rk : 4 * rk + 4) + 4 * (warp - 8) + (lane & 3), D_ / 2 - 1);
        uint32_t fgb = lds32(warp < 8 ? sb + OFF_MISC + (uint32_t)offsetof(Misc, c2) + 8 + 16 * lane : sb + OFF_GB + 16 * (warp - 8) + 4 * (lane & 3));
        const int ftok = warp < 8 ? warp : lane >> 2;
        uint32_t fkey = pass ? M.fin[ftok] : M.sel[ftok];
        const bool fon = warp < 8 ? (MINE(fkey) && lane < (cl < 14 ? 20 : 8)) : warp < (rk < 4 ? 18 : 16);
        const uint32_t hv = lds32(sb + OFF_H2S + ftok * (ROWP * 2) + 4 * fP);
        uint32_t p = sb + OFF_RS + pass * 80 + ((warp - 8) >> 1) * 640 + (lane >> 3) * 160 + (lane & 7) * 8 + 4 * (warp & 1);
        float4* ap = &S->acc3[pass * (72 * 32) + (fP >> 2) * 32 + 4 * ftok + (fP & 3)];
        bf16* op = out + ((~fkey >> 3) & 2047u) * D_ + 2 * fP;
        asm volatile("" : "+r"(p), "+l"(ap), "+l"(op));
        float s0 = 0.f, s1 = 0.f, s2 = 1.0f, s3 = 0.f;
        if (warp >= 8) {
            if (fon) {
                mbar_wait(MB(pass ? MB_RS2 : MB_RS), 0);
                uint32_t v[8];
#pragma unroll
                for (int i = 0; i < 8; i++) v[i] = lds32(p + i * 3200);
                s0 = ((lo2f(v[0]) + lo2f(v[1])) + (lo2f(v[2]) + lo2f(v[3]))) + ((lo2f(v[4]) + lo2f(v[5])) + (lo2f(v[6]) + lo2f(v[7])));
                s1 = ((hi2f(v[0]) + hi2f(v[1])) + (hi2f(v[2]) + hi2f(v[3]))) + ((hi2f(v[4]) + hi2f(v[5])) + (hi2f(v[6]) + hi2f(v[7])));
            }
        } else if (fon) {
            const uint32_t row = ROW(fkey);
            const unsigned short* vp = (const unsigned short*)(sm + OFF_V + 2 * lane * VP) + row;
            const uint32_t xv = add2(lds32(sb + OFF_X + XI(row >> 5) + ((row >> 3) & 3) * XG + (row & 7) * 80 + 4 * lane), (uint32_t)vp[0] | ((uint32_t)vp[VP / 2] << 16));
            s2 = (float)(((xv & 0xFFFFu) << 5) | 1u); s3 = (float)(xv >> 16);
            mbar_wait(MB(MB_OUT), 0);
        }
        float4 o = make_float4(0.f, 0.f, 0.f, 0.f);
        if (fon) o = atom4(ap, s0, s1, s2, s3);
        uint32_t redo = 0;
        if (!pass) {
            mbar_wait(MB(MB_FIN), 0);
            redo = M.fin[8];
            fkey = M.fin[ftok];
        }
        const float rs = sigm(hi2f(fkey ^ (((int)~fkey >> 31) | 0x80000000u)));
        uint32_t rs2 = pack2(rs, rs);
        s2 = fmaxf(s2 + 8388608.f, rs); s3 = fmaxf(s3 + 8388608.f, rs);
        if (rs > 2.f) s0 = s1 = rs;
        uint32_t msk = redo ? 0u : 16u;
        asm volatile("" : "+r"(rs2), "+r"(fgb), "+f"(s2), "+f"(s3), "+r"(msk), "+f"(s0), "+f"(s1));
        const uint32_t z = __float_as_uint(o.z + s2), zh = __float_as_uint(o.w + s3);
        const uint32_t xv = __byte_perm(z >> 5, zh, 0x5410);
        asm volatile("{\n.reg .pred q;\nsetp.ne.u32 q, %2, 0;\n@q st.global.u32 [%0], %1;\n}" ::"l"(op), "r"(add2(xv, mul2(fgb, add2(hv, mul2(pack2(o.x + s0, o.y + s1), rs2))))), "r"(z & msk) : "memory");
        return redo;
    };
    if (fin(0)) {
        const int gi = fresh_tid(), kk = (gi * 911) >> 16, seg = gi - 72 * kk;
        __syncwarp();
        if (warp < 8) {
            const uint32_t key = M.fin[warp];
            if (MINE(key) && lane < (cl < 14 ? 5 : 2)) {
                const uint4 a = lds128(sb + OFF_H2T + ROW(key) * 80 + 16 * lane);
                st_rlx4(&S->h2c[(128 + warp) * 72 + 5 * cl + lane], make_uint4(~a.x, ~a.y, ~a.z, ~a.w));
            }
            __syncwarp();
        }
        RBAR();
        if (warp < 18) {
            uint4 gv = make_uint4(0, 0, 0, 0);
#pragma unroll 1
            for (int it = 0; it < SPIN_MAX && gv.x == 0u; it++) gv = ld_rlx4(&S->h2c[128 * 72 + gi]);
            *(uint4*)(sm + OFF_H2S + kk * (ROWP * 2) + seg * 16) = make_uint4(~gv.x, ~gv.y, ~gv.z, ~gv.w);
        }
        RBAR();
        ffn1();
        ldwd();
        RBAR();
        gate();
        RBAR();
        ffn2(1);
        fin(1);
    }
    }
    }
}

typedef CUresult (*EncodeFn)(CUtensorMap*, CUtensorMapDataType, cuuint32_t, void*, const cuuint64_t*, const cuuint64_t*,
                             const cuuint32_t*, const cuuint32_t*, CUtensorMapInterleave, CUtensorMapSwizzle,
                             CUtensorMapL2promotion, CUtensorMapFloatOOBfill);

static void make_map(EncodeFn fn, CUtensorMap* m, const void* ptr, uint64_t cols, uint64_t rows, uint32_t bc, uint32_t br,
                     CUtensorMapSwizzle sw, int five) {
    cuuint64_t dims[5] = {cols, rows, 4, 4, 288};
    cuuint64_t strides[4] = {cols * 2 * (five ? 32 : 1), cols * 2 * 512, cols * 2 * 64, cols * 2};
    cuuint32_t box[5] = {bc, br, 4, 4, 8};
    cuuint32_t es[5] = {1, 1, 1, 1, 1};
    CUresult rc = fn(m, CU_TENSOR_MAP_DATA_TYPE_BFLOAT16, five ? 5 : 2, (void*)ptr, dims, strides, box, es, CU_TENSOR_MAP_INTERLEAVE_NONE,
                     sw, (CUtensorMapL2promotion)(five || sw ? 0 : br == 72 ? L2M : L2P), CU_TENSOR_MAP_FLOAT_OOB_FILL_NONE);
    (void)rc;
}

static void launch(void* const* d_in, const int* in_sizes, int n_in, void* d_out, int out_size) {
    static EncodeFn enc = nullptr;
    static CUtensorMap tmm, tmg, tmu, tmd, tmo;
    static Scratch* sp = nullptr;
    static const void* cached[6] = {nullptr, nullptr, nullptr, nullptr, nullptr, nullptr};
    if (!enc) {
        cudaDriverEntryPointQueryResult qr;
        void* fn = nullptr;
        cudaGetDriverEntryPoint("cuTensorMapEncodeTiled", &fn, cudaEnableDefault, &qr);
        enc = (EncodeFn)fn;
        cudaFuncSetAttribute(clus_kernel, cudaFuncAttributeMaxDynamicSharedMemorySize, SMEM_TOTAL);
        cudaGetSymbolAddress((void**)&sp, g_s);
    }
    if (cached[0] != d_in[13] || cached[1] != d_in[9] || cached[2] != d_in[10] || cached[3] != d_in[11] || cached[4] != d_in[0] || cached[5] != d_out) {
        make_map(enc, &tmo, d_out, D_, 2, 40, 2, CU_TENSOR_MAP_SWIZZLE_NONE, 1);
        make_map(enc, &tmm, d_in[13], 6 * D_, D_, 40, 72, CU_TENSOR_MAP_SWIZZLE_NONE, 0);
        make_map(enc, &tmg, d_in[9], F_, D_, 40, 192, CU_TENSOR_MAP_SWIZZLE_NONE, 0);
        make_map(enc, &tmu, d_in[10], F_, D_, 40, 192, CU_TENSOR_MAP_SWIZZLE_NONE, 0);
        make_map(enc, &tmd, d_in[11], D_, F_, 64, 40, CU_TENSOR_MAP_SWIZZLE_128B, 0);
        cached[0] = d_in[13]; cached[1] = d_in[9]; cached[2] = d_in[10]; cached[3] = d_in[11]; cached[4] = d_in[0]; cached[5] = d_out;
    }
    clus_kernel<<<G_, NTHR, SMEM_TOTAL>>>((const bf16*)d_in[0], (const bf16*)d_in[1], (const bf16*)d_in[2], (const bf16*)d_in[3], (const bf16*)d_in[4],
                                          (const bf16*)d_in[5], (const bf16*)d_in[12], sp, (const bf16*)d_in[6], (const bf16*)d_in[8], (const bf16*)d_in[13],
                                          (bf16*)d_out, tmm, tmg, tmu, tmd, tmo);
}


static bool fits() {
    cudaFuncSetAttribute(clus_kernel, cudaFuncAttributeMaxDynamicSharedMemorySize, SMEM_TOTAL);
    cudaLaunchConfig_t cfg = {};
    cudaLaunchAttribute at;
    at.id = cudaLaunchAttributeClusterDimension;
    at.val.clusterDim.x = 8; at.val.clusterDim.y = 1; at.val.clusterDim.z = 1;
    cfg.gridDim = dim3(G_); cfg.blockDim = dim3(NTHR); cfg.dynamicSmemBytes = SMEM_TOTAL; cfg.attrs = &at; cfg.numAttrs = 1;
    int n = 0;
    const bool ok = cudaOccupancyMaxActiveClusters(&n, clus_kernel, &cfg) == cudaSuccess && n >= NCL;
    cudaGetLastError();
    return ok;
}
}
#undef L_
#undef D_
#undef N_
#undef F_
#undef G_
#undef NCL
#undef NTHR
#undef SPIN_MAX
#undef NRS
#undef OFF_WG
#undef OFF_WU
#undef KSCR
#undef OFF_WM0
#undef OFF_STG
#undef OFF_MG2
#undef OFF_CH
#undef CHS
#undef UP
#undef UB
#undef XO_TF
#undef XO_U8
#undef XO_U16
#undef XO_ZA
#undef XO_ZB
#undef XO_ZC
#undef XO_ZD
#undef XO_TD
#undef XO_K1024
#undef XO_DSK
#undef XO_KLAST
#undef XO_MBU
#undef OFF_X
#undef XG
#undef XI
#undef XN
#undef OFF_V
#undef VP
#undef OFF_EK
#undef OFF_WM2
#undef OFF_MG1
#undef OFF_SC
#undef OFF_C1
#undef OFF_MISC
#undef OFF_WD
#undef OFF_H2T
#undef OFF_OUT
#undef OFF_GB
#undef ROWP
#undef OFF_H2S
#undef OFF_FFR
#undef OFF_ACT
#undef OFF_RS
#undef SMEM_TOTAL
#undef CBAR
#undef RBAR
#undef PROXY_FENCE
#undef D4
#undef O4
#undef WG_FENCE
#undef WG_COMMIT
#undef WG_WAIT
#undef TQ
#undef MB
#undef UF
#undef DS
#undef Q4
#undef RD_
#undef M2W
#undef WS
#undef WMS
#undef PQT
#undef PQD
#undef L2P
#undef L2M
#undef PDE
#undef WMD
#undef CWP
#undef CWD
#undef ROW
#undef RKT
#undef MINE
#undef CE
#undef POP
#undef CGT
#undef CL_ARRIVE
#undef CL_WAIT
#undef TA
#undef PH

namespace v4 {

#define L_ 2048
#define D_ 576
#define N_ 128
#define F_ 4608
#define G_ 128
#define NTHR 640
#define SPIN_MAX (1 << 18)
#define SENT 0u
#define HINT_N 182u

typedef __nv_bfloat16 bf16;

struct Scratch {
    uint4 xn[G_ * G_ * 10];
    uint4 v[G_ * D_ * 2];
    uint2 part[G_ * G_ * 9];
    uint4 h2w[L_ * 96];
    unsigned int rec[G_ * 8];
    unsigned int modw[6 * D_];
    unsigned int ticket[64];
    unsigned int cnt[64];
    unsigned int hint[64];
};
__device__ __align__(1024) Scratch g_s;

#define OFF_WG 0
#define OFF_WU 46080
#define OFF_CH 92160
#define CHS 20784
#define ULBO 656
#define XO_U8 6272
#define XO_U16 10368
#define XO_ZA 5248
#define XO_ZB 8448
#define XO_ZC 11648
#define XO_ZD 13824
#define XO_TD 16000
#define XO_TF 18624
#define XO_K1024 20672
#define KSCR 3456
#define OFF_TILE 196096
#define ROWP 584
#define OFF_MISC 214784
#define OFF_WD OFF_CH
#define OFF_H2T (OFF_CH + 3 * CHS)
#define OFF_H2S (OFF_H2T + 18688)
#define OFF_FFR (OFF_H2S + 9344)
#define OFF_FIN OFF_FFR
#define OFF_ACT (OFF_FFR + 10240)

struct Misc {
    __align__(16) uint4 sent[256];
    __align__(16) uint4 box[11 * 14];
    union {
        struct {
            __align__(16) float2 part[18][16];
            float rp[18][16];
        };
        struct {
            __align__(16) unsigned short st1[3][16];
            __align__(16) float p1[16][4], p2[16][4];
        };
    };
    __align__(16) bf16 cb1[D_], sb[D_], gb[D_];
    __align__(16) bf16 sc[D_];
    __align__(16) unsigned int cand[64], skey[16];
    __align__(16) float kinv[5][4], klast[5][4];
    unsigned int pk[4][8];
    __align__(16) uint4 st2[16];
    unsigned int wr[D_ / 2];
    float modx[32];
    unsigned int rank[16];
    volatile unsigned int flag;
    unsigned int e1cnt;
    unsigned long long mbar[5];
    unsigned int epoch;
};
#define SMEM_TOTAL (OFF_MISC + (int)sizeof(Misc))
static_assert(SMEM_TOTAL <= 232448, "smem");

__device__ __forceinline__ float lo2f(uint32_t w) { return __uint_as_float(w << 16); }
__device__ __forceinline__ float hi2f(uint32_t w) { return __uint_as_float(w & 0xFFFF0000u); }
__device__ __forceinline__ uint32_t pack2(float lo, float hi) { uint32_t r; asm("cvt.rn.bf16x2.f32 %0, %1, %2;" : "=r"(r) : "f"(hi), "f"(lo)); return r; }
__device__ __forceinline__ float bfr(float x) { return __uint_as_float(pack2(0.f, x)); }
__device__ __forceinline__ uint32_t f2bits(float x) { return pack2(x, 0.f); }
__device__ __forceinline__ uint32_t packh(float lo, float hi) { uint32_t r; asm("cvt.rn.f16x2.f32 %0, %1, %2;" : "=r"(r) : "f"(hi), "f"(lo)); return r; }
__device__ __forceinline__ float frcp(float x) { float r; asm("rcp.approx.ftz.f32 %0, %1;" : "=f"(r) : "f"(x)); return r; }
__device__ __forceinline__ float fsqrt(float x) { float r; asm("sqrt.approx.f32 %0, %1;" : "=f"(r) : "f"(x)); return r; }
__device__ __forceinline__ float fex2(float x) { float r; asm("ex2.approx.ftz.f32 %0, %1;" : "=f"(r) : "f"(x)); return r; }
__device__ __forceinline__ float silu(float x) { return __fdividef(x, 1.0f + __expf(-x)); }
__device__ __forceinline__ uint32_t add2(uint32_t a, uint32_t b) { uint32_t r; asm("add.rn.bf16x2 %0, %1, %2;" : "=r"(r) : "r"(a), "r"(b)); return r; }
__device__ __forceinline__ uint32_t sub2(uint32_t a, uint32_t b) { uint32_t r; asm("sub.rn.bf16x2 %0, %1, %2;" : "=r"(r) : "r"(a), "r"(b)); return r; }
__device__ __forceinline__ uint32_t mul2(uint32_t a, uint32_t b) { uint32_t r; asm("mul.rn.bf16x2 %0, %1, %2;" : "=r"(r) : "r"(a), "r"(b)); return r; }
__device__ __forceinline__ uint32_t fma2(uint32_t a, uint32_t b, uint32_t c) { uint32_t r; asm("fma.rn.bf16x2 %0, %1, %2, %3;" : "=r"(r) : "r"(a), "r"(b), "r"(c)); return r; }
__device__ __forceinline__ uint32_t norm2(uint32_t x, uint32_t m, uint32_t rh, uint32_t rl) { const uint32_t d = sub2(x, m); return fma2(d, rh, mul2(d, rl)); }

__device__ __forceinline__ void mma_bf16(float* c, uint32_t a0, uint32_t a1, uint32_t a2, uint32_t a3, uint32_t b0, uint32_t b1) {
    asm volatile("mma.sync.aligned.m16n8k16.row.col.f32.bf16.bf16.f32 {%0,%1,%2,%3}, {%4,%5,%6,%7}, {%8,%9}, {%0,%1,%2,%3};\n"
                 : "+f"(c[0]), "+f"(c[1]), "+f"(c[2]), "+f"(c[3]) : "r"(a0), "r"(a1), "r"(a2), "r"(a3), "r"(b0), "r"(b1));
}
__device__ __forceinline__ void mma_f16(float* c, const uint32_t* a, uint32_t b0, uint32_t b1) {
    asm volatile("mma.sync.aligned.m16n8k16.row.col.f32.f16.f16.f32 {%0,%1,%2,%3}, {%4,%5,%6,%7}, {%8,%9}, {%0,%1,%2,%3};\n"
                 : "+f"(c[0]), "+f"(c[1]), "+f"(c[2]), "+f"(c[3]) : "r"(a[0]), "r"(a[1]), "r"(a[2]), "r"(a[3]), "r"(b0), "r"(b1));
}
__device__ __forceinline__ void ldsm_x4(uint32_t* r, uint32_t addr) {
    asm volatile("ldmatrix.sync.aligned.m8n8.x4.shared.b16 {%0,%1,%2,%3}, [%4];" : "=r"(r[0]), "=r"(r[1]), "=r"(r[2]), "=r"(r[3]) : "r"(addr) : "memory");
}
__device__ __forceinline__ void ldsm_x4_t(uint32_t* r, uint32_t addr) {
    asm volatile("ldmatrix.sync.aligned.m8n8.x4.trans.shared.b16 {%0,%1,%2,%3}, [%4];" : "=r"(r[0]), "=r"(r[1]), "=r"(r[2]), "=r"(r[3]) : "r"(addr) : "memory");
}
__device__ __forceinline__ void stsm_x4(uint32_t addr, uint32_t r0, uint32_t r1, uint32_t r2, uint32_t r3) {
    asm volatile("stmatrix.sync.aligned.m8n8.x4.shared.b16 [%0], {%1,%2,%3,%4};" ::"r"(addr), "r"(r0), "r"(r1), "r"(r2), "r"(r3) : "memory");
}
__device__ __forceinline__ void stsm_x4_t(uint32_t addr, uint32_t r0, uint32_t r1, uint32_t r2, uint32_t r3) {
    asm volatile("stmatrix.sync.aligned.m8n8.x4.trans.shared.b16 [%0], {%1,%2,%3,%4};" ::"r"(addr), "r"(r0), "r"(r1), "r"(r2), "r"(r3) : "memory");
}
__device__ __forceinline__ uint32_t movm(uint32_t a) { uint32_t r; asm volatile("movmatrix.sync.aligned.m8n8.trans.b16 %0, %1;" : "=r"(r) : "r"(a)); return r; }
__device__ __forceinline__ uint32_t lds32(uint32_t a) { uint32_t v; asm volatile("ld.shared.u32 %0, [%1];" : "=r"(v) : "r"(a)); return v; }
__device__ __forceinline__ void sts32(uint32_t a, uint32_t v) { asm volatile("st.shared.u32 [%0], %1;" ::"r"(a), "r"(v) : "memory"); }
__device__ __forceinline__ void sts16(uint32_t a, uint32_t v) { asm volatile("st.shared.u16 [%0], %1;" ::"r"(a), "h"((unsigned short)v) : "memory"); }
__device__ __forceinline__ void named_bar(int id, int n) { asm volatile("bar.sync %0, %1;" ::"r"(id), "r"(n) : "memory"); }
__device__ __forceinline__ void named_arrive(int id, int n) { asm volatile("bar.arrive %0, %1;" ::"r"(id), "r"(n) : "memory"); }
#define CBAR() asm volatile("bar.sync 0, 640;" ::: "memory")
#define PROXY_FENCE() asm volatile("fence.proxy.async.shared::cta;" ::: "memory")

#define D4(d, o) "+f"(d[o]), "+f"(d[o + 1]), "+f"(d[o + 2]), "+f"(d[o + 3])
__device__ __forceinline__ void wg32(float* d, uint32_t a0, uint32_t a1, uint32_t a2, uint32_t a3, uint64_t desc) {
    asm volatile("wgmma.mma_async.sync.aligned.m64n32k16.f32.bf16.bf16 {%0,%1,%2,%3,%4,%5,%6,%7,%8,%9,%10,%11,%12,%13,%14,%15}, {%16,%17,%18,%19}, %20, 1, 1, 1, 0;"
                 : D4(d, 0), D4(d, 4), D4(d, 8), D4(d, 12) : "r"(a0), "r"(a1), "r"(a2), "r"(a3), "l"(desc));
}
__device__ __forceinline__ void wg48(float* d, uint32_t a0, uint32_t a1, uint32_t a2, uint32_t a3, uint64_t desc) {
    asm volatile("wgmma.mma_async.sync.aligned.m64n48k16.f32.bf16.bf16 {%0,%1,%2,%3,%4,%5,%6,%7,%8,%9,%10,%11,%12,%13,%14,%15,%16,%17,%18,%19,%20,%21,%22,%23}, {%24,%25,%26,%27}, %28, 1, 1, 1, 0;"
                 : D4(d, 0), D4(d, 4), D4(d, 8), D4(d, 12), D4(d, 16), D4(d, 20) : "r"(a0), "r"(a1), "r"(a2), "r"(a3), "l"(desc));
}
#define O4(d, o) "=f"(d[o]), "=f"(d[o + 1]), "=f"(d[o + 2]), "=f"(d[o + 3])
__device__ __forceinline__ void wg32z(float* d, uint32_t a0, uint32_t a1, uint32_t a2, uint32_t a3, uint64_t desc) {
    asm volatile("wgmma.mma_async.sync.aligned.m64n32k16.f32.bf16.bf16 {%0,%1,%2,%3,%4,%5,%6,%7,%8,%9,%10,%11,%12,%13,%14,%15}, {%16,%17,%18,%19}, %20, 0, 1, 1, 0;"
                 : O4(d, 0), O4(d, 4), O4(d, 8), O4(d, 12) : "r"(a0), "r"(a1), "r"(a2), "r"(a3), "l"(desc));
}
__device__ __forceinline__ void wg48z(float* d, uint32_t a0, uint32_t a1, uint32_t a2, uint32_t a3, uint64_t desc) {
    asm volatile("wgmma.mma_async.sync.aligned.m64n48k16.f32.bf16.bf16 {%0,%1,%2,%3,%4,%5,%6,%7,%8,%9,%10,%11,%12,%13,%14,%15,%16,%17,%18,%19,%20,%21,%22,%23}, {%24,%25,%26,%27}, %28, 0, 1, 1, 0;"
                 : O4(d, 0), O4(d, 4), O4(d, 8), O4(d, 12), O4(d, 16), O4(d, 20) : "r"(a0), "r"(a1), "r"(a2), "r"(a3), "l"(desc));
}
#define WG_FENCE() asm volatile("wgmma.fence.sync.aligned;" ::: "memory")
#define WG_COMMIT() asm volatile("wgmma.commit_group.sync.aligned;" ::: "memory")
#define WG_WAIT(n) asm volatile("wgmma.wait_group.sync.aligned " #n ";" ::: "memory")
#define TQ(p, k) p[2 * (k) + 1], p[2 * (k) + 2], p[2 * (k)], p[2 * (k) + 1]

__device__ __forceinline__ uint4 ld_nc4(const void* p) { uint4 v; asm volatile("ld.global.nc.v4.u32 {%0,%1,%2,%3}, [%4];" : "=r"(v.x), "=r"(v.y), "=r"(v.z), "=r"(v.w) : "l"(p)); return v; }
__device__ __forceinline__ unsigned short ld_nc16(const void* p) { unsigned short v; asm volatile("ld.global.nc.u16 %0, [%1];" : "=h"(v) : "l"(p)); return v; }
__device__ __forceinline__ uint32_t ld_nc(const void* p) { uint32_t v; asm volatile("ld.global.nc.u32 %0, [%1];" : "=r"(v) : "l"(p)); return v; }
__device__ __forceinline__ uint32_t ld_rlx(const unsigned int* p) { uint32_t v; asm volatile("ld.relaxed.gpu.global.u32 %0, [%1];" : "=r"(v) : "l"(p) : "memory"); return v; }
__device__ __forceinline__ uint2 ld_rlx2(const void* p) { uint2 v; asm volatile("ld.relaxed.gpu.global.v2.u32 {%0,%1}, [%2];" : "=r"(v.x), "=r"(v.y) : "l"(p) : "memory"); return v; }
__device__ __forceinline__ uint4 ld_rlx4(const void* p) { uint4 v; asm volatile("ld.relaxed.gpu.global.v4.u32 {%0,%1,%2,%3}, [%4];" : "=r"(v.x), "=r"(v.y), "=r"(v.z), "=r"(v.w) : "l"(p) : "memory"); return v; }
__device__ __forceinline__ void st_rlx(unsigned int* p, uint32_t v) { asm volatile("st.relaxed.gpu.global.u32 [%0], %1;" ::"l"(p), "r"(v) : "memory"); }
__device__ __forceinline__ void st_rlx2(void* p, uint32_t a, uint32_t b) { asm volatile("st.relaxed.gpu.global.v2.u32 [%0], {%1,%2};" ::"l"(p), "r"(a), "r"(b) : "memory"); }
__device__ __forceinline__ void st_rlx4(void* p, uint4 v) { asm volatile("st.relaxed.gpu.global.v4.u32 [%0], {%1,%2,%3,%4};" ::"l"(p), "r"(v.x), "r"(v.y), "r"(v.z), "r"(v.w) : "memory"); }
__device__ __forceinline__ void red_inc(unsigned int* p) { asm volatile("red.relaxed.gpu.global.add.u32 [%0], 1;" ::"l"(p) : "memory"); }

__device__ __forceinline__ void mbar_init(uint32_t a, int cnt) { asm volatile("mbarrier.init.shared::cta.b64 [%0], %1;" ::"r"(a), "r"(cnt) : "memory"); }
__device__ __forceinline__ void mbar_expect(uint32_t a, uint32_t bytes) { asm volatile("mbarrier.arrive.expect_tx.shared::cta.b64 _, [%0], %1;" ::"r"(a), "r"(bytes) : "memory"); }
__device__ __forceinline__ void mbar_wait(uint32_t a, uint32_t parity) {
    uint32_t ok = 0;
    int it = 0;
    do {
        asm volatile("{\n.reg .pred p;\nmbarrier.try_wait.parity.shared::cta.b64 p, [%1], %2;\nselp.u32 %0, 1, 0, p;\n}" : "=r"(ok) : "r"(a), "r"(parity) : "memory");
    } while (!ok && ++it < SPIN_MAX);
}
__device__ __forceinline__ void tma2d(uint32_t dst, const CUtensorMap* tm, int c0, int c1, uint32_t mbar) {
    asm volatile("cp.async.bulk.tensor.2d.shared::cluster.global.mbarrier::complete_tx::bytes [%0], [%1, {%3, %4}], [%2];"
                 ::"r"(dst), "l"(tm), "r"(mbar), "r"(c0), "r"(c1) : "memory");
}
__device__ __forceinline__ void bulk_s2g(void* dst, uint32_t src, uint32_t bytes) {
    asm volatile("cp.async.bulk.global.shared::cta.bulk_group [%0], [%1], %2;" ::"l"(dst), "r"(src), "r"(bytes) : "memory");
}
__device__ __forceinline__ uint32_t ld_acq(const unsigned int* p) { uint32_t v; asm volatile("ld.acquire.gpu.global.u32 %0, [%1];" : "=r"(v) : "l"(p) : "memory"); return v; }
__device__ __forceinline__ void bulk_pf(const void* src, uint32_t bytes) { asm volatile("cp.async.bulk.prefetch.L2.global [%0], %1;" ::"l"(src), "r"(bytes) : "memory"); }

__device__ __forceinline__ uint32_t wait_epoch(Misc& M) {
    uint32_t e = 0;
#pragma unroll 1
    for (int it = 0; it < (SPIN_MAX << 4) && e == 0; it++) e = *(volatile unsigned int*)&M.epoch;
    return e;
}
__device__ __forceinline__ void wait_reset(const unsigned int* ctr, uint32_t epoch) {
#pragma unroll 1
    for (int it = 0; it < SPIN_MAX; it++)
        if ((int)(ld_acq(ctr) - G_ * epoch) >= 0) break;
}
struct cplx { float x, y; };
__device__ __forceinline__ cplx cmul(cplx a, cplx b) { cplx r; r.x = a.x * b.x - a.y * b.y; r.y = a.x * b.y + a.y * b.x; return r; }
__device__ __forceinline__ cplx csq(cplx a) { cplx r; r.x = a.x * a.x - a.y * a.y; r.y = 2.0f * a.x * a.y; return r; }
__device__ __forceinline__ uint32_t hcm(uint32_t x, uint32_t y, uint32_t yp) {
    const __half2 X = *(const __half2*)&x, Y = *(const __half2*)&y, YP = *(const __half2*)&yp;
    const __half2 r = __hfma2(__high2half2(X), YP, __hmul2(__low2half2(X), Y));
    return *(const uint32_t*)&r;
}
__device__ __forceinline__ void ln_stats(float s1, float s2, float& meanb, float& rinv) {
    const float mean = s1 * (1.0f / D_);
    const float den = bfr(fsqrt(bfr(bfr(fmaxf(fmaf(-mean, mean, s2 * (1.0f / D_)), 0.f)) + 1e-5f)));
    meanb = bfr(mean);
    rinv = frcp(den);
}

__device__ __forceinline__ int fresh_tid() { int v; asm volatile("mov.u32 %0, %tid.x;" : "=r"(v)); return v; }
__device__ __forceinline__ void conv_channel(unsigned char* sm, Scratch* S, uint32_t gidx, uint32_t epoch, const void* pf_src,
                                             const CUtensorMap* tmu, int f0) {
    Misc& M = *(Misc*)(sm + OFF_MISC);
    const uint32_t sb = (uint32_t)__cvta_generic_to_shared(sm);
    const int tid = fresh_tid(), lane = tid & 31, g = lane >> 2, t = lane & 3, lr = lane & 7, lm = lane >> 3;
    const int warp_ = __shfl_sync(0xffffffffu, tid >> 5, 0), wgi = warp_ >> 2, w = warp_ & 3;
    const uint32_t cb = sb + OFF_CH + wgi * CHS, tag16 = (epoch % 65535u) + 1u;
    float D[16];
    uint32_t gaw, rcnt = 0;
    {
        {
            const uint32_t a8 = cb + lr * ULBO + (lm + 9) * 16 + w * 64, b8 = cb + XO_U8 + lm * 128 + lr * 16 + w * 512;
            const uint32_t a16 = cb + (((2 * lr) & 7) + (lm & 1)) * ULBO + (9 + (lr >> 2) + (lm & 2)) * 16 + w * 64;
            const uint32_t b16 = cb + XO_U16 + (lm & 1) * 512 + lr * 16 + (lm >> 1) * 128 + (w >> 1) * 1024 + (w & 1) * 256;
            uint32_t r[3][4];
            ldsm_x4_t(r[0], a8);
            ldsm_x4_t(r[1], a16);
            if (w < 2) ldsm_x4_t(r[2], a8 + 256);
            stsm_x4(b8, r[0][0], r[0][1], r[0][2], r[0][3]);
            stsm_x4(b16, r[1][0], r[1][1], r[1][2], r[1][3]);
            if (w < 2) stsm_x4(b8 + 2048, r[2][0], r[2][1], r[2][2], r[2][3]);
        }
        PROXY_FENCE();
        named_bar(1 + wgi, 128);
        {
            float Z8[24], Z16[16];
            const uint32_t pf = cb + XO_TF + (w >> 1) * 512 + (8 + 16 * (w & 1) + g - 2 * t) * 4;
            uint32_t p[13], q[9], z16[8];
#pragma unroll
            for (int s = 0; s < 9; s++) q[s] = lds32(pf + 1024 + s * 32);
            const uint32_t d8 = ((((cb + XO_U8) & 0x3FFFF) >> 4) | ((128 >> 4) << 16));
#define DZ(o) (((uint64_t)(512 >> 4) << 32) | (uint64_t)(d8 + (o)))
            WG_FENCE();
#pragma unroll
            for (int e = 0; e < 4; e++) {
                if (e == 0) wg32z(Z16, TQ(q, e), DZ(256 + 16));
                else wg32(Z16, TQ(q, e), DZ(256 - (e >> 1) * 64 + (1 - (e & 1)) * 16));
            }
            WG_COMMIT();
#pragma unroll
            for (int s = 0; s < 13; s++) p[s] = lds32(pf + s * 32);
            WG_WAIT(0);
#pragma unroll
            for (int i = 0; i < 8; i++) z16[i] = pack2(Z16[2 * i], Z16[2 * i + 1]);
            WG_FENCE();
#pragma unroll
            for (int e = 0; e < 6; e++) {
                if (e == 0) wg48z(Z8, TQ(p, e), DZ(16));
                else wg48(Z8, TQ(p, e), DZ(-(e >> 1) * 32 + (1 - (e & 1)) * 16));
            }
            WG_COMMIT();
            WG_WAIT(0);
            named_bar(1 + wgi, 128);
            const uint32_t za = cb + ((w >> 1) ? XO_ZB : XO_ZA) + lr * 400 + (1 + 2 * (w & 1) + (lm & 1) + 4 * (lm >> 1)) * 16;
#pragma unroll
            for (int i = 0; i < 3; i++)
                stsm_x4(za + i * 128, pack2(Z8[8 * i], Z8[8 * i + 1]), pack2(Z8[8 * i + 2], Z8[8 * i + 3]), pack2(Z8[8 * i + 4], Z8[8 * i + 5]), pack2(Z8[8 * i + 6], Z8[8 * i + 7]));
            const int Cz = 2 * (16 * (w & 1) + 8 * (lm & 1) + lr) + (lm >> 1);
            const uint32_t zc = cb + ((w >> 1) ? XO_ZD : XO_ZC) + (Cz & 7) * 272 + (1 + (Cz >> 3)) * 16;
#pragma unroll
            for (int ob = 0; ob < 2; ob++) stsm_x4(zc + ob * 128, z16[4 * ob], z16[4 * ob + 1], z16[4 * ob + 2], z16[4 * ob + 3]);
            if (lane < 8) *(uint4*)(sm + (cb - sb) + ((w < 2) ? (XO_ZA + w * 3200 + lane * 400) : (XO_ZC + (w - 2) * 2176 + lane * 272))) = make_uint4(0, 0, 0, 0);
        }
        gaw = ld_rlx(&S->modw[gidx]);
        if (tmu && wgi >= 2 && (tid & 127) == 96) {
            const uint32_t mbu = sb + OFF_MISC + (uint32_t)offsetof(Misc, mbar) + 24;
            if (wgi == 2) mbar_expect(mbu, 36864);
            tma2d(sb + OFF_WU + (wgi - 2) * 12288, tmu, f0, 192 * (wgi - 2), mbu);
        }
        __syncwarp();
        if ((tid & 127) == 64) rcnt = ld_rlx(S->cnt);
        {
#pragma unroll
            for (int i = 0; i < 16; i++) D[i] = 0.f;
            uint32_t pa = cb + XO_TD + (8 + 16 * w + g - 2 * t) * 4;
            uint32_t dlo = (((cb + 9 * 16) & 0x3FFFF) >> 4) | ((ULBO >> 4) << 16);
#define DS(o) (((uint64_t)(128 >> 4) << 32) | (uint64_t)(dlo + (o)))
#define KST (2 * (ULBO / 16))
            uint32_t pA[9], pB[9];
#pragma unroll
            for (int s = 0; s < 9; s++) pA[s] = lds32(pa + s * 32);
#pragma unroll 1
            for (int j = 0; j < 4; j++) {
                WG_FENCE();
#pragma unroll
                for (int q = 0; q < 4; q++) wg32(D, TQ(pA, q), DS((3 - q) * KST));
                WG_COMMIT();
                WG_WAIT(1);
#pragma unroll
                for (int s = 0; s < 9; s++) pB[s] = lds32(pa + 256 + s * 32);
                WG_FENCE();
#pragma unroll
                for (int q = 0; q < 4; q++) wg32(D, TQ(pB, q), DS((3 - q) * KST - 1));
                WG_COMMIT();
                WG_WAIT(1);
#pragma unroll
                for (int s = 0; s < 9; s++) pA[s] = lds32(pa + 512 + s * 32);
                dlo -= 2; pa += 512;
            }
            pB[1] = lds32(pa + 256 + 32); pB[2] = lds32(pa + 256 + 64);
            WG_FENCE();
#pragma unroll
            for (int q = 0; q < 4; q++) wg32(D, TQ(pA, q), DS((3 - q) * KST));
            wg32(D, pB[1], pB[2], pA[8], pB[1], DS(3 * KST - 1));
            WG_COMMIT();
        }
        if (tid == 128) bulk_pf(pf_src, 16 * D_ * 2);
        if ((tid & 127) == 64) {
#pragma unroll 1
            for (int it = 0; it < SPIN_MAX && (int)(rcnt - G_ * epoch) < 0; it++) rcnt = ld_rlx(S->cnt);
        }
    }
    {
        named_bar(1 + wgi, 128);
        {
            const uint4* pq = M.box + (6 + g - 2 * t);
#define QM(q) (q).x, (q).y, (q).z, (q).w
            uint32_t bA[2][6], bB[2][6], bC[3][4], bD[2][4], bU[2][4];
            const uint32_t k2 = lds32(cb + XO_K1024);
            uint32_t ofs[3];
#pragma unroll
            for (int d = 0; d < 3; d++) ofs[d] = cb + ((w - d) < 0 ? 0 : 16) + (lr + 8 * (lm >> 1)) * 16;
#define COL(d) (2 * ((w - (d)) & 3) + (lm & 1))
            WG_WAIT(0);
            uint4 m[4];
#pragma unroll
            for (int d = 0; d < 2; d++) {
                const uint32_t a = XO_ZA + COL(d) * 400 + ofs[d];
                ldsm_x4(bA[d], a); ldsm_x4(bB[d], a + 3200);
                uint32_t r[4];
                ldsm_x4(r, a + 256 + (lm >> 1) * (3200 - 128));
                bA[d][4] = r[0]; bA[d][5] = r[1]; bB[d][4] = r[2]; bB[d][5] = r[3];
            }
#pragma unroll
            for (int i = 0; i < 4; i++) m[i] = pq[14 * i];
#pragma unroll
            for (int d = 0; d < 2; d++)
#pragma unroll
                for (int c = 0; c < 3; c++) mma_bf16(D + 4 + 4 * c, QM(m[d]), bA[d][2 * c], bA[d][2 * c + 1]);
#pragma unroll
            for (int d = 0; d < 3; d++) ldsm_x4(bC[d], XO_ZC + COL(d) * 272 + ofs[d]);
#pragma unroll
            for (int d = 0; d < 2; d++)
#pragma unroll
                for (int c = 0; c < 3; c++) mma_bf16(D + 4 + 4 * c, QM(m[2 + d]), bB[d][2 * c], bB[d][2 * c + 1]);
#pragma unroll
            for (int i = 0; i < 3; i++) m[i] = pq[14 * (4 + i)];
#pragma unroll
            for (int d = 0; d < 2; d++) { ldsm_x4(bD[d], XO_ZD + COL(d) * 272 + ofs[d]); ldsm_x4(bU[d], COL(d) * ULBO + 128 + ofs[d]); }
#pragma unroll
            for (int d = 0; d < 3; d++)
#pragma unroll
                for (int c = 0; c < 2; c++) mma_bf16(D + 8 + 4 * c, QM(m[d]), bC[d][2 * c], bC[d][2 * c + 1]);
#pragma unroll
            for (int i = 0; i < 4; i++) m[i] = pq[14 * (7 + i)];
#pragma unroll
            for (int d = 0; d < 2; d++)
#pragma unroll
                for (int c = 0; c < 2; c++) mma_bf16(D + 8 + 4 * c, QM(m[d]), bD[d][2 * c], bD[d][2 * c + 1]);
#pragma unroll
            for (int d = 0; d < 2; d++) {
                m[2 + d].x &= k2; m[2 + d].y &= k2; m[2 + d].z &= k2; m[2 + d].w &= k2;
#pragma unroll
                for (int c = 0; c < 2; c++) mma_bf16(D + 8 + 4 * c, QM(m[2 + d]), bU[d][2 * c], bU[d][2 * c + 1]);
            }
        }
        {
#pragma unroll 1
            for (int it = 0; it < SPIN_MAX && (gaw >> 16) != tag16; it++) gaw = ld_rlx(&S->modw[gidx]);
            const uint32_t ga2 = __byte_perm(gaw, 0, 0x1010), dk2 = M.pk[3][wgi];
            const uint32_t ua = cb + (2 * w + (lm & 1)) * ULBO + (9 + lr + 8 * (lm >> 1)) * 16;
            const uint32_t ya = cb + XO_TD + w * 1024;
            const uint32_t sa = ya + (lr + 8 * (lm >> 1)) * 32 + (((lm & 1) ^ ((lane >> 2) & 1)) << 4);
#pragma unroll
            for (int cc = 0; cc < 2; cc++) {
                uint32_t u[4], v[4];
                ldsm_x4_t(u, ua + cc * 256);
#pragma unroll
                for (int m = 0; m < 4; m++) {
                    const int c = 2 * cc + (m >> 1), h = m & 1;
                    v[m] = ~mul2(ga2, add2(pack2(D[4 * c + 2 * h], D[4 * c + 2 * h + 1]), mul2(u[m], dk2)));
                }
                stsm_x4_t(sa + cc * 512, v[0], v[1], v[2], v[3]);
            }
            __syncwarp();
            const int sw = (lane >> 3) & 1;
            const uint32_t vo = (uint32_t)(((4 * (lane >> 1) + w) * D_ + gidx - 2 * D_) * 32 + (lane & 1) * 16);
            const unsigned char* yp = sm + (ya - sb) + (lane >> 1) * 32 + (lane & 1) * 8;
#pragma unroll
            for (int i = 0; i < 2; i++) {
                const uint2 A = *(const uint2*)(yp + i * 512 + (sw << 4)), B = *(const uint2*)(yp + i * 512 + ((sw ^ 1) << 4));
                st_rlx4((char*)S->v + vo + i * (64 * D_ * 32), make_uint4(A.x, B.x, A.y, B.y));
            }
        }
    }
}

__global__ void __launch_bounds__(NTHR, 1)
mega_kernel(const bf16* __restrict__ x, const bf16* __restrict__ logAr, const bf16* __restrict__ Aim,
            const bf16* __restrict__ Cr, const bf16* __restrict__ Ci, const bf16* __restrict__ logdt, const bf16* __restrict__ c_in,
            Scratch* __restrict__ S, const bf16* __restrict__ Dskip, const bf16* __restrict__ w_r, const bf16* __restrict__ w_down,
            bf16* __restrict__ out,
            const __grid_constant__ CUtensorMap tm_wm, const __grid_constant__ CUtensorMap tm_wg, const __grid_constant__ CUtensorMap tm_wu,
            const __grid_constant__ CUtensorMap tm_wd, const __grid_constant__ CUtensorMap tm_wd32,
            const __grid_constant__ CUtensorMap tm_wg32, const __grid_constant__ CUtensorMap tm_wu32) {
    extern __shared__ __align__(1024) unsigned char sm[];
    Misc& M = *(Misc*)(sm + OFF_MISC);
    const uint32_t sb = (uint32_t)__cvta_generic_to_shared(sm);
    const int tid = threadIdx.x, warp = __shfl_sync(0xffffffffu, tid >> 5, 0), lane = tid & 31;
    const int g = lane >> 2, t = lane & 3, lr = lane & 7, lm = lane >> 3;
    const int wgi = warp >> 2, w = warp & 3;
    const int b = blockIdx.x;
    const int nch = 5 - (b & 1), cs = 9 * (b >> 1) + 5 * (b & 1);
    const int f0 = 72 * (b >> 1) + 32 * (b & 1), nf = 32 + 8 * (b & 1);
    const bool has_ch = wgi < nch;
    const uint32_t mb0 = sb + OFF_MISC + offsetof(Misc, mbar), mb_wm = mb0, mb_wg = mb0 + 16, mb_wu = mb0 + 24, mb_wd = mb0 + 32;
    const uint32_t cb = sb + OFF_CH + wgi * CHS;

    if (wgi == 3) {
        M.sent[tid - 384] = make_uint4(SENT, SENT, SENT, SENT);
        M.sent[tid - 256] = make_uint4(SENT, SENT, SENT, SENT);
        if (tid == 384) {
            M.epoch = 0u; M.flag = 0u; M.e1cnt = 0u;
#pragma unroll
            for (int i = 0; i < 5; i++) mbar_init(mb0 + 8 * i, 1);
        }
        PROXY_FENCE();
        __syncwarp();
        if (warp == 12) { named_arrive(8, 160); if (b & 1) named_arrive(14, 64); }
        if (warp != 15) named_arrive(9, 128);
    }
    unsigned short r_ldt = 0, r_lar = 0, r_aim = 0, r_cr = 0, r_ci = 0;
    if (has_ch) {
        const int d = cs + wgi, n = d * N_ + (tid & 127);
        r_ldt = ld_nc16((const unsigned short*)logdt + d);
        r_lar = ld_nc16((const unsigned short*)logAr + n);
        r_aim = ld_nc16((const unsigned short*)Aim + n);
        r_cr = ld_nc16((const unsigned short*)Cr + n);
        r_ci = ld_nc16((const unsigned short*)Ci + n);
    } else {
        const unsigned short* cp = (const unsigned short*)c_in + (tid - 512);
        r_ldt = ld_nc16(cp); r_lar = ld_nc16(cp + 128); r_aim = ld_nc16(cp + 256); r_cr = ld_nc16(cp + 384);
        if (tid < 576) r_ci = ld_nc16(cp + 512);
    }
    uint4 xr[9];
    if (wgi == 4) {
        const uint4* p = (const uint4*)(x + (size_t)16 * b * D_) + (tid - 512);
#pragma unroll
        for (int i = 0; i < 9; i++) xr[i] = ld_nc4(p + 128 * i);
    }
    uint32_t wrv = 0;
    if (tid >= 128 && tid < 416) wrv = ld_nc((const uint32_t*)w_r + (tid - 128));
    if (warp == 2 && lane < nch) M.pk[3][lane] = (uint32_t)ld_nc16((const unsigned short*)Dskip + cs + lane) * 0x10001u;
    if (tid == 384) {
        const unsigned int tk = atomicAdd(S->ticket, 1u);
        *(volatile unsigned int*)&M.epoch = (tk >> 7) + 1u;
    }
    if (has_ch) {
        for (int i = tid & 127; i < 296; i += 128) *(uint4*)(sm + OFF_CH + wgi * CHS + XO_TD + i * 16) = make_uint4(0, 0, 0, 0);
    }
    if (tid < 154) {
        const int idx = (tid * 4682) >> 16, dl = tid - 14 * idx - 6;
        const int a = (0x44332221100ull >> (4 * idx)) & 7, d = (0x10102101010ull >> (4 * idx)) & 3;
        const int lo = (0x35c36 >> (4 * a)) & 15, wd = (0x16824 >> (4 * a)) & 15;
        const uint32_t one = (a == 4) ? 0xFFFFu : 0x3F80u;
        auto mk = [&](int l) { return (((unsigned)(l - lo) <= (unsigned)wd) ? one : 0u) | (((unsigned)(l - 1 - lo) <= (unsigned)wd) ? (one << 16) : 0u); };
        const int l0 = 16 * d + dl;
        M.box[tid] = make_uint4(mk(l0), mk(l0 + 8), mk(l0 - 8), mk(l0));
    }
    uint32_t xo[6];
#pragma unroll
    for (int i = 0; i < 6; i++) {
        const int ch = 16 * (warp + 16 * (i >> 1)) + 8 * (i & 1) + g;
        const int pr = (ch * 7282) >> 16, rm = ch - 9 * pr, hi = rm >= 5;
        xo[i] = (uint32_t)((((2 * pr + hi) * G_ + b) * 5 + rm - 5 * hi) * 32 + t * 8);
    }
    auto e1_store = [&]() {
        named_bar(11, 640);
        uint32_t mm[2], rhh[2], rll[2];
#pragma unroll
        for (int h = 0; h < 2; h++) {
            mm[h] = ((const uint32_t*)M.st1[0])[t + 4 * h]; rhh[h] = ((const uint32_t*)M.st1[1])[t + 4 * h]; rll[h] = ((const uint32_t*)M.st1[2])[t + 4 * h];
        }
        const uint32_t ta = sb + OFF_TILE + (lr + 8 * (lm & 1)) * (ROWP * 2) + (lm >> 1) * 16 + warp * 32;
#pragma unroll
        for (int i = 0; i < 3; i++) {
            if (i < 2 || warp < 4) {
                uint32_t r[4];
                ldsm_x4_t(r, ta + i * 512);
#pragma unroll
                for (int h = 0; h < 2; h++)
                    st_rlx2((char*)S->xn + xo[2 * i + h], ~norm2(r[2 * h], mm[0], rhh[0], rll[0]), ~norm2(r[2 * h + 1], mm[1], rhh[1], rll[1]));
            }
        }
        __syncwarp();
        if (lane == 0 && atomicAdd(&M.e1cnt, 1u) == 15u) red_inc(S->hint);
    };
    const float p_ldt = lo2f(r_ldt), p_lar = lo2f(r_lar), p_aim = lo2f(r_aim), p_cr = lo2f(r_cr), p_ci = lo2f(r_ci);
    cplx z1 = {0.f, 0.f}, z16 = z1, z256 = z1, C = z1;
    const uint32_t scr = cb + w * KSCR, ws = scr + lane * 4;
    float acc[5][4];
    uint32_t afr[4][4], cz[4];
    cplx z2 = {0.f, 0.f};
    const uint32_t ba = scr + lr * 144 + lm * 16;
    auto tile = [&](float* c, int rg) {
        __syncwarp();
        c[0] = c[1] = c[2] = c[3] = 0.f;
        uint32_t bb[2][4];
        ldsm_x4(bb[0], ba + rg * 1152);
        ldsm_x4(bb[1], ba + rg * 1152 + 64);
        mma_f16(c, afr[0], bb[0][0], bb[0][1]);
        mma_f16(c, afr[1], bb[0][2], bb[0][3]);
        mma_f16(c, afr[2], bb[1][0], bb[1][1]);
        mma_f16(c, afr[3], bb[1][2], bb[1][3]);
    };
#define CJ(z) packh((z).x, -(z).y)
#define CJP(z) packh((z).y, (z).x)
    uint32_t ex = 0;
    if (has_ch) {
        const float dt = bfr(expf(p_ldt));
        const float al = -bfr(expf(p_lar)) * dt * 1.4426950408889634f;
        const float th = p_aim * dt;
        const float th_ = th * 0.15915494309189535f;
        const float tl_ = fmaf(th, 0.15915494309189535f, -th_) + th * 6.4206382e-9f;
        auto anchor = [&](float s) {
            float f = th_ * s;
            f -= rintf(f);
            f = fmaf(tl_, s, f) * 6.283185307179586f;
            const float e = fex2(al * s);
            return cplx{e * __cosf(f), e * __sinf(f)};
        };
        const float cx = p_cr * dt * 2.0f, cy = p_ci * dt * 2.0f;
        ex = __reduce_max_sync(0xffffffffu, __float_as_uint(fmaxf(fabsf(cx), fabsf(cy)))) >> 23;
        const float scl = __uint_as_float((254u - ex) << 23);
        C = cplx{cx * scl, cy * scl};
        z1 = anchor(1.f); z16 = anchor(16.f); z256 = anchor(256.f);
            {
                const cplx z32 = csq(z16), z48 = cmul(z32, z16), z64 = csq(z32), z128 = csq(z64), z192 = cmul(z128, z64);
                const uint32_t y[3] = {packh(z16.x, z16.y), packh(z32.x, z32.y), packh(z48.x, z48.y)};
                const uint32_t yp[3] = {packh(-z16.y, z16.x), packh(-z32.y, z32.x), packh(-z48.y, z48.x)};
                const uint32_t xx[3] = {packh(z64.x, z64.y), packh(z128.x, z128.y), packh(z192.x, z192.y)};
                sts32(ws, 0x00003C00u);
#pragma unroll
                for (int j = 0; j < 3; j++) sts32(ws + (1 + j) * 144, y[j]);
#pragma unroll
                for (int i = 0; i < 3; i++) {
                    sts32(ws + (4 + 4 * i) * 144, xx[i]);
#pragma unroll
                    for (int j = 0; j < 3; j++) sts32(ws + (5 + 4 * i + j) * 144, hcm(xx[i], y[j], yp[j]));
                }
            }
    }
    if (wgi == 4) {
        if (!has_ch) {
            const int i = tid - 512;
            ((unsigned short*)M.sc)[i] = (unsigned short)f2bits(silu(lo2f(r_ldt)));
            ((unsigned short*)M.sc)[i + 128] = (unsigned short)f2bits(silu(lo2f(r_lar)));
            ((unsigned short*)M.sc)[i + 256] = (unsigned short)f2bits(silu(lo2f(r_aim)));
            ((unsigned short*)M.sc)[i + 384] = (unsigned short)f2bits(silu(lo2f(r_cr)));
            if (i < 64) ((unsigned short*)M.sc)[i + 512] = (unsigned short)f2bits(silu(lo2f(r_ci)));
            if (warp == 16) {
                named_bar(14, 64);
                if (lane == 0) {
                    mbar_expect(mb_wm, 36864);
#pragma unroll
                    for (int k = 0; k < 3; k++) tma2d(sb + OFF_WU + k * 12288, &tm_wm, 32 * (b >> 1), 192 * k, mb_wm);
                }
                __syncwarp();
            }
        }
#pragma unroll
        for (int i = 0; i < 9; i++) {
            const int c = tid - 512 + 128 * i, rr = (c * 911) >> 16;
            *(uint4*)(sm + OFF_TILE + rr * (ROWP * 2 - 1152) + c * 16) = xr[i];
        }
        named_bar(8, 160);
        {
            float c1[4] = {0.f, 0.f, 0.f, 0.f}, cl[4] = {0.f, 0.f, 0.f, 0.f}, chh[4] = {0.f, 0.f, 0.f, 0.f};
            const uint32_t a0 = sb + OFF_TILE + (lane & 15) * (ROWP * 2) + (lane >> 4) * 16 + w * 288;
            uint32_t a[9][4];
#pragma unroll
            for (int ks = 0; ks < 9; ks++) ldsm_x4(a[ks], a0 + ks * 32);
#pragma unroll
            for (int ks = 0; ks < 9; ks++) {
                mma_bf16(c1, a[ks][0], a[ks][1], a[ks][2], a[ks][3], 0x3F803F80u, 0x3F803F80u);
                mma_bf16(cl, a[ks][0], a[ks][1], a[ks][2], a[ks][3], a[ks][0], a[ks][2]);
                mma_bf16(chh, a[ks][0], a[ks][1], a[ks][2], a[ks][3], a[ks][1], a[ks][3]);
            }
            if (t == 0) { M.p1[g][w] = c1[0]; M.p1[g + 8][w] = c1[2]; }
            if (t == (g >> 1)) { M.p2[g][w] = (g & 1) ? cl[1] : cl[0]; M.p2[g + 8][w] = (g & 1) ? chh[3] : chh[2]; }
        }
        named_bar(5, 128);
        if (warp == 16) {
            const float4 q1 = *(const float4*)M.p1[lane & 15], q2 = *(const float4*)M.p2[lane & 15];
            float meanb, rinv;
            ln_stats((q1.x + q1.y) + (q1.z + q1.w), (q2.x + q2.y) + (q2.z + q2.w), meanb, rinv);
            const float rh = bfr(rinv);
            if (lane < 16) { M.st1[0][lane] = (unsigned short)f2bits(meanb); M.st1[1][lane] = (unsigned short)f2bits(rh); M.st1[2][lane] = (unsigned short)f2bits(rinv - rh); }
        }
        __syncwarp();
        named_arrive(11, 640);
    }
    auto publish_reset = [&]() {
        if (tid == 480) {
            asm volatile("cp.async.bulk.wait_group 0;" ::: "memory");
            asm volatile("fence.proxy.async;" ::: "memory");
            red_inc(S->cnt);
        }
    };
    uint32_t epoch = 0, tag16 = 0, pre = 0;
    auto mod_tile = [&](int rd) {
        const uint32_t* s2 = (const uint32_t*)M.sc + 144 * (w >> 1) + t;
        uint32_t bb[18][2];
#pragma unroll
        for (int ks = 0; ks < 18; ks++) { bb[ks][0] = (g == 0) ? s2[8 * ks] : 0u; bb[ks][1] = (g == 0) ? s2[8 * ks + 4] : 0u; }
        float acc[2][4] = {{0.f, 0.f, 0.f, 0.f}, {0.f, 0.f, 0.f, 0.f}};
        const int row = lr + 8 * (lm >> 1);
        const uint32_t wa = sb + OFF_WU + (288 * (w >> 1) + row) * 64 + ((((2 * (w & 1) + (lm & 1)) ^ (row >> 1)) & 3) << 4);
        mbar_wait(mb_wm + 8 * rd, 0);
        if (rd == 0)
#pragma unroll
        for (int kb = 0; kb < 2; kb++) {
            uint32_t a[9][4];
#pragma unroll
            for (int ks = 0; ks < 9; ks++) ldsm_x4_t(a[ks], wa + (9 * kb + ks) * 1024);
#pragma unroll
            for (int ks = 0; ks < 9; ks++) mma_bf16(acc[ks & 1], a[ks][0], a[ks][1], a[ks][2], a[ks][3], bb[9 * kb + ks][0], bb[9 * kb + ks][1]);
        }
        const float v0 = acc[0][0] + acc[1][0], v1 = acc[0][2] + acc[1][2];
        float* mx = M.modx + 16 * (w & 1) + g;
        if (w >= 2 && t == 0) { mx[0] = v0; mx[8] = v1; }
        named_bar(5, 128);
        if (w < 2 && t == 0) {
            unsigned int* mp = &S->modw[32 * ((b >> 1) + 64 * rd) + 16 * w + g];
            st_rlx(mp, f2bits(v0 + mx[0]) | (tag16 << 16));
            st_rlx(mp + 8, f2bits(v1 + mx[8]) | (tag16 << 16));
        }
        if (rd == 0 && w < 2 && b < 108) {
            named_bar(7, 64);
            if (tid == 512) red_inc(S->hint);
        }
    };
    if (has_ch) {
        {
            z2 = csq(z1);
            const cplx z3 = cmul(z2, z1), z4 = csq(z2), z8 = csq(z4);
            const cplx c4 = cmul(C, z4), c8 = cmul(C, z8), c12 = cmul(c8, z4);
            cz[0] = packh(C.x, -C.y); cz[1] = packh(c4.x, -c4.y); cz[2] = packh(c8.x, -c8.y); cz[3] = packh(c12.x, -c12.y);
            __syncwarp();
#pragma unroll
            for (int s = 0; s < 4; s++) ldsm_x4(afr[s], scr + (lr + 8 * (lm & 1)) * 144 + (2 * s + (lm >> 1)) * 16);
            {
                const uint32_t y[3] = {CJ(z1), CJ(z2), CJ(z3)}, yp[3] = {CJP(z1), CJP(z2), CJP(z3)};
#pragma unroll
                for (int tt = 0; tt < 2; tt++) {
                    const int rg = tt ? 0 : 2;
#pragma unroll
                    for (int i = 0; i < 2; i++) {
                        sts32(ws + rg * 1152 + (4 * i) * 144, cz[2 * tt + i]);
#pragma unroll
                        for (int j = 0; j < 3; j++) sts32(ws + rg * 1152 + (4 * i + 1 + j) * 144, hcm(cz[2 * tt + i], y[j], yp[j]));
                    }
                    tile(acc[tt], rg);
                }
            }
            if (tid >= 128 && tid < 416) M.wr[tid - 128] = wrv;
            if (wgi < 4) e1_store();
    if (warp == 15) {
        named_bar(9, 128);
        if (lane == 0) {
#pragma unroll 1
            for (int i = 0; i < 5; i++) {
                bulk_s2g((char*)&S->v[(size_t)b * 1152] + i * 4096, sb + OFF_MISC, i < 4 ? 4096 : 2048);
                if (i < 3) bulk_s2g((char*)&S->part[(size_t)b * 1152] + i * 4096, sb + OFF_MISC, i < 2 ? 4096 : 1024);
            }
            bulk_s2g(&S->rec[8 * b], sb + OFF_MISC, 32);
            asm volatile("cp.async.bulk.commit_group;" ::: "memory");
        }
        __syncwarp();
    }
            const cplx z258 = cmul(z256, z2), z512 = csq(z256), z768 = cmul(z512, z256);
            {
                const uint32_t a0 = CJ(z256), a0p = CJP(z256), a1 = CJ(z258), a1p = CJP(z258);
#pragma unroll
                for (int i = 0; i < 4; i++) { sts32(ws + 1152 + (2 * i) * 144, hcm(cz[i], a0, a0p)); sts32(ws + 1152 + (2 * i + 1) * 144, hcm(cz[i], a1, a1p)); }
                tile(acc[2], 1);
            }
            {
                const uint32_t a0 = CJ(z512), a0p = CJP(z512), a1 = CJ(z768), a1p = CJP(z768);
#pragma unroll
                for (int i = 0; i < 4; i++) { sts32(ws + 2304 + i * 144, hcm(cz[i], a0, a0p)); sts32(ws + 2304 + (4 + i) * 144, hcm(cz[i], a1, a1p)); }
                tile(acc[3], 2);
            }
            if (warp == 3) {
                if (lane == 15) pre = ld_rlx(S->hint);
            }
            const cplx z1024 = csq(z512);
            {
                const cplx zk[4] = {z1024, cmul(z1024, z256), csq(z768), cmul(z1024, z768)};
#pragma unroll
                for (int h = 0; h < 4; h++) {
                    const uint32_t a0 = CJ(zk[h]), a0p = CJP(zk[h]);
                    sts32(ws + (2 * h) * 144, hcm(cz[0], a0, a0p));
                    sts32(ws + (2 * h + 1) * 144, hcm(cz[2], a0, a0p));
                }
                tile(acc[4], 0);
            }
            const cplx z2048 = csq(z1024);
            float last = C.x * z2048.x - C.y * z2048.y;
#pragma unroll
            for (int o = 16; o; o >>= 1) last += __shfl_xor_sync(0xffffffffu, last, o);
            __syncwarp();
#pragma unroll
            for (int i = 0; i < 5; i++) *(float4*)(sm + (scr - sb) + i * 512 + lane * 16) = make_float4(acc[i][0], acc[i][1], acc[i][2], acc[i][3]);
            if (lane == 0) { const float inv = __uint_as_float(ex << 23); M.kinv[wgi][w] = inv; M.klast[wgi][w] = last * inv; }
        }
        if (tid == 111 && (int)(pre - HINT_N * wait_epoch(M)) >= 0) M.flag = 1u;
        named_bar(1 + wgi, 128);
        const uint32_t td = cb + XO_TD + 64 * 4, tf = cb + XO_TF - 32 * 4;
        if (tid == 111 && !M.flag) pre = ld_rlx(S->hint);
        const float4 ki = *(const float4*)M.kinv[wgi];
        auto fsum = [&](int off, uint32_t& r0, uint32_t& r1) {
            const unsigned char* p = sm + (cb - sb) + off;
            const float4 a = *(const float4*)p, b2 = *(const float4*)(p + KSCR), c = *(const float4*)(p + 2 * KSCR), d = *(const float4*)(p + 3 * KSCR);
            r0 = pack2(fmaf(a.y, ki.x, b2.y * ki.y) + fmaf(c.y, ki.z, d.y * ki.w), fmaf(a.x, ki.x, b2.x * ki.y) + fmaf(c.x, ki.z, d.x * ki.w));
            r1 = pack2(fmaf(a.w, ki.x, b2.w * ki.y) + fmaf(c.w, ki.z, d.w * ki.w), fmaf(a.z, ki.x, b2.z * ki.y) + fmaf(c.z, ki.z, d.z * ki.w));
        };
        uint32_t r[2], q[2];
        fsum(w * 512 + lane * 16, r[0], r[1]);
        fsum(2048 + w * 128 + lr * 16, q[0], q[1]);
        if (tid == 111) {
            if ((int)(pre - HINT_N * M.epoch) >= 0) M.flag = 1u;
            else pre = ld_rlx(S->hint);
        }
        __syncwarp();
        if (w < 2) {
            const uint32_t p = td + (16 * g + 8 * w + 2 * t) * 4;
#pragma unroll
            for (int h = 0; h < 2; h++) { sts16(p + h * 512, r[h] >> 16); sts32(p + h * 512 + 4, r[h]); sts16(p + h * 512 + 10, r[h]); }
        } else if (w == 2) {
            const uint32_t p = td + (256 + 16 * g + 4 * t) * 4;
#pragma unroll
            for (int h = 0; h < 2; h++) {
                const uint32_t k0 = r[h] >> 16;
                if (h || lane) { sts16(p + h * 512 - 4, k0); sts16(p + h * 512 + 2, k0); }
                sts16(p + h * 512, k0); sts32(p + h * 512 + 4, __byte_perm(r[h], 0, 0x3232)); sts32(p + h * 512 + 8, r[h]); sts16(p + h * 512 + 14, r[h]);
            }
        } else {
            const uint32_t p = tf + (64 + 32 * (t >> 1) + 2 * g + (t & 1)) * 4;
#pragma unroll
            for (int h = 0; h < 2; h++) {
                const uint32_t k0 = r[h] >> 16;
                sts16(p + h * 64 + 512, r[h]); sts16(p + h * 64 + 518, r[h]);
                if (h || lane) { sts16(p + h * 64 - 4, k0); sts16(p + h * 64 + 2, k0); }
            }
            if (lane == 0) {
                const uint32_t dd = __byte_perm(r[0], 0, 0x3232);
                sts16(td + 511 * 4, dd); sts32(td + 512 * 4, dd); sts32(td + 513 * 4, dd); sts32(td + 514 * 4, dd); sts16(td + 515 * 4 + 2, dd);
            }
        }
        if (lane < 8) {
            const uint32_t p = tf + 1024 + (64 + 16 * t + 2 * w + g) * 4;
#pragma unroll
            for (int h = 0; h < 2; h++) {
                const uint32_t k0 = q[h] >> 16;
                sts16(p + h * 32 + 512, q[h]); sts16(p + h * 32 + 518, q[h]);
                if (h || (tid & 127)) { sts16(p + h * 32 - 4, k0); sts16(p + h * 32 + 2, k0); }
            }
            if ((tid & 127) == 0) {
                const float4 kl4 = *(const float4*)M.klast[wgi];
                const uint32_t kl = f2bits((kl4.x + kl4.y) + (kl4.z + kl4.w)), dd = __byte_perm(q[0], 0, 0x3232);
                sts16(tf + 127 * 4, dd); sts16(tf + 128 * 4 + 2, dd); sts32(cb + XO_K1024, dd);
                sts16(tf + 1024 + 127 * 4, kl); sts16(tf + 1024 + 128 * 4 + 2, kl);
            }
        }
        __syncwarp();
    } else {
        const int i = tid - 512, idx = b >> 1;
        tag16 = (wait_epoch(M) % 65535u) + 1u;
        mod_tile(0);
        if (i == 0 && idx < 44) {
            PROXY_FENCE();
            mbar_expect(mb_wm + 8, 36864);
#pragma unroll
            for (int k = 0; k < 3; k++) tma2d(sb + OFF_WU + k * 12288, &tm_wm, 32 * (idx + 64), 192 * k, mb_wm + 8);
        }
        __syncwarp();
    }
    if (tid == 111) {
        epoch = wait_epoch(M);
#pragma unroll 1
        for (int it = 0; it < SPIN_MAX && (int)(pre - HINT_N * epoch) < 0; it++) pre = ld_rlx(S->hint);
        M.flag = 1u;
    }
    __syncwarp();
    const int ubp = (tid * 13108) >> 16, uloc = tid - 5 * ubp;
    const uint4* usrc = &S->xn[(size_t)b * 1280 + 2 * tid];
    uint4 ua = make_uint4(0, 0, 0, 0), uc = ua;
    uint32_t usa = 0, uca = 0;
    if (lane == 0) {
#pragma unroll 1
        for (int it = 0; it < (SPIN_MAX << 4) && !M.flag; it++) { }
    }
    __syncwarp();
    if (uloc < nch) {
 ua = ld_rlx4(usrc); uc = ld_rlx4(usrc + 1); usa = ld_rlx(&S->modw[cs + uloc]); uca = ld_rlx(&S->modw[D_ + cs + uloc]); }
    CBAR();
    epoch = M.epoch;
    tag16 = (epoch % 65535u) + 1u;
    {
        const int bp = ubp, loc = uloc;
        if (loc < nch) {
            const uint4* src = usrc;
            uint4 a = ua, c = uc;
#pragma unroll 1
            for (int it = 0; it < SPIN_MAX && (a.x == SENT || a.z == SENT || c.x == SENT || c.z == SENT || (usa >> 16) != tag16 || (uca >> 16) != tag16); it++) {
                a = ld_rlx4(src); c = ld_rlx4(src + 1); usa = ld_rlx(&S->modw[cs + loc]); uca = ld_rlx(&S->modw[D_ + cs + loc]);
            }
            const uint32_t sa = __byte_perm(usa, 0, 0x1010), ca = pack2(1.0f + lo2f(uca), 1.0f + lo2f(uca));
            unsigned char* up = sm + OFF_CH + loc * CHS + ((2 * bp) & 7) * ULBO + ((bp >> 2) + 9) * 16;
            *(uint4*)up = make_uint4(add2(mul2(~a.x, ca), sa), add2(mul2(~a.z, ca), sa), add2(mul2(~c.x, ca), sa), add2(mul2(~c.z, ca), sa));
            *(uint4*)(up + ULBO) = make_uint4(add2(mul2(~a.y, ca), sa), add2(mul2(~a.w, ca), sa), add2(mul2(~c.y, ca), sa), add2(mul2(~c.w, ca), sa));
        }
        publish_reset();
        const int i = tid & 127;
        unsigned char* cp = sm + OFF_CH + wgi * CHS;
        *(uint4*)(cp + XO_U8 - 1024 + (i >> 6) * 4096 + (i & 63) * 16) = make_uint4(0, 0, 0, 0);
        if (i < 72) { const int c = (i * 57) >> 9; *(uint4*)(cp + c * ULBO + (i - 9 * c) * 16) = make_uint4(0, 0, 0, 0); }
    }
    PROXY_FENCE();
    CBAR();
    if (w == 2 && lane == 0) {
        bulk_s2g((char*)&S->xn[(size_t)b * 1280] + wgi * 4096, sb + OFF_MISC, 4096);
        asm volatile("cp.async.bulk.commit_group;" ::: "memory");
    }
        if (tid == 416) {
            mbar_expect(mb_wg, nf * D_ * 2);
            tma2d(sb + OFF_WG, (b & 1) ? &tm_wg : &tm_wg32, f0, 0, mb_wg);
        }
    if (tid == 96 || tid == 224) tma2d(sb + OFF_WG + (1 + (tid >> 7)) * (nf * 384), (b & 1) ? &tm_wg : &tm_wg32, f0, 192 * (1 + (tid >> 7)), mb_wg);
    if (has_ch) {
        __syncwarp();
        conv_channel(sm, S, 2 * D_ + cs + wgi, epoch, w_down + (size_t)f0 * D_, (b & 1) ? nullptr : &tm_wu32, f0);
    } else {
        const int idx = b >> 1;
        if (idx < 44) mod_tile(1);
        if (tid == 512) {
            PROXY_FENCE();
            mbar_expect(mb_wu, 46080);
#pragma unroll 1
            for (int i = 0; i < 3; i++) {
                tma2d(sb + OFF_WU + i * 15360, &tm_wu, f0, 192 * i, mb_wu);
                const long long c0 = clock64();
                int it = 0;
                while (clock64() - c0 < 1200 && ++it < 4096) { }
            }
            wait_reset(S->cnt, epoch);
        }
        named_bar(5, 128);
    }
    {
    const int tid = fresh_tid(), warp = __shfl_sync(0xffffffffu, tid >> 5, 0), lane = tid & 31;
    const int g = lane >> 2, t = lane & 3, lr = lane & 7, lm = lane >> 3;
    uint32_t v3 = 0, v4 = 0, v5 = 0;
    auto load_consts = [&]() {
        if (tid < D_) { v3 = ld_rlx(&S->modw[3 * D_ + tid]); v4 = ld_rlx(&S->modw[4 * D_ + tid]); v5 = ld_rlx(&S->modw[5 * D_ + tid]); }
    };
    if (tid == 0) bulk_pf(w_down + (size_t)(f0 + 16) * D_, (nf - 16) * D_ * 2);
    uint32_t x1[2][4], wr2[2][2];
    if (warp < 18) {
        const char* vp = (const char*)S->v + ((size_t)b * D_ + 32 * warp + g) * 32 + t * 8;
        uint2 v[4];
#pragma unroll
        for (int i = 0; i < 4; i++) v[i] = ld_rlx2(vp + i * 256);
#pragma unroll
        for (int j = 0; j < 2; j++) {
            const uint32_t* wp = M.wr + 16 * warp + 8 * j + t;
            wr2[j][0] = (g == 0) ? wp[0] : 0u;
            wr2[j][1] = (g == 0) ? wp[4] : 0u;
            ldsm_x4(x1[j], sb + OFF_TILE + (lr + 8 * (lm & 1)) * (ROWP * 2) + (lm >> 1) * 16 + warp * 64 + j * 32);
        }
#pragma unroll 1
        for (int it = 0; it < SPIN_MAX && ((v3 >> 16) != tag16 || (v4 >> 16) != tag16 || (v5 >> 16) != tag16); it++) load_consts();
        ((unsigned short*)M.sb)[tid] = (unsigned short)v3;
        ((unsigned short*)M.cb1)[tid] = (unsigned short)f2bits(1.0f + lo2f(v4));
        ((unsigned short*)M.gb)[tid] = (unsigned short)v5;
#pragma unroll 1
        for (int it = 0; it < SPIN_MAX; it++) {
            bool bad = false;
#pragma unroll
            for (int i = 0; i < 4; i++) if (v[i].x == SENT) { v[i] = ld_rlx2(vp + i * 256); bad = true; }
            if (!bad) break;
        }
        __syncwarp();
        float c1[4] = {0.f, 0.f, 0.f, 0.f}, cl[4] = {0.f, 0.f, 0.f, 0.f}, chh[4] = {0.f, 0.f, 0.f, 0.f};
#pragma unroll
        for (int j = 0; j < 2; j++) {
            x1[j][0] = add2(x1[j][0], movm(~v[2 * j].x)); x1[j][1] = add2(x1[j][1], movm(~v[2 * j].y));
            x1[j][2] = add2(x1[j][2], movm(~v[2 * j + 1].x)); x1[j][3] = add2(x1[j][3], movm(~v[2 * j + 1].y));
            mma_bf16(c1, x1[j][0], x1[j][1], x1[j][2], x1[j][3], 0x3F803F80u, 0x3F803F80u);
            mma_bf16(cl, x1[j][0], x1[j][1], x1[j][2], x1[j][3], x1[j][0], x1[j][2]);
            mma_bf16(chh, x1[j][0], x1[j][1], x1[j][2], x1[j][3], x1[j][1], x1[j][3]);
        }
        float* pp = (float*)&M.part[warp][g];
        if (t == 0) { pp[0] = c1[0]; pp[16] = c1[2]; }
        if (t == (g >> 1)) { pp[1] = (g & 1) ? cl[1] : cl[0]; pp[17] = (g & 1) ? chh[3] : chh[2]; }
    }
    CBAR();
    if (warp < 18) {
        const int tok = lane & 15, hf = lane >> 4;
        uint32_t kc[2][2][2];
#pragma unroll
        for (int j = 0; j < 2; j++)
#pragma unroll
            for (int q = 0; q < 2; q++) { kc[j][q][0] = ((const uint32_t*)M.cb1)[16 * warp + 8 * j + 4 * q + t]; kc[j][q][1] = ((const uint32_t*)M.sb)[16 * warp + 8 * j + 4 * q + t]; }
        named_bar(13, 608);
        uint32_t st[2][3];
#pragma unroll
        for (int h = 0; h < 2; h++) { const uint4 q = M.st2[g + 8 * h]; st[h][0] = q.x; st[h][1] = q.y; st[h][2] = q.z; }
        float rc[4] = {0.f, 0.f, 0.f, 0.f};
        uint32_t h2[2][4];
#pragma unroll
        for (int j = 0; j < 2; j++) {
#pragma unroll
            for (int r = 0; r < 4; r++) {
                h2[j][r] = add2(mul2(norm2(x1[j][r], st[r & 1][0], st[r & 1][1], st[r & 1][2]), kc[j][r >> 1][0]), kc[j][r >> 1][1]);
            }
            mma_bf16(rc, h2[j][0], h2[j][1], h2[j][2], h2[j][3], wr2[j][0], wr2[j][1]);
        }
        if (t == 0) { M.rp[warp][g] = rc[0]; M.rp[warp][g + 8] = rc[2]; }
        if (warp == 0) {
            named_bar(12, 576);
            float r = M.rp[9 * hf][tok];
#pragma unroll
            for (int i = 1; i < 9; i++) r += M.rp[9 * hf + i][tok];
            r += __shfl_xor_sync(0xffffffffu, r, 16);
            const uint32_t rbits = f2bits(r);
            const uint32_t key = 0x80000000u | ((rbits ^ ((rbits & 0x8000u) ? 0xFFFFu : 0x8000u)) << 11) | (uint32_t)(2047 - (16 * b + tok));
            int rank = 0;
#pragma unroll
            for (int j = 1; j < 16; j++) rank += __shfl_xor_sync(0xffffffffu, key, j) > key;
            if (lane < 16) { M.skey[rank] = key; M.rank[rank] = tok; }
            __syncwarp();
            if (lane < 2) st_rlx4(&S->rec[8 * b + 4 * lane], *(const uint4*)&M.skey[4 * lane]);
        } else named_arrive(12, 576);
#pragma unroll
        for (int j = 0; j < 2; j++) {
            uint32_t o[4];
#pragma unroll
            for (int r = 0; r < 4; r++) o[r] = add2(x1[j][r], mul2(((const uint32_t*)M.gb)[16 * warp + 8 * j + 4 * (r >> 1) + t], h2[j][r]));
            const uint32_t to = (lr + 8 * (lm & 1)) * (ROWP * 2) + (lm >> 1) * 16 + warp * 64 + j * 32;
            stsm_x4(sb + OFF_H2T + to, h2[j][0], h2[j][1], h2[j][2], h2[j][3]);
            stsm_x4(sb + OFF_TILE + to, o[0], o[1], o[2], o[3]);
        }
    } else if (warp == 19) {
        const int tok = lane & 15, hf = lane >> 4;
        float2 s = M.part[9 * hf][tok];
#pragma unroll
        for (int i = 1; i < 9; i++) { const float2 q = M.part[9 * hf + i][tok]; s.x += q.x; s.y += q.y; }
        s.x += __shfl_xor_sync(0xffffffffu, s.x, 16); s.y += __shfl_xor_sync(0xffffffffu, s.y, 16);
        float meanb, rinv;
        ln_stats(s.x, s.y, meanb, rinv);
        const float rh = bfr(rinv);
        if (lane < 16) M.st2[tok] = make_uint4(pack2(meanb, meanb), pack2(rh, rh), pack2(rinv - rh, rinv - rh), 0u);
        __syncwarp();
        named_arrive(13, 608);
    } else if (lane < 9) {
        PROXY_FENCE();
        if (lane == 0) mbar_expect(mb_wd, nf * D_ * 2);
        tma2d(sb + OFF_WD + lane * 5120, (b & 1) ? &tm_wd : &tm_wd32, 64 * lane, f0, mb_wd);
    }
    CBAR();
    uint32_t wf[9][4], wd[2][3][4];
    const int fmt = warp >> 2, fsl = warp & 3;
    auto load_wf = [&]() {
        mbar_wait(mb_wg, 0);
        mbar_wait(mb_wu, 0);
        if (fmt < 4 || nf > 32) {
            const int half = lm & 1;
            const uint32_t base = (fmt == 4) ? ((half ? OFF_WU : OFF_WG) + 64)
                                             : ((fmt >> 1) * OFF_WU + (((2 * (fmt & 1) + half) ^ ((b & 1) ? 0 : (lr >> 1))) << 4));
            const uint32_t wa = sb + base + (144 * fsl + lr + 8 * (lm >> 1)) * (2 * nf);
#pragma unroll
            for (int ks = 0; ks < 9; ks++) ldsm_x4_t(wf[ks], wa + ks * (32 * nf));
        }
    mbar_wait(mb_wd, 0);
    {
#pragma unroll
        for (int i = 0; i < 2; i++) {
            const int mt = warp + 20 * i;
            const uint32_t wa = sb + OFF_WD + (mt >> 2) * 5120 + lr * 128 + (((2 * (mt & 3) + (lm & 1)) ^ lr) << 4);
#pragma unroll
            for (int ks = 0; ks < 3; ks++)
                if ((i == 0 || warp < 16) && (ks < 2 || nf > 32)) ldsm_x4_t(wd[i][ks], wa + ks * 2048 + ((ks < 2) ? (lm >> 1) * 1024 : 0));
        }
    }
    };
    if (warp >= 8) {
        if (warp < 16) {
            const int tk = M.rank[warp - 8];
            const uint32_t* hp = (const uint32_t*)(sm + OFF_H2T + tk * (ROWP * 2)) + lane;
            uint4* dst = &S->h2w[(size_t)(16 * b + tk) * 96 + lane];
#pragma unroll
            for (int j = 0; j < 3; j++) st_rlx4(dst + 32 * j, make_uint4(hp[96 * j], hp[96 * j + 32], hp[96 * j + 64], epoch));
        }
        load_wf();
    } else {
        const uint4* rp = (const uint4*)S->rec + tid;
        load_wf();
        uint4 rk = ld_rlx4(rp);
#pragma unroll 1
        for (int it = 0; it < SPIN_MAX && !rk.x; it++) rk = ld_rlx4(rp);
        __syncwarp();
        uint32_t mine = 0;
#pragma unroll
        for (int rnd = 0; rnd < 8; rnd++) {
            const uint32_t m = __reduce_max_sync(0xffffffffu, rk.x);
            if (rk.x == m) { rk.x = rk.y; rk.y = rk.z; rk.z = rk.w; rk.w = 0u; }
            if (lane == rnd) mine = m;
        }
        if (lane < 8) M.cand[8 * warp + lane] = mine;
    }
    CBAR();
    uint32_t selv = 0;
    if (warp < 12) {
        uint2 k = *(const uint2*)&M.cand[2 * lane];
#pragma unroll
        for (int rnd = 0; rnd < 8; rnd++) {
            const uint32_t m = __reduce_max_sync(0xffffffffu, k.x);
            if (k.x == m) { k.x = k.y; k.y = 0u; }
            if (lr == rnd) selv = m;
        }
        if (tid < 8) M.skey[tid] = selv;
    }
    const uint32_t seltok = 2047u - (selv & 2047u);
    const int fo = tid >> 3;
    const int fW = 9 * b + (fo >> 2), fcomp = fo & 3;
    const int fd = 16 * (fW >> 5) + ((fW >> 2) & 7) + 8 * (fcomp >> 1), fk = 2 * (fW & 3) + (fcomp & 1);
    const uint32_t fsel = __shfl_sync(0xffffffffu, selv, fk);
    uint32_t fx = 0, fv = 0;
    bf16(*h2s)[ROWP] = (bf16(*)[ROWP])(sm + OFF_H2S);
    if (warp < 12) {
        uint4 wv[2];
        const uint4* hp[2];
#pragma unroll
        for (int r = 0; r < 2; r++) {
            const int wi = warp + 12 * r, k = wi / 3, j = wi - 3 * k;
            hp[r] = &S->h2w[(size_t)__shfl_sync(0xffffffffu, seltok, k) * 96 + 32 * j + lane];
            wv[r] = ld_rlx4(hp[r]);
        }
        if (tid < 288 && (tid & 7) == 0) {
            const uint32_t ft = 2047u - (fsel & 2047u), pr = (ft & 15u) >> 1;
            fx = ((const unsigned short*)x)[(size_t)ft * D_ + fd];
            asm volatile("ld.relaxed.gpu.global.u16 %0, [%1];" : "=r"(fv)
                         : "l"((const unsigned short*)S->v + ((size_t)(ft >> 4) * D_ + fd) * 16 + ((pr & 3u) * 2 + (pr >> 2)) * 2 + (ft & 1u)) : "memory");
        }
#pragma unroll 1
        for (int it = 0; it < SPIN_MAX && (wv[0].w != epoch || wv[1].w != epoch); it++) { wv[0] = ld_rlx4(hp[0]); wv[1] = ld_rlx4(hp[1]); }
#pragma unroll
        for (int r = 0; r < 2; r++) {
            const int wi = warp + 12 * r, k = wi / 3, j = wi - 3 * k;
            uint32_t* dst = (uint32_t*)&h2s[k][0] + 96 * j + lane;
            dst[0] = wv[r].x; dst[32] = wv[r].y; dst[64] = wv[r].z;
        }
    }
    CBAR();
    float* ffr = (float*)(sm + OFF_FFR);
    if (fmt < 4 || nf > 32) {
        float acc[2][4] = {{0.f, 0.f, 0.f, 0.f}, {0.f, 0.f, 0.f, 0.f}};
        const uint32_t ha = sb + OFF_H2S + lr * (ROWP * 2) + (144 * fsl) * 2 + lm * 16;
#pragma unroll
        for (int k2 = 0; k2 < 5; k2++) {
            uint32_t hb[4];
            ldsm_x4(hb, ha + k2 * 64 - ((k2 == 4) ? (lm >> 1) * 32 : 0));
            mma_bf16(acc[0], wf[2 * k2][0], wf[2 * k2][1], wf[2 * k2][2], wf[2 * k2][3], hb[0], hb[1]);
            if (k2 < 4) mma_bf16(acc[1], wf[2 * k2 + 1][0], wf[2 * k2 + 1][1], wf[2 * k2 + 1][2], wf[2 * k2 + 1][3], hb[2], hb[3]);
        }
        float* o = ffr + ((fsl * 80 + 16 * fmt + g) * 8 + 2 * t);
        *(float2*)o = make_float2(acc[0][0] + acc[1][0], acc[0][1] + acc[1][1]);
        *(float2*)(o + 64) = make_float2(acc[0][2] + acc[1][2], acc[0][3] + acc[1][3]);
    }
    CBAR();
    bf16(*act)[56] = (bf16(*)[56])(sm + OFF_ACT);
    if (tid < 384) {
        const int f = tid >> 3, a = tid & 7;
        float v = 0.f;
        if (f < nf) {
            const int rg = (f < 32) ? f : f + 32, ru = (f < 32) ? f + 32 : f + 40;
            const float* pg = ffr + rg * 8 + a;
            const float* pu = ffr + ru * 8 + a;
            float gg = bfr((pg[0] + pg[640]) + (pg[1280] + pg[1920]));
            gg = bfr(silu(gg));
            const float uu = bfr((pu[0] + pu[640]) + (pu[1280] + pu[1920]));
            v = gg * uu;
        }
        act[a][f] = __ushort_as_bfloat16((unsigned short)f2bits(v));
    }
    CBAR();
    {
        uint32_t bq[3][2];
#pragma unroll
        for (int ks = 0; ks < 3; ks++) {
            bq[ks][0] = *(const uint32_t*)&act[g][16 * ks + 2 * t];
            bq[ks][1] = *(const uint32_t*)&act[g][16 * ks + 2 * t + 8];
        }
#pragma unroll
        for (int i = 0; i < 2; i++) {
            if (i == 0 || warp < 16) {
                float acc[4] = {0.f, 0.f, 0.f, 0.f};
#pragma unroll
                for (int ks = 0; ks < 3; ks++)
                    if (ks < 2 || nf > 32) mma_bf16(acc, wd[i][ks][0], wd[i][ks][1], wd[i][ks][2], wd[i][ks][3], bq[ks][0], bq[ks][1]);
                const int W = (warp + 20 * i) * 32 + lane, c = (W * 7282) >> 16;
                st_rlx2(&S->part[(c * G_ + b) * 9 + W - 9 * c], ~pack2(acc[0], acc[1]), ~pack2(acc[2], acc[3]));
            }
        }
    }
    if (warp >= 4) {
        const int tk = warp - 4;
        if (!__any_sync(0xffffffffu, 2047u - (M.skey[lr] & 2047u) == (uint32_t)(16 * b + tk))) {
            const uint4* src = (const uint4*)(sm + OFF_TILE + tk * (ROWP * 2));
            uint4* dst = (uint4*)(out + (size_t)(16 * b + tk) * D_);
            dst[lane] = src[lane]; dst[lane + 32] = src[lane + 32];
            if (lane < 8) dst[lane + 64] = src[lane + 64];
        }
    }
    float4* fin = (float4*)(sm + OFF_FIN);
    uint32_t rb = (fsel >> 11) & 0xFFFFu;
    rb ^= (rb & 0x8000u) ? 0x8000u : 0xFFFFu;
    const float rs = bfr(__fdividef(1.0f, 1.0f + __expf(-lo2f(rb))));
    const float fh2 = (tid < 288) ? __bfloat162float(h2s[fk][fd]) : 0.f, fgb = (tid < 288) ? __bfloat162float(M.gb[fd]) : 0.f;
    const float fx1 = bfr(lo2f(fx) + lo2f(~fv));
    if (tid < 576) {
        const uint2* src = &S->part[(size_t)b * 1152 + tid];
        uint2 a = ld_rlx2(src), c = ld_rlx2(src + 576);
#pragma unroll 1
        for (int it = 0; it < SPIN_MAX && (a.x == SENT || c.x == SENT); it++) {
            if (a.x == SENT) a = ld_rlx2(src);
            if (c.x == SENT) c = ld_rlx2(src + 576);
        }
        fin[tid] = make_float4(lo2f(~a.x) + lo2f(~c.x), hi2f(~a.x) + hi2f(~c.x), lo2f(~a.y) + lo2f(~c.y), hi2f(~a.y) + hi2f(~c.y));
    }
    CBAR();
    if (tid < 288) {
        const int part = tid & 7;
        const float* f = (const float*)fin + part * 36 + fo;
        float s = ((f[0] + f[288]) + (f[576] + f[864])) + ((f[1152] + f[1440]) + (f[1728] + f[2016]));
        s += __shfl_xor_sync(0xffffffffu, s, 1);
        s += __shfl_xor_sync(0xffffffffu, s, 2);
        s += __shfl_xor_sync(0xffffffffu, s, 4);
        const float upd = bfr(bfr(s) * rs);
        const float ov = fx1 + bfr(fgb * bfr(fh2 + upd));
        if (part == 0) out[(size_t)(2047u - (fsel & 2047u)) * D_ + fd] = __ushort_as_bfloat16((unsigned short)f2bits(ov));
    }
    if ((warp & 3) == 2 && lane == 0) asm volatile("cp.async.bulk.wait_group 0;" ::: "memory");
    }
}

typedef CUresult (*EncodeFn)(CUtensorMap*, CUtensorMapDataType, cuuint32_t, void*, const cuuint64_t*, const cuuint64_t*,
                             const cuuint32_t*, const cuuint32_t*, CUtensorMapInterleave, CUtensorMapSwizzle,
                             CUtensorMapL2promotion, CUtensorMapFloatOOBfill);

static void make_map(EncodeFn fn, CUtensorMap* m, const void* ptr, uint64_t cols, uint64_t rows, uint32_t bc, uint32_t br,
                     CUtensorMapSwizzle sw) {
    cuuint64_t dims[2] = {cols, rows};
    cuuint64_t strides[1] = {cols * 2};
    cuuint32_t box[2] = {bc, br};
    cuuint32_t es[2] = {1, 1};
    CUresult rc = fn(m, CU_TENSOR_MAP_DATA_TYPE_BFLOAT16, 2, (void*)ptr, dims, strides, box, es, CU_TENSOR_MAP_INTERLEAVE_NONE,
                     sw, CU_TENSOR_MAP_L2_PROMOTION_NONE, CU_TENSOR_MAP_FLOAT_OOB_FILL_NONE);
    (void)rc;
}

static void launch(void* const* d_in, const int* in_sizes, int n_in, void* d_out, int out_size) {
    static EncodeFn enc = nullptr;
    static CUtensorMap tmm, tmg, tmu, tmd, tmd32, tmg32, tmu32;
    static Scratch* sp = nullptr;
    static const void* cached[4] = {nullptr, nullptr, nullptr, nullptr};
    if (!enc) {
        cudaDriverEntryPointQueryResult qr;
        void* fn = nullptr;
        cudaGetDriverEntryPoint("cuTensorMapEncodeTiled", &fn, cudaEnableDefault, &qr);
        enc = (EncodeFn)fn;
        cudaFuncSetAttribute(mega_kernel, cudaFuncAttributeMaxDynamicSharedMemorySize, SMEM_TOTAL);
        cudaGetSymbolAddress((void**)&sp, g_s);
    }
    if (cached[0] != d_in[13] || cached[1] != d_in[9] || cached[2] != d_in[10] || cached[3] != d_in[11]) {
        make_map(enc, &tmm, d_in[13], 6 * D_, D_, 32, 192, CU_TENSOR_MAP_SWIZZLE_64B);
        make_map(enc, &tmg, d_in[9], F_, D_, 40, 192, CU_TENSOR_MAP_SWIZZLE_NONE);
        make_map(enc, &tmu, d_in[10], F_, D_, 40, 192, CU_TENSOR_MAP_SWIZZLE_NONE);
        make_map(enc, &tmg32, d_in[9], F_, D_, 32, 192, CU_TENSOR_MAP_SWIZZLE_64B);
        make_map(enc, &tmu32, d_in[10], F_, D_, 32, 192, CU_TENSOR_MAP_SWIZZLE_64B);
        make_map(enc, &tmd, d_in[11], D_, F_, 64, 40, CU_TENSOR_MAP_SWIZZLE_128B);
        make_map(enc, &tmd32, d_in[11], D_, F_, 64, 32, CU_TENSOR_MAP_SWIZZLE_128B);
        cached[3] = d_in[11];
        cached[0] = d_in[13]; cached[1] = d_in[9]; cached[2] = d_in[10];
    }
    mega_kernel<<<G_, NTHR, SMEM_TOTAL>>>((const bf16*)d_in[0], (const bf16*)d_in[1], (const bf16*)d_in[2], (const bf16*)d_in[3],
                                          (const bf16*)d_in[4], (const bf16*)d_in[5], (const bf16*)d_in[12], sp, (const bf16*)d_in[6],
                                          (const bf16*)d_in[8], (const bf16*)d_in[11], (bf16*)d_out, tmm, tmg, tmu, tmd, tmd32, tmg32, tmu32);
}

}

extern "C" void kernel_launch(void* const* d_in, const int* in_sizes, int n_in, void* d_out, int out_size) {
    static int mode = -1;
    if (mode < 0) mode = v5::fits() ? 1 : 0;
    if (mode) v5::launch(d_in, in_sizes, n_in, d_out, out_size);
    else v4::launch(d_in, in_sizes, n_in, d_out, out_size);
}
```

```cpp
#include <cuda_runtime.h>
#include <cuda.h>
#include <cuda_bf16.h>
#include <cuda_fp16.h>
#include <stdint.h>

namespace v5 {

#define L_ 2048
#define D_ 576
#define N_ 128
#define F_ 4608
#define G_ 120
#define NCL 15
#define NTHR 768
#define SPIN_MAX (1 << 18)

typedef __nv_bfloat16 bf16;

struct Scratch {
    float4 acc1[L_ + 8];
    float4 acc2[L_];
    uint4 h2c[137 * 72];
    float4 rs[39 * 8];
    float4 acc3[2 * 72 * 32 + 96];
};
#define NRS 124
static_assert(137 * 72 + 2 * 72 * 32 + 39 * 8 + 96 == NRS * G_, "16 B units cleared early in a launch (h2c, acc3, rs)");
__device__ __align__(1024) Scratch g_s;

#define OFF_WG 0
#define OFF_WU 46080
#define KSCR 3456
#define OFF_WM0 69120
#define OFF_STG OFF_WM0
#define OFF_MG2 86400
#define OFF_CH 92160
#define CHS 18688
#define UP 3808
#define UB 192
#define XO_TF 1216
#define XO_U8 2016
#define XO_U16 3328
#define XO_ZA 1232
#define XO_ZB 2016
#define XO_ZC 2800
#define XO_ZD 3328
#define XO_TD 16000
#define XO_K1024 18624
#define XO_DSK 18628
#define XO_KLAST 18656
#define XO_MBU 18672
#define OFF_X 185600
#define XG 672
#define XI(i) (((i) >> 1) * 5520 + ((i) & 1) * 2752)
#define XN(n) ((((n) >> 1) & 3) * XG + (2 * ((n) >> 3) + ((n) & 1)) * 80)
#define OFF_V 207616
#define VP 528
#define OFF_EK (OFF_V + 512)
#define OFF_WM2 OFF_V
#define OFF_MG1 (OFF_V + 17280)
#define OFF_SC (OFF_V + 19840)
#define OFF_C1 (OFF_V + 20640)
#define OFF_MISC 228736
#define OFF_WD OFF_CH
#define OFF_H2T (OFF_CH + 46080)
#define OFF_OUT (OFF_CH + 66560)
#define OFF_GB (OFF_CH + 87040)
#define OFF_AT (OFF_CH + 88064)
#define ROWP 584
#define OFF_H2S 0
#define OFF_FFR 9344
#define OFF_ACT 19584
#define OFF_RS 20480

enum { MB_WM2, MB_MG1, MB_MG2, MB_KEY, MB_V, MB_RS, MB_WG, MB_WU, MB_WD, MB_KEY2, MB_EK, MB_RS2, MB_V1, MB_V2, MB_C2, MB_CW, MB_KD, MB_CD, MB_OUT, MB_FIN, MB_N };

struct Misc {
    union {
        __align__(16) uint4 box[11 * 16];
        struct { unsigned int cand[128], key[256], cand2[128], sel[8], selo[8]; };
    };
    __align__(16) uint4 c2[20];
    __align__(16) unsigned int fin[12];
    unsigned int ga[8], wr[20];
    float cws[2];
    unsigned long long mbar[MB_N];
};
#define SMEM_TOTAL (OFF_MISC + (int)sizeof(Misc))
static_assert(SMEM_TOTAL <= 232448, "smem");

__device__ __forceinline__ float lo2f(uint32_t w) { return __uint_as_float(w << 16); }
__device__ __forceinline__ float hi2f(uint32_t w) { return __uint_as_float(w & 0xFFFF0000u); }
__device__ __forceinline__ uint32_t pack2(float lo, float hi) { uint32_t r; asm("cvt.rn.bf16x2.f32 %0, %1, %2;" : "=r"(r) : "f"(hi), "f"(lo)); return r; }
__device__ __forceinline__ float bfr(float x) { return __uint_as_float(pack2(0.f, x)); }
__device__ __forceinline__ uint32_t f2bits(float x) { return pack2(x, 0.f); }
__device__ __forceinline__ uint32_t packh(float lo, float hi) { uint32_t r; asm("cvt.rn.f16x2.f32 %0, %1, %2;" : "=r"(r) : "f"(hi), "f"(lo)); return r; }
__device__ __forceinline__ float frcp(float x) { float r; asm("rcp.approx.ftz.f32 %0, %1;" : "=f"(r) : "f"(x)); return r; }
__device__ __forceinline__ float fsqrt(float x) { float r; asm("sqrt.approx.ftz.f32 %0, %1;" : "=f"(r) : "f"(x)); return r; }
__device__ __forceinline__ float fex2(float x) { float r; asm("ex2.approx.ftz.f32 %0, %1;" : "=f"(r) : "f"(x)); return r; }
__device__ __forceinline__ float sigm(float x) { return frcp(1.0f + fex2(x * -1.4426950408889634f)); }
__device__ __forceinline__ float silu(float x) { return x * sigm(x); }
__device__ __forceinline__ uint32_t add2(uint32_t a, uint32_t b) { uint32_t r; asm("add.rn.bf16x2 %0, %1, %2;" : "=r"(r) : "r"(a), "r"(b)); return r; }
__device__ __forceinline__ uint32_t sub2(uint32_t a, uint32_t b) { uint32_t r; asm("sub.rn.bf16x2 %0, %1, %2;" : "=r"(r) : "r"(a), "r"(b)); return r; }
__device__ __forceinline__ uint32_t mul2(uint32_t a, uint32_t b) { uint32_t r; asm("mul.rn.bf16x2 %0, %1, %2;" : "=r"(r) : "r"(a), "r"(b)); return r; }
__device__ __forceinline__ uint32_t fma2(uint32_t a, uint32_t b, uint32_t c) { uint32_t r; asm("fma.rn.bf16x2 %0, %1, %2, %3;" : "=r"(r) : "r"(a), "r"(b), "r"(c)); return r; }
__device__ __forceinline__ uint32_t norm2(uint32_t x, uint32_t m, uint32_t rh, uint32_t rl) { const uint32_t d = sub2(x, m); return fma2(d, rh, mul2(d, rl)); }

__device__ __forceinline__ void mma_bf16(float* c, uint32_t a0, uint32_t a1, uint32_t a2, uint32_t a3, uint32_t b0, uint32_t b1) {
    asm volatile("mma.sync.aligned.m16n8k16.row.col.f32.bf16.bf16.f32 {%0,%1,%2,%3}, {%4,%5,%6,%7}, {%8,%9}, {%0,%1,%2,%3};\n"
                 : "+f"(c[0]), "+f"(c[1]), "+f"(c[2]), "+f"(c[3]) : "r"(a0), "r"(a1), "r"(a2), "r"(a3), "r"(b0), "r"(b1));
}
__device__ __forceinline__ void mma_f16(float* c, const uint32_t* a, uint32_t b0, uint32_t b1) {
    asm volatile("mma.sync.aligned.m16n8k16.row.col.f32.f16.f16.f32 {%0,%1,%2,%3}, {%4,%5,%6,%7}, {%8,%9}, {%0,%1,%2,%3};\n"
                 : "+f"(c[0]), "+f"(c[1]), "+f"(c[2]), "+f"(c[3]) : "r"(a[0]), "r"(a[1]), "r"(a[2]), "r"(a[3]), "r"(b0), "r"(b1));
}
__device__ __forceinline__ void ldsm_x4(uint32_t* r, uint32_t addr) {
    asm volatile("ldmatrix.sync.aligned.m8n8.x4.shared.b16 {%0,%1,%2,%3}, [%4];" : "=r"(r[0]), "=r"(r[1]), "=r"(r[2]), "=r"(r[3]) : "r"(addr) : "memory");
}
__device__ __forceinline__ void ldsm_x4_t(uint32_t* r, uint32_t addr) {
    asm volatile("ldmatrix.sync.aligned.m8n8.x4.trans.shared.b16 {%0,%1,%2,%3}, [%4];" : "=r"(r[0]), "=r"(r[1]), "=r"(r[2]), "=r"(r[3]) : "r"(addr) : "memory");
}
__device__ __forceinline__ void stsm_x4(uint32_t addr, uint32_t r0, uint32_t r1, uint32_t r2, uint32_t r3) {
    asm volatile("stmatrix.sync.aligned.m8n8.x4.shared.b16 [%0], {%1,%2,%3,%4};" ::"r"(addr), "r"(r0), "r"(r1), "r"(r2), "r"(r3) : "memory");
}
__device__ __forceinline__ void stsm_x4_t(uint32_t addr, uint32_t r0, uint32_t r1, uint32_t r2, uint32_t r3) {
    asm volatile("stmatrix.sync.aligned.m8n8.x4.trans.shared.b16 [%0], {%1,%2,%3,%4};" ::"r"(addr), "r"(r0), "r"(r1), "r"(r2), "r"(r3) : "memory");
}
__device__ __forceinline__ uint32_t movm(uint32_t a) { uint32_t r; asm volatile("movmatrix.sync.aligned.m8n8.trans.b16 %0, %1;" : "=r"(r) : "r"(a)); return r; }
__device__ __forceinline__ uint32_t lds32(uint32_t a) { uint32_t v; asm volatile("ld.shared.u32 %0, [%1];" : "=r"(v) : "r"(a)); return v; }
__device__ __forceinline__ void sts32(uint32_t a, uint32_t v) { asm volatile("st.shared.u32 [%0], %1;" ::"r"(a), "r"(v) : "memory"); }
__device__ __forceinline__ void sts16(uint32_t a, uint32_t v) { asm volatile("st.shared.u16 [%0], %1;" ::"r"(a), "h"((unsigned short)v) : "memory"); }
__device__ __forceinline__ void named_bar(int id, int n) { asm volatile("bar.sync %0, %1;" ::"r"(id), "r"(n) : "memory"); }
__device__ __forceinline__ void named_arrive(int id, int n) { asm volatile("bar.arrive %0, %1;" ::"r"(id), "r"(n) : "memory"); }
#define CBAR() asm volatile("bar.sync 0, 640;" ::: "memory")
#define RBAR() asm volatile("bar.sync 0;" ::: "memory")
#define PROXY_FENCE() asm volatile("fence.proxy.async.shared::cta;" ::: "memory")

#define D4(d, o) "+f"(d[o]), "+f"(d[o + 1]), "+f"(d[o + 2]), "+f"(d[o + 3])
__device__ __forceinline__ void wg32(float* d, uint32_t a0, uint32_t a1, uint32_t a2, uint32_t a3, uint64_t desc) {
    asm volatile("wgmma.mma_async.sync.aligned.m64n32k16.f32.bf16.bf16 {%0,%1,%2,%3,%4,%5,%6,%7,%8,%9,%10,%11,%12,%13,%14,%15}, {%16,%17,%18,%19}, %20, 1, 1, 1, 0;"
                 : D4(d, 0), D4(d, 4), D4(d, 8), D4(d, 12) : "r"(a0), "r"(a1), "r"(a2), "r"(a3), "l"(desc));
}
__device__ __forceinline__ void wg48(float* d, uint32_t a0, uint32_t a1, uint32_t a2, uint32_t a3, uint64_t desc) {
    asm volatile("wgmma.mma_async.sync.aligned.m64n48k16.f32.bf16.bf16 {%0,%1,%2,%3,%4,%5,%6,%7,%8,%9,%10,%11,%12,%13,%14,%15,%16,%17,%18,%19,%20,%21,%22,%23}, {%24,%25,%26,%27}, %28, 1, 1, 1, 0;"
                 : D4(d, 0), D4(d, 4), D4(d, 8), D4(d, 12), D4(d, 16), D4(d, 20) : "r"(a0), "r"(a1), "r"(a2), "r"(a3), "l"(desc));
}
__device__ __forceinline__ void wg64(float* d, uint32_t a0, uint32_t a1, uint32_t a2, uint32_t a3, uint64_t desc) {
    asm volatile("wgmma.mma_async.sync.aligned.m64n64k16.f32.bf16.bf16 {%0,%1,%2,%3,%4,%5,%6,%7,%8,%9,%10,%11,%12,%13,%14,%15,%16,%17,%18,%19,%20,%21,%22,%23,%24,%25,%26,%27,%28,%29,%30,%31}, {%32,%33,%34,%35}, %36, 1, 1, 1, 0;"
                 : D4(d, 0), D4(d, 4), D4(d, 8), D4(d, 12), D4(d, 16), D4(d, 20), D4(d, 24), D4(d, 28) : "r"(a0), "r"(a1), "r"(a2), "r"(a3), "l"(desc));
}
#define O4(d, o) "=f"(d[o]), "=f"(d[o + 1]), "=f"(d[o + 2]), "=f"(d[o + 3])
__device__ __forceinline__ void wg32z(float* d, uint32_t a0, uint32_t a1, uint32_t a2, uint32_t a3, uint64_t desc) {
    asm volatile("wgmma.mma_async.sync.aligned.m64n32k16.f32.bf16.bf16 {%0,%1,%2,%3,%4,%5,%6,%7,%8,%9,%10,%11,%12,%13,%14,%15}, {%16,%17,%18,%19}, %20, 0, 1, 1, 0;"
                 : O4(d, 0), O4(d, 4), O4(d, 8), O4(d, 12) : "r"(a0), "r"(a1), "r"(a2), "r"(a3), "l"(desc));
}
__device__ __forceinline__ void wg48z(float* d, uint32_t a0, uint32_t a1, uint32_t a2, uint32_t a3, uint64_t desc) {
    asm volatile("wgmma.mma_async.sync.aligned.m64n48k16.f32.bf16.bf16 {%0,%1,%2,%3,%4,%5,%6,%7,%8,%9,%10,%11,%12,%13,%14,%15,%16,%17,%18,%19,%20,%21,%22,%23}, {%24,%25,%26,%27}, %28, 0, 1, 1, 0;"
                 : O4(d, 0), O4(d, 4), O4(d, 8), O4(d, 12), O4(d, 16), O4(d, 20) : "r"(a0), "r"(a1), "r"(a2), "r"(a3), "l"(desc));
}
__device__ __forceinline__ void wg56(float* d, uint32_t a0, uint32_t a1, uint32_t a2, uint32_t a3, uint64_t desc) {
    asm volatile("wgmma.mma_async.sync.aligned.m64n56k16.f32.bf16.bf16 {%0,%1,%2,%3,%4,%5,%6,%7,%8,%9,%10,%11,%12,%13,%14,%15,%16,%17,%18,%19,%20,%21,%22,%23,%24,%25,%26,%27}, {%28,%29,%30,%31}, %32, 1, 1, 1, 0;"
                 : D4(d, 0), D4(d, 4), D4(d, 8), D4(d, 12), D4(d, 16), D4(d, 20), D4(d, 24) : "r"(a0), "r"(a1), "r"(a2), "r"(a3), "l"(desc));
}
__device__ __forceinline__ void wg64z(float* d, uint32_t a0, uint32_t a1, uint32_t a2, uint32_t a3, uint64_t desc) {
    asm volatile("wgmma.mma_async.sync.aligned.m64n64k16.f32.bf16.bf16 {%0,%1,%2,%3,%4,%5,%6,%7,%8,%9,%10,%11,%12,%13,%14,%15,%16,%17,%18,%19,%20,%21,%22,%23,%24,%25,%26,%27,%28,%29,%30,%31}, {%32,%33,%34,%35}, %36, 0, 1, 1, 0;"
                 : O4(d, 0), O4(d, 4), O4(d, 8), O4(d, 12), O4(d, 16), O4(d, 20), O4(d, 24), O4(d, 28) : "r"(a0), "r"(a1), "r"(a2), "r"(a3), "l"(desc));
}
#define WG_FENCE() asm volatile("wgmma.fence.sync.aligned;" ::: "memory")
#define WG_COMMIT() asm volatile("wgmma.commit_group.sync.aligned;" ::: "memory")
#define WG_WAIT(n) asm volatile("wgmma.wait_group.sync.aligned " #n ";" ::: "memory")
#define TQ(p, k) p[2 * (k) + 1], p[2 * (k) + 2], p[2 * (k)], p[2 * (k) + 1]

__device__ __forceinline__ uint4 ld_nc4(const void* p) { uint4 v; asm volatile("ld.global.nc.v4.u32 {%0,%1,%2,%3}, [%4];" : "=r"(v.x), "=r"(v.y), "=r"(v.z), "=r"(v.w) : "l"(p)); return v; }
__device__ __forceinline__ uint2 ld_nc2(const void* p) { uint2 v; asm volatile("ld.global.nc.v2.u32 {%0,%1}, [%2];" : "=r"(v.x), "=r"(v.y) : "l"(p)); return v; }
__device__ __forceinline__ unsigned short ld_nc16(const void* p) { unsigned short v; asm volatile("ld.global.nc.u16 %0, [%1];" : "=h"(v) : "l"(p)); return v; }
__device__ __forceinline__ uint32_t ld_nc(const void* p) { uint32_t v; asm volatile("ld.global.nc.u32 %0, [%1];" : "=r"(v) : "l"(p)); return v; }
__device__ __forceinline__ uint32_t ld_rlx(const unsigned int* p) { uint32_t v; asm volatile("ld.relaxed.gpu.global.u32 %0, [%1];" : "=r"(v) : "l"(p) : "memory"); return v; }
__device__ __forceinline__ uint2 ld_rlx2(const void* p) { uint2 v; asm volatile("ld.relaxed.gpu.global.v2.u32 {%0,%1}, [%2];" : "=r"(v.x), "=r"(v.y) : "l"(p) : "memory"); return v; }
__device__ __forceinline__ uint4 ld_rlx4(const void* p) { uint4 v; asm volatile("ld.relaxed.gpu.global.v4.u32 {%0,%1,%2,%3}, [%4];" : "=r"(v.x), "=r"(v.y), "=r"(v.z), "=r"(v.w) : "l"(p) : "memory"); return v; }
__device__ __forceinline__ void st_rlx(unsigned int* p, uint32_t v) { asm volatile("st.relaxed.gpu.global.u32 [%0], %1;" ::"l"(p), "r"(v) : "memory"); }
__device__ __forceinline__ void st_rlx2(void* p, uint32_t a, uint32_t b) { asm volatile("st.relaxed.gpu.global.v2.u32 [%0], {%1,%2};" ::"l"(p), "r"(a), "r"(b) : "memory"); }
__device__ __forceinline__ void st_rlx4(void* p, uint4 v) { asm volatile("st.relaxed.gpu.global.v4.u32 [%0], {%1,%2,%3,%4};" ::"l"(p), "r"(v.x), "r"(v.y), "r"(v.z), "r"(v.w) : "memory"); }
__device__ __forceinline__ void red_inc(unsigned int* p) { asm volatile("red.relaxed.gpu.global.add.u32 [%0], 1;" ::"l"(p) : "memory"); }

__device__ __forceinline__ void mbar_init(uint32_t a, int cnt) { asm volatile("mbarrier.init.shared::cta.b64 [%0], %1;" ::"r"(a), "r"(cnt) : "memory"); }
__device__ __forceinline__ void mbar_expect(uint32_t a, uint32_t bytes) { asm volatile("mbarrier.arrive.expect_tx.shared::cta.b64 _, [%0], %1;" ::"r"(a), "r"(bytes) : "memory"); }
__device__ __forceinline__ void mbar_wait(uint32_t a, uint32_t parity) {
    uint32_t ok;
    int it = 0;
    do {
        ++it;
        asm volatile("{\n.reg .pred p;\nmbarrier.try_wait.parity.shared::cta.b64 p, [%1], %2;\nselp.u32 %0, 1, 0, p;\n}" : "=r"(ok) : "r"(a), "r"(parity) : "memory");
    } while (!ok & (it < SPIN_MAX));
}
__device__ __forceinline__ bool mbar_test(uint32_t a, uint32_t parity) {
    uint32_t ok;
    asm volatile("{\n.reg .pred p;\nmbarrier.test_wait.parity.shared::cta.b64 p, [%1], %2;\nselp.u32 %0, 1, 0, p;\n}" : "=r"(ok) : "r"(a), "r"(parity) : "memory");
    return __all_sync(0xffffffffu, ok);
}
__device__ __forceinline__ void tma2d(uint32_t dst, const CUtensorMap* tm, int c0, int c1, uint32_t mbar) {
    asm volatile("cp.async.bulk.tensor.2d.shared::cluster.global.mbarrier::complete_tx::bytes [%0], [%1, {%3, %4}], [%2];"
                 ::"r"(dst), "l"(tm), "r"(mbar), "r"(c0), "r"(c1) : "memory");
}
__device__ __forceinline__ void bulk_s2g(void* dst, uint32_t src, uint32_t bytes) {
    asm volatile("cp.async.bulk.global.shared::cta.bulk_group [%0], [%1], %2;" ::"l"(dst), "r"(src), "r"(bytes) : "memory");
}
__device__ __forceinline__ uint32_t ld_acq(const unsigned int* p) { uint32_t v; asm volatile("ld.acquire.gpu.global.u32 %0, [%1];" : "=r"(v) : "l"(p) : "memory"); return v; }
__device__ __forceinline__ void bulk_pf(const void* src, uint32_t bytes) { asm volatile("cp.async.bulk.prefetch.L2.global [%0], %1;" ::"l"(src), "r"(bytes) : "memory"); }

struct cplx { float x, y; };
__device__ __forceinline__ cplx cmul(cplx a, cplx b) { cplx r; r.x = a.x * b.x - a.y * b.y; r.y = a.x * b.y + a.y * b.x; return r; }
__device__ __forceinline__ cplx csq(cplx a) { cplx r; r.x = a.x * a.x - a.y * a.y; r.y = 2.0f * a.x * a.y; return r; }
__device__ __forceinline__ uint32_t hcm(uint32_t x, uint32_t y, uint32_t yp) {
    const __half2 X = *(const __half2*)&x, Y = *(const __half2*)&y, YP = *(const __half2*)&yp;
    const __half2 r = __hfma2(__high2half2(X), YP, __hmul2(__low2half2(X), Y));
    return *(const uint32_t*)&r;
}
__device__ __forceinline__ uint32_t hcn(uint32_t x, uint32_t y, uint32_t yq) {
    const __half2 X = *(const __half2*)&x, Y = *(const __half2*)&y, YQ = *(const __half2*)&yq;
    const __half2 r = __hfma2(__hneg2(__high2half2(X)), YQ, __hmul2(__low2half2(X), Y));
    return *(const uint32_t*)&r;
}
__device__ __forceinline__ float2 hsum4(uint32_t a, uint32_t b, uint32_t c, uint32_t d) {
    return __half22float2(__hadd2(__hadd2(*(const __half2*)&a, *(const __half2*)&b), __hadd2(*(const __half2*)&c, *(const __half2*)&d)));
}
__device__ __forceinline__ uint32_t amax2(uint32_t a, uint32_t b) { uint32_t r; asm("max.xorsign.abs.bf16x2 %0, %1, %2;" : "=r"(r) : "r"(a), "r"(b)); return r; }
__device__ __forceinline__ void ln_stats(float s1, float s2, float& meanb, float& rinv) {
    const float mean = s1 * (1.0f / D_);
    const float den = bfr(fsqrt(bfr(bfr(fmaxf(fmaf(-mean, mean, s2 * (1.0f / D_)), 0.f)) + 1e-5f)));
    meanb = bfr(mean);
    rinv = frcp(den);
}

__device__ __forceinline__ int fresh_tid() { int v; asm volatile("mov.u32 %0, %tid.x;" : "=r"(v)); return v - 128; }
__device__ __forceinline__ void mma_k8(float* c, uint32_t a0, uint32_t a1, uint32_t b0) {
    asm volatile("mma.sync.aligned.m16n8k8.row.col.f32.bf16.bf16.f32 {%0,%1,%2,%3}, {%4,%5}, {%6}, {%0,%1,%2,%3};\n"
                 : "+f"(c[0]), "+f"(c[1]), "+f"(c[2]), "+f"(c[3]) : "r"(a0), "r"(a1), "r"(b0));
}
__device__ __forceinline__ void ldsm_x2(uint32_t* r, uint32_t addr) {
    asm volatile("ldmatrix.sync.aligned.m8n8.x2.shared.b16 {%0,%1}, [%2];" : "=r"(r[0]), "=r"(r[1]) : "r"(addr) : "memory");
}
__device__ __forceinline__ void ldsm_x2_t(uint32_t* r, uint32_t addr) {
    asm volatile("ldmatrix.sync.aligned.m8n8.x2.trans.shared.b16 {%0,%1}, [%2];" : "=r"(r[0]), "=r"(r[1]) : "r"(addr) : "memory");
}
__device__ __forceinline__ void stsm_x2(uint32_t addr, uint32_t r0, uint32_t r1) {
    asm volatile("stmatrix.sync.aligned.m8n8.x2.shared.b16 [%0], {%1,%2};" ::"r"(addr), "r"(r0), "r"(r1) : "memory");
}
__device__ __forceinline__ uint4 lds128(uint32_t a) { uint4 v; asm volatile("ld.shared.v4.u32 {%0,%1,%2,%3}, [%4];" : "=r"(v.x), "=r"(v.y), "=r"(v.z), "=r"(v.w) : "r"(a) : "memory"); return v; }
__device__ __forceinline__ uint32_t mapa(uint32_t a, uint32_t r) { uint32_t o; asm("mapa.shared::cluster.u32 %0, %1, %2;" : "=r"(o) : "r"(a), "r"(r)); return o; }
__device__ __forceinline__ void sta4(uint32_t dst, uint4 v, uint32_t mb) {
    asm volatile("st.async.weak.shared::cluster.mbarrier::complete_tx::bytes.v4.b32 [%0], {%1,%2,%3,%4}, [%5];" ::"r"(dst), "r"(v.x), "r"(v.y), "r"(v.z), "r"(v.w), "r"(mb) : "memory");
}
__device__ __forceinline__ void sta2(uint32_t dst, uint32_t a, uint32_t b, uint32_t mb) {
    asm volatile("st.async.weak.shared::cluster.mbarrier::complete_tx::bytes.v2.b32 [%0], {%1,%2}, [%3];" ::"r"(dst), "r"(a), "r"(b), "r"(mb) : "memory");
}
__device__ __forceinline__ void mbar_arrive(uint32_t a) { asm volatile("mbarrier.arrive.shared::cta.b64 _, [%0];" ::"r"(a) : "memory"); }
__device__ __forceinline__ void red4(float4* p, float a, float b, float c) {
    asm volatile("red.relaxed.gpu.global.add.v4.f32 [%0], {%1,%2,%3,%4};" ::"l"(p), "f"(a), "f"(b), "f"(c), "f"(1.0f) : "memory");
}
__device__ __forceinline__ void red4p(bool on, float4* p, float a, float b, float c) {
    asm volatile("{\n.reg .pred q;\nsetp.ne.u32 q, %5, 0;\n@q red.relaxed.gpu.global.add.v4.f32 [%0], {%1,%2,%3,%4};\n}" ::"l"(p), "f"(a), "f"(b), "f"(c), "f"(1.0f), "r"((uint32_t)on) : "memory");
}
__device__ __forceinline__ float4 atom4(float4* p, float a, float b, float c, float d) {
    float4 v;
    asm volatile("atom.relaxed.gpu.global.add.v4.f32 {%0,%1,%2,%3}, [%4], {%5,%6,%7,%8};" : "=f"(v.x), "=f"(v.y), "=f"(v.z), "=f"(v.w) : "l"(p), "f"(a), "f"(b), "f"(c), "f"(d) : "memory");
    return v;
}
__device__ __forceinline__ uint2 lds64(uint32_t a) { uint2 v; asm volatile("ld.shared.v2.u32 {%0,%1}, [%2];" : "=r"(v.x), "=r"(v.y) : "r"(a) : "memory"); return v; }
__device__ __forceinline__ float4 ld_rlx4f(const float4* p) { float4 v; asm volatile("ld.relaxed.gpu.global.v4.f32 {%0,%1,%2,%3}, [%4];" : "=f"(v.x), "=f"(v.y), "=f"(v.z), "=f"(v.w) : "l"(p) : "memory"); return v; }
__device__ __forceinline__ void tma5d_st(const CUtensorMap* tm, int c0, int c4, uint32_t src) {
    asm volatile("cp.async.bulk.tensor.5d.global.shared::cta.bulk_group [%0, {%2, %4, %4, %4, %3}], [%1];" ::"l"(tm), "r"(src), "r"(c0), "r"(c4), "r"(0) : "memory");
}
__device__ __forceinline__ void tma2d_pf(const CUtensorMap* tm, int c0, int c1) {
    asm volatile("cp.async.bulk.prefetch.tensor.2d.L2.global [%0, {%1, %2}];" ::"l"(tm), "r"(c0), "r"(c1) : "memory");
}
__device__ __forceinline__ void pace(int clk) {
    const long long c0 = clock64();
    int it = 0;
    while (clock64() - c0 < clk && ++it < 4096) { }
}
__device__ __forceinline__ uint32_t sign2(uint32_t a) { uint32_t r; asm("prmt.b32 %0, %1, 0, 0xBB99;" : "=r"(r) : "r"(a)); return r; }
#define MB(i) (sb + OFF_MISC + (uint32_t)offsetof(Misc, mbar) + 8 * (i))
__device__ __forceinline__ uint32_t box_tap(int i) {
    const int f = (i * 205) >> 13, l = i - 40 * f - 6 - ((0x35C36 >> (4 * f)) & 15);
    const unsigned wd = (0x16824 >> (4 * f)) & 15, one = f == 4 ? 0xFFFFu : 0x3F80u;
    return ((unsigned)l <= wd ? one : 0u) | ((unsigned)(l - 1) <= wd ? one << 16 : 0u);
}
#define SD 500
#define UF(u) ((u) < 4 ? (u) + 5 : (u) == 4 ? 13 : (u) < 10 ? (u) - 5 : (u) - 1)
template <class F>
__device__ __forceinline__ void conv_channel(unsigned char* sm, uint32_t rank, uint32_t fixa, uint32_t fixv, F& late) {
    Misc& M = *(Misc*)(sm + OFF_MISC);
    const uint32_t sb = (uint32_t)__cvta_generic_to_shared(sm);
    const int tid = fresh_tid(), lane = tid & 31, g = lane >> 2, t = lane & 3, lr = lane & 7, lm = lane >> 3;
    const int warp_ = __shfl_sync(0xffffffffu, tid >> 5, 0), wgi = warp_ >> 2, w = warp_ & 3;
    const uint32_t cb = sb + OFF_CH + wgi * CHS;
    float D[32];
    const uint32_t dlo = ((cb & 0x3FFFF) >> 4) | ((UP >> 4) << 16);
#define DS(o, z, bl) (((uint64_t)(128 >> 4) << 32) | (uint64_t)(dlo + (o) / 16 + (((z) & 1) ? 0 : UP / 8) - ((z) >> 1) * (bl)))
    const uint32_t pf = cb + XO_TF + (w >> 1) * UP + (8 + 16 * (w & 1) + g - 2 * t) * 4;
    uint32_t p[13], r9[9];
    named_bar(1 + wgi, 128);
    if (fixa) sts16(fixa, fixv);
#pragma unroll
    for (int s = 0; s < 13; s++) p[s] = lds32(pf + s * 32);
    {
        const uint32_t a8 = cb + UB + t * UP + g * 16 + w * 128, b8 = cb + XO_U8 + lm * UP + lr * 16 + w * 128;
        const uint32_t a16 = cb + UB + (2 * (lr & 1) + (lm & 1)) * UP + ((lr >> 1) + 2 * (lm & 2)) * 16 + w * 128;
        const uint32_t b16 = cb + XO_U16 + (2 * (w & 1) + (lm >> 1)) * UP + (lane & 15) * 16 + (w >> 1) * 256;
        uint32_t r[3][4];
        mbar_wait(cb + XO_MBU, 0);
        ldsm_x4_t(r[0], a8);
        ldsm_x4_t(r[1], a16);
        if (w < 2) ldsm_x4_t(r[2], a8 + 512);
        stsm_x4(b8, r[0][0], r[0][1], r[0][2], r[0][3]);
        stsm_x4(b16, r[1][0], r[1][1], r[1][2], r[1][3]);
        if (w < 2) stsm_x4(b8 + 512, r[2][0], r[2][1], r[2][2], r[2][3]);
    }
    PROXY_FENCE();
    named_bar(1 + wgi, 128);
    const uint32_t pa = cb + XO_TD + (40 + 8 * w + g - 2 * t) * 4, pq = sb + OFF_MISC + (8 * w - 18 + g - 2 * t) * 4;
    uint32_t q[3][8], k2;
    auto ld = [&](int u) {
        uint32_t* d = q[u % 3];
        const int f = UF(u);
        if (f >= 5) {
#pragma unroll
            for (int i = 0; i < 8; i++) d[i] = (f == 13 && i > 4) ? 0u : lds32(pa + (f - 5) * 256 + i * 32);
        } else {
            const int lo = f == 2, hi = f == 2 ? 3 : (f == 1 || f == 4) ? 1 : 2;
#pragma unroll
            for (int i = 0; i < 8; i++) {
                if (f < 3) d[i] = 0u;
                if (i >= lo && i <= hi + 3) {
                    asm volatile("{\n.reg .pred p;\nsetp.le.u32 p, %2, %3;\n@p ld.shared.u32 %0, [%1];\n}" : "+r"(d[i]) : "r"(pq + f * 160 + i * 32), "r"(w + i - 3 - lo), "r"(hi - lo));
                    if (f == 4) asm volatile("and.b32 %0, %0, %1;" : "+r"(d[i]) : "r"(k2));
                }
            }
        }
    };
    auto go = [&](int u) {
        const int f = UF(u);
        WG_FENCE();
#pragma unroll
        for (int z = 0; z < 2; z++) {
            const uint32_t* a = q[u % 3] + 2 * z;
#define Q4 a[1], a[5], a[0], a[4]
            if (f == 5 && z == 0) wg64z(D, Q4, DS(UB, 0, 2));
            else if (f < 2) wg48(D + 8, Q4, DS(f ? XO_ZB : XO_ZA, z, 0));
            else if (f < 5) wg32(D + 16, Q4, DS(f == 2 ? XO_ZC : f == 3 ? XO_ZD : UB, z, 0));
            else if (f < 9) wg64(D, Q4, DS(UB, 2 * (f - 5) + z, 2));
            else if (f == 13) wg48(D + 8, Q4, DS(UB, z, 0));
            else wg56(D + 4, Q4, DS(UB + 128, 2 * (f - 5) + z, 2));
        }
        WG_COMMIT();
    };
    {
        float Z8[24], Z16[16];
        uint32_t z8[12], z16[8];
        const uint32_t za = cb + ((w >> 1) ? XO_ZB : XO_ZA) + t * UP + (4 * (w & 1) + (g & 3) + 8 * (g >> 2)) * 16;
        const uint32_t zc = cb + ((w >> 1) ? XO_ZD : XO_ZC) + (2 * (lr & 1) + (lm >> 1)) * UP + (((lane & 15) >> 1) + 8 * (w & 1)) * 16;
        WG_FENCE();
#pragma unroll
        for (int e = 0; e < 6; e++) {
            if (e == 0) wg48z(Z8, TQ(p, e), DS(XO_U8, e, 8));
            else wg48(Z8, TQ(p, e), DS(XO_U8, e, 8));
        }
        WG_COMMIT();
        late();
        WG_WAIT(0);
        asm volatile("setmaxnreg.inc.sync.aligned.u32 88;");
#pragma unroll
        for (int s = 0; s < 9; s++) r9[s] = lds32(pf + 2 * UP + s * 32);
#pragma unroll
        for (int i = 0; i < 12; i++) asm volatile("cvt.rn.bf16x2.f32 %0, %1, %2;" : "=r"(z8[i]) : "f"(Z8[2 * i + 1]), "f"(Z8[2 * i]));
        WG_FENCE();
#pragma unroll
        for (int e = 0; e < 4; e++) {
            if (e == 0) wg32z(Z16, TQ(r9, e), DS(XO_U16, e, 16));
            else wg32(Z16, TQ(r9, e), DS(XO_U16, e, 16));
        }
        WG_COMMIT();
        WG_WAIT(0);
#pragma unroll
        for (int i = 0; i < 8; i++) asm volatile("cvt.rn.bf16x2.f32 %0, %1, %2;" : "=r"(z16[i]) : "f"(Z16[2 * i + 1]), "f"(Z16[2 * i]));
        named_bar(1 + wgi, 128);
#pragma unroll
        for (int i = 0; i < 3; i++) stsm_x4(za + i * 256, z8[4 * i], z8[4 * i + 1], z8[4 * i + 2], z8[4 * i + 3]);
#pragma unroll
        for (int ob = 0; ob < 2; ob++) stsm_x4(zc + ob * 256, z16[4 * ob], z16[4 * ob + 1], z16[4 * ob + 2], z16[4 * ob + 3]);
    }
    {
#define RD_(o) _Pragma("unroll") for (int i = o; i < 32; i++) { float y_; asm volatile("mov.b32 %0, %1;" : "=f"(y_) : "f"(D[i])); D[i] = y_; }
        ld(0); ld(1);
        go(0);
        ld(2);
        go(1);
        k2 = lds32(cb + XO_K1024);
#pragma unroll
        for (int u = 2; u < 14; u++) {
            WG_WAIT(1);
            if (u < 13) ld(u + 1);
            if (u == 4 || u == 7 || u == 10) { WG_WAIT(0); RD_(u == 4 ? 8 : u == 7 ? 16 : 4); }
            go(u);
            if (u == 3 && wgi == 4) { const uint32_t c0 = clock(); for (int k = 0; k < 1024 && (uint32_t)clock() - c0 < SD; k++) { } }
            if (u == 3) { PROXY_FENCE(); named_bar(1 + wgi, 128); }
        }
    }
    {
        const int tid = fresh_tid(), lane = tid & 31, lr = lane & 7, lm = lane >> 3;
        uint32_t u[2][4];
        const uint32_t ua = cb + UB + w * UP + lm * 256 + lr * 16;
        ldsm_x4_t(u[0], ua); ldsm_x4_t(u[1], ua + 128);
        const uint32_t dk2 = __byte_perm(lds32(cb + XO_DSK), 0, (rank & 1) ? 0x3232 : 0x1010);
#pragma unroll
        for (int i = 0; i < 8; i++) u[i >> 2][i & 3] = mul2(u[i >> 2][i & 3], dk2);
        mbar_wait(MB(MB_C2), 0);
        const uint32_t ga2 = M.ga[wgi];
        const int src = (lane & 28) | ((lane + 3) & 3);
        WG_WAIT(0);
        float s[8];
#pragma unroll
        for (int j = 0; j < 8; j++) s[j] = __shfl_sync(0xffffffffu, (lane & 3) < 3 ? D[4 * j + 3] : j ? D[4 * j - 1] : 0.f, src);
#pragma unroll
        for (int h = 0; h < 2; h++) {
            const uint32_t rb = mapa(sb, w + 4 * h);
#pragma unroll
            for (int j = 0; j < 4; j++) u[h][j] = mul2(ga2, add2(pack2(D[8 * j + 4 * h] + s[2 * j + h], D[8 * j + 4 * h + 1] + D[8 * j + 4 * h + 2]), u[h][j]));
            sta4(rb + OFF_V + (8 * wgi + rank) * VP + lane * 16, make_uint4(u[h][0], u[h][1], u[h][2], u[h][3]), rb + (MB(wgi < 2 ? MB_V : MB_V1 - 1 + (wgi >> 1)) - sb));
        }
    }
}
#define M2W 4
#define WS 0x3210
#define WMS(p) if (warp == 7) { if (p == 0) CL_WAIT(); if (lane == 0) { _Pragma("unroll") for (int i = 2; i < 6; i++) if (((WS >> (4 * (i - 2))) & 15) == p) tma2d(sb + (i == 5 ? OFF_WM0 + 11520 : OFF_WM2 + (i - 2) * 5760), &tm_wm, i * D_ + 40 * cl, 72 * rk, MB(MB_WM2)); } __syncwarp(); }
#define PQT 10
#define PQD 100
#define L2P 2
#define L2M 2
#define PDE 100
#define WMD 400
#define CWP 200
#define CWD 3000
#define ROW(key) (((~(key) << 2) & 0xE0u) | ((~(key) >> 6) & 24u) | ((~(key) >> 11) & 6u) | ((~(key) >> 8) & 1u))
#define RKT (((rk & 4) << 6) | ((rk & 3) << 3))
#define MINE(key) ((~(key) & 0x8C0u) == (uint32_t)(RKT << 3))
#define CE(a, b) { const uint32_t hi_ = max(a, b); b = min(a, b); a = hi_; }
#define POP(k, m) if (k.x == m) { k.x = k.y; k.y = k.z; k.z = k.w; k.w = 0u; }
#define CGT(c, a, b, n) asm volatile("{\n.reg .pred p;\nsetp.gt.u32 p, %1, %2;\n@p add.u32 %0, %0, " #n ";\n}" : "+r"(c) : "r"(a), "r"(b))
#define CL_ARRIVE() asm volatile("barrier.cluster.arrive.relaxed.aligned;" ::: "memory")
#define CL_WAIT() asm volatile("barrier.cluster.wait.aligned;" ::: "memory")
__global__ void __cluster_dims__(8, 1, 1) __launch_bounds__(NTHR, 1)
clus_kernel(const bf16* __restrict__ x, const bf16* __restrict__ logAr, const bf16* __restrict__ Aim, const bf16* __restrict__ Cr, const bf16* __restrict__ Ci,
            const bf16* __restrict__ logdt, const bf16* __restrict__ c_in, Scratch* __restrict__ S, const bf16* __restrict__ Dskip,
            const bf16* __restrict__ w_r, const bf16* __restrict__ w_mod, bf16* __restrict__ out,
            const __grid_constant__ CUtensorMap tm_wm, const __grid_constant__ CUtensorMap tm_wg,
            const __grid_constant__ CUtensorMap tm_wu, const __grid_constant__ CUtensorMap tm_wd, const __grid_constant__ CUtensorMap tm_out) {
    extern __shared__ __align__(1024) unsigned char sm[];
    Misc& M = *(Misc*)(sm + OFF_MISC);
    const uint32_t sb = (uint32_t)__cvta_generic_to_shared(sm);
    const int tid = threadIdx.x < 128 ? threadIdx.x + 640 : threadIdx.x - 128, warp = __shfl_sync(0xffffffffu, tid >> 5, 0), lane = tid & 31;
    const int g = lane >> 2, t = lane & 3, lr = lane & 7, lm = lane >> 3;
    const int wgi = warp >> 2, w = warp & 3;
    const int b = blockIdx.x, cl = b >> 3, rk = b & 7;
    auto mod_ld = [&](uint32_t (*a)[4], uint32_t s0, uint32_t s1, int i) {
        const uint32_t wa = sb + ((lm & 1) ? s1 : s0) + (lr + 8 * (lm >> 1)) * 80 + i * 16;
#pragma unroll
        for (int ks = 0; ks < 4; ks++) ldsm_x4_t(a[ks], wa + ks * 1280);
        ldsm_x2_t(a[4], wa + 5120);
    };
    auto mod_mma2 = [&](float* d, float* e, uint32_t (*a)[4], uint32_t (*c)[4], const uint32_t* bs) {
        mma_k8(d, a[4][0], a[4][1], bs[8]); mma_k8(e, c[4][0], c[4][1], bs[8]);
#pragma unroll
        for (int ks = 0; ks < 4; ks++) {
            mma_bf16(d, a[ks][0], a[ks][1], a[ks][2], a[ks][3], bs[2 * ks], bs[2 * ks + 1]);
            mma_bf16(e, c[ks][0], c[ks][1], c[ks][2], c[ks][3], bs[2 * ks], bs[2 * ks + 1]);
        }
    };
    auto mod_st = [&](const float* d, uint32_t dst, int mb) {
#pragma unroll
        for (int h = 0; h < 2; h++) {
            const uint32_t rb = mapa(sb, t + 4 * h);
            sta2(rb + dst + g * 8, __float_as_uint(d[0]), __float_as_uint(d[2]), rb + (MB(mb) - sb));
        }
    };
    auto gsum = [&](uint32_t a, int pitch) {
        float4 s = make_float4(0.f, 0.f, 0.f, 0.f);
#pragma unroll
        for (int i = 0; i < 8; i++) { const float4 q = *(const float4*)(sm + a + i * pitch); s.x += q.x; s.y += q.y; s.z += q.z; s.w += q.w; }
        return make_uint2(pack2(s.x, s.z), pack2(s.y, s.w));
    };
    auto one_plus = [&](uint32_t v) { return pack2(1.0f + lo2f(v), 1.0f + hi2f(v)); };
    auto mkc1 = [&]() {
        const int lane = fresh_tid() & 31;
        const uint2 v = gsum(OFF_MG1 + 16 * min(lane, 19), 320);
        const uint32_t c1 = one_plus(v.x);
        if (lane < 20) *(uint4*)(sm + OFF_C1 + 16 * lane) = make_uint4(__byte_perm(c1, 0, 0x1010), __byte_perm(v.y, 0, 0x1010), __byte_perm(c1, 0, 0x3232), __byte_perm(v.y, 0, 0x3232));
        __syncwarp();
        named_arrive(10, 160);
    };
    if (wgi == 5) {
        CL_ARRIVE();
        const uint32_t c_a = ld_nc((const uint32_t*)c_in + 36 * rk + lane), c_b = ld_nc((const uint32_t*)c_in + 36 * rk + 32 + t);
        {
            pace(WMD);
            const char* wp = (const char*)(w_mod + (72 * rk + 18 * w) * (6 * D_) + 40 * cl);
#pragma unroll
            for (int i = 0; i < 3; i++) {
                const uint32_t c = lane + 32 * i, row = (c * 205) >> 10;
                const char* p = wp + (row * (12 * D_ - 80) + 16 * c);
                if (c < 90) {
                    asm volatile("cp.async.cg.shared.global [%0], [%1], 16;" ::"r"(sb + OFF_WM0 + 1440 * w + 16 * c), "l"(p) : "memory");
                    asm volatile("cp.async.cg.shared.global [%0], [%1], 16;" ::"r"(sb + OFF_WM0 + 5760 + 1440 * w + 16 * c), "l"(p + 2 * D_) : "memory");
                }
            }
            if (w == 3 && lane < 20)
                asm volatile("cp.async.ca.shared.global [%0], [%1], 4, %2;" ::"r"(sb + OFF_MISC + (uint32_t)offsetof(Misc, c2) + 12 + 16 * lane), "l"((const uint32_t*)w_r + min(20 * cl + lane, D_ / 2 - 1)),
                             "r"(20 * cl + lane < D_ / 2 ? 4 : 0) : "memory");
            asm volatile("cp.async.commit_group;" ::: "memory");
        }
        {
            uint32_t bs[9], a[5][4], c[5][4];
            float d[4] = {0.f, 0.f, 0.f, 0.f}, e[4] = {0.f, 0.f, 0.f, 0.f};
            const uint32_t sc = pack2(silu(lo2f(c_a)), silu(hi2f(c_a)));
            bs[8] = pack2(silu(lo2f(c_b)), silu(hi2f(c_b)));
            if (w == 2) { sts32(sb + OFF_SC + 4 * lane, sc); sts32(sb + OFF_SC + 128 + 4 * t, bs[8]); }
#pragma unroll
            for (int ks = 0; ks < 8; ks++) bs[ks] = __shfl_sync(0xffffffffu, sc, 4 * ks + t);
            CL_WAIT();
            asm volatile("cp.async.wait_group 0;" ::: "memory");
            named_bar(10, 128);
            mod_ld(a, OFF_WM0 + 5760, OFF_WM0, w);
            mod_ld(c, OFF_WM0 + 5760, OFF_WM0, 4);
            mod_mma2(d, e, a, c, bs);
            mod_st(d, OFF_MG1 + rk * 320 + 64 * w, MB_MG1);
            if (w == 1) mod_st(e, OFF_MG1 + rk * 320 + 256, MB_MG1);
        }
        {
            const int n0 = 8 * w + 2 * (rk & 1), n1 = 8 * w + ((n0 + 4 + t) & 7);
            const float4* ap = &S->acc1[256 * rk + 8 * (n0 + t) + g];
            const float4* aq = &S->acc1[256 * rk + 8 * n1 + g];
            named_bar(9, 640);
            float4 pa = ld_rlx4f(ap), pb = ld_rlx4f(aq);
            uint32_t xq[2][5][4];
            uint2 cc[5];
            const uint32_t xa = sb + OFF_X + XI(2 * lm + (lr & 1)) + XN(n0 + (lr >> 1)), xb = sb + OFF_X + XI(2 * lm + (lr & 1)) + XN(8 * w + ((n0 + 4 + (lr >> 1)) & 7));
            const uint32_t ua = mapa(sb, g) + OFF_CH;
#pragma unroll
            for (int j = 0; j < 5; j++) ldsm_x4_t(xq[0][j], xa + 16 * j);
#pragma unroll 1
            for (int it = 0; it < SPIN_MAX && (pa.w != (float)NCL || pb.w != (float)NCL); it++) {
                pa = ld_rlx4f(ap); pb = ld_rlx4f(aq);
            }
            __syncwarp();
            float m0, r0, m1, r1;
            ln_stats(pa.x, pa.y, m0, r0);
            ln_stats(pb.x, pb.y, m1, r1);
            const uint32_t rh = pack2(r0, r1), rl = pack2(r0 - lo2f(rh), r1 - hi2f(rh));
            const uint32_t stage = sb + OFF_STG + w * 512;
            stsm_x4_t(stage + lane * 16, pack2(m0, m1), rh, rl, rl);
            __syncwarp();
            named_bar(10, 160);
            uint4 st[2][3];
#pragma unroll
            for (int q = 0; q < 2; q++)
#pragma unroll
                for (int i = 0; i < 3; i++) st[q][i] = lds128(stage + 128 * i + (2 * t + q) * 16);
#pragma unroll
            for (int j = 0; j < 5; j++) cc[j] = *(const uint2*)(sm + OFF_C1 + 64 * j + 8 * g);
            ldsm_x4_t(xq[1][0], xb);
            const uint32_t ub = ua + (rk & 3) * UP + UB + (8 * w + 8 * (rk >> 2)) * 16, u0 = ub + (n0 + t) * 16, u1 = ub + n1 * 16;
#pragma unroll
            for (int j = 0; j < 5; j++) {
                if (j >= 2 && cl == 14) break;
                if (j < 4) ldsm_x4_t(xq[1][j + 1], xb + 16 * (j + 1));
#pragma unroll
                for (int q = 0; q < 2; q++) {
                    const uint4 sm_ = st[q][0], sh = st[q][1], sl = st[q][2];
                    const uint32_t v0 = add2(mul2(norm2(xq[q][j][0], sm_.x, sh.x, sl.x), cc[j].x), cc[j].y), v1 = add2(mul2(norm2(xq[q][j][1], sm_.y, sh.y, sl.y), cc[j].x), cc[j].y);
                    const uint32_t v2 = add2(mul2(norm2(xq[q][j][2], sm_.z, sh.z, sl.z), cc[j].x), cc[j].y), v3 = add2(mul2(norm2(xq[q][j][3], sm_.w, sh.w, sl.w), cc[j].x), cc[j].y);
                    asm volatile("{\n.reg .pred p;\nsetp.ne.u32 p, %6, %7;\n"
                                 "@p st.async.weak.shared::cluster.mbarrier::complete_tx::bytes.v4.b32 [%0], {%1,%2,%3,%4}, [%5];\n"
                                 "@!p st.shared.v4.b32 [%0], {%1,%2,%3,%4};\n}"
                                 ::"r"((q ? u1 : u0) + j * CHS), "r"(v0), "r"(v1), "r"(v2), "r"(v3), "r"(ua + j * CHS + XO_MBU), "r"(g), "r"(rk) : "memory");
                }
                __syncwarp();
                if (lane == 0) mbar_arrive(sb + OFF_CH + XO_MBU + j * CHS);
            }
        }
        asm volatile("setmaxnreg.dec.sync.aligned.u32 40;");
        {
        int cl;
        asm volatile("mov.u32 %0, %clusterid.x;" : "=r"(cl));
        const int w = __shfl_sync(0xffffffffu, (fresh_tid() >> 5) & 3, 0);
        if (w) named_arrive(11, 128); else named_bar(11, 128);
        if (w == 0) {
            const int lane = fresh_tid() & 31;
            mbar_wait(MB(MB_KD), 0);
            PROXY_FENCE();
            if (lane == 0) {
                tma2d(sb + OFF_WU + 15360, &tm_wu, 40 * b, 192, MB(MB_WU));
                tma2d_pf(&tm_wu, 40 * b, 384);
                mbar_wait(MB(MB_C2), 0);
                PROXY_FENCE();
                tma2d(sb + OFF_WU + 2 * 15360, &tm_wu, 40 * b, 384, MB(MB_WU));
#pragma unroll 1
                for (int i = 0; i < 9; i++) { pace(PDE); tma2d_pf(&tm_wd, 64 * i, 40 * b); }
                mbar_wait(MB(MB_WU), 0);
            }
            __syncwarp();
        } else if (w == 2) {
            if ((fresh_tid() & 31) == 0) {
                float4 v;
                int it = 0;
                pace(CWD);
                for (;;) { v = ld_rlx4f(&S->acc1[L_]); if (++it >= SPIN_MAX || (v.z == (float)G_ && v.w == (float)NCL)) break; pace(CWP); }
                M.cws[0] = v.x; M.cws[1] = v.y;
                mbar_arrive(MB(MB_CW));
            }
            __syncwarp();
            mbar_wait(MB(MB_C2), 0);
            const int lane = fresh_tid() & 31;
            if (rk == 0 && lane < (cl < 14 ? 5 : 2)) st_rlx4(&S->h2c[136 * 72 + 5 * cl + lane], make_uint4(~M.c2[4 * lane].z, ~M.c2[4 * lane + 1].z, ~M.c2[4 * lane + 2].z, ~M.c2[4 * lane + 3].z));
        } else if (w == 3) {
            const int lane = fresh_tid() & 31, l20 = min(lane, 19);
            mbar_wait(MB(MB_MG2), 0);
            const uint2 v = gsum(OFF_MG2 + 16 * l20, 640), u = gsum(OFF_MG2 + 320 + 16 * l20, 640);
            const uint32_t wr = lane < 20 ? M.c2[lane].w : 0u, cb1 = one_plus(v.x), cw = mul2(cb1, wr);
            if (lane < 20) {
                M.c2[lane] = make_uint4(cb1, v.y, u.x, cw);
                M.wr[lane] = wr;
                unsigned e;
                asm volatile("mov.u32 %0, %cluster_ctarank;" : "=r"(e));
                if ((lane & 3) == (e >> 1)) M.ga[lane >> 2] = __byte_perm(u.y, 0, (e & 1) ? 0x3232 : 0x1010);
            }
            __syncwarp();
            if (lane == 0) mbar_arrive(MB(MB_C2));
            if (rk == 0) {
                float a = lo2f(cw) + hi2f(cw), s = lo2f(v.y) * lo2f(wr) + hi2f(v.y) * hi2f(wr);
#pragma unroll
                for (int o = 16; o; o >>= 1) { a += __shfl_xor_sync(0xffffffffu, a, o); s += __shfl_xor_sync(0xffffffffu, s, o); }
                if (lane == 0) red4(&S->acc1[L_], a, s, 0.f);
            }
        }
        {
        const int lane = fresh_tid() & 31, t = lane & 3, lr = lane & 7, lm = lane >> 3;
        __syncwarp();
        if (w >= 2) {
            uint32_t aw[5];
#pragma unroll
            for (int j = 0; j < 5; j++) aw[j] = M.wr[4 * j + t];
            const int lst = 16 * (lm & 1) + 2 * rk + (w & 1);
            const uint32_t rb = mapa(sb, lr);
            float4* p = &S->rs[8 * lst];
            float4* pr = &S->rs[8 * (16 * (t >> 1) + 2 * rk + (w & 1)) + (t & 1)];
            named_bar(6, 576);
            uint4 k = *(const uint4*)&M.key[128 * (w & 1) + 4 * lane];
            CE(k.x, k.y); CE(k.z, k.w); CE(k.x, k.z); CE(k.y, k.w); CE(k.y, k.z);
            uint32_t m[4], mine = 0;
#pragma unroll
            for (int rnd = 0; rnd < 8; rnd++) {
                const uint32_t v = __reduce_max_sync(0xffffffffu, k.x);
                POP(k, v);
                if (rnd < 4 || (lm & 1)) m[rnd & 3] = v;
                if (rnd == lr) mine = v;
            }
            const uint32_t ra = sb + OFF_H2T + ROW(mine) * 80;
            uint32_t bq[6];
            float rr[4] = {0.f, 0.f, 0.f, 0.f};
            ldsm_x4(bq, ra + 16 * lm); ldsm_x2(bq + 4, ra + 64);
            if (lane < 16) sta4(rb + OFF_MISC + (uint32_t)offsetof(Misc, cand) + lst * 16, make_uint4(m[0], m[1], m[2], m[3]), rb + (MB(MB_KEY2) - sb));
            mma_bf16(rr, aw[0], aw[0], aw[1], aw[1], bq[0], bq[1]); mma_bf16(rr, aw[2], aw[2], aw[3], aw[3], bq[2], bq[3]); mma_k8(rr, aw[4], aw[4], bq[4]);
            if (lane < 4) red4(pr, rr[0], 0.f, rr[1]);
            float4 e0 = ld_rlx4f(p), e1 = ld_rlx4f(p + 1);
#pragma unroll 1
            for (int it = 0; it < SPIN_MAX && (e0.w != (float)NCL || e1.w != (float)NCL); it++) {
                e0 = ld_rlx4f(p); e1 = ld_rlx4f(p + 1);
            }
            const uint32_t r0 = pack2(e0.x, e0.z), r1 = pack2(e1.x, e1.z);
            const uint32_t o0 = r0 ^ (sign2(r0) | 0x80008000u), o1 = r1 ^ (sign2(r1) | 0x80008000u);
            if (lane < 16) sta4(rb + OFF_EK + lst * VP, make_uint4((o0 << 16) | (m[0] & 0x3FFFu), (o0 & 0xFFFF0000u) | (m[1] & 0x3FFFu), (o1 << 16) | (m[2] & 0x3FFFu), (o1 & 0xFFFF0000u) | (m[3] & 0x3FFFu)),
                                rb + (MB(MB_EK) - sb));
        } else if (w == 0) {
            named_bar(8, 64);
            if (lane == 0) {
                PROXY_FENCE();
                tma5d_st(&tm_out, 40 * cl, RKT, sb + OFF_OUT);
                asm volatile("cp.async.bulk.commit_group;" ::: "memory");
                asm volatile("cp.async.bulk.wait_group 0;" ::: "memory");
                asm volatile("fence.acq_rel.gpu;" ::: "memory");
                mbar_arrive(MB(MB_OUT));
            }
        } else {
            uint32_t sl = 0;
            mbar_wait(MB(MB_KEY2), 0);
            uint4 k = *(const uint4*)&M.cand[4 * lane];
            named_bar(14, 64);
#pragma unroll
            for (int s = 0; s < 8; s++) {
                const uint32_t v = M.sel[s] & ~1u;
                if (k.x == v) sl |= 8 + s;
                if (k.y == v) sl |= (8 + s) << 8;
                if (k.z == v) sl |= (8 + s) << 16;
                if (k.w == v) sl |= (8 + s) << 24;
            }
            const uint32_t found = __reduce_add_sync(0xffffffffu, __popc(sl & 0x08080808u));
            mbar_wait(MB(MB_EK), 0);
            if (b == 0 && lane == 0) st_rlx4(&S->acc1[L_], make_uint4(0, 0, 0, 0));
            if (lane < 16 || cl == 14) st_rlx4(&S->acc2[256 * rk + 16 * cl + lane], make_uint4(0, 0, 0, 0));
            k = lds128(sb + OFF_EK + lane * VP);
            const bool s0 = sl & 8u, s1 = sl & 0x800u, s2 = sl & 0x80000u, s3 = sl & 0x8000000u;
            if (s0) M.fin[sl & 7u] = k.x;
            if (s1) M.fin[(sl >> 8) & 7u] = k.y;
            if (s2) M.fin[(sl >> 16) & 7u] = k.z;
            if (s3) M.fin[(sl >> 24) & 7u] = k.w;
            const uint32_t lo = min(min(s0 ? k.x : ~0u, s1 ? k.y : ~0u), min(s2 ? k.z : ~0u, s3 ? k.w : ~0u));
            const uint32_t hi = max(max(s0 ? 0u : k.x, s1 ? 0u : k.y), max(s2 ? 0u : k.z, s3 ? 0u : k.w));
            const uint32_t hi2 = __reduce_max_sync(0xffffffffu, hi), lo2 = __reduce_min_sync(0xffffffffu, lo);
            bool redo = found != 8u;
            if (hi2 > lo2) {
                const uint32_t h = hi2 | 0xFFFFu, l = lo2 & 0xFFFF0000u;
                const uint32_t n = __reduce_add_sync(0xffffffffu, ((s0 ? k.x <= h : (k.x >= l) << 8) + (s1 ? k.y <= h : (k.y >= l) << 8)) + ((s2 ? k.z <= h : (k.z >= l) << 8) + (s3 ? k.w <= h : (k.w >= l) << 8)));
                redo = redo || (h >> 16) - (l >> 16) > 1u || ((n & 255u) > 1u && n >= 512u) || (n & 255u) + (n >> 8) > 9u;
            }
            if (redo) {
                CE(k.x, k.y); CE(k.z, k.w); CE(k.x, k.z); CE(k.y, k.w); CE(k.y, k.z);
                __syncwarp();
#pragma unroll 1
                for (int rnd = 0; rnd < 8; rnd++) {
                    const uint32_t m8 = __reduce_max_sync(0xffffffffu, k.x);
                    POP(k, m8);
                    if (lane == 0) M.fin[rnd] = m8;
                }
            }
            if (lane == 0) M.fin[8] = redo;
            __syncwarp();
            if (lane == 0) mbar_arrive(MB(MB_FIN));
        }
        }
        }
    } else {
    if (warp != 19) CL_ARRIVE();
    const int chn = 40 * cl + 8 * wgi + rk;
    const bool has_ch = chn < D_;
    const uint32_t cb = sb + OFF_CH + wgi * CHS;
    auto ldx = [&]() {
    if (warp < 16) {
        const char* xp = (const char*)(x + (512 * (warp >> 2) + 64 * (warp & 3) + RKT) * D_ + 40 * cl);
        const uint32_t dst = sb + OFF_X + XN(2 * warp) + XI(lm) + 16 * lr;
        xp += lm * (2 * D_) + 16 * lr;
#pragma unroll
        for (int i = 0; i < 4; i++)
            if (lr < 5) asm volatile("cp.async.cg.shared.global [%0], [%1], 16, %2;" ::"r"(dst + XI(4 * (i & 1)) + 80 * (i >> 1)), "l"(xp + ((i & 1) * 4 + (i >> 1) * 32) * (2 * D_)),
                                     "r"((cl < 14 || lr < 2) ? 16 : 0) : "memory");
    }
    };
    unsigned short r_ldt = 0, r_lar = 0, r_aim = 0;
    uint2 r_cr, r_ci;
    {
        const int n = min(chn, D_ - 1) * N_ + 4 * lane;
        r_ldt = ld_nc16((const unsigned short*)logdt + min(chn, D_ - 1));
        r_lar = ld_nc16((const unsigned short*)logAr + n + w);
        r_aim = ld_nc16((const unsigned short*)Aim + n + w);
        r_cr = ld_nc2(Cr + n);
        r_ci = ld_nc2(Ci + n);
    }
    if (warp == 19) {
        if (lane == 0) asm volatile("prefetch.tensormap [%0];" ::"l"(&tm_wm) : "memory");
        const uint32_t lo = 90u | (10u << 8) | (20u << 16) | (2u << 24), hi = 32u | ((rk < 4 ? 40u : 32u) << 8) | (180u << 16) | (180u << 24);
        const uint32_t tx = lane < 8 ? (((lane & 4 ? hi : lo) >> (8 * (lane & 3))) & 255u) : lane == 8 ? 180u : lane < 11 ? 2u : lane == 11 ? (hi >> 8) & 255u : lane >= MB_C2 ? 14u : cl == 14 ? 0u : lane == 12 ? 32u : 16u;
        if (lane == 0) {
#pragma unroll
            for (int i = 0; i < MB_N; i++) mbar_init(MB(i), i == MB_KD || i == MB_CD ? 20 : 1);
#pragma unroll
            for (int i = 0; i < 5; i++) mbar_init(sb + OFF_CH + XO_MBU + i * CHS, 5);
        }
        __syncwarp();
        if (lane < MB_C2 + 5) mbar_expect(lane < MB_C2 ? MB(lane) : sb + OFF_CH + XO_MBU + (lane - MB_C2) * CHS, tx << 8);
        asm volatile("fence.mbarrier_init.release.cluster;" ::: "memory");
        __syncwarp();
        CL_ARRIVE();
    }
    ldx();
    uint32_t rz[4] = {0u, 0u, 0u, 0u};
    auto rst2 = [&]() {
        if (fresh_tid() == 576) asm volatile("red.relaxed.gpu.global.add.f32 [%0], %1;" ::"l"(&S->acc1[L_].z), "f"(__uint_as_float(0x3F800000u | rz[0] | rz[1] | rz[2] | rz[3])) : "memory");
        __syncwarp();
    };
    auto rst = [&]() {
        if (warp == 18) {
            const int lane = fresh_tid() & 31;
            uint4* rp = S->h2c + NRS * b + lane;
#pragma unroll
            for (int i = 0; i < 4; i++) if (i < 3 || lane < NRS - 96) st_rlx4(rp + 32 * i, make_uint4(0, 0, 0, 0));
#pragma unroll
            for (int i = 0; i < 4; i++) asm volatile("atom.relaxed.gpu.global.or.b32 %0, [%1], 0;" : "=r"(rz[i]) : "l"((unsigned int*)(rp + (i < 3 || lane < NRS - 96 ? 32 * i : 0)) + (i & 1)) : "memory");
        }
    };
    if ((tid & 127) == 32) asm volatile("cp.async.ca.shared.global [%0], [%1], 4;" ::"r"(cb + XO_DSK), "l"((const uint32_t*)Dskip + (min(chn, D_ - 1) >> 1)) : "memory");
    asm volatile("cp.async.commit_group;" ::: "memory");
    auto mod2 = [&]() {
        if (wgi == M2W) {
            const int lane = fresh_tid() & 31, t = lane & 3;
            const uint32_t wa = sb + ((lane & 7) + ((lane >> 1) & 8)) * 80, p0 = wa + ((lane & 8) ? OFF_WM2 + 5760 : OFF_WM2 + 11520), p1 = wa + ((lane & 8) ? OFF_WM2 : OFF_WM0 + 11520);
            auto ld = [&](uint32_t (*a)[4], uint32_t p) {
#pragma unroll
                for (int ks = 0; ks < 4; ks++) ldsm_x4_t(a[ks], p + ks * 1280);
                ldsm_x2_t(a[4], p + 5120);
            };
            const uint32_t rb = mapa(sb, t), rd = mapa(sb, 4) - mapa(sb, 0), dst = rb + OFF_MG2 + rk * 640 + (lane >> 2) * 8;
            auto st = [&](const float* d, uint32_t o) {
                sta2(dst + o, __float_as_uint(d[0]), __float_as_uint(d[2]), rb + (MB(MB_MG2) - sb));
                sta2(dst + rd + o, __float_as_uint(d[0]), __float_as_uint(d[2]), rb + rd + (MB(MB_MG2) - sb));
            };
            uint32_t bs[9], a[5][4], c[5][4];
            float d[4] = {0.f, 0.f, 0.f, 0.f}, e[4] = {0.f, 0.f, 0.f, 0.f};
            mbar_wait(MB(MB_MG1), 0);
#pragma unroll
            for (int ks = 0; ks < 9; ks++) bs[ks] = lds32(sb + OFF_SC + 16 * ks + 4 * t);
            mbar_wait(MB(MB_WM2), 0);
            __syncwarp();
            ld(a, p0 + 16 * w);
            ld(c, p1 + 16 * w);
            {
                float h[6][4];
#pragma unroll
                for (int i = 0; i < 24; i++) h[i >> 2][i & 3] = 0.f;
                mma_k8(h[0], a[4][0], a[4][1], bs[8]); mma_k8(h[3], c[4][0], c[4][1], bs[8]);
#pragma unroll
                for (int ks = 0; ks < 4; ks++) {
                    mma_bf16(h[(ks + 1) % 3], a[ks][0], a[ks][1], a[ks][2], a[ks][3], bs[2 * ks], bs[2 * ks + 1]);
                    mma_bf16(h[3 + (ks + 1) % 3], c[ks][0], c[ks][1], c[ks][2], c[ks][3], bs[2 * ks], bs[2 * ks + 1]);
                }
                d[0] = h[0][0] + h[1][0] + h[2][0]; d[2] = h[0][2] + h[1][2] + h[2][2];
                e[0] = h[3][0] + h[4][0] + h[5][0]; e[2] = h[3][2] + h[4][2] + h[5][2];
                ld(a, ((w & 1) ? p1 : p0) + 64);
                st(d, 64 * w);
                st(e, 320 + 64 * w);
#pragma unroll
                for (int i = 0; i < 20; i++) h[i >> 2][i & 3] = 0.f;
                mma_k8(h[4], a[4][0], a[4][1], bs[8]);
#pragma unroll
                for (int ks = 0; ks < 4; ks++) mma_bf16(h[ks], a[ks][0], a[ks][1], a[ks][2], a[ks][3], bs[2 * ks], bs[2 * ks + 1]);
                d[0] = (h[0][0] + h[1][0]) + (h[2][0] + h[3][0]) + h[4][0]; d[2] = (h[0][2] + h[1][2]) + (h[2][2] + h[3][2]) + h[4][2];
            }
            if (w < 2) st(d, 320 * w + 256);
            __syncwarp();
        }
    };
    auto ln1 = [&]() {
        if (warp < 16) {
            uint32_t a[10];
            const uint32_t xa = sb + OFF_X + XN(2 * warp) + (lm & 1) * 80 + XI(lr) + (lm >> 1) * 16;
            asm volatile("cp.async.wait_group 0;" ::: "memory");
            __syncwarp();
            ldsm_x4(a, xa); ldsm_x4(a + 4, xa + 32); ldsm_x2(a + 8, xa + 64);
            named_arrive(9, 640);
            float c1[4] = {0.f, 0.f, 0.f, 0.f}, c2[4] = {0.f, 0.f, 0.f, 0.f}, c3[4] = {0.f, 0.f, 0.f, 0.f};
#pragma unroll
            for (int j = 0; j < 2; j++) {
                mma_bf16(c1, a[4 * j], a[4 * j + 1], a[4 * j + 2], a[4 * j + 3], 0x3F803F80u, 0x3F803F80u);
                mma_bf16(c2, a[4 * j], a[4 * j + 1], a[4 * j + 2], a[4 * j + 3], a[4 * j], a[4 * j + 2]);
                mma_bf16(c3, a[4 * j], a[4 * j + 1], a[4 * j + 2], a[4 * j + 3], a[4 * j + 1], a[4 * j + 3]);
            }
            mma_k8(c1, a[8], a[9], 0x3F803F80u); mma_k8(c2, a[8], a[9], a[8]); mma_k8(c3, a[8], a[9], a[9]);
            float4* p = &S->acc1[256 * rk + 16 * warp + g];
            red4p(t == (g >> 1), p, c1[0], (g & 1) ? c2[1] : c2[0], 0.f);
            red4p(t == (g >> 1), p + 8, c1[2], (g & 1) ? c3[3] : c3[2], 0.f);
        }
    };
    {
        unsigned char* cp = sm + OFF_CH + wgi * CHS + lane * 16;
        const uint4 z = make_uint4(0, 0, 0, 0);
        *(uint4*)(cp + w * UP + XO_TF) = z;
        *(uint4*)(cp + w * UP + (lane < 16 ? XO_U8 - 256 : XO_U16 - 512)) = z;
        if (lane < 16) *(uint4*)(cp + (lane < 8 ? w * UP + UB - 128 : XO_TD + (4 * w + (lane < 12 ? -8 : 145 - 12)) * 16)) = z;
    }
    if (tid < 200) ((uint32_t*)M.box)[tid] = box_tap(tid);
    const uint32_t scr = sb + warp * KSCR, ws = scr + lane * 4;
    uint32_t fixa = 0, fixv = 0;
    {
        uint32_t zr;
        asm volatile("ld.volatile.shared.u32 %0, [%1];" : "=r"(zr) : "r"(cb + XO_TF + w * UP + lane * 16) : "memory");
        const float p_ldt = __uint_as_float(r_ldt * 65536u + zr), p_lar = __uint_as_float(r_lar * 65536u + zr), p_aim = __uint_as_float(r_aim * 65536u + zr);
        const float p_cr = __uint_as_float((uint32_t)((((uint64_t)r_cr.y << 32) | r_cr.x) >> (16 * w)) * 65536u + zr), p_ci = __uint_as_float((uint32_t)((((uint64_t)r_ci.y << 32) | r_ci.x) >> (16 * w)) * 65536u + zr);
        float acc[5][4];
        uint32_t afr[4][4], cz[4], cq[4], bb[2][8];
        const uint32_t ba = scr + lr * 144 + lm * 16;
        auto tld = [&](int i) {
            __syncwarp();
            ldsm_x4(bb[i & 1], ba + ((i + 2) % 3) * 1152);
            ldsm_x4(bb[i & 1] + 4, ba + ((i + 2) % 3) * 1152 + 64);
        };
        auto tmm = [&](int i) {
            float* c = acc[i];
            c[0] = c[1] = c[2] = c[3] = 0.f;
#pragma unroll
            for (int s = 0; s < 4; s++) mma_f16(c, afr[s], bb[i & 1][2 * s], bb[i & 1][2 * s + 1]);
        };
#define TA(i) if (i == 1) tmm(0); WMS(i); tld(i); tmm(i);
#define PH(z) packh((z).x, (z).y)
        const float dt = bfr(expf(p_ldt));
        const float al = -bfr(expf(p_lar)) * dt * 1.4426950408889634f;
        const float th = p_aim * dt;
        const float th_ = th * 0.15915494309189535f;
        const float tl_ = fmaf(th, 0.15915494309189535f, -th_) + th * 6.4206382e-9f;
        auto anchor = [&](float s) {
            float f = th_ * s;
            f -= rintf(f);
            f = fmaf(tl_, s, f) * 6.283185307179586f;
            const float e = fex2(al * s);
            return cplx{e * __cosf(f), e * __sinf(f)};
        };
        const uint32_t cm = amax2(amax2(r_cr.x, r_cr.y), amax2(r_ci.x, r_ci.y));
        const uint32_t ex = __reduce_max_sync(0xffffffffu, __float_as_uint(fmaxf(fabsf(lo2f(cm)), fabsf(__uint_as_float(cm))))) & 0x7F800000u;
        const float scl = __uint_as_float(0x7F000000u - ex), inv = (dt + dt) * __uint_as_float(ex);
        const cplx C = cplx{p_cr * scl, p_ci * scl};
        const cplx z1 = anchor(1.f), z16 = anchor(16.f), z256 = anchor(256.f);
        {
            const cplx z32 = csq(z16), z48 = cmul(z32, z16), z64 = csq(z32), z128 = csq(z64), z192 = cmul(z128, z64);
            const uint32_t y[3] = {packh(z16.x, z16.y), packh(z32.x, z32.y), packh(z48.x, z48.y)};
            const uint32_t yp[3] = {packh(-z16.y, z16.x), packh(-z32.y, z32.x), packh(-z48.y, z48.x)};
            const uint32_t xx[3] = {packh(z64.x, z64.y), packh(z128.x, z128.y), packh(z192.x, z192.y)};
            sts32(ws, 0x00003C00u);
#pragma unroll
            for (int j = 0; j < 3; j++) sts32(ws + (1 + j) * 144, y[j]);
#pragma unroll
            for (int i = 0; i < 3; i++) {
                sts32(ws + (4 + 4 * i) * 144, xx[i]);
#pragma unroll
                for (int j = 0; j < 3; j++) sts32(ws + (5 + 4 * i + j) * 144, hcm(xx[i], y[j], yp[j]));
            }
        }
        ln1();
        WMS(0);
        const cplx z2 = csq(z1);
        {
            const cplx z3 = cmul(z2, z1), z4 = csq(z2), z8 = csq(z4);
            const cplx c4 = cmul(C, z4), c8 = cmul(C, z8), c12 = cmul(c8, z4);
            cz[0] = packh(C.x, -C.y); cz[1] = packh(c4.x, -c4.y); cz[2] = packh(c8.x, -c8.y); cz[3] = packh(c12.x, -c12.y);
            cq[0] = packh(C.y, C.x); cq[1] = packh(c4.y, c4.x); cq[2] = packh(c8.y, c8.x); cq[3] = packh(c12.y, c12.x);
            __syncwarp();
#pragma unroll
            for (int s = 0; s < 4; s++) ldsm_x4(afr[s], scr + (lr + 8 * (lm & 1)) * 144 + (lm >> 1) * 16 + 32 * s);
            const uint32_t y[3] = {PH(z1), PH(z2), PH(z3)};
#pragma unroll
            for (int tt = 0; tt < 2; tt++) {
                const int rg = tt ? 0 : 2;
#pragma unroll
                for (int i = 0; i < 2; i++) {
                    sts32(ws + rg * 1152 + (4 * i) * 144, cz[2 * tt + i]);
#pragma unroll
                    for (int j = 0; j < 3; j++) sts32(ws + rg * 1152 + (4 * i + 1 + j) * 144, hcn(y[j], cz[2 * tt + i], cq[2 * tt + i]));
                }
                if (tt == 0) tld(0);
            }
            TA(1)
        }
        const cplx z258 = cmul(z256, z2), z512 = csq(z256), z768 = cmul(z512, z256);
        {
            const uint32_t a0 = PH(z256), a1 = PH(z258);
#pragma unroll
            for (int i = 0; i < 4; i++) { sts32(ws + 1152 + (2 * i) * 144, hcn(a0, cz[i], cq[i])); sts32(ws + 1152 + (2 * i + 1) * 144, hcn(a1, cz[i], cq[i])); }
            TA(2)
        }
        {
            const uint32_t a0 = PH(z512), a1 = PH(z768);
#pragma unroll
            for (int i = 0; i < 4; i++) { sts32(ws + 2304 + i * 144, hcn(a0, cz[i], cq[i])); sts32(ws + 2304 + (4 + i) * 144, hcn(a1, cz[i], cq[i])); }
            TA(3)
        }
        const cplx z1024 = csq(z512);
        {
            const cplx zk[4] = {z1024, cmul(z1024, z256), csq(z768), cmul(z1024, z768)};
#pragma unroll
            for (int h = 0; h < 4; h++) {
                const uint32_t a0 = PH(zk[h]);
                sts32(ws + (2 * h) * 144, hcn(a0, cz[0], cq[0]));
                sts32(ws + (2 * h + 1) * 144, hcn(a0, cz[2], cq[2]));
            }
            tld(4);
            tmm(4);
        }
        const cplx z2048 = csq(z1024);
        const uint32_t last = __reduce_add_sync(0xffffffffu, __float_as_uint(fmaf(-C.y, z2048.y, fmaf(C.x, z2048.x, 12.f))));
        __syncwarp();
#pragma unroll
        for (int i = 0; i < 5; i++) *(uint2*)(sm + (scr - sb) + i * 256 + ((lane * 8) ^ (i == 1 ? 64 : 0))) = make_uint2(packh(acc[i][1], acc[i][0]), packh(acc[i][3], acc[i][2]));
        if (lane == 0) sts32(cb + XO_KLAST + 4 * w, last);
        asm volatile("cp.async.wait_group 0;" ::: "memory");
        if (warp != 7) CL_WAIT();
        named_bar(1 + wgi, 128);
        if (warp == 16) { mbar_wait(MB(MB_MG1), 0); mkc1(); }
        const uint32_t td = cb + XO_TD + 64 * 4, tf = cb + XO_TF - 32 * 4;
        auto fsum = [&](int off, uint32_t& r0, uint32_t& r1) {
            const unsigned char* p = sm + wgi * (4 * KSCR) + off;
            const uint2 a = *(const uint2*)p, b2 = *(const uint2*)(p + KSCR), c = *(const uint2*)(p + 2 * KSCR), d = *(const uint2*)(p + 3 * KSCR);
            const float2 u = hsum4(a.x, b2.x, c.x, d.x), v = hsum4(a.y, b2.y, c.y, d.y);
            r0 = pack2(u.x * inv, u.y * inv);
            r1 = pack2(v.x * inv, v.y * inv);
        };
        const int role = (w + wgi) & 3;
        const int fo = role ? (role + 1) * 256 + lane * 8 : (((g & 1) * 320) ^ (lm * 32)) + t * 8;
        uint32_t r[2];
        fsum(fo, r[0], r[1]);
        if (role == 0) {
            uint32_t q[2], v[4];
            fsum(fo + 128, q[0], q[1]);
            const uint32_t c[4] = {r[0], q[0], r[1], q[1]};
#pragma unroll
            for (int i = 0; i < 4; i++) v[i] = __shfl_sync(0xffffffffu, c[i], (lane + 31) & 31);
            if (lane == 0) mbar_arrive(MB(MB_KD));
#pragma unroll
            for (int i = 0; i < 4; i++) *(uint2*)(sm + (td - sb) + lane * 8 + i * 256) = make_uint2(__byte_perm(c[i], lane ? v[i] : i ? v[i - 1] : 0u, 0x5432), c[i]);
            if (lane == 0) { fixa = td + 256 * 4 + 2; fixv = v[3]; }
        } else if (role == 1) {
            const uint32_t v0 = __shfl_sync(0xffffffffu, r[0], (lane + 1) & 31), v1 = __shfl_sync(0xffffffffu, r[1], (lane + 1) & 31);
            if (lane == 0) mbar_arrive(MB(MB_KD));
#pragma unroll
            for (int h = 0; h < 2; h++) {
                const uint32_t dd = __byte_perm(r[h], 0, 0x3232);
                *(uint4*)(sm + (td - sb) + 1024 + lane * 16 + h * 512) = make_uint4(dd, dd, r[h], __byte_perm((h || lane == 31) ? v1 : v0, r[h], 0x5432));
            }
        } else {
            __syncwarp();
            if (lane == 0) mbar_arrive(MB(MB_KD));
            const uint32_t p = role == 2 ? tf + (64 + 32 * (t >> 1) + 2 * g + (t & 1)) * 4 : tf + 2 * UP + (64 + 16 * t + g) * 4, p1 = p + (role == 2 ? 64 : 32);
            const uint32_t k0 = r[0] >> 16, k1 = r[1] >> 16;
            sts16(p + UP, r[0]); sts16(p + UP + 6, r[0]); sts16(p1 + UP, r[1]); sts16(p1 + UP + 6, r[1]);
            sts16(p1 - 4, k1); sts16(p1 + 2, k1);
            const uint32_t dd = __byte_perm(r[0], 0, 0x3232);
            if (lane) { sts16(p - 4, k0); sts16(p + 2, k0); }
            else if (role == 2) {
                *(uint4*)(sm + (td - sb) + 512 * 4) = make_uint4(dd, dd, dd, r[0] & 0xFFFF0000u);
                fixa = td + 511 * 4; fixv = k0;
            } else {
                const uint4 kl4 = *(const uint4*)(sm + (cb - sb) + XO_KLAST);
                const uint32_t kl = f2bits((float)(int)(kl4.x + kl4.y + kl4.z + kl4.w - 128u * 0x41400000u) * 9.5367431640625e-7f * inv);
                sts16(tf + 127 * 4, dd); sts16(tf + 128 * 4 + 2, dd); sts32(cb + XO_K1024, dd);
                sts16(tf + 2 * UP + 127 * 4, kl); sts16(tf + 2 * UP + 128 * 4 + 2, kl);
            }
        }
        __syncwarp();
        rst();
        mod2();
        if (wgi == 3) {
            mbar_wait(MB(MB_KD), 0);
            mbar_wait(MB(MB_WM2), 0);
            PROXY_FENCE();
            if (lane == 0) tma2d(sb + w * 15360, w < 3 ? &tm_wg : &tm_wu, 40 * b, w < 3 ? 192 * w : 0, w < 3 ? MB(MB_WG) : MB(MB_WU));
            __syncwarp();
        }
    }
    if (has_ch) {
        conv_channel(sm, rk, fixa, fixv, rst2);
    } else {
        rst2();
        asm volatile("setmaxnreg.inc.sync.aligned.u32 88;");
        mbar_wait(MB(MB_WG), 0);
        mbar_wait(MB(MB_C2), 0);
    }
    {
    const int tid = fresh_tid(), warp = __shfl_sync(0xffffffffu, tid >> 5, 0), lane = tid & 31;
    const int g = lane >> 2, t = lane & 3, lr = lane & 7, lm = lane >> 3;
    __syncwarp();
    if (lane == 0) mbar_arrive(MB(MB_CD));
    uint32_t x1[10];
    uint32_t wf[9][4], wd[2][3][4];
    const int fmt = warp >> 2, fsl = warp & 3;
    uint32_t wa = sb + ((fmt == 4) ? (((lm & 1) ? OFF_WU : OFF_WG) + 64) : ((fmt >> 1) * OFF_WU + ((2 * (fmt & 1) + (lm & 1)) << 4))) + (144 * fsl + lr + 8 * (lm >> 1)) * 80;
    asm volatile("" : "+r"(wa));
    auto ldwf = [&]() {
#pragma unroll
        for (int ks = 0; ks < 9; ks++) ldsm_x4_t(wf[ks], wa + ks * 1280);
    };
    if (warp < 16) {
        uint32_t bw[5], v[10];
#pragma unroll
        for (int j = 0; j < 5; j++) bw[j] = (g & 1) ? M.c2[4 * j + t].w : 0x3F803F80u;
        const uint32_t xa = sb + OFF_X + XI(warp >> 1) + (2 * (warp & 1) + (lm & 1)) * XG + lr * 80 + (lm >> 1) * 16;
        uint32_t va = sb + OFF_V + (8 * (lm >> 1) + lr) * VP + 32 * warp + 16 * (lm & 1);
        uint32_t vb = cl == 14 ? xa + 32 : va + 16 * VP, vc = cl == 14 ? xa + 32 : va + 32 * VP;
        float4* p = &S->acc2[256 * rk + 16 * warp + g];
        asm volatile("" : "+r"(va), "+r"(vb), "+r"(vc), "+l"(p));
        ldsm_x4(x1, xa); ldsm_x4(x1 + 4, xa + 32); ldsm_x2(x1 + 8, xa + 64);
        float c1[4] = {0.f, 0.f, 0.f, 0.f}, c2[4] = {0.f, 0.f, 0.f, 0.f}, c3[4] = {0.f, 0.f, 0.f, 0.f};
#pragma unroll
        for (int j = 0; j < 2; j++) {
            mbar_wait(MB(j ? MB_V1 : MB_V), 0);
            ldsm_x4_t(v + 4 * j, j ? vb : va);
#pragma unroll
            for (int i = 4 * j; i < 4 * j + 4; i++) x1[i] = add2(x1[i], v[i]);
            mma_bf16(c1, x1[4 * j], x1[4 * j + 1], x1[4 * j + 2], x1[4 * j + 3], bw[2 * j], bw[2 * j + 1]);
            mma_bf16(c2, x1[4 * j], x1[4 * j + 1], x1[4 * j + 2], x1[4 * j + 3], x1[4 * j], x1[4 * j + 2]);
            mma_bf16(c3, x1[4 * j], x1[4 * j + 1], x1[4 * j + 2], x1[4 * j + 3], x1[4 * j + 1], x1[4 * j + 3]);
        }
        mbar_wait(MB(MB_V2), 0);
        ldsm_x2_t(v + 8, vc);
        x1[8] = add2(x1[8], v[8]); x1[9] = add2(x1[9], v[9]);
        mma_k8(c1, x1[8], x1[9], bw[4]); mma_k8(c2, x1[8], x1[9], x1[8]); mma_k8(c3, x1[8], x1[9], x1[9]);
        if (t == (g >> 1)) {
            red4(p, c1[0], (g & 1) ? c2[1] : c2[0], c1[1]);
            red4(p + 8, c1[2], (g & 1) ? c3[3] : c3[2], c1[3]);
        }
        __syncwarp();
    }
    if (warp >= 16) { mbar_wait(MB(MB_WG), 0); mbar_wait(MB(MB_WU), 0); ldwf(); }
    if (warp == 16) {
        const int v = min(lane, 19), vm = v >> 2, vs = v & 3, d0 = (v * 13) >> 6;
        const uint32_t r0 = mapa(sb, d0), r1 = mapa(sb, 4 + (vm & 3)), g0 = sb + OFF_FFR + (32 * v + (v < 8 ? 0 : 256)) * 4;
        uint4* tp = (uint4*)(sm + OFF_AT);
        mbar_wait(MB(MB_CD), 0);
        tp[lane] = make_uint4(lr * 128 + (((lm & 1) ^ lr) << 4) + (lm >> 1) * 1024, lr * (ROWP * 2) + lm * 16, lm * 160 + lr * 8, 0u);
        tp[32 + lane] = make_uint4(sb + OFF_ACT + lr * 112 + lm * 16, sb + OFF_ACT + lr * 112 + lm * 2, 0u, 0u);
        tp[64 + 3 * v] = make_uint4(sb + OFF_WD + vm * 5120, sb + OFF_H2S + 288 * vs, sb + OFF_FFR + (vs * 80 + 16 * vm) * 32, 32 * vs);
        tp[65 + 3 * v] = make_uint4(r0 + OFF_RS + (rk * 5 + v - 5 * d0) * 640, r1 + OFF_RS + (rk * 5 + vs) * 640, r0 + (MB(MB_RS) - sb), r1 + (MB(MB_RS) - sb));
        tp[66 + 3 * v] = make_uint4(g0, g0 + (v < 8 ? 1024 : 256), 0u, 0u);
    }
    if (warp >= 17) {
        if (warp == 17) mbar_wait(MB(MB_CD), 0);
        else if (warp == 18) named_bar(9, 64);
        else named_bar(7, 64);
        PROXY_FENCE();
        if (lane < 3) tma2d(sb + OFF_WD + (3 * (warp - 17) + lane) * 5120, &tm_wd, 64 * (3 * (warp - 17) + lane), 40 * b, MB(MB_WD));
        if (warp == 19 && (lane < 16 || cl == 14)) st_rlx4(&S->acc1[256 * rk + 16 * cl + lane], make_uint4(0, 0, 0, 0));
        __syncwarp();
    }
    uint32_t h2[10];
    uint32_t ta = sb + OFF_H2T + (16 * warp + (lane & 15)) * 80 + (lane >> 4) * 16;
    if (warp < 16) {
        const float4* ap = &S->acc2[256 * rk + 32 * (warp >> 1) + lane];
        mbar_wait(MB(MB_WG + (warp >> 3)), 0); ldwf();
        float4 s = ld_rlx4f(ap);
        const int pj = lane >= 5, pc = lane - 5 * pj;
        uint2 kp[4];
#pragma unroll
        for (int j = 0; j < 4; j++) kp[j] = *(const uint2*)&M.c2[4 * min(pc, 4) + j];
        mbar_wait(MB(MB_CW), 0);
        const float cw = M.cws[0], sbw = M.cws[1];
        uint32_t tk0 = (2047 - (((lane & 6) << 8) + ((lane & 24) << 3) + ((lane & 1) << 5) + RKT + (warp >> 1))) << 3;
        uint32_t ka = sb + OFF_MISC + (uint32_t)offsetof(Misc, key) + (32 * (warp >> 1) + lane) * 4;
        uint32_t rb = mapa(sb, 4 * (warp & 1) + t), cd = rb + OFF_MISC + (uint32_t)offsetof(Misc, cand2) + (8 * rk + (warp >> 1)) * 8;
        uint4* dst = &S->h2c[(2 * (8 * rk + (warp >> 1)) + pj) * 72 + 5 * cl + pc];
        uint32_t pa = sb + OFF_OUT + 32 * (warp >> 1) * 80 + 16 * pc, kca = sb + OFF_MISC + (uint32_t)offsetof(Misc, c2) + 16 * t;
        int wo = lane < 10 && pc < (cl < 14 ? 5 : 2) ? warp & 1 : 2;
        asm volatile("" : "+r"(tk0), "+r"(ta), "+r"(rb), "+r"(cd), "+r"(pa), "+l"(dst), "+r"(wo));
        mbar_wait(MB(MB_CD), 0);
        stsm_x4(ta + (OFF_OUT - OFF_H2T), x1[0], x1[1], x1[2], x1[3]); stsm_x4(ta + (OFF_OUT - OFF_H2T) + 32, x1[4], x1[5], x1[6], x1[7]); stsm_x2(ta + (OFF_OUT - OFF_H2T) + 64, x1[8], x1[9]);
#pragma unroll 1
        for (int it = 0; it < SPIN_MAX && s.w != (float)NCL; it++) {
            if (s.w < (float)PQT) { const uint32_t c0 = clock(); for (int k = 0; k < 1024 && (uint32_t)clock() - c0 < PQD; k++) { } }
            s = ld_rlx4f(ap);
        }
        __syncwarp();
        if (warp == 0) named_arrive(9, 64);
        float meanb, rinv;
        ln_stats(s.x, s.y, meanb, rinv);
        const uint32_t rbits = __float_as_uint(fmaf(fmaf(-meanb, cw, s.z), rinv, sbw));
        const uint32_t key = ((rbits ^ (((int)rbits >> 31) | 0x80000000u)) & 0xFFFFC000u) | tk0;
        const uint32_t m0 = __reduce_max_sync(0xffffffffu, key);
        const uint32_t mr = pack2(meanb, rinv), rl = f2bits(rinv - hi2f(mr));
        const uint32_t m1 = __reduce_max_sync(0xffffffffu, key == m0 ? 0u : key);
        if (lane < 4) sta2(cd, m0, m1 | 1u, rb + (MB(MB_KEY) - sb));
        int si = 16 * (warp & 1) + g;
        {
            const uint32_t b0 = __ballot_sync(0xffffffffu, key == m0), b1 = __ballot_sync(0xffffffffu, key == m1);
            int row;
            asm("bfind.u32 %0, %1;" : "=r"(row) : "r"(pj ? b1 : b0));
            const uint4 a = lds128(pa + 80 * row);
            const uint32_t s0 = __shfl_sync(0xffffffffu, mr, row), s1 = __shfl_sync(0xffffffffu, rl, row);
            const uint32_t qm = __byte_perm(s0, 0, 0x1010), qh = __byte_perm(s0, 0, 0x3232), ql = __byte_perm(s1, 0, 0x1010);
            const uint32_t v0 = norm2(a.x, qm, qh, ql);
            asm volatile("{\n.reg .pred p;\nsetp.eq.s32 p, %5, %6;\n@p st.relaxed.gpu.global.v4.u32 [%0], {%1,%2,%3,%4};\n}" ::"l"(dst),
                         "r"(~add2(mul2(v0, kp[0].x), kp[0].y)), "r"(~add2(mul2(norm2(a.y, qm, qh, ql), kp[1].x), kp[1].y)),
                         "r"(~add2(mul2(norm2(a.z, qm, qh, ql), kp[2].x), kp[2].y)), "r"(~add2(mul2(norm2(a.w, qm, qh, ql), kp[3].x), kp[3].y)), "r"(row >> 4), "r"(wo) : "memory");
            si |= (add2(mul2(v0, kp[0].x), kp[0].y) ^ add2(mul2(norm2(a.w, qm, qh, ql), kp[3].x), kp[3].y)) & ~31u;
        }
        if (warp == 0) named_arrive(7, 64);
        uint2 kc[5];
#pragma unroll
        for (int j = 0; j < 5; j++) kc[j] = lds64(kca + 64 * j);
        uint32_t st[2][2];
#pragma unroll
        for (int h = 0; h < 2; h++) { st[h][0] = __shfl_sync(0xffffffffu, mr, si + 8 * h); st[h][1] = __shfl_sync(0xffffffffu, rl, si + 8 * h); }
        sts32(ka, key);
#pragma unroll
        for (int i = 0; i < 10; i++)
            h2[i] = add2(mul2(norm2(x1[i], __byte_perm(st[i & 1][0], 0, 0x1010), __byte_perm(st[i & 1][0], 0, 0x3232), __byte_perm(st[i & 1][1], 0, 0x1010)), kc[i >> 1].x), kc[i >> 1].y);
        stsm_x4(ta, h2[0], h2[1], h2[2], h2[3]); stsm_x4(ta + 32, h2[4], h2[5], h2[6], h2[7]); stsm_x2(ta + 64, h2[8], h2[9]);
        __syncwarp();
        named_arrive(6, 576);
    }
    auto outt = [&]() {
        if (warp < 16) {
            uint32_t o[10];
#pragma unroll
            for (int i = 0; i < 10; i++) o[i] = add2(x1[i], mul2(M.c2[4 * (i >> 1) + t].z, h2[i]));
            stsm_x4(ta + (OFF_OUT - OFF_H2T), o[0], o[1], o[2], o[3]); stsm_x4(ta + (OFF_OUT - OFF_H2T) + 32, o[4], o[5], o[6], o[7]); stsm_x2(ta + (OFF_OUT - OFF_H2T) + 64, o[8], o[9]);
        }
    };
    outt();
    uint4 gv = make_uint4(1, 1, 1, 1);
    const unsigned char* gp;
    uint32_t gdst;
    {
        const int gi = 32 * warp + lane, kk = (gi * 911) >> 16, seg = gi - 72 * kk;
        uint32_t ca = sb + OFF_MISC + (uint32_t)offsetof(Misc, cand2), sa = ca + 544 + 4 * (kk & 7);
        gp = (const unsigned char*)&S->h2c[seg];
        gdst = sb + OFF_H2S + kk * (ROWP * 2) + seg * 16;
        if (warp == 18) {
            gp = (const unsigned char*)&S->h2c[136 * 72 + min(2 * (rk < 4 ? 5 * rk : 4 * rk + 4) + lane, 71)];
            gdst = sb + OFF_GB + 16 * lane;
            if (lane < 10) gv = ld_rlx4(gp);
        }
        asm volatile("" : "+r"(sa), "+r"(gdst), "+l"(gp));
        mbar_wait(MB(MB_KEY), 0);
        if (warp < 16) {
            const uint4 o = lds128(ca + 16 * lane);
            uint32_t hd[4], sc[4];
#pragma unroll
            for (int q = 0; q < 4; q++) { const uint2 a = lds64(ca + 8 * warp + 128 * q); hd[q] = a.x; sc[q] = a.y; }
            const uint32_t mx = max(o.x, o.z);
            uint32_t n[4];
#pragma unroll
            for (int q = 0; q < 4; q++) n[q] = __popc(__ballot_sync(0xffffffffu, mx > hd[q]));
            auto rank = [&](uint32_t k) {
                return (__popc(__ballot_sync(0xffffffffu, o.x > k)) + __popc(__ballot_sync(0xffffffffu, o.y > k))) + (__popc(__ballot_sync(0xffffffffu, o.z > k)) + __popc(__ballot_sync(0xffffffffu, o.w > k)));
            };
#pragma unroll
            for (int q = 0; q < 4; q++) {
                if (n[q] < 8) {
                    const uint32_t r0 = rank(hd[q]), r1 = rank(sc[q]);
                    if (r0 < 8) { sts32(ca + 544 + 4 * r0, (2 * warp + 32 * q) * 1152); sts32(ca + 512 + 4 * r0, hd[q]); }
                    if (r1 < 8) { sts32(ca + 544 + 4 * r1, (2 * warp + 32 * q + 1) * 1152); sts32(ca + 512 + 4 * r1, sc[q]); }
                }
            }
        }
        named_bar(13, 640);
        if (warp < 18) {
            gp += lds32(sa);
            gv = ld_rlx4(gp);
        } else if (warp == 18) named_arrive(14, 64);
        else named_arrive(8, 64);
    }
    uint32_t wda, ha, fo, pg, pu, pv, pa, rd[2], rm[2];
    {
        const uint32_t tl = sb + OFF_AT + 16 * lane, tw = sb + OFF_AT + 1024 + 48 * warp;
        const uint4 a = lds128(tl), c = lds128(tw), d = lds128(tw + 16);
        const uint2 e = lds64(tl + 512), f = lds64(tw + 32);
        wda = (a.x ^ c.w) + c.x; ha = a.y + c.y; fo = c.z + 8 * lane; pg = f.x + 4 * lane; pu = f.y + 4 * lane; pv = e.y + 8 * warp; pa = e.x;
        rd[0] = d.x + a.z; rd[1] = d.y + a.z; rm[0] = d.z; rm[1] = d.w;
        asm volatile("" : "+r"(wda), "+r"(ha), "+r"(fo), "+r"(pg), "+r"(pu), "+r"(pv), "+r"(pa), "+r"(rd[0]), "+r"(rd[1]), "+r"(rm[0]), "+r"(rm[1]));
    }
    const uint32_t zz = ((wda | ha | fo) | (pu | pv | pa) | (rd[0] | rd[1])) >> 31;
    auto ldwd = [&]() {
#pragma unroll
        for (int i = 0; i < 2; i++)
#pragma unroll
            for (int ks = 0; ks < 3; ks++)
                if (i == 0 || warp < 16) {
                    if (ks == 2) ldsm_x2_t(wd[i][ks], wda + ks * 2048 + i * 5 * 5120);
                    else ldsm_x4_t(wd[i][ks], wda + ks * 2048 + i * 5 * 5120);
                }
    };
    if ((gv.x | zz) == 0u) {
        int it = 0;
#pragma unroll 1
        do gv = ld_rlx4(gp); while (++it < SPIN_MAX && gv.x == 0u);
    }
    asm volatile("st.shared.v4.u32 [%0], {%1,%2,%3,%4};" ::"r"(gdst), "r"(~gv.x), "r"(~gv.y), "r"(~gv.z), "r"(~gv.w) : "memory");
    CBAR();
    auto ffn1 = [&]() {
        float acc[2][4] = {{0.f, 0.f, 0.f, 0.f}, {0.f, 0.f, 0.f, 0.f}};
        uint32_t hb[5][4];
#pragma unroll
        for (int k2 = 0; k2 < 5; k2++) if (k2 < 4) ldsm_x4(hb[k2], ha + k2 * 64); else ldsm_x2(hb[k2], ha + 256);
#pragma unroll
        for (int k2 = 0; k2 < 5; k2++) {
            mma_bf16(acc[0], wf[2 * k2][0], wf[2 * k2][1], wf[2 * k2][2], wf[2 * k2][3], hb[k2][0], hb[k2][1]);
            if (k2 < 4) mma_bf16(acc[1], wf[2 * k2 + 1][0], wf[2 * k2 + 1][1], wf[2 * k2 + 1][2], wf[2 * k2 + 1][3], hb[k2][2], hb[k2][3]);
        }
        asm volatile("st.shared.v2.f32 [%0], {%1,%2};" ::"r"(fo), "f"(acc[0][0] + acc[1][0]), "f"(acc[0][1] + acc[1][1]) : "memory");
        asm volatile("st.shared.v2.f32 [%0+256], {%1,%2};" ::"r"(fo), "f"(acc[0][2] + acc[1][2]), "f"(acc[0][3] + acc[1][3]) : "memory");
    };
    ffn1();
    auto gate = [&]() {
        if (warp < 10) {
            float a[8];
#pragma unroll
            for (int i = 0; i < 8; i++) a[i] = __uint_as_float(lds32((i & 4 ? pu : pg) + (i & 3) * 2560));
            float gg = bfr((a[0] + a[1]) + (a[2] + a[3]));
            gg = bfr(silu(gg));
            const float uu = bfr((a[4] + a[5]) + (a[6] + a[7]));
            sts16(pv, f2bits(gg * uu));
        }
    };
    if (warp < 10) { CBAR(); gate(); }
    else named_arrive(0, 640);
    mbar_wait(MB(MB_WD), 0);
    ldwd();
    named_bar(12, 640);
    auto ffn2 = [&](int pass) {
        uint32_t bq[6];
        ldsm_x4(bq, pa); ldsm_x2(bq + 4, pa + 64);
        float acc[2][4] = {{0.f, 0.f, 0.f, 0.f}, {0.f, 0.f, 0.f, 0.f}};
        uint32_t r[2][2];
#pragma unroll
        for (int ks = 0; ks < 3; ks++)
#pragma unroll
            for (int i = 0; i < 2; i++) {
                if (ks == 2) mma_k8(acc[i], wd[i][ks][0], wd[i][ks][1], bq[4]);
                else mma_bf16(acc[i], wd[i][ks][0], wd[i][ks][1], wd[i][ks][2], wd[i][ks][3], bq[2 * ks], bq[2 * ks + 1]);
            }
#pragma unroll
        for (int i = 0; i < 2; i++) { r[i][0] = movm(pack2(acc[i][0], acc[i][1])); r[i][1] = movm(pack2(acc[i][2], acc[i][3])); }
#pragma unroll
        for (int j = 0; j < 2; j++)
            if (j == 0 || warp < 16) sta2(rd[j] + 80 * pass, r[j][0], r[j][1], rm[j] + pass * 8 * (MB_RS2 - MB_RS));
    };
    ffn2(0);
    auto fin = [&](int pass) {
        const int lane = fresh_tid() & 31;
        const int fP = min(warp < 8 ? 20 * cl + lane : 8 * (rk < 4 ? 5 * rk : 4 * rk + 4) + 4 * (warp - 8) + (lane & 3), D_ / 2 - 1);
        uint32_t fgb = lds32(warp < 8 ? sb + OFF_MISC + (uint32_t)offsetof(Misc, c2) + 8 + 16 * lane : sb + OFF_GB + 16 * (warp - 8) + 4 * (lane & 3));
        const int ftok = warp < 8 ? warp : lane >> 2;
        uint32_t fkey = pass ? M.fin[ftok] : M.sel[ftok];
        const bool fon = warp < 8 ? (MINE(fkey) && lane < (cl < 14 ? 20 : 8)) : warp < (rk < 4 ? 18 : 16);
        const uint32_t hv = lds32(sb + OFF_H2S + ftok * (ROWP * 2) + 4 * fP);
        uint32_t p = sb + OFF_RS + pass * 80 + ((warp - 8) >> 1) * 640 + (lane >> 3) * 160 + (lane & 7) * 8 + 4 * (warp & 1);
        float4* ap = &S->acc3[pass * (72 * 32) + (fP >> 2) * 32 + 4 * ftok + (fP & 3)];
        bf16* op = out + ((~fkey >> 3) & 2047u) * D_ + 2 * fP;
        asm volatile("" : "+r"(p), "+l"(ap), "+l"(op));
        float s0 = 0.f, s1 = 0.f, s2 = 1.0f, s3 = 0.f;
        if (warp >= 8) {
            if (fon) {
                mbar_wait(MB(pass ? MB_RS2 : MB_RS), 0);
                uint32_t v[8];
#pragma unroll
                for (int i = 0; i < 8; i++) v[i] = lds32(p + i * 3200);
                s0 = ((lo2f(v[0]) + lo2f(v[1])) + (lo2f(v[2]) + lo2f(v[3]))) + ((lo2f(v[4]) + lo2f(v[5])) + (lo2f(v[6]) + lo2f(v[7])));
                s1 = ((hi2f(v[0]) + hi2f(v[1])) + (hi2f(v[2]) + hi2f(v[3]))) + ((hi2f(v[4]) + hi2f(v[5])) + (hi2f(v[6]) + hi2f(v[7])));
            }
        } else if (fon) {
            const uint32_t row = ROW(fkey);
            const unsigned short* vp = (const unsigned short*)(sm + OFF_V + 2 * lane * VP) + row;
            const uint32_t xv = add2(lds32(sb + OFF_X + XI(row >> 5) + ((row >> 3) & 3) * XG + (row & 7) * 80 + 4 * lane), (uint32_t)vp[0] | ((uint32_t)vp[VP / 2] << 16));
            s2 = (float)(((xv & 0xFFFFu) << 5) | 1u); s3 = (float)(xv >> 16);
            mbar_wait(MB(MB_OUT), 0);
        }
        float4 o = make_float4(0.f, 0.f, 0.f, 0.f);
        if (fon) o = atom4(ap, s0, s1, s2, s3);
        uint32_t redo = 0;
        if (!pass) {
            mbar_wait(MB(MB_FIN), 0);
            redo = M.fin[8];
            fkey = M.fin[ftok];
        }
        const float rs = sigm(hi2f(fkey ^ (((int)~fkey >> 31) | 0x80000000u)));
        uint32_t rs2 = pack2(rs, rs);
        s2 = fmaxf(s2 + 8388608.f, rs); s3 = fmaxf(s3 + 8388608.f, rs);
        if (rs > 2.f) s0 = s1 = rs;
        uint32_t msk = redo ? 0u : 16u;
        asm volatile("" : "+r"(rs2), "+r"(fgb), "+f"(s2), "+f"(s3), "+r"(msk), "+f"(s0), "+f"(s1));
        const uint32_t z = __float_as_uint(o.z + s2), zh = __float_as_uint(o.w + s3);
        const uint32_t xv = __byte_perm(z >> 5, zh, 0x5410);
        asm volatile("{\n.reg .pred q;\nsetp.ne.u32 q, %2, 0;\n@q st.global.u32 [%0], %1;\n}" ::"l"(op), "r"(add2(xv, mul2(fgb, add2(hv, mul2(pack2(o.x + s0, o.y + s1), rs2))))), "r"(z & msk) : "memory");
        return redo;
    };
    if (fin(0)) {
        const int gi = fresh_tid(), kk = (gi * 911) >> 16, seg = gi - 72 * kk;
        __syncwarp();
        if (warp < 8) {
            const uint32_t key = M.fin[warp];
            if (MINE(key) && lane < (cl < 14 ? 5 : 2)) {
                const uint4 a = lds128(sb + OFF_H2T + ROW(key) * 80 + 16 * lane);
                st_rlx4(&S->h2c[(128 + warp) * 72 + 5 * cl + lane], make_uint4(~a.x, ~a.y, ~a.z, ~a.w));
            }
            __syncwarp();
        }
        RBAR();
        if (warp < 18) {
            uint4 gv = make_uint4(0, 0, 0, 0);
#pragma unroll 1
            for (int it = 0; it < SPIN_MAX && gv.x == 0u; it++) gv = ld_rlx4(&S->h2c[128 * 72 + gi]);
            *(uint4*)(sm + OFF_H2S + kk * (ROWP * 2) + seg * 16) = make_uint4(~gv.x, ~gv.y, ~gv.z, ~gv.w);
        }
        RBAR();
        ffn1();
        ldwd();
        RBAR();
        gate();
        RBAR();
        ffn2(1);
        fin(1);
    }
    }
    }
}

typedef CUresult (*EncodeFn)(CUtensorMap*, CUtensorMapDataType, cuuint32_t, void*, const cuuint64_t*, const cuuint64_t*,
                             const cuuint32_t*, const cuuint32_t*, CUtensorMapInterleave, CUtensorMapSwizzle,
                             CUtensorMapL2promotion, CUtensorMapFloatOOBfill);

static void make_map(EncodeFn fn, CUtensorMap* m, const void* ptr, uint64_t cols, uint64_t rows, uint32_t bc, uint32_t br,
                     CUtensorMapSwizzle sw, int five) {
    cuuint64_t dims[5] = {cols, rows, 4, 4, 288};
    cuuint64_t strides[4] = {cols * 2 * (five ? 32 : 1), cols * 2 * 512, cols * 2 * 64, cols * 2};
    cuuint32_t box[5] = {bc, br, 4, 4, 8};
    cuuint32_t es[5] = {1, 1, 1, 1, 1};
    CUresult rc = fn(m, CU_TENSOR_MAP_DATA_TYPE_BFLOAT16, five ? 5 : 2, (void*)ptr, dims, strides, box, es, CU_TENSOR_MAP_INTERLEAVE_NONE,
                     sw, (CUtensorMapL2promotion)(five || sw ? 0 : br == 72 ? L2M : L2P), CU_TENSOR_MAP_FLOAT_OOB_FILL_NONE);
    (void)rc;
}

static void launch(void* const* d_in, const int* in_sizes, int n_in, void* d_out, int out_size) {
    static EncodeFn enc = nullptr;
    static CUtensorMap tmm, tmg, tmu, tmd, tmo;
    static Scratch* sp = nullptr;
    static const void* cached[6] = {nullptr, nullptr, nullptr, nullptr, nullptr, nullptr};
    if (!enc) {
        cudaDriverEntryPointQueryResult qr;
        void* fn = nullptr;
        cudaGetDriverEntryPoint("cuTensorMapEncodeTiled", &fn, cudaEnableDefault, &qr);
        enc = (EncodeFn)fn;
        cudaFuncSetAttribute(clus_kernel, cudaFuncAttributeMaxDynamicSharedMemorySize, SMEM_TOTAL);
        cudaGetSymbolAddress((void**)&sp, g_s);
    }
    if (cached[0] != d_in[13] || cached[1] != d_in[9] || cached[2] != d_in[10] || cached[3] != d_in[11] || cached[4] != d_in[0] || cached[5] != d_out) {
        make_map(enc, &tmo, d_out, D_, 2, 40, 2, CU_TENSOR_MAP_SWIZZLE_NONE, 1);
        make_map(enc, &tmm, d_in[13], 6 * D_, D_, 40, 72, CU_TENSOR_MAP_SWIZZLE_NONE, 0);
        make_map(enc, &tmg, d_in[9], F_, D_, 40, 192, CU_TENSOR_MAP_SWIZZLE_NONE, 0);
        make_map(enc, &tmu, d_in[10], F_, D_, 40, 192, CU_TENSOR_MAP_SWIZZLE_NONE, 0);
        make_map(enc, &tmd, d_in[11], D_, F_, 64, 40, CU_TENSOR_MAP_SWIZZLE_128B, 0);
        cached[0] = d_in[13]; cached[1] = d_in[9]; cached[2] = d_in[10]; cached[3] = d_in[11]; cached[4] = d_in[0]; cached[5] = d_out;
    }
    clus_kernel<<<G_, NTHR, SMEM_TOTAL>>>((const bf16*)d_in[0], (const bf16*)d_in[1], (const bf16*)d_in[2], (const bf16*)d_in[3], (const bf16*)d_in[4],
                                          (const bf16*)d_in[5], (const bf16*)d_in[12], sp, (const bf16*)d_in[6], (const bf16*)d_in[8], (const bf16*)d_in[13],
                                          (bf16*)d_out, tmm, tmg, tmu, tmd, tmo);
}


static bool fits() {
    cudaFuncSetAttribute(clus_kernel, cudaFuncAttributeMaxDynamicSharedMemorySize, SMEM_TOTAL);
    cudaLaunchConfig_t cfg = {};
    cudaLaunchAttribute at;
    at.id = cudaLaunchAttributeClusterDimension;
    at.val.clusterDim.x = 8; at.val.clusterDim.y = 1; at.val.clusterDim.z = 1;
    cfg.gridDim = dim3(G_); cfg.blockDim = dim3(NTHR); cfg.dynamicSmemBytes = SMEM_TOTAL; cfg.attrs = &at; cfg.numAttrs = 1;
    int n = 0;
    const bool ok = cudaOccupancyMaxActiveClusters(&n, clus_kernel, &cfg) == cudaSuccess && n >= NCL;
    cudaGetLastError();
    return ok;
}
}
#undef L_
#undef D_
#undef N_
#undef F_
#undef G_
#undef NCL
#undef NTHR
#undef SPIN_MAX
#undef NRS
#undef OFF_WG
#undef OFF_WU
#undef KSCR
#undef OFF_WM0
#undef OFF_STG
#undef OFF_MG2
#undef OFF_CH
#undef CHS
#undef UP
#undef UB
#undef XO_TF
#undef XO_U8
#undef XO_U16
#undef XO_ZA
#undef XO_ZB
#undef XO_ZC
#undef XO_ZD
#undef XO_TD
#undef XO_K1024
#undef XO_DSK
#undef XO_KLAST
#undef XO_MBU
#undef OFF_X
#undef XG
#undef XI
#undef XN
#undef OFF_V
#undef VP
#undef OFF_EK
#undef OFF_WM2
#undef OFF_MG1
#undef OFF_SC
#undef OFF_C1
#undef OFF_MISC
#undef OFF_WD
#undef OFF_H2T
#undef OFF_OUT
#undef OFF_GB
#undef OFF_AT
#undef ROWP
#undef OFF_H2S
#undef OFF_FFR
#undef OFF_ACT
#undef OFF_RS
#undef SMEM_TOTAL
#undef CBAR
#undef RBAR
#undef PROXY_FENCE
#undef D4
#undef O4
#undef WG_FENCE
#undef WG_COMMIT
#undef WG_WAIT
#undef TQ
#undef MB
#undef SD
#undef UF
#undef DS
#undef Q4
#undef RD_
#undef M2W
#undef WS
#undef WMS
#undef PQT
#undef PQD
#undef L2P
#undef L2M
#undef PDE
#undef WMD
#undef CWP
#undef CWD
#undef ROW
#undef RKT
#undef MINE
#undef CE
#undef POP
#undef CGT
#undef CL_ARRIVE
#undef CL_WAIT
#undef TA
#undef PH

namespace v4 {

#define L_ 2048
#define D_ 576
#define N_ 128
#define F_ 4608
#define G_ 128
#define NTHR 640
#define SPIN_MAX (1 << 18)
#define SENT 0u
#define HINT_N 182u

typedef __nv_bfloat16 bf16;

struct Scratch {
    uint4 xn[G_ * G_ * 10];
    uint4 v[G_ * D_ * 2];
    uint2 part[G_ * G_ * 9];
    uint4 h2w[L_ * 96];
    unsigned int rec[G_ * 8];
    unsigned int modw[6 * D_];
    unsigned int ticket[64];
    unsigned int cnt[64];
    unsigned int hint[64];
};
__device__ __align__(1024) Scratch g_s;

#define OFF_WG 0
#define OFF_WU 46080
#define OFF_CH 92160
#define CHS 20784
#define ULBO 656
#define XO_U8 6272
#define XO_U16 10368
#define XO_ZA 5248
#define XO_ZB 8448
#define XO_ZC 11648
#define XO_ZD 13824
#define XO_TD 16000
#define XO_TF 18624
#define XO_K1024 20672
#define KSCR 3456
#define OFF_TILE 196096
#define ROWP 584
#define OFF_MISC 214784
#define OFF_WD OFF_CH
#define OFF_H2T (OFF_CH + 3 * CHS)
#define OFF_H2S (OFF_H2T + 18688)
#define OFF_FFR (OFF_H2S + 9344)
#define OFF_FIN OFF_FFR
#define OFF_ACT (OFF_FFR + 10240)

struct Misc {
    __align__(16) uint4 sent[256];
    __align__(16) uint4 box[11 * 14];
    union {
        struct {
            __align__(16) float2 part[18][16];
            float rp[18][16];
        };
        struct {
            __align__(16) unsigned short st1[3][16];
            __align__(16) float p1[16][4], p2[16][4];
        };
    };
    __align__(16) bf16 cb1[D_], sb[D_], gb[D_];
    __align__(16) bf16 sc[D_];
    __align__(16) unsigned int cand[64], skey[16];
    __align__(16) float kinv[5][4], klast[5][4];
    unsigned int pk[4][8];
    __align__(16) uint4 st2[16];
    unsigned int wr[D_ / 2];
    float modx[32];
    unsigned int rank[16];
    volatile unsigned int flag;
    unsigned int e1cnt;
    unsigned long long mbar[5];
    unsigned int epoch;
};
#define SMEM_TOTAL (OFF_MISC + (int)sizeof(Misc))
static_assert(SMEM_TOTAL <= 232448, "smem");

__device__ __forceinline__ float lo2f(uint32_t w) { return __uint_as_float(w << 16); }
__device__ __forceinline__ float hi2f(uint32_t w) { return __uint_as_float(w & 0xFFFF0000u); }
__device__ __forceinline__ uint32_t pack2(float lo, float hi) { uint32_t r; asm("cvt.rn.bf16x2.f32 %0, %1, %2;" : "=r"(r) : "f"(hi), "f"(lo)); return r; }
__device__ __forceinline__ float bfr(float x) { return __uint_as_float(pack2(0.f, x)); }
__device__ __forceinline__ uint32_t f2bits(float x) { return pack2(x, 0.f); }
__device__ __forceinline__ uint32_t packh(float lo, float hi) { uint32_t r; asm("cvt.rn.f16x2.f32 %0, %1, %2;" : "=r"(r) : "f"(hi), "f"(lo)); return r; }
__device__ __forceinline__ float frcp(float x) { float r; asm("rcp.approx.ftz.f32 %0, %1;" : "=f"(r) : "f"(x)); return r; }
__device__ __forceinline__ float fsqrt(float x) { float r; asm("sqrt.approx.f32 %0, %1;" : "=f"(r) : "f"(x)); return r; }
__device__ __forceinline__ float fex2(float x) { float r; asm("ex2.approx.ftz.f32 %0, %1;" : "=f"(r) : "f"(x)); return r; }
__device__ __forceinline__ float silu(float x) { return __fdividef(x, 1.0f + __expf(-x)); }
__device__ __forceinline__ uint32_t add2(uint32_t a, uint32_t b) { uint32_t r; asm("add.rn.bf16x2 %0, %1, %2;" : "=r"(r) : "r"(a), "r"(b)); return r; }
__device__ __forceinline__ uint32_t sub2(uint32_t a, uint32_t b) { uint32_t r; asm("sub.rn.bf16x2 %0, %1, %2;" : "=r"(r) : "r"(a), "r"(b)); return r; }
__device__ __forceinline__ uint32_t mul2(uint32_t a, uint32_t b) { uint32_t r; asm("mul.rn.bf16x2 %0, %1, %2;" : "=r"(r) : "r"(a), "r"(b)); return r; }
__device__ __forceinline__ uint32_t fma2(uint32_t a, uint32_t b, uint32_t c) { uint32_t r; asm("fma.rn.bf16x2 %0, %1, %2, %3;" : "=r"(r) : "r"(a), "r"(b), "r"(c)); return r; }
__device__ __forceinline__ uint32_t norm2(uint32_t x, uint32_t m, uint32_t rh, uint32_t rl) { const uint32_t d = sub2(x, m); return fma2(d, rh, mul2(d, rl)); }

__device__ __forceinline__ void mma_bf16(float* c, uint32_t a0, uint32_t a1, uint32_t a2, uint32_t a3, uint32_t b0, uint32_t b1) {
    asm volatile("mma.sync.aligned.m16n8k16.row.col.f32.bf16.bf16.f32 {%0,%1,%2,%3}, {%4,%5,%6,%7}, {%8,%9}, {%0,%1,%2,%3};\n"
                 : "+f"(c[0]), "+f"(c[1]), "+f"(c[2]), "+f"(c[3]) : "r"(a0), "r"(a1), "r"(a2), "r"(a3), "r"(b0), "r"(b1));
}
__device__ __forceinline__ void mma_f16(float* c, const uint32_t* a, uint32_t b0, uint32_t b1) {
    asm volatile("mma.sync.aligned.m16n8k16.row.col.f32.f16.f16.f32 {%0,%1,%2,%3}, {%4,%5,%6,%7}, {%8,%9}, {%0,%1,%2,%3};\n"
                 : "+f"(c[0]), "+f"(c[1]), "+f"(c[2]), "+f"(c[3]) : "r"(a[0]), "r"(a[1]), "r"(a[2]), "r"(a[3]), "r"(b0), "r"(b1));
}
__device__ __forceinline__ void ldsm_x4(uint32_t* r, uint32_t addr) {
    asm volatile("ldmatrix.sync.aligned.m8n8.x4.shared.b16 {%0,%1,%2,%3}, [%4];" : "=r"(r[0]), "=r"(r[1]), "=r"(r[2]), "=r"(r[3]) : "r"(addr) : "memory");
}
__device__ __forceinline__ void ldsm_x4_t(uint32_t* r, uint32_t addr) {
    asm volatile("ldmatrix.sync.aligned.m8n8.x4.trans.shared.b16 {%0,%1,%2,%3}, [%4];" : "=r"(r[0]), "=r"(r[1]), "=r"(r[2]), "=r"(r[3]) : "r"(addr) : "memory");
}
__device__ __forceinline__ void stsm_x4(uint32_t addr, uint32_t r0, uint32_t r1, uint32_t r2, uint32_t r3) {
    asm volatile("stmatrix.sync.aligned.m8n8.x4.shared.b16 [%0], {%1,%2,%3,%4};" ::"r"(addr), "r"(r0), "r"(r1), "r"(r2), "r"(r3) : "memory");
}
__device__ __forceinline__ void stsm_x4_t(uint32_t addr, uint32_t r0, uint32_t r1, uint32_t r2, uint32_t r3) {
    asm volatile("stmatrix.sync.aligned.m8n8.x4.trans.shared.b16 [%0], {%1,%2,%3,%4};" ::"r"(addr), "r"(r0), "r"(r1), "r"(r2), "r"(r3) : "memory");
}
__device__ __forceinline__ uint32_t movm(uint32_t a) { uint32_t r; asm volatile("movmatrix.sync.aligned.m8n8.trans.b16 %0, %1;" : "=r"(r) : "r"(a)); return r; }
__device__ __forceinline__ uint32_t lds32(uint32_t a) { uint32_t v; asm volatile("ld.shared.u32 %0, [%1];" : "=r"(v) : "r"(a)); return v; }
__device__ __forceinline__ void sts32(uint32_t a, uint32_t v) { asm volatile("st.shared.u32 [%0], %1;" ::"r"(a), "r"(v) : "memory"); }
__device__ __forceinline__ void sts16(uint32_t a, uint32_t v) { asm volatile("st.shared.u16 [%0], %1;" ::"r"(a), "h"((unsigned short)v) : "memory"); }
__device__ __forceinline__ void named_bar(int id, int n) { asm volatile("bar.sync %0, %1;" ::"r"(id), "r"(n) : "memory"); }
__device__ __forceinline__ void named_arrive(int id, int n) { asm volatile("bar.arrive %0, %1;" ::"r"(id), "r"(n) : "memory"); }
#define CBAR() asm volatile("bar.sync 0, 640;" ::: "memory")
#define PROXY_FENCE() asm volatile("fence.proxy.async.shared::cta;" ::: "memory")

#define D4(d, o) "+f"(d[o]), "+f"(d[o + 1]), "+f"(d[o + 2]), "+f"(d[o + 3])
__device__ __forceinline__ void wg32(float* d, uint32_t a0, uint32_t a1, uint32_t a2, uint32_t a3, uint64_t desc) {
    asm volatile("wgmma.mma_async.sync.aligned.m64n32k16.f32.bf16.bf16 {%0,%1,%2,%3,%4,%5,%6,%7,%8,%9,%10,%11,%12,%13,%14,%15}, {%16,%17,%18,%19}, %20, 1, 1, 1, 0;"
                 : D4(d, 0), D4(d, 4), D4(d, 8), D4(d, 12) : "r"(a0), "r"(a1), "r"(a2), "r"(a3), "l"(desc));
}
__device__ __forceinline__ void wg48(float* d, uint32_t a0, uint32_t a1, uint32_t a2, uint32_t a3, uint64_t desc) {
    asm volatile("wgmma.mma_async.sync.aligned.m64n48k16.f32.bf16.bf16 {%0,%1,%2,%3,%4,%5,%6,%7,%8,%9,%10,%11,%12,%13,%14,%15,%16,%17,%18,%19,%20,%21,%22,%23}, {%24,%25,%26,%27}, %28, 1, 1, 1, 0;"
                 : D4(d, 0), D4(d, 4), D4(d, 8), D4(d, 12), D4(d, 16), D4(d, 20) : "r"(a0), "r"(a1), "r"(a2), "r"(a3), "l"(desc));
}
#define O4(d, o) "=f"(d[o]), "=f"(d[o + 1]), "=f"(d[o + 2]), "=f"(d[o + 3])
__device__ __forceinline__ void wg32z(float* d, uint32_t a0, uint32_t a1, uint32_t a2, uint32_t a3, uint64_t desc) {
    asm volatile("wgmma.mma_async.sync.aligned.m64n32k16.f32.bf16.bf16 {%0,%1,%2,%3,%4,%5,%6,%7,%8,%9,%10,%11,%12,%13,%14,%15}, {%16,%17,%18,%19}, %20, 0, 1, 1, 0;"
                 : O4(d, 0), O4(d, 4), O4(d, 8), O4(d, 12) : "r"(a0), "r"(a1), "r"(a2), "r"(a3), "l"(desc));
}
__device__ __forceinline__ void wg48z(float* d, uint32_t a0, uint32_t a1, uint32_t a2, uint32_t a3, uint64_t desc) {
    asm volatile("wgmma.mma_async.sync.aligned.m64n48k16.f32.bf16.bf16 {%0,%1,%2,%3,%4,%5,%6,%7,%8,%9,%10,%11,%12,%13,%14,%15,%16,%17,%18,%19,%20,%21,%22,%23}, {%24,%25,%26,%27}, %28, 0, 1, 1, 0;"
                 : O4(d, 0), O4(d, 4), O4(d, 8), O4(d, 12), O4(d, 16), O4(d, 20) : "r"(a0), "r"(a1), "r"(a2), "r"(a3), "l"(desc));
}
#define WG_FENCE() asm volatile("wgmma.fence.sync.aligned;" ::: "memory")
#define WG_COMMIT() asm volatile("wgmma.commit_group.sync.aligned;" ::: "memory")
#define WG_WAIT(n) asm volatile("wgmma.wait_group.sync.aligned " #n ";" ::: "memory")
#define TQ(p, k) p[2 * (k) + 1], p[2 * (k) + 2], p[2 * (k)], p[2 * (k) + 1]

__device__ __forceinline__ uint4 ld_nc4(const void* p) { uint4 v; asm volatile("ld.global.nc.v4.u32 {%0,%1,%2,%3}, [%4];" : "=r"(v.x), "=r"(v.y), "=r"(v.z), "=r"(v.w) : "l"(p)); return v; }
__device__ __forceinline__ unsigned short ld_nc16(const void* p) { unsigned short v; asm volatile("ld.global.nc.u16 %0, [%1];" : "=h"(v) : "l"(p)); return v; }
__device__ __forceinline__ uint32_t ld_nc(const void* p) { uint32_t v; asm volatile("ld.global.nc.u32 %0, [%1];" : "=r"(v) : "l"(p)); return v; }
__device__ __forceinline__ uint32_t ld_rlx(const unsigned int* p) { uint32_t v; asm volatile("ld.relaxed.gpu.global.u32 %0, [%1];" : "=r"(v) : "l"(p) : "memory"); return v; }
__device__ __forceinline__ uint2 ld_rlx2(const void* p) { uint2 v; asm volatile("ld.relaxed.gpu.global.v2.u32 {%0,%1}, [%2];" : "=r"(v.x), "=r"(v.y) : "l"(p) : "memory"); return v; }
__device__ __forceinline__ uint4 ld_rlx4(const void* p) { uint4 v; asm volatile("ld.relaxed.gpu.global.v4.u32 {%0,%1,%2,%3}, [%4];" : "=r"(v.x), "=r"(v.y), "=r"(v.z), "=r"(v.w) : "l"(p) : "memory"); return v; }
__device__ __forceinline__ void st_rlx(unsigned int* p, uint32_t v) { asm volatile("st.relaxed.gpu.global.u32 [%0], %1;" ::"l"(p), "r"(v) : "memory"); }
__device__ __forceinline__ void st_rlx2(void* p, uint32_t a, uint32_t b) { asm volatile("st.relaxed.gpu.global.v2.u32 [%0], {%1,%2};" ::"l"(p), "r"(a), "r"(b) : "memory"); }
__device__ __forceinline__ void st_rlx4(void* p, uint4 v) { asm volatile("st.relaxed.gpu.global.v4.u32 [%0], {%1,%2,%3,%4};" ::"l"(p), "r"(v.x), "r"(v.y), "r"(v.z), "r"(v.w) : "memory"); }
__device__ __forceinline__ void red_inc(unsigned int* p) { asm volatile("red.relaxed.gpu.global.add.u32 [%0], 1;" ::"l"(p) : "memory"); }

__device__ __forceinline__ void mbar_init(uint32_t a, int cnt) { asm volatile("mbarrier.init.shared::cta.b64 [%0], %1;" ::"r"(a), "r"(cnt) : "memory"); }
__device__ __forceinline__ void mbar_expect(uint32_t a, uint32_t bytes) { asm volatile("mbarrier.arrive.expect_tx.shared::cta.b64 _, [%0], %1;" ::"r"(a), "r"(bytes) : "memory"); }
__device__ __forceinline__ void mbar_wait(uint32_t a, uint32_t parity) {
    uint32_t ok = 0;
    int it = 0;
    do {
        asm volatile("{\n.reg .pred p;\nmbarrier.try_wait.parity.shared::cta.b64 p, [%1], %2;\nselp.u32 %0, 1, 0, p;\n}" : "=r"(ok) : "r"(a), "r"(parity) : "memory");
    } while (!ok && ++it < SPIN_MAX);
}
__device__ __forceinline__ void tma2d(uint32_t dst, const CUtensorMap* tm, int c0, int c1, uint32_t mbar) {
    asm volatile("cp.async.bulk.tensor.2d.shared::cluster.global.mbarrier::complete_tx::bytes [%0], [%1, {%3, %4}], [%2];"
                 ::"r"(dst), "l"(tm), "r"(mbar), "r"(c0), "r"(c1) : "memory");
}
__device__ __forceinline__ void bulk_s2g(void* dst, uint32_t src, uint32_t bytes) {
    asm volatile("cp.async.bulk.global.shared::cta.bulk_group [%0], [%1], %2;" ::"l"(dst), "r"(src), "r"(bytes) : "memory");
}
__device__ __forceinline__ uint32_t ld_acq(const unsigned int* p) { uint32_t v; asm volatile("ld.acquire.gpu.global.u32 %0, [%1];" : "=r"(v) : "l"(p) : "memory"); return v; }
__device__ __forceinline__ void bulk_pf(const void* src, uint32_t bytes) { asm volatile("cp.async.bulk.prefetch.L2.global [%0], %1;" ::"l"(src), "r"(bytes) : "memory"); }

__device__ __forceinline__ uint32_t wait_epoch(Misc& M) {
    uint32_t e = 0;
#pragma unroll 1
    for (int it = 0; it < (SPIN_MAX << 4) && e == 0; it++) e = *(volatile unsigned int*)&M.epoch;
    return e;
}
__device__ __forceinline__ void wait_reset(const unsigned int* ctr, uint32_t epoch) {
#pragma unroll 1
    for (int it = 0; it < SPIN_MAX; it++)
        if ((int)(ld_acq(ctr) - G_ * epoch) >= 0) break;
}
struct cplx { float x, y; };
__device__ __forceinline__ cplx cmul(cplx a, cplx b) { cplx r; r.x = a.x * b.x - a.y * b.y; r.y = a.x * b.y + a.y * b.x; return r; }
__device__ __forceinline__ cplx csq(cplx a) { cplx r; r.x = a.x * a.x - a.y * a.y; r.y = 2.0f * a.x * a.y; return r; }
__device__ __forceinline__ uint32_t hcm(uint32_t x, uint32_t y, uint32_t yp) {
    const __half2 X = *(const __half2*)&x, Y = *(const __half2*)&y, YP = *(const __half2*)&yp;
    const __half2 r = __hfma2(__high2half2(X), YP, __hmul2(__low2half2(X), Y));
    return *(const uint32_t*)&r;
}
__device__ __forceinline__ void ln_stats(float s1, float s2, float& meanb, float& rinv) {
    const float mean = s1 * (1.0f / D_);
    const float den = bfr(fsqrt(bfr(bfr(fmaxf(fmaf(-mean, mean, s2 * (1.0f / D_)), 0.f)) + 1e-5f)));
    meanb = bfr(mean);
    rinv = frcp(den);
}

__device__ __forceinline__ int fresh_tid() { int v; asm volatile("mov.u32 %0, %tid.x;" : "=r"(v)); return v; }
__device__ __forceinline__ void conv_channel(unsigned char* sm, Scratch* S, uint32_t gidx, uint32_t epoch, const void* pf_src,
                                             const CUtensorMap* tmu, int f0) {
    Misc& M = *(Misc*)(sm + OFF_MISC);
    const uint32_t sb = (uint32_t)__cvta_generic_to_shared(sm);
    const int tid = fresh_tid(), lane = tid & 31, g = lane >> 2, t = lane & 3, lr = lane & 7, lm = lane >> 3;
    const int warp_ = __shfl_sync(0xffffffffu, tid >> 5, 0), wgi = warp_ >> 2, w = warp_ & 3;
    const uint32_t cb = sb + OFF_CH + wgi * CHS, tag16 = (epoch % 65535u) + 1u;
    float D[16];
    uint32_t gaw, rcnt = 0;
    {
        {
            const uint32_t a8 = cb + lr * ULBO + (lm + 9) * 16 + w * 64, b8 = cb + XO_U8 + lm * 128 + lr * 16 + w * 512;
            const uint32_t a16 = cb + (((2 * lr) & 7) + (lm & 1)) * ULBO + (9 + (lr >> 2) + (lm & 2)) * 16 + w * 64;
            const uint32_t b16 = cb + XO_U16 + (lm & 1) * 512 + lr * 16 + (lm >> 1) * 128 + (w >> 1) * 1024 + (w & 1) * 256;
            uint32_t r[3][4];
            ldsm_x4_t(r[0], a8);
            ldsm_x4_t(r[1], a16);
            if (w < 2) ldsm_x4_t(r[2], a8 + 256);
            stsm_x4(b8, r[0][0], r[0][1], r[0][2], r[0][3]);
            stsm_x4(b16, r[1][0], r[1][1], r[1][2], r[1][3]);
            if (w < 2) stsm_x4(b8 + 2048, r[2][0], r[2][1], r[2][2], r[2][3]);
        }
        PROXY_FENCE();
        named_bar(1 + wgi, 128);
        {
            float Z8[24], Z16[16];
            const uint32_t pf = cb + XO_TF + (w >> 1) * 512 + (8 + 16 * (w & 1) + g - 2 * t) * 4;
            uint32_t p[13], q[9], z16[8];
#pragma unroll
            for (int s = 0; s < 9; s++) q[s] = lds32(pf + 1024 + s * 32);
            const uint32_t d8 = ((((cb + XO_U8) & 0x3FFFF) >> 4) | ((128 >> 4) << 16));
#define DZ(o) (((uint64_t)(512 >> 4) << 32) | (uint64_t)(d8 + (o)))
            WG_FENCE();
#pragma unroll
            for (int e = 0; e < 4; e++) {
                if (e == 0) wg32z(Z16, TQ(q, e), DZ(256 + 16));
                else wg32(Z16, TQ(q, e), DZ(256 - (e >> 1) * 64 + (1 - (e & 1)) * 16));
            }
            WG_COMMIT();
#pragma unroll
            for (int s = 0; s < 13; s++) p[s] = lds32(pf + s * 32);
            WG_WAIT(0);
#pragma unroll
            for (int i = 0; i < 8; i++) z16[i] = pack2(Z16[2 * i], Z16[2 * i + 1]);
            WG_FENCE();
#pragma unroll
            for (int e = 0; e < 6; e++) {
                if (e == 0) wg48z(Z8, TQ(p, e), DZ(16));
                else wg48(Z8, TQ(p, e), DZ(-(e >> 1) * 32 + (1 - (e & 1)) * 16));
            }
            WG_COMMIT();
            WG_WAIT(0);
            named_bar(1 + wgi, 128);
            const uint32_t za = cb + ((w >> 1) ? XO_ZB : XO_ZA) + lr * 400 + (1 + 2 * (w & 1) + (lm & 1) + 4 * (lm >> 1)) * 16;
#pragma unroll
            for (int i = 0; i < 3; i++)
                stsm_x4(za + i * 128, pack2(Z8[8 * i], Z8[8 * i + 1]), pack2(Z8[8 * i + 2], Z8[8 * i + 3]), pack2(Z8[8 * i + 4], Z8[8 * i + 5]), pack2(Z8[8 * i + 6], Z8[8 * i + 7]));
            const int Cz = 2 * (16 * (w & 1) + 8 * (lm & 1) + lr) + (lm >> 1);
            const uint32_t zc = cb + ((w >> 1) ? XO_ZD : XO_ZC) + (Cz & 7) * 272 + (1 + (Cz >> 3)) * 16;
#pragma unroll
            for (int ob = 0; ob < 2; ob++) stsm_x4(zc + ob * 128, z16[4 * ob], z16[4 * ob + 1], z16[4 * ob + 2], z16[4 * ob + 3]);
            if (lane < 8) *(uint4*)(sm + (cb - sb) + ((w < 2) ? (XO_ZA + w * 3200 + lane * 400) : (XO_ZC + (w - 2) * 2176 + lane * 272))) = make_uint4(0, 0, 0, 0);
        }
        gaw = ld_rlx(&S->modw[gidx]);
        if (tmu && wgi >= 2 && (tid & 127) == 96) {
            const uint32_t mbu = sb + OFF_MISC + (uint32_t)offsetof(Misc, mbar) + 24;
            if (wgi == 2) mbar_expect(mbu, 36864);
            tma2d(sb + OFF_WU + (wgi - 2) * 12288, tmu, f0, 192 * (wgi - 2), mbu);
        }
        __syncwarp();
        if ((tid & 127) == 64) rcnt = ld_rlx(S->cnt);
        {
#pragma unroll
            for (int i = 0; i < 16; i++) D[i] = 0.f;
            uint32_t pa = cb + XO_TD + (8 + 16 * w + g - 2 * t) * 4;
            uint32_t dlo = (((cb + 9 * 16) & 0x3FFFF) >> 4) | ((ULBO >> 4) << 16);
#define DS(o) (((uint64_t)(128 >> 4) << 32) | (uint64_t)(dlo + (o)))
#define KST (2 * (ULBO / 16))
            uint32_t pA[9], pB[9];
#pragma unroll
            for (int s = 0; s < 9; s++) pA[s] = lds32(pa + s * 32);
#pragma unroll 1
            for (int j = 0; j < 4; j++) {
                WG_FENCE();
#pragma unroll
                for (int q = 0; q < 4; q++) wg32(D, TQ(pA, q), DS((3 - q) * KST));
                WG_COMMIT();
                WG_WAIT(1);
#pragma unroll
                for (int s = 0; s < 9; s++) pB[s] = lds32(pa + 256 + s * 32);
                WG_FENCE();
#pragma unroll
                for (int q = 0; q < 4; q++) wg32(D, TQ(pB, q), DS((3 - q) * KST - 1));
                WG_COMMIT();
                WG_WAIT(1);
#pragma unroll
                for (int s = 0; s < 9; s++) pA[s] = lds32(pa + 512 + s * 32);
                dlo -= 2; pa += 512;
            }
            pB[1] = lds32(pa + 256 + 32); pB[2] = lds32(pa + 256 + 64);
            WG_FENCE();
#pragma unroll
            for (int q = 0; q < 4; q++) wg32(D, TQ(pA, q), DS((3 - q) * KST));
            wg32(D, pB[1], pB[2], pA[8], pB[1], DS(3 * KST - 1));
            WG_COMMIT();
        }
        if (tid == 128) bulk_pf(pf_src, 16 * D_ * 2);
        if ((tid & 127) == 64) {
#pragma unroll 1
            for (int it = 0; it < SPIN_MAX && (int)(rcnt - G_ * epoch) < 0; it++) rcnt = ld_rlx(S->cnt);
        }
    }
    {
        named_bar(1 + wgi, 128);
        {
            const uint4* pq = M.box + (6 + g - 2 * t);
#define QM(q) (q).x, (q).y, (q).z, (q).w
            uint32_t bA[2][6], bB[2][6], bC[3][4], bD[2][4], bU[2][4];
            const uint32_t k2 = lds32(cb + XO_K1024);
            uint32_t ofs[3];
#pragma unroll
            for (int d = 0; d < 3; d++) ofs[d] = cb + ((w - d) < 0 ? 0 : 16) + (lr + 8 * (lm >> 1)) * 16;
#define COL(d) (2 * ((w - (d)) & 3) + (lm & 1))
            WG_WAIT(0);
            uint4 m[4];
#pragma unroll
            for (int d = 0; d < 2; d++) {
                const uint32_t a = XO_ZA + COL(d) * 400 + ofs[d];
                ldsm_x4(bA[d], a); ldsm_x4(bB[d], a + 3200);
                uint32_t r[4];
                ldsm_x4(r, a + 256 + (lm >> 1) * (3200 - 128));
                bA[d][4] = r[0]; bA[d][5] = r[1]; bB[d][4] = r[2]; bB[d][5] = r[3];
            }
#pragma unroll
            for (int i = 0; i < 4; i++) m[i] = pq[14 * i];
#pragma unroll
            for (int d = 0; d < 2; d++)
#pragma unroll
                for (int c = 0; c < 3; c++) mma_bf16(D + 4 + 4 * c, QM(m[d]), bA[d][2 * c], bA[d][2 * c + 1]);
#pragma unroll
            for (int d = 0; d < 3; d++) ldsm_x4(bC[d], XO_ZC + COL(d) * 272 + ofs[d]);
#pragma unroll
            for (int d = 0; d < 2; d++)
#pragma unroll
                for (int c = 0; c < 3; c++) mma_bf16(D + 4 + 4 * c, QM(m[2 + d]), bB[d][2 * c], bB[d][2 * c + 1]);
#pragma unroll
            for (int i = 0; i < 3; i++) m[i] = pq[14 * (4 + i)];
#pragma unroll
            for (int d = 0; d < 2; d++) { ldsm_x4(bD[d], XO_ZD + COL(d) * 272 + ofs[d]); ldsm_x4(bU[d], COL(d) * ULBO + 128 + ofs[d]); }
#pragma unroll
            for (int d = 0; d < 3; d++)
#pragma unroll
                for (int c = 0; c < 2; c++) mma_bf16(D + 8 + 4 * c, QM(m[d]), bC[d][2 * c], bC[d][2 * c + 1]);
#pragma unroll
            for (int i = 0; i < 4; i++) m[i] = pq[14 * (7 + i)];
#pragma unroll
            for (int d = 0; d < 2; d++)
#pragma unroll
                for (int c = 0; c < 2; c++) mma_bf16(D + 8 + 4 * c, QM(m[d]), bD[d][2 * c], bD[d][2 * c + 1]);
#pragma unroll
            for (int d = 0; d < 2; d++) {
                m[2 + d].x &= k2; m[2 + d].y &= k2; m[2 + d].z &= k2; m[2 + d].w &= k2;
#pragma unroll
                for (int c = 0; c < 2; c++) mma_bf16(D + 8 + 4 * c, QM(m[2 + d]), bU[d][2 * c], bU[d][2 * c + 1]);
            }
        }
        {
#pragma unroll 1
            for (int it = 0; it < SPIN_MAX && (gaw >> 16) != tag16; it++) gaw = ld_rlx(&S->modw[gidx]);
            const uint32_t ga2 = __byte_perm(gaw, 0, 0x1010), dk2 = M.pk[3][wgi];
            const uint32_t ua = cb + (2 * w + (lm & 1)) * ULBO + (9 + lr + 8 * (lm >> 1)) * 16;
            const uint32_t ya = cb + XO_TD + w * 1024;
            const uint32_t sa = ya + (lr + 8 * (lm >> 1)) * 32 + (((lm & 1) ^ ((lane >> 2) & 1)) << 4);
#pragma unroll
            for (int cc = 0; cc < 2; cc++) {
                uint32_t u[4], v[4];
                ldsm_x4_t(u, ua + cc * 256);
#pragma unroll
                for (int m = 0; m < 4; m++) {
                    const int c = 2 * cc + (m >> 1), h = m & 1;
                    v[m] = ~mul2(ga2, add2(pack2(D[4 * c + 2 * h], D[4 * c + 2 * h + 1]), mul2(u[m], dk2)));
                }
                stsm_x4_t(sa + cc * 512, v[0], v[1], v[2], v[3]);
            }
            __syncwarp();
            const int sw = (lane >> 3) & 1;
            const uint32_t vo = (uint32_t)(((4 * (lane >> 1) + w) * D_ + gidx - 2 * D_) * 32 + (lane & 1) * 16);
            const unsigned char* yp = sm + (ya - sb) + (lane >> 1) * 32 + (lane & 1) * 8;
#pragma unroll
            for (int i = 0; i < 2; i++) {
                const uint2 A = *(const uint2*)(yp + i * 512 + (sw << 4)), B = *(const uint2*)(yp + i * 512 + ((sw ^ 1) << 4));
                st_rlx4((char*)S->v + vo + i * (64 * D_ * 32), make_uint4(A.x, B.x, A.y, B.y));
            }
        }
    }
}

__global__ void __launch_bounds__(NTHR, 1)
mega_kernel(const bf16* __restrict__ x, const bf16* __restrict__ logAr, const bf16* __restrict__ Aim,
            const bf16* __restrict__ Cr, const bf16* __restrict__ Ci, const bf16* __restrict__ logdt, const bf16* __restrict__ c_in,
            Scratch* __restrict__ S, const bf16* __restrict__ Dskip, const bf16* __restrict__ w_r, const bf16* __restrict__ w_down,
            bf16* __restrict__ out,
            const __grid_constant__ CUtensorMap tm_wm, const __grid_constant__ CUtensorMap tm_wg, const __grid_constant__ CUtensorMap tm_wu,
            const __grid_constant__ CUtensorMap tm_wd, const __grid_constant__ CUtensorMap tm_wd32,
            const __grid_constant__ CUtensorMap tm_wg32, const __grid_constant__ CUtensorMap tm_wu32) {
    extern __shared__ __align__(1024) unsigned char sm[];
    Misc& M = *(Misc*)(sm + OFF_MISC);
    const uint32_t sb = (uint32_t)__cvta_generic_to_shared(sm);
    const int tid = threadIdx.x, warp = __shfl_sync(0xffffffffu, tid >> 5, 0), lane = tid & 31;
    const int g = lane >> 2, t = lane & 3, lr = lane & 7, lm = lane >> 3;
    const int wgi = warp >> 2, w = warp & 3;
    const int b = blockIdx.x;
    const int nch = 5 - (b & 1), cs = 9 * (b >> 1) + 5 * (b & 1);
    const int f0 = 72 * (b >> 1) + 32 * (b & 1), nf = 32 + 8 * (b & 1);
    const bool has_ch = wgi < nch;
    const uint32_t mb0 = sb + OFF_MISC + offsetof(Misc, mbar), mb_wm = mb0, mb_wg = mb0 + 16, mb_wu = mb0 + 24, mb_wd = mb0 + 32;
    const uint32_t cb = sb + OFF_CH + wgi * CHS;

    if (wgi == 3) {
        M.sent[tid - 384] = make_uint4(SENT, SENT, SENT, SENT);
        M.sent[tid - 256] = make_uint4(SENT, SENT, SENT, SENT);
        if (tid == 384) {
            M.epoch = 0u; M.flag = 0u; M.e1cnt = 0u;
#pragma unroll
            for (int i = 0; i < 5; i++) mbar_init(mb0 + 8 * i, 1);
        }
        PROXY_FENCE();
        __syncwarp();
        if (warp == 12) { named_arrive(8, 160); if (b & 1) named_arrive(14, 64); }
        if (warp != 15) named_arrive(9, 128);
    }
    unsigned short r_ldt = 0, r_lar = 0, r_aim = 0, r_cr = 0, r_ci = 0;
    if (has_ch) {
        const int d = cs + wgi, n = d * N_ + (tid & 127);
        r_ldt = ld_nc16((const unsigned short*)logdt + d);
        r_lar = ld_nc16((const unsigned short*)logAr + n);
        r_aim = ld_nc16((const unsigned short*)Aim + n);
        r_cr = ld_nc16((const unsigned short*)Cr + n);
        r_ci = ld_nc16((const unsigned short*)Ci + n);
    } else {
        const unsigned short* cp = (const unsigned short*)c_in + (tid - 512);
        r_ldt = ld_nc16(cp); r_lar = ld_nc16(cp + 128); r_aim = ld_nc16(cp + 256); r_cr = ld_nc16(cp + 384);
        if (tid < 576) r_ci = ld_nc16(cp + 512);
    }
    uint4 xr[9];
    if (wgi == 4) {
        const uint4* p = (const uint4*)(x + (size_t)16 * b * D_) + (tid - 512);
#pragma unroll
        for (int i = 0; i < 9; i++) xr[i] = ld_nc4(p + 128 * i);
    }
    uint32_t wrv = 0;
    if (tid >= 128 && tid < 416) wrv = ld_nc((const uint32_t*)w_r + (tid - 128));
    if (warp == 2 && lane < nch) M.pk[3][lane] = (uint32_t)ld_nc16((const unsigned short*)Dskip + cs + lane) * 0x10001u;
    if (tid == 384) {
        const unsigned int tk = atomicAdd(S->ticket, 1u);
        *(volatile unsigned int*)&M.epoch = (tk >> 7) + 1u;
    }
    if (has_ch) {
        for (int i = tid & 127; i < 296; i += 128) *(uint4*)(sm + OFF_CH + wgi * CHS + XO_TD + i * 16) = make_uint4(0, 0, 0, 0);
    }
    if (tid < 154) {
        const int idx = (tid * 4682) >> 16, dl = tid - 14 * idx - 6;
        const int a = (0x44332221100ull >> (4 * idx)) & 7, d = (0x10102101010ull >> (4 * idx)) & 3;
        const int lo = (0x35c36 >> (4 * a)) & 15, wd = (0x16824 >> (4 * a)) & 15;
        const uint32_t one = (a == 4) ? 0xFFFFu : 0x3F80u;
        auto mk = [&](int l) { return (((unsigned)(l - lo) <= (unsigned)wd) ? one : 0u) | (((unsigned)(l - 1 - lo) <= (unsigned)wd) ? (one << 16) : 0u); };
        const int l0 = 16 * d + dl;
        M.box[tid] = make_uint4(mk(l0), mk(l0 + 8), mk(l0 - 8), mk(l0));
    }
    uint32_t xo[6];
#pragma unroll
    for (int i = 0; i < 6; i++) {
        const int ch = 16 * (warp + 16 * (i >> 1)) + 8 * (i & 1) + g;
        const int pr = (ch * 7282) >> 16, rm = ch - 9 * pr, hi = rm >= 5;
        xo[i] = (uint32_t)((((2 * pr + hi) * G_ + b) * 5 + rm - 5 * hi) * 32 + t * 8);
    }
    auto e1_store = [&]() {
        named_bar(11, 640);
        uint32_t mm[2], rhh[2], rll[2];
#pragma unroll
        for (int h = 0; h < 2; h++) {
            mm[h] = ((const uint32_t*)M.st1[0])[t + 4 * h]; rhh[h] = ((const uint32_t*)M.st1[1])[t + 4 * h]; rll[h] = ((const uint32_t*)M.st1[2])[t + 4 * h];
        }
        const uint32_t ta = sb + OFF_TILE + (lr + 8 * (lm & 1)) * (ROWP * 2) + (lm >> 1) * 16 + warp * 32;
#pragma unroll
        for (int i = 0; i < 3; i++) {
            if (i < 2 || warp < 4) {
                uint32_t r[4];
                ldsm_x4_t(r, ta + i * 512);
#pragma unroll
                for (int h = 0; h < 2; h++)
                    st_rlx2((char*)S->xn + xo[2 * i + h], ~norm2(r[2 * h], mm[0], rhh[0], rll[0]), ~norm2(r[2 * h + 1], mm[1], rhh[1], rll[1]));
            }
        }
        __syncwarp();
        if (lane == 0 && atomicAdd(&M.e1cnt, 1u) == 15u) red_inc(S->hint);
    };
    const float p_ldt = lo2f(r_ldt), p_lar = lo2f(r_lar), p_aim = lo2f(r_aim), p_cr = lo2f(r_cr), p_ci = lo2f(r_ci);
    cplx z1 = {0.f, 0.f}, z16 = z1, z256 = z1, C = z1;
    const uint32_t scr = cb + w * KSCR, ws = scr + lane * 4;
    float acc[5][4];
    uint32_t afr[4][4], cz[4];
    cplx z2 = {0.f, 0.f};
    const uint32_t ba = scr + lr * 144 + lm * 16;
    auto tile = [&](float* c, int rg) {
        __syncwarp();
        c[0] = c[1] = c[2] = c[3] = 0.f;
        uint32_t bb[2][4];
        ldsm_x4(bb[0], ba + rg * 1152);
        ldsm_x4(bb[1], ba + rg * 1152 + 64);
        mma_f16(c, afr[0], bb[0][0], bb[0][1]);
        mma_f16(c, afr[1], bb[0][2], bb[0][3]);
        mma_f16(c, afr[2], bb[1][0], bb[1][1]);
        mma_f16(c, afr[3], bb[1][2], bb[1][3]);
    };
#define CJ(z) packh((z).x, -(z).y)
#define CJP(z) packh((z).y, (z).x)
    uint32_t ex = 0;
    if (has_ch) {
        const float dt = bfr(expf(p_ldt));
        const float al = -bfr(expf(p_lar)) * dt * 1.4426950408889634f;
        const float th = p_aim * dt;
        const float th_ = th * 0.15915494309189535f;
        const float tl_ = fmaf(th, 0.15915494309189535f, -th_) + th * 6.4206382e-9f;
        auto anchor = [&](float s) {
            float f = th_ * s;
            f -= rintf(f);
            f = fmaf(tl_, s, f) * 6.283185307179586f;
            const float e = fex2(al * s);
            return cplx{e * __cosf(f), e * __sinf(f)};
        };
        const float cx = p_cr * dt * 2.0f, cy = p_ci * dt * 2.0f;
        ex = __reduce_max_sync(0xffffffffu, __float_as_uint(fmaxf(fabsf(cx), fabsf(cy)))) >> 23;
        const float scl = __uint_as_float((254u - ex) << 23);
        C = cplx{cx * scl, cy * scl};
        z1 = anchor(1.f); z16 = anchor(16.f); z256 = anchor(256.f);
            {
                const cplx z32 = csq(z16), z48 = cmul(z32, z16), z64 = csq(z32), z128 = csq(z64), z192 = cmul(z128, z64);
                const uint32_t y[3] = {packh(z16.x, z16.y), packh(z32.x, z32.y), packh(z48.x, z48.y)};
                const uint32_t yp[3] = {packh(-z16.y, z16.x), packh(-z32.y, z32.x), packh(-z48.y, z48.x)};
                const uint32_t xx[3] = {packh(z64.x, z64.y), packh(z128.x, z128.y), packh(z192.x, z192.y)};
                sts32(ws, 0x00003C00u);
#pragma unroll
                for (int j = 0; j < 3; j++) sts32(ws + (1 + j) * 144, y[j]);
#pragma unroll
                for (int i = 0; i < 3; i++) {
                    sts32(ws + (4 + 4 * i) * 144, xx[i]);
#pragma unroll
                    for (int j = 0; j < 3; j++) sts32(ws + (5 + 4 * i + j) * 144, hcm(xx[i], y[j], yp[j]));
                }
            }
    }
    if (wgi == 4) {
        if (!has_ch) {
            const int i = tid - 512;
            ((unsigned short*)M.sc)[i] = (unsigned short)f2bits(silu(lo2f(r_ldt)));
            ((unsigned short*)M.sc)[i + 128] = (unsigned short)f2bits(silu(lo2f(r_lar)));
            ((unsigned short*)M.sc)[i + 256] = (unsigned short)f2bits(silu(lo2f(r_aim)));
            ((unsigned short*)M.sc)[i + 384] = (unsigned short)f2bits(silu(lo2f(r_cr)));
            if (i < 64) ((unsigned short*)M.sc)[i + 512] = (unsigned short)f2bits(silu(lo2f(r_ci)));
            if (warp == 16) {
                named_bar(14, 64);
                if (lane == 0) {
                    mbar_expect(mb_wm, 36864);
#pragma unroll
                    for (int k = 0; k < 3; k++) tma2d(sb + OFF_WU + k * 12288, &tm_wm, 32 * (b >> 1), 192 * k, mb_wm);
                }
                __syncwarp();
            }
        }
#pragma unroll
        for (int i = 0; i < 9; i++) {
            const int c = tid - 512 + 128 * i, rr = (c * 911) >> 16;
            *(uint4*)(sm + OFF_TILE + rr * (ROWP * 2 - 1152) + c * 16) = xr[i];
        }
        named_bar(8, 160);
        {
            float c1[4] = {0.f, 0.f, 0.f, 0.f}, cl[4] = {0.f, 0.f, 0.f, 0.f}, chh[4] = {0.f, 0.f, 0.f, 0.f};
            const uint32_t a0 = sb + OFF_TILE + (lane & 15) * (ROWP * 2) + (lane >> 4) * 16 + w * 288;
            uint32_t a[9][4];
#pragma unroll
            for (int ks = 0; ks < 9; ks++) ldsm_x4(a[ks], a0 + ks * 32);
#pragma unroll
            for (int ks = 0; ks < 9; ks++) {
                mma_bf16(c1, a[ks][0], a[ks][1], a[ks][2], a[ks][3], 0x3F803F80u, 0x3F803F80u);
                mma_bf16(cl, a[ks][0], a[ks][1], a[ks][2], a[ks][3], a[ks][0], a[ks][2]);
                mma_bf16(chh, a[ks][0], a[ks][1], a[ks][2], a[ks][3], a[ks][1], a[ks][3]);
            }
            if (t == 0) { M.p1[g][w] = c1[0]; M.p1[g + 8][w] = c1[2]; }
            if (t == (g >> 1)) { M.p2[g][w] = (g & 1) ? cl[1] : cl[0]; M.p2[g + 8][w] = (g & 1) ? chh[3] : chh[2]; }
        }
        named_bar(5, 128);
        if (warp == 16) {
            const float4 q1 = *(const float4*)M.p1[lane & 15], q2 = *(const float4*)M.p2[lane & 15];
            float meanb, rinv;
            ln_stats((q1.x + q1.y) + (q1.z + q1.w), (q2.x + q2.y) + (q2.z + q2.w), meanb, rinv);
            const float rh = bfr(rinv);
            if (lane < 16) { M.st1[0][lane] = (unsigned short)f2bits(meanb); M.st1[1][lane] = (unsigned short)f2bits(rh); M.st1[2][lane] = (unsigned short)f2bits(rinv - rh); }
        }
        __syncwarp();
        named_arrive(11, 640);
    }
    auto publish_reset = [&]() {
        if (tid == 480) {
            asm volatile("cp.async.bulk.wait_group 0;" ::: "memory");
            asm volatile("fence.proxy.async;" ::: "memory");
            red_inc(S->cnt);
        }
    };
    uint32_t epoch = 0, tag16 = 0, pre = 0;
    auto mod_tile = [&](int rd) {
        const uint32_t* s2 = (const uint32_t*)M.sc + 144 * (w >> 1) + t;
        uint32_t bb[18][2];
#pragma unroll
        for (int ks = 0; ks < 18; ks++) { bb[ks][0] = (g == 0) ? s2[8 * ks] : 0u; bb[ks][1] = (g == 0) ? s2[8 * ks + 4] : 0u; }
        float acc[2][4] = {{0.f, 0.f, 0.f, 0.f}, {0.f, 0.f, 0.f, 0.f}};
        const int row = lr + 8 * (lm >> 1);
        const uint32_t wa = sb + OFF_WU + (288 * (w >> 1) + row) * 64 + ((((2 * (w & 1) + (lm & 1)) ^ (row >> 1)) & 3) << 4);
        mbar_wait(mb_wm + 8 * rd, 0);
        if (rd == 0)
#pragma unroll
        for (int kb = 0; kb < 2; kb++) {
            uint32_t a[9][4];
#pragma unroll
            for (int ks = 0; ks < 9; ks++) ldsm_x4_t(a[ks], wa + (9 * kb + ks) * 1024);
#pragma unroll
            for (int ks = 0; ks < 9; ks++) mma_bf16(acc[ks & 1], a[ks][0], a[ks][1], a[ks][2], a[ks][3], bb[9 * kb + ks][0], bb[9 * kb + ks][1]);
        }
        const float v0 = acc[0][0] + acc[1][0], v1 = acc[0][2] + acc[1][2];
        float* mx = M.modx + 16 * (w & 1) + g;
        if (w >= 2 && t == 0) { mx[0] = v0; mx[8] = v1; }
        named_bar(5, 128);
        if (w < 2 && t == 0) {
            unsigned int* mp = &S->modw[32 * ((b >> 1) + 64 * rd) + 16 * w + g];
            st_rlx(mp, f2bits(v0 + mx[0]) | (tag16 << 16));
            st_rlx(mp + 8, f2bits(v1 + mx[8]) | (tag16 << 16));
        }
        if (rd == 0 && w < 2 && b < 108) {
            named_bar(7, 64);
            if (tid == 512) red_inc(S->hint);
        }
    };
    if (has_ch) {
        {
            z2 = csq(z1);
            const cplx z3 = cmul(z2, z1), z4 = csq(z2), z8 = csq(z4);
            const cplx c4 = cmul(C, z4), c8 = cmul(C, z8), c12 = cmul(c8, z4);
            cz[0] = packh(C.x, -C.y); cz[1] = packh(c4.x, -c4.y); cz[2] = packh(c8.x, -c8.y); cz[3] = packh(c12.x, -c12.y);
            __syncwarp();
#pragma unroll
            for (int s = 0; s < 4; s++) ldsm_x4(afr[s], scr + (lr + 8 * (lm & 1)) * 144 + (2 * s + (lm >> 1)) * 16);
            {
                const uint32_t y[3] = {CJ(z1), CJ(z2), CJ(z3)}, yp[3] = {CJP(z1), CJP(z2), CJP(z3)};
#pragma unroll
                for (int tt = 0; tt < 2; tt++) {
                    const int rg = tt ? 0 : 2;
#pragma unroll
                    for (int i = 0; i < 2; i++) {
                        sts32(ws + rg * 1152 + (4 * i) * 144, cz[2 * tt + i]);
#pragma unroll
                        for (int j = 0; j < 3; j++) sts32(ws + rg * 1152 + (4 * i + 1 + j) * 144, hcm(cz[2 * tt + i], y[j], yp[j]));
                    }
                    tile(acc[tt], rg);
                }
            }
            if (tid >= 128 && tid < 416) M.wr[tid - 128] = wrv;
            if (wgi < 4) e1_store();
    if (warp == 15) {
        named_bar(9, 128);
        if (lane == 0) {
#pragma unroll 1
            for (int i = 0; i < 5; i++) {
                bulk_s2g((char*)&S->v[(size_t)b * 1152] + i * 4096, sb + OFF_MISC, i < 4 ? 4096 : 2048);
                if (i < 3) bulk_s2g((char*)&S->part[(size_t)b * 1152] + i * 4096, sb + OFF_MISC, i < 2 ? 4096 : 1024);
            }
            bulk_s2g(&S->rec[8 * b], sb + OFF_MISC, 32);
            asm volatile("cp.async.bulk.commit_group;" ::: "memory");
        }
        __syncwarp();
    }
            const cplx z258 = cmul(z256, z2), z512 = csq(z256), z768 = cmul(z512, z256);
            {
                const uint32_t a0 = CJ(z256), a0p = CJP(z256), a1 = CJ(z258), a1p = CJP(z258);
#pragma unroll
                for (int i = 0; i < 4; i++) { sts32(ws + 1152 + (2 * i) * 144, hcm(cz[i], a0, a0p)); sts32(ws + 1152 + (2 * i + 1) * 144, hcm(cz[i], a1, a1p)); }
                tile(acc[2], 1);
            }
            {
                const uint32_t a0 = CJ(z512), a0p = CJP(z512), a1 = CJ(z768), a1p = CJP(z768);
#pragma unroll
                for (int i = 0; i < 4; i++) { sts32(ws + 2304 + i * 144, hcm(cz[i], a0, a0p)); sts32(ws + 2304 + (4 + i) * 144, hcm(cz[i], a1, a1p)); }
                tile(acc[3], 2);
            }
            if (warp == 3) {
                if (lane == 15) pre = ld_rlx(S->hint);
            }
            const cplx z1024 = csq(z512);
            {
                const cplx zk[4] = {z1024, cmul(z1024, z256), csq(z768), cmul(z1024, z768)};
#pragma unroll
                for (int h = 0; h < 4; h++) {
                    const uint32_t a0 = CJ(zk[h]), a0p = CJP(zk[h]);
                    sts32(ws + (2 * h) * 144, hcm(cz[0], a0, a0p));
                    sts32(ws + (2 * h + 1) * 144, hcm(cz[2], a0, a0p));
                }
                tile(acc[4], 0);
            }
            const cplx z2048 = csq(z1024);
            float last = C.x * z2048.x - C.y * z2048.y;
#pragma unroll
            for (int o = 16; o; o >>= 1) last += __shfl_xor_sync(0xffffffffu, last, o);
            __syncwarp();
#pragma unroll
            for (int i = 0; i < 5; i++) *(float4*)(sm + (scr - sb) + i * 512 + lane * 16) = make_float4(acc[i][0], acc[i][1], acc[i][2], acc[i][3]);
            if (lane == 0) { const float inv = __uint_as_float(ex << 23); M.kinv[wgi][w] = inv; M.klast[wgi][w] = last * inv; }
        }
        if (tid == 111 && (int)(pre - HINT_N * wait_epoch(M)) >= 0) M.flag = 1u;
        named_bar(1 + wgi, 128);
        const uint32_t td = cb + XO_TD + 64 * 4, tf = cb + XO_TF - 32 * 4;
        if (tid == 111 && !M.flag) pre = ld_rlx(S->hint);
        const float4 ki = *(const float4*)M.kinv[wgi];
        auto fsum = [&](int off, uint32_t& r0, uint32_t& r1) {
            const unsigned char* p = sm + (cb - sb) + off;
            const float4 a = *(const float4*)p, b2 = *(const float4*)(p + KSCR), c = *(const float4*)(p + 2 * KSCR), d = *(const float4*)(p + 3 * KSCR);
            r0 = pack2(fmaf(a.y, ki.x, b2.y * ki.y) + fmaf(c.y, ki.z, d.y * ki.w), fmaf(a.x, ki.x, b2.x * ki.y) + fmaf(c.x, ki.z, d.x * ki.w));
            r1 = pack2(fmaf(a.w, ki.x, b2.w * ki.y) + fmaf(c.w, ki.z, d.w * ki.w), fmaf(a.z, ki.x, b2.z * ki.y) + fmaf(c.z, ki.z, d.z * ki.w));
        };
        uint32_t r[2], q[2];
        fsum(w * 512 + lane * 16, r[0], r[1]);
        fsum(2048 + w * 128 + lr * 16, q[0], q[1]);
        if (tid == 111) {
            if ((int)(pre - HINT_N * M.epoch) >= 0) M.flag = 1u;
            else pre = ld_rlx(S->hint);
        }
        __syncwarp();
        if (w < 2) {
            const uint32_t p = td + (16 * g + 8 * w + 2 * t) * 4;
#pragma unroll
            for (int h = 0; h < 2; h++) { sts16(p + h * 512, r[h] >> 16); sts32(p + h * 512 + 4, r[h]); sts16(p + h * 512 + 10, r[h]); }
        } else if (w == 2) {
            const uint32_t p = td + (256 + 16 * g + 4 * t) * 4;
#pragma unroll
            for (int h = 0; h < 2; h++) {
                const uint32_t k0 = r[h] >> 16;
                if (h || lane) { sts16(p + h * 512 - 4, k0); sts16(p + h * 512 + 2, k0); }
                sts16(p + h * 512, k0); sts32(p + h * 512 + 4, __byte_perm(r[h], 0, 0x3232)); sts32(p + h * 512 + 8, r[h]); sts16(p + h * 512 + 14, r[h]);
            }
        } else {
            const uint32_t p = tf + (64 + 32 * (t >> 1) + 2 * g + (t & 1)) * 4;
#pragma unroll
            for (int h = 0; h < 2; h++) {
                const uint32_t k0 = r[h] >> 16;
                sts16(p + h * 64 + 512, r[h]); sts16(p + h * 64 + 518, r[h]);
                if (h || lane) { sts16(p + h * 64 - 4, k0); sts16(p + h * 64 + 2, k0); }
            }
            if (lane == 0) {
                const uint32_t dd = __byte_perm(r[0], 0, 0x3232);
                sts16(td + 511 * 4, dd); sts32(td + 512 * 4, dd); sts32(td + 513 * 4, dd); sts32(td + 514 * 4, dd); sts16(td + 515 * 4 + 2, dd);
            }
        }
        if (lane < 8) {
            const uint32_t p = tf + 1024 + (64 + 16 * t + 2 * w + g) * 4;
#pragma unroll
            for (int h = 0; h < 2; h++) {
                const uint32_t k0 = q[h] >> 16;
                sts16(p + h * 32 + 512, q[h]); sts16(p + h * 32 + 518, q[h]);
                if (h || (tid & 127)) { sts16(p + h * 32 - 4, k0); sts16(p + h * 32 + 2, k0); }
            }
            if ((tid & 127) == 0) {
                const float4 kl4 = *(const float4*)M.klast[wgi];
                const uint32_t kl = f2bits((kl4.x + kl4.y) + (kl4.z + kl4.w)), dd = __byte_perm(q[0], 0, 0x3232);
                sts16(tf + 127 * 4, dd); sts16(tf + 128 * 4 + 2, dd); sts32(cb + XO_K1024, dd);
                sts16(tf + 1024 + 127 * 4, kl); sts16(tf + 1024 + 128 * 4 + 2, kl);
            }
        }
        __syncwarp();
    } else {
        const int i = tid - 512, idx = b >> 1;
        tag16 = (wait_epoch(M) % 65535u) + 1u;
        mod_tile(0);
        if (i == 0 && idx < 44) {
            PROXY_FENCE();
            mbar_expect(mb_wm + 8, 36864);
#pragma unroll
            for (int k = 0; k < 3; k++) tma2d(sb + OFF_WU + k * 12288, &tm_wm, 32 * (idx + 64), 192 * k, mb_wm + 8);
        }
        __syncwarp();
    }
    if (tid == 111) {
        epoch = wait_epoch(M);
#pragma unroll 1
        for (int it = 0; it < SPIN_MAX && (int)(pre - HINT_N * epoch) < 0; it++) pre = ld_rlx(S->hint);
        M.flag = 1u;
    }
    __syncwarp();
    const int ubp = (tid * 13108) >> 16, uloc = tid - 5 * ubp;
    const uint4* usrc = &S->xn[(size_t)b * 1280 + 2 * tid];
    uint4 ua = make_uint4(0, 0, 0, 0), uc = ua;
    uint32_t usa = 0, uca = 0;
    if (lane == 0) {
#pragma unroll 1
        for (int it = 0; it < (SPIN_MAX << 4) && !M.flag; it++) { }
    }
    __syncwarp();
    if (uloc < nch) {
 ua = ld_rlx4(usrc); uc = ld_rlx4(usrc + 1); usa = ld_rlx(&S->modw[cs + uloc]); uca = ld_rlx(&S->modw[D_ + cs + uloc]); }
    CBAR();
    epoch = M.epoch;
    tag16 = (epoch % 65535u) + 1u;
    {
        const int bp = ubp, loc = uloc;
        if (loc < nch) {
            const uint4* src = usrc;
            uint4 a = ua, c = uc;
#pragma unroll 1
            for (int it = 0; it < SPIN_MAX && (a.x == SENT || a.z == SENT || c.x == SENT || c.z == SENT || (usa >> 16) != tag16 || (uca >> 16) != tag16); it++) {
                a = ld_rlx4(src); c = ld_rlx4(src + 1); usa = ld_rlx(&S->modw[cs + loc]); uca = ld_rlx(&S->modw[D_ + cs + loc]);
            }
            const uint32_t sa = __byte_perm(usa, 0, 0x1010), ca = pack2(1.0f + lo2f(uca), 1.0f + lo2f(uca));
            unsigned char* up = sm + OFF_CH + loc * CHS + ((2 * bp) & 7) * ULBO + ((bp >> 2) + 9) * 16;
            *(uint4*)up = make_uint4(add2(mul2(~a.x, ca), sa), add2(mul2(~a.z, ca), sa), add2(mul2(~c.x, ca), sa), add2(mul2(~c.z, ca), sa));
            *(uint4*)(up + ULBO) = make_uint4(add2(mul2(~a.y, ca), sa), add2(mul2(~a.w, ca), sa), add2(mul2(~c.y, ca), sa), add2(mul2(~c.w, ca), sa));
        }
        publish_reset();
        const int i = tid & 127;
        unsigned char* cp = sm + OFF_CH + wgi * CHS;
        *(uint4*)(cp + XO_U8 - 1024 + (i >> 6) * 4096 + (i & 63) * 16) = make_uint4(0, 0, 0, 0);
        if (i < 72) { const int c = (i * 57) >> 9; *(uint4*)(cp + c * ULBO + (i - 9 * c) * 16) = make_uint4(0, 0, 0, 0); }
    }
    PROXY_FENCE();
    CBAR();
    if (w == 2 && lane == 0) {
        bulk_s2g((char*)&S->xn[(size_t)b * 1280] + wgi * 4096, sb + OFF_MISC, 4096);
        asm volatile("cp.async.bulk.commit_group;" ::: "memory");
    }
        if (tid == 416) {
            mbar_expect(mb_wg, nf * D_ * 2);
            tma2d(sb + OFF_WG, (b & 1) ? &tm_wg : &tm_wg32, f0, 0, mb_wg);
        }
    if (tid == 96 || tid == 224) tma2d(sb + OFF_WG + (1 + (tid >> 7)) * (nf * 384), (b & 1) ? &tm_wg : &tm_wg32, f0, 192 * (1 + (tid >> 7)), mb_wg);
    if (has_ch) {
        __syncwarp();
        conv_channel(sm, S, 2 * D_ + cs + wgi, epoch, w_down + (size_t)f0 * D_, (b & 1) ? nullptr : &tm_wu32, f0);
    } else {
        const int idx = b >> 1;
        if (idx < 44) mod_tile(1);
        if (tid == 512) {
            PROXY_FENCE();
            mbar_expect(mb_wu, 46080);
#pragma unroll 1
            for (int i = 0; i < 3; i++) {
                tma2d(sb + OFF_WU + i * 15360, &tm_wu, f0, 192 * i, mb_wu);
                const long long c0 = clock64();
                int it = 0;
                while (clock64() - c0 < 1200 && ++it < 4096) { }
            }
            wait_reset(S->cnt, epoch);
        }
        named_bar(5, 128);
    }
    {
    const int tid = fresh_tid(), warp = __shfl_sync(0xffffffffu, tid >> 5, 0), lane = tid & 31;
    const int g = lane >> 2, t = lane & 3, lr = lane & 7, lm = lane >> 3;
    uint32_t v3 = 0, v4 = 0, v5 = 0;
    auto load_consts = [&]() {
        if (tid < D_) { v3 = ld_rlx(&S->modw[3 * D_ + tid]); v4 = ld_rlx(&S->modw[4 * D_ + tid]); v5 = ld_rlx(&S->modw[5 * D_ + tid]); }
    };
    if (tid == 0) bulk_pf(w_down + (size_t)(f0 + 16) * D_, (nf - 16) * D_ * 2);
    uint32_t x1[2][4], wr2[2][2];
    if (warp < 18) {
        const char* vp = (const char*)S->v + ((size_t)b * D_ + 32 * warp + g) * 32 + t * 8;
        uint2 v[4];
#pragma unroll
        for (int i = 0; i < 4; i++) v[i] = ld_rlx2(vp + i * 256);
#pragma unroll
        for (int j = 0; j < 2; j++) {
            const uint32_t* wp = M.wr + 16 * warp + 8 * j + t;
            wr2[j][0] = (g == 0) ? wp[0] : 0u;
            wr2[j][1] = (g == 0) ? wp[4] : 0u;
            ldsm_x4(x1[j], sb + OFF_TILE + (lr + 8 * (lm & 1)) * (ROWP * 2) + (lm >> 1) * 16 + warp * 64 + j * 32);
        }
#pragma unroll 1
        for (int it = 0; it < SPIN_MAX && ((v3 >> 16) != tag16 || (v4 >> 16) != tag16 || (v5 >> 16) != tag16); it++) load_consts();
        ((unsigned short*)M.sb)[tid] = (unsigned short)v3;
        ((unsigned short*)M.cb1)[tid] = (unsigned short)f2bits(1.0f + lo2f(v4));
        ((unsigned short*)M.gb)[tid] = (unsigned short)v5;
#pragma unroll 1
        for (int it = 0; it < SPIN_MAX; it++) {
            bool bad = false;
#pragma unroll
            for (int i = 0; i < 4; i++) if (v[i].x == SENT) { v[i] = ld_rlx2(vp + i * 256); bad = true; }
            if (!bad) break;
        }
        __syncwarp();
        float c1[4] = {0.f, 0.f, 0.f, 0.f}, cl[4] = {0.f, 0.f, 0.f, 0.f}, chh[4] = {0.f, 0.f, 0.f, 0.f};
#pragma unroll
        for (int j = 0; j < 2; j++) {
            x1[j][0] = add2(x1[j][0], movm(~v[2 * j].x)); x1[j][1] = add2(x1[j][1], movm(~v[2 * j].y));
            x1[j][2] = add2(x1[j][2], movm(~v[2 * j + 1].x)); x1[j][3] = add2(x1[j][3], movm(~v[2 * j + 1].y));
            mma_bf16(c1, x1[j][0], x1[j][1], x1[j][2], x1[j][3], 0x3F803F80u, 0x3F803F80u);
            mma_bf16(cl, x1[j][0], x1[j][1], x1[j][2], x1[j][3], x1[j][0], x1[j][2]);
            mma_bf16(chh, x1[j][0], x1[j][1], x1[j][2], x1[j][3], x1[j][1], x1[j][3]);
        }
        float* pp = (float*)&M.part[warp][g];
        if (t == 0) { pp[0] = c1[0]; pp[16] = c1[2]; }
        if (t == (g >> 1)) { pp[1] = (g & 1) ? cl[1] : cl[0]; pp[17] = (g & 1) ? chh[3] : chh[2]; }
    }
    CBAR();
    if (warp < 18) {
        const int tok = lane & 15, hf = lane >> 4;
        uint32_t kc[2][2][2];
#pragma unroll
        for (int j = 0; j < 2; j++)
#pragma unroll
            for (int q = 0; q < 2; q++) { kc[j][q][0] = ((const uint32_t*)M.cb1)[16 * warp + 8 * j + 4 * q + t]; kc[j][q][1] = ((const uint32_t*)M.sb)[16 * warp + 8 * j + 4 * q + t]; }
        named_bar(13, 608);
        uint32_t st[2][3];
#pragma unroll
        for (int h = 0; h < 2; h++) { const uint4 q = M.st2[g + 8 * h]; st[h][0] = q.x; st[h][1] = q.y; st[h][2] = q.z; }
        float rc[4] = {0.f, 0.f, 0.f, 0.f};
        uint32_t h2[2][4];
#pragma unroll
        for (int j = 0; j < 2; j++) {
#pragma unroll
            for (int r = 0; r < 4; r++) {
                h2[j][r] = add2(mul2(norm2(x1[j][r], st[r & 1][0], st[r & 1][1], st[r & 1][2]), kc[j][r >> 1][0]), kc[j][r >> 1][1]);
            }
            mma_bf16(rc, h2[j][0], h2[j][1], h2[j][2], h2[j][3], wr2[j][0], wr2[j][1]);
        }
        if (t == 0) { M.rp[warp][g] = rc[0]; M.rp[warp][g + 8] = rc[2]; }
        if (warp == 0) {
            named_bar(12, 576);
            float r = M.rp[9 * hf][tok];
#pragma unroll
            for (int i = 1; i < 9; i++) r += M.rp[9 * hf + i][tok];
            r += __shfl_xor_sync(0xffffffffu, r, 16);
            const uint32_t rbits = f2bits(r);
            const uint32_t key = 0x80000000u | ((rbits ^ ((rbits & 0x8000u) ? 0xFFFFu : 0x8000u)) << 11) | (uint32_t)(2047 - (16 * b + tok));
            int rank = 0;
#pragma unroll
            for (int j = 1; j < 16; j++) rank += __shfl_xor_sync(0xffffffffu, key, j) > key;
            if (lane < 16) { M.skey[rank] = key; M.rank[rank] = tok; }
            __syncwarp();
            if (lane < 2) st_rlx4(&S->rec[8 * b + 4 * lane], *(const uint4*)&M.skey[4 * lane]);
        } else named_arrive(12, 576);
#pragma unroll
        for (int j = 0; j < 2; j++) {
            uint32_t o[4];
#pragma unroll
            for (int r = 0; r < 4; r++) o[r] = add2(x1[j][r], mul2(((const uint32_t*)M.gb)[16 * warp + 8 * j + 4 * (r >> 1) + t], h2[j][r]));
            const uint32_t to = (lr + 8 * (lm & 1)) * (ROWP * 2) + (lm >> 1) * 16 + warp * 64 + j * 32;
            stsm_x4(sb + OFF_H2T + to, h2[j][0], h2[j][1], h2[j][2], h2[j][3]);
            stsm_x4(sb + OFF_TILE + to, o[0], o[1], o[2], o[3]);
        }
    } else if (warp == 19) {
        const int tok = lane & 15, hf = lane >> 4;
        float2 s = M.part[9 * hf][tok];
#pragma unroll
        for (int i = 1; i < 9; i++) { const float2 q = M.part[9 * hf + i][tok]; s.x += q.x; s.y += q.y; }
        s.x += __shfl_xor_sync(0xffffffffu, s.x, 16); s.y += __shfl_xor_sync(0xffffffffu, s.y, 16);
        float meanb, rinv;
        ln_stats(s.x, s.y, meanb, rinv);
        const float rh = bfr(rinv);
        if (lane < 16) M.st2[tok] = make_uint4(pack2(meanb, meanb), pack2(rh, rh), pack2(rinv - rh, rinv - rh), 0u);
        __syncwarp();
        named_arrive(13, 608);
    } else if (lane < 9) {
        PROXY_FENCE();
        if (lane == 0) mbar_expect(mb_wd, nf * D_ * 2);
        tma2d(sb + OFF_WD + lane * 5120, (b & 1) ? &tm_wd : &tm_wd32, 64 * lane, f0, mb_wd);
    }
    CBAR();
    uint32_t wf[9][4], wd[2][3][4];
    const int fmt = warp >> 2, fsl = warp & 3;
    auto load_wf = [&]() {
        mbar_wait(mb_wg, 0);
        mbar_wait(mb_wu, 0);
        if (fmt < 4 || nf > 32) {
            const int half = lm & 1;
            const uint32_t base = (fmt == 4) ? ((half ? OFF_WU : OFF_WG) + 64)
                                             : ((fmt >> 1) * OFF_WU + (((2 * (fmt & 1) + half) ^ ((b & 1) ? 0 : (lr >> 1))) << 4));
            const uint32_t wa = sb + base + (144 * fsl + lr + 8 * (lm >> 1)) * (2 * nf);
#pragma unroll
            for (int ks = 0; ks < 9; ks++) ldsm_x4_t(wf[ks], wa + ks * (32 * nf));
        }
    mbar_wait(mb_wd, 0);
    {
#pragma unroll
        for (int i = 0; i < 2; i++) {
            const int mt = warp + 20 * i;
            const uint32_t wa = sb + OFF_WD + (mt >> 2) * 5120 + lr * 128 + (((2 * (mt & 3) + (lm & 1)) ^ lr) << 4);
#pragma unroll
            for (int ks = 0; ks < 3; ks++)
                if ((i == 0 || warp < 16) && (ks < 2 || nf > 32)) ldsm_x4_t(wd[i][ks], wa + ks * 2048 + ((ks < 2) ? (lm >> 1) * 1024 : 0));
        }
    }
    };
    if (warp >= 8) {
        if (warp < 16) {
            const int tk = M.rank[warp - 8];
            const uint32_t* hp = (const uint32_t*)(sm + OFF_H2T + tk * (ROWP * 2)) + lane;
            uint4* dst = &S->h2w[(size_t)(16 * b + tk) * 96 + lane];
#pragma unroll
            for (int j = 0; j < 3; j++) st_rlx4(dst + 32 * j, make_uint4(hp[96 * j], hp[96 * j + 32], hp[96 * j + 64], epoch));
        }
        load_wf();
    } else {
        const uint4* rp = (const uint4*)S->rec + tid;
        load_wf();
        uint4 rk = ld_rlx4(rp);
#pragma unroll 1
        for (int it = 0; it < SPIN_MAX && !rk.x; it++) rk = ld_rlx4(rp);
        __syncwarp();
        uint32_t mine = 0;
#pragma unroll
        for (int rnd = 0; rnd < 8; rnd++) {
            const uint32_t m = __reduce_max_sync(0xffffffffu, rk.x);
            if (rk.x == m) { rk.x = rk.y; rk.y = rk.z; rk.z = rk.w; rk.w = 0u; }
            if (lane == rnd) mine = m;
        }
        if (lane < 8) M.cand[8 * warp + lane] = mine;
    }
    CBAR();
    uint32_t selv = 0;
    if (warp < 12) {
        uint2 k = *(const uint2*)&M.cand[2 * lane];
#pragma unroll
        for (int rnd = 0; rnd < 8; rnd++) {
            const uint32_t m = __reduce_max_sync(0xffffffffu, k.x);
            if (k.x == m) { k.x = k.y; k.y = 0u; }
            if (lr == rnd) selv = m;
        }
        if (tid < 8) M.skey[tid] = selv;
    }
    const uint32_t seltok = 2047u - (selv & 2047u);
    const int fo = tid >> 3;
    const int fW = 9 * b + (fo >> 2), fcomp = fo & 3;
    const int fd = 16 * (fW >> 5) + ((fW >> 2) & 7) + 8 * (fcomp >> 1), fk = 2 * (fW & 3) + (fcomp & 1);
    const uint32_t fsel = __shfl_sync(0xffffffffu, selv, fk);
    uint32_t fx = 0, fv = 0;
    bf16(*h2s)[ROWP] = (bf16(*)[ROWP])(sm + OFF_H2S);
    if (warp < 12) {
        uint4 wv[2];
        const uint4* hp[2];
#pragma unroll
        for (int r = 0; r < 2; r++) {
            const int wi = warp + 12 * r, k = wi / 3, j = wi - 3 * k;
            hp[r] = &S->h2w[(size_t)__shfl_sync(0xffffffffu, seltok, k) * 96 + 32 * j + lane];
            wv[r] = ld_rlx4(hp[r]);
        }
        if (tid < 288 && (tid & 7) == 0) {
            const uint32_t ft = 2047u - (fsel & 2047u), pr = (ft & 15u) >> 1;
            fx = ((const unsigned short*)x)[(size_t)ft * D_ + fd];
            asm volatile("ld.relaxed.gpu.global.u16 %0, [%1];" : "=r"(fv)
                         : "l"((const unsigned short*)S->v + ((size_t)(ft >> 4) * D_ + fd) * 16 + ((pr & 3u) * 2 + (pr >> 2)) * 2 + (ft & 1u)) : "memory");
        }
#pragma unroll 1
        for (int it = 0; it < SPIN_MAX && (wv[0].w != epoch || wv[1].w != epoch); it++) { wv[0] = ld_rlx4(hp[0]); wv[1] = ld_rlx4(hp[1]); }
#pragma unroll
        for (int r = 0; r < 2; r++) {
            const int wi = warp + 12 * r, k = wi / 3, j = wi - 3 * k;
            uint32_t* dst = (uint32_t*)&h2s[k][0] + 96 * j + lane;
            dst[0] = wv[r].x; dst[32] = wv[r].y; dst[64] = wv[r].z;
        }
    }
    CBAR();
    float* ffr = (float*)(sm + OFF_FFR);
    if (fmt < 4 || nf > 32) {
        float acc[2][4] = {{0.f, 0.f, 0.f, 0.f}, {0.f, 0.f, 0.f, 0.f}};
        const uint32_t ha = sb + OFF_H2S + lr * (ROWP * 2) + (144 * fsl) * 2 + lm * 16;
#pragma unroll
        for (int k2 = 0; k2 < 5; k2++) {
            uint32_t hb[4];
            ldsm_x4(hb, ha + k2 * 64 - ((k2 == 4) ? (lm >> 1) * 32 : 0));
            mma_bf16(acc[0], wf[2 * k2][0], wf[2 * k2][1], wf[2 * k2][2], wf[2 * k2][3], hb[0], hb[1]);
            if (k2 < 4) mma_bf16(acc[1], wf[2 * k2 + 1][0], wf[2 * k2 + 1][1], wf[2 * k2 + 1][2], wf[2 * k2 + 1][3], hb[2], hb[3]);
        }
        float* o = ffr + ((fsl * 80 + 16 * fmt + g) * 8 + 2 * t);
        *(float2*)o = make_float2(acc[0][0] + acc[1][0], acc[0][1] + acc[1][1]);
        *(float2*)(o + 64) = make_float2(acc[0][2] + acc[1][2], acc[0][3] + acc[1][3]);
    }
    CBAR();
    bf16(*act)[56] = (bf16(*)[56])(sm + OFF_ACT);
    if (tid < 384) {
        const int f = tid >> 3, a = tid & 7;
        float v = 0.f;
        if (f < nf) {
            const int rg = (f < 32) ? f : f + 32, ru = (f < 32) ? f + 32 : f + 40;
            const float* pg = ffr + rg * 8 + a;
            const float* pu = ffr + ru * 8 + a;
            float gg = bfr((pg[0] + pg[640]) + (pg[1280] + pg[1920]));
            gg = bfr(silu(gg));
            const float uu = bfr((pu[0] + pu[640]) + (pu[1280] + pu[1920]));
            v = gg * uu;
        }
        act[a][f] = __ushort_as_bfloat16((unsigned short)f2bits(v));
    }
    CBAR();
    {
        uint32_t bq[3][2];
#pragma unroll
        for (int ks = 0; ks < 3; ks++) {
            bq[ks][0] = *(const uint32_t*)&act[g][16 * ks + 2 * t];
            bq[ks][1] = *(const uint32_t*)&act[g][16 * ks + 2 * t + 8];
        }
#pragma unroll
        for (int i = 0; i < 2; i++) {
            if (i == 0 || warp < 16) {
                float acc[4] = {0.f, 0.f, 0.f, 0.f};
#pragma unroll
                for (int ks = 0; ks < 3; ks++)
                    if (ks < 2 || nf > 32) mma_bf16(acc, wd[i][ks][0], wd[i][ks][1], wd[i][ks][2], wd[i][ks][3], bq[ks][0], bq[ks][1]);
                const int W = (warp + 20 * i) * 32 + lane, c = (W * 7282) >> 16;
                st_rlx2(&S->part[(c * G_ + b) * 9 + W - 9 * c], ~pack2(acc[0], acc[1]), ~pack2(acc[2], acc[3]));
            }
        }
    }
    if (warp >= 4) {
        const int tk = warp - 4;
        if (!__any_sync(0xffffffffu, 2047u - (M.skey[lr] & 2047u) == (uint32_t)(16 * b + tk))) {
            const uint4* src = (const uint4*)(sm + OFF_TILE + tk * (ROWP * 2));
            uint4* dst = (uint4*)(out + (size_t)(16 * b + tk) * D_);
            dst[lane] = src[lane]; dst[lane + 32] = src[lane + 32];
            if (lane < 8) dst[lane + 64] = src[lane + 64];
        }
    }
    float4* fin = (float4*)(sm + OFF_FIN);
    uint32_t rb = (fsel >> 11) & 0xFFFFu;
    rb ^= (rb & 0x8000u) ? 0x8000u : 0xFFFFu;
    const float rs = bfr(__fdividef(1.0f, 1.0f + __expf(-lo2f(rb))));
    const float fh2 = (tid < 288) ? __bfloat162float(h2s[fk][fd]) : 0.f, fgb = (tid < 288) ? __bfloat162float(M.gb[fd]) : 0.f;
    const float fx1 = bfr(lo2f(fx) + lo2f(~fv));
    if (tid < 576) {
        const uint2* src = &S->part[(size_t)b * 1152 + tid];
        uint2 a = ld_rlx2(src), c = ld_rlx2(src + 576);
#pragma unroll 1
        for (int it = 0; it < SPIN_MAX && (a.x == SENT || c.x == SENT); it++) {
            if (a.x == SENT) a = ld_rlx2(src);
            if (c.x == SENT) c = ld_rlx2(src + 576);
        }
        fin[tid] = make_float4(lo2f(~a.x) + lo2f(~c.x), hi2f(~a.x) + hi2f(~c.x), lo2f(~a.y) + lo2f(~c.y), hi2f(~a.y) + hi2f(~c.y));
    }
    CBAR();
    if (tid < 288) {
        const int part = tid & 7;
        const float* f = (const float*)fin + part * 36 + fo;
        float s = ((f[0] + f[288]) + (f[576] + f[864])) + ((f[1152] + f[1440]) + (f[1728] + f[2016]));
        s += __shfl_xor_sync(0xffffffffu, s, 1);
        s += __shfl_xor_sync(0xffffffffu, s, 2);
        s += __shfl_xor_sync(0xffffffffu, s, 4);
        const float upd = bfr(bfr(s) * rs);
        const float ov = fx1 + bfr(fgb * bfr(fh2 + upd));
        if (part == 0) out[(size_t)(2047u - (fsel & 2047u)) * D_ + fd] = __ushort_as_bfloat16((unsigned short)f2bits(ov));
    }
    if ((warp & 3) == 2 && lane == 0) asm volatile("cp.async.bulk.wait_group 0;" ::: "memory");
    }
}

typedef CUresult (*EncodeFn)(CUtensorMap*, CUtensorMapDataType, cuuint32_t, void*, const cuuint64_t*, const cuuint64_t*,
                             const cuuint32_t*, const cuuint32_t*, CUtensorMapInterleave, CUtensorMapSwizzle,
                             CUtensorMapL2promotion, CUtensorMapFloatOOBfill);

static void make_map(EncodeFn fn, CUtensorMap* m, const void* ptr, uint64_t cols, uint64_t rows, uint32_t bc, uint32_t br,
                     CUtensorMapSwizzle sw) {
    cuuint64_t dims[2] = {cols, rows};
    cuuint64_t strides[1] = {cols * 2};
    cuuint32_t box[2] = {bc, br};
    cuuint32_t es[2] = {1, 1};
    CUresult rc = fn(m, CU_TENSOR_MAP_DATA_TYPE_BFLOAT16, 2, (void*)ptr, dims, strides, box, es, CU_TENSOR_MAP_INTERLEAVE_NONE,
                     sw, CU_TENSOR_MAP_L2_PROMOTION_NONE, CU_TENSOR_MAP_FLOAT_OOB_FILL_NONE);
    (void)rc;
}

static void launch(void* const* d_in, const int* in_sizes, int n_in, void* d_out, int out_size) {
    static EncodeFn enc = nullptr;
    static CUtensorMap tmm, tmg, tmu, tmd, tmd32, tmg32, tmu32;
    static Scratch* sp = nullptr;
    static const void* cached[4] = {nullptr, nullptr, nullptr, nullptr};
    if (!enc) {
        cudaDriverEntryPointQueryResult qr;
        void* fn = nullptr;
        cudaGetDriverEntryPoint("cuTensorMapEncodeTiled", &fn, cudaEnableDefault, &qr);
        enc = (EncodeFn)fn;
        cudaFuncSetAttribute(mega_kernel, cudaFuncAttributeMaxDynamicSharedMemorySize, SMEM_TOTAL);
        cudaGetSymbolAddress((void**)&sp, g_s);
    }
    if (cached[0] != d_in[13] || cached[1] != d_in[9] || cached[2] != d_in[10] || cached[3] != d_in[11]) {
        make_map(enc, &tmm, d_in[13], 6 * D_, D_, 32, 192, CU_TENSOR_MAP_SWIZZLE_64B);
        make_map(enc, &tmg, d_in[9], F_, D_, 40, 192, CU_TENSOR_MAP_SWIZZLE_NONE);
        make_map(enc, &tmu, d_in[10], F_, D_, 40, 192, CU_TENSOR_MAP_SWIZZLE_NONE);
        make_map(enc, &tmg32, d_in[9], F_, D_, 32, 192, CU_TENSOR_MAP_SWIZZLE_64B);
        make_map(enc, &tmu32, d_in[10], F_, D_, 32, 192, CU_TENSOR_MAP_SWIZZLE_64B);
        make_map(enc, &tmd, d_in[11], D_, F_, 64, 40, CU_TENSOR_MAP_SWIZZLE_128B);
        make_map(enc, &tmd32, d_in[11], D_, F_, 64, 32, CU_TENSOR_MAP_SWIZZLE_128B);
        cached[3] = d_in[11];
        cached[0] = d_in[13]; cached[1] = d_in[9]; cached[2] = d_in[10];
    }
    mega_kernel<<<G_, NTHR, SMEM_TOTAL>>>((const bf16*)d_in[0], (const bf16*)d_in[1], (const bf16*)d_in[2], (const bf16*)d_in[3],
                                          (const bf16*)d_in[4], (const bf16*)d_in[5], (const bf16*)d_in[12], sp, (const bf16*)d_in[6],
                                          (const bf16*)d_in[8], (const bf16*)d_in[11], (bf16*)d_out, tmm, tmg, tmu, tmd, tmd32, tmg32, tmu32);
}

}

extern "C" void kernel_launch(void* const* d_in, const int* in_sizes, int n_in, void* d_out, int out_size) {
    static int mode = -1;
    if (mode < 0) mode = v5::fits() ? 1 : 0;
    if (mode) v5::launch(d_in, in_sizes, n_in, d_out, out_size);
    else v4::launch(d_in, in_sizes, n_in, d_out, out_size);
}
```

```cpp
#include <cuda_runtime.h>
#include <cuda.h>
#include <cuda_bf16.h>
#include <cuda_fp16.h>
#include <stdint.h>

namespace v5 {

#define L_ 2048
#define D_ 576
#define N_ 128
#define F_ 4608
#define G_ 120
#define NCL 15
#define NTHR 768
#define SPIN_MAX (1 << 18)

typedef __nv_bfloat16 bf16;

struct Scratch {
    float4 acc1[L_ + 8];
    float4 acc2[L_];
    uint4 h2c[137 * 72];
    float4 rs[39 * 8];
    float4 acc3[2 * 72 * 32 + 96];
};
#define NRS 124
static_assert(137 * 72 + 2 * 72 * 32 + 39 * 8 + 96 == NRS * G_, "16 B units cleared early in a launch (h2c, acc3, rs)");
__device__ __align__(1024) Scratch g_s;

#define OFF_WG 0
#define OFF_WU 46080
#define KSCR 3456
#define OFF_WM0 69120
#define OFF_STG OFF_WM0
#define OFF_MG2 86400
#define OFF_CH 92160
#define CHS 18688
#define UP 3808
#define UB 192
#define XO_TF 1216
#define XO_U8 2016
#define XO_U16 3328
#define XO_ZA 1232
#define XO_ZB 2016
#define XO_ZC 2800
#define XO_ZD 3328
#define XO_TD 16000
#define XO_K1024 18624
#define XO_DSK 18628
#define XO_KLAST 18656
#define XO_MBU 18672
#define OFF_X 185600
#define XG 672
#define XI(i) (((i) >> 1) * 5520 + ((i) & 1) * 2752)
#define XN(n) ((((n) >> 1) & 3) * XG + (2 * ((n) >> 3) + ((n) & 1)) * 80)
#define OFF_V 207616
#define VP 528
#define OFF_EK (OFF_V + 512)
#define OFF_WM2 OFF_V
#define OFF_MG1 (OFF_V + 17280)
#define OFF_SC (OFF_V + 19840)
#define OFF_C1 (OFF_V + 20640)
#define OFF_MISC 228736
#define OFF_WD OFF_CH
#define OFF_H2T (OFF_CH + 46080)
#define OFF_OUT (OFF_CH + 66560)
#define OFF_GB (OFF_CH + 87040)
#define OFF_AT (OFF_CH + 88064)
#define ROWP 584
#define OFF_H2S 0
#define OFF_FFR 9344
#define OFF_ACT 19584
#define OFF_RS 20480

enum { MB_WM2, MB_MG1, MB_MG2, MB_KEY, MB_V, MB_RS, MB_WG, MB_WU, MB_WD, MB_KEY2, MB_EK, MB_RS2, MB_V1, MB_V2, MB_C2, MB_CW, MB_KD, MB_CD, MB_OUT, MB_FIN, MB_N };

struct Misc {
    union {
        __align__(16) uint4 box[11 * 16];
        struct { unsigned int cand[128], key[256], cand2[128], sel[16]; };
    };
    __align__(16) uint4 c2[20];
    __align__(16) unsigned int fin[12];
    unsigned int ga[8], wr[20];
    float cws[2];
    unsigned long long mbar[MB_N];
};
#define SMEM_TOTAL (OFF_MISC + (int)sizeof(Misc))
static_assert(SMEM_TOTAL <= 232448, "smem");

__device__ __forceinline__ float lo2f(uint32_t w) { return __uint_as_float(w << 16); }
__device__ __forceinline__ float hi2f(uint32_t w) { return __uint_as_float(w & 0xFFFF0000u); }
__device__ __forceinline__ uint32_t pack2(float lo, float hi) { uint32_t r; asm("cvt.rn.bf16x2.f32 %0, %1, %2;" : "=r"(r) : "f"(hi), "f"(lo)); return r; }
__device__ __forceinline__ float bfr(float x) { return __uint_as_float(pack2(0.f, x)); }
__device__ __forceinline__ uint32_t f2bits(float x) { return pack2(x, 0.f); }
__device__ __forceinline__ uint32_t packh(float lo, float hi) { uint32_t r; asm("cvt.rn.f16x2.f32 %0, %1, %2;" : "=r"(r) : "f"(hi), "f"(lo)); return r; }
__device__ __forceinline__ float frcp(float x) { float r; asm("rcp.approx.ftz.f32 %0, %1;" : "=f"(r) : "f"(x)); return r; }
__device__ __forceinline__ float fsqrt(float x) { float r; asm("sqrt.approx.ftz.f32 %0, %1;" : "=f"(r) : "f"(x)); return r; }
__device__ __forceinline__ float fex2(float x) { float r; asm("ex2.approx.ftz.f32 %0, %1;" : "=f"(r) : "f"(x)); return r; }
__device__ __forceinline__ float sigm(float x) { return frcp(1.0f + fex2(x * -1.4426950408889634f)); }
__device__ __forceinline__ float silu(float x) { return x * sigm(x); }
__device__ __forceinline__ uint32_t add2(uint32_t a, uint32_t b) { uint32_t r; asm("add.rn.bf16x2 %0, %1, %2;" : "=r"(r) : "r"(a), "r"(b)); return r; }
__device__ __forceinline__ uint32_t sub2(uint32_t a, uint32_t b) { uint32_t r; asm("sub.rn.bf16x2 %0, %1, %2;" : "=r"(r) : "r"(a), "r"(b)); return r; }
__device__ __forceinline__ uint32_t mul2(uint32_t a, uint32_t b) { uint32_t r; asm("mul.rn.bf16x2 %0, %1, %2;" : "=r"(r) : "r"(a), "r"(b)); return r; }
__device__ __forceinline__ uint32_t fma2(uint32_t a, uint32_t b, uint32_t c) { uint32_t r; asm("fma.rn.bf16x2 %0, %1, %2, %3;" : "=r"(r) : "r"(a), "r"(b), "r"(c)); return r; }
__device__ __forceinline__ uint32_t norm2(uint32_t x, uint32_t m, uint32_t rh, uint32_t rl) { const uint32_t d = sub2(x, m); return fma2(d, rh, mul2(d, rl)); }

__device__ __forceinline__ void mma_bf16(float* c, uint32_t a0, uint32_t a1, uint32_t a2, uint32_t a3, uint32_t b0, uint32_t b1) {
    asm volatile("mma.sync.aligned.m16n8k16.row.col.f32.bf16.bf16.f32 {%0,%1,%2,%3}, {%4,%5,%6,%7}, {%8,%9}, {%0,%1,%2,%3};\n"
                 : "+f"(c[0]), "+f"(c[1]), "+f"(c[2]), "+f"(c[3]) : "r"(a0), "r"(a1), "r"(a2), "r"(a3), "r"(b0), "r"(b1));
}
__device__ __forceinline__ void mma_f16(float* c, const uint32_t* a, uint32_t b0, uint32_t b1) {
    asm volatile("mma.sync.aligned.m16n8k16.row.col.f32.f16.f16.f32 {%0,%1,%2,%3}, {%4,%5,%6,%7}, {%8,%9}, {%0,%1,%2,%3};\n"
                 : "+f"(c[0]), "+f"(c[1]), "+f"(c[2]), "+f"(c[3]) : "r"(a[0]), "r"(a[1]), "r"(a[2]), "r"(a[3]), "r"(b0), "r"(b1));
}
__device__ __forceinline__ void ldsm_x4(uint32_t* r, uint32_t addr) {
    asm volatile("ldmatrix.sync.aligned.m8n8.x4.shared.b16 {%0,%1,%2,%3}, [%4];" : "=r"(r[0]), "=r"(r[1]), "=r"(r[2]), "=r"(r[3]) : "r"(addr) : "memory");
}
__device__ __forceinline__ void ldsm_x4_t(uint32_t* r, uint32_t addr) {
    asm volatile("ldmatrix.sync.aligned.m8n8.x4.trans.shared.b16 {%0,%1,%2,%3}, [%4];" : "=r"(r[0]), "=r"(r[1]), "=r"(r[2]), "=r"(r[3]) : "r"(addr) : "memory");
}
__device__ __forceinline__ void stsm_x4(uint32_t addr, uint32_t r0, uint32_t r1, uint32_t r2, uint32_t r3) {
    asm volatile("stmatrix.sync.aligned.m8n8.x4.shared.b16 [%0], {%1,%2,%3,%4};" ::"r"(addr), "r"(r0), "r"(r1), "r"(r2), "r"(r3) : "memory");
}
__device__ __forceinline__ void stsm_x4_t(uint32_t addr, uint32_t r0, uint32_t r1, uint32_t r2, uint32_t r3) {
    asm volatile("stmatrix.sync.aligned.m8n8.x4.trans.shared.b16 [%0], {%1,%2,%3,%4};" ::"r"(addr), "r"(r0), "r"(r1), "r"(r2), "r"(r3) : "memory");
}
__device__ __forceinline__ uint32_t movm(uint32_t a) { uint32_t r; asm volatile("movmatrix.sync.aligned.m8n8.trans.b16 %0, %1;" : "=r"(r) : "r"(a)); return r; }
__device__ __forceinline__ uint32_t lds32(uint32_t a) { uint32_t v; asm volatile("ld.shared.u32 %0, [%1];" : "=r"(v) : "r"(a)); return v; }
__device__ __forceinline__ void sts32(uint32_t a, uint32_t v) { asm volatile("st.shared.u32 [%0], %1;" ::"r"(a), "r"(v) : "memory"); }
__device__ __forceinline__ void sts16(uint32_t a, uint32_t v) { asm volatile("st.shared.u16 [%0], %1;" ::"r"(a), "h"((unsigned short)v) : "memory"); }
__device__ __forceinline__ void named_bar(int id, int n) { asm volatile("bar.sync %0, %1;" ::"r"(id), "r"(n) : "memory"); }
__device__ __forceinline__ void named_arrive(int id, int n) { asm volatile("bar.arrive %0, %1;" ::"r"(id), "r"(n) : "memory"); }
#define CBAR() asm volatile("bar.sync 0, 640;" ::: "memory")
#define RBAR() asm volatile("bar.sync 0;" ::: "memory")
#define PROXY_FENCE() asm volatile("fence.proxy.async.shared::cta;" ::: "memory")

#define D4(d, o) "+f"(d[o]), "+f"(d[o + 1]), "+f"(d[o + 2]), "+f"(d[o + 3])
__device__ __forceinline__ void wg32(float* d, uint32_t a0, uint32_t a1, uint32_t a2, uint32_t a3, uint64_t desc) {
    asm volatile("wgmma.mma_async.sync.aligned.m64n32k16.f32.bf16.bf16 {%0,%1,%2,%3,%4,%5,%6,%7,%8,%9,%10,%11,%12,%13,%14,%15}, {%16,%17,%18,%19}, %20, 1, 1, 1, 0;"
                 : D4(d, 0), D4(d, 4), D4(d, 8), D4(d, 12) : "r"(a0), "r"(a1), "r"(a2), "r"(a3), "l"(desc));
}
__device__ __forceinline__ void wg48(float* d, uint32_t a0, uint32_t a1, uint32_t a2, uint32_t a3, uint64_t desc) {
    asm volatile("wgmma.mma_async.sync.aligned.m64n48k16.f32.bf16.bf16 {%0,%1,%2,%3,%4,%5,%6,%7,%8,%9,%10,%11,%12,%13,%14,%15,%16,%17,%18,%19,%20,%21,%22,%23}, {%24,%25,%26,%27}, %28, 1, 1, 1, 0;"
                 : D4(d, 0), D4(d, 4), D4(d, 8), D4(d, 12), D4(d, 16), D4(d, 20) : "r"(a0), "r"(a1), "r"(a2), "r"(a3), "l"(desc));
}
__device__ __forceinline__ void wg64(float* d, uint32_t a0, uint32_t a1, uint32_t a2, uint32_t a3, uint64_t desc) {
    asm volatile("wgmma.mma_async.sync.aligned.m64n64k16.f32.bf16.bf16 {%0,%1,%2,%3,%4,%5,%6,%7,%8,%9,%10,%11,%12,%13,%14,%15,%16,%17,%18,%19,%20,%21,%22,%23,%24,%25,%26,%27,%28,%29,%30,%31}, {%32,%33,%34,%35}, %36, 1, 1, 1, 0;"
                 : D4(d, 0), D4(d, 4), D4(d, 8), D4(d, 12), D4(d, 16), D4(d, 20), D4(d, 24), D4(d, 28) : "r"(a0), "r"(a1), "r"(a2), "r"(a3), "l"(desc));
}
#define O4(d, o) "=f"(d[o]), "=f"(d[o + 1]), "=f"(d[o + 2]), "=f"(d[o + 3])
__device__ __forceinline__ void wg32z(float* d, uint32_t a0, uint32_t a1, uint32_t a2, uint32_t a3, uint64_t desc) {
    asm volatile("wgmma.mma_async.sync.aligned.m64n32k16.f32.bf16.bf16 {%0,%1,%2,%3,%4,%5,%6,%7,%8,%9,%10,%11,%12,%13,%14,%15}, {%16,%17,%18,%19}, %20, 0, 1, 1, 0;"
                 : O4(d, 0), O4(d, 4), O4(d, 8), O4(d, 12) : "r"(a0), "r"(a1), "r"(a2), "r"(a3), "l"(desc));
}
__device__ __forceinline__ void wg48z(float* d, uint32_t a0, uint32_t a1, uint32_t a2, uint32_t a3, uint64_t desc) {
    asm volatile("wgmma.mma_async.sync.aligned.m64n48k16.f32.bf16.bf16 {%0,%1,%2,%3,%4,%5,%6,%7,%8,%9,%10,%11,%12,%13,%14,%15,%16,%17,%18,%19,%20,%21,%22,%23}, {%24,%25,%26,%27}, %28, 0, 1, 1, 0;"
                 : O4(d, 0), O4(d, 4), O4(d, 8), O4(d, 12), O4(d, 16), O4(d, 20) : "r"(a0), "r"(a1), "r"(a2), "r"(a3), "l"(desc));
}
__device__ __forceinline__ void wg56(float* d, uint32_t a0, uint32_t a1, uint32_t a2, uint32_t a3, uint64_t desc) {
    asm volatile("wgmma.mma_async.sync.aligned.m64n56k16.f32.bf16.bf16 {%0,%1,%2,%3,%4,%5,%6,%7,%8,%9,%10,%11,%12,%13,%14,%15,%16,%17,%18,%19,%20,%21,%22,%23,%24,%25,%26,%27}, {%28,%29,%30,%31}, %32, 1, 1, 1, 0;"
                 : D4(d, 0), D4(d, 4), D4(d, 8), D4(d, 12), D4(d, 16), D4(d, 20), D4(d, 24) : "r"(a0), "r"(a1), "r"(a2), "r"(a3), "l"(desc));
}
__device__ __forceinline__ void wg64z(float* d, uint32_t a0, uint32_t a1, uint32_t a2, uint32_t a3, uint64_t desc) {
    asm volatile("wgmma.mma_async.sync.aligned.m64n64k16.f32.bf16.bf16 {%0,%1,%2,%3,%4,%5,%6,%7,%8,%9,%10,%11,%12,%13,%14,%15,%16,%17,%18,%19,%20,%21,%22,%23,%24,%25,%26,%27,%28,%29,%30,%31}, {%32,%33,%34,%35}, %36, 0, 1, 1, 0;"
                 : O4(d, 0), O4(d, 4), O4(d, 8), O4(d, 12), O4(d, 16), O4(d, 20), O4(d, 24), O4(d, 28) : "r"(a0), "r"(a1), "r"(a2), "r"(a3), "l"(desc));
}
#define WG_FENCE() asm volatile("wgmma.fence.sync.aligned;" ::: "memory")
#define WG_COMMIT() asm volatile("wgmma.commit_group.sync.aligned;" ::: "memory")
#define WG_WAIT(n) asm volatile("wgmma.wait_group.sync.aligned " #n ";" ::: "memory")
#define TQ(p, k) p[2 * (k) + 1], p[2 * (k) + 2], p[2 * (k)], p[2 * (k) + 1]

__device__ __forceinline__ uint4 ld_nc4(const void* p) { uint4 v; asm volatile("ld.global.nc.v4.u32 {%0,%1,%2,%3}, [%4];" : "=r"(v.x), "=r"(v.y), "=r"(v.z), "=r"(v.w) : "l"(p)); return v; }
__device__ __forceinline__ uint2 ld_nc2(const void* p) { uint2 v; asm volatile("ld.global.nc.v2.u32 {%0,%1}, [%2];" : "=r"(v.x), "=r"(v.y) : "l"(p)); return v; }
__device__ __forceinline__ unsigned short ld_nc16(const void* p) { unsigned short v; asm volatile("ld.global.nc.u16 %0, [%1];" : "=h"(v) : "l"(p)); return v; }
__device__ __forceinline__ uint32_t ld_nc(const void* p) { uint32_t v; asm volatile("ld.global.nc.u32 %0, [%1];" : "=r"(v) : "l"(p)); return v; }
__device__ __forceinline__ uint32_t ld_rlx(const unsigned int* p) { uint32_t v; asm volatile("ld.relaxed.gpu.global.u32 %0, [%1];" : "=r"(v) : "l"(p) : "memory"); return v; }
__device__ __forceinline__ uint2 ld_rlx2(const void* p) { uint2 v; asm volatile("ld.relaxed.gpu.global.v2.u32 {%0,%1}, [%2];" : "=r"(v.x), "=r"(v.y) : "l"(p) : "memory"); return v; }
__device__ __forceinline__ uint4 ld_rlx4(const void* p) { uint4 v; asm volatile("ld.relaxed.gpu.global.v4.u32 {%0,%1,%2,%3}, [%4];" : "=r"(v.x), "=r"(v.y), "=r"(v.z), "=r"(v.w) : "l"(p) : "memory"); return v; }
__device__ __forceinline__ void st_rlx(unsigned int* p, uint32_t v) { asm volatile("st.relaxed.gpu.global.u32 [%0], %1;" ::"l"(p), "r"(v) : "memory"); }
__device__ __forceinline__ void st_rlx2(void* p, uint32_t a, uint32_t b) { asm volatile("st.relaxed.gpu.global.v2.u32 [%0], {%1,%2};" ::"l"(p), "r"(a), "r"(b) : "memory"); }
__device__ __forceinline__ void st_rlx4(void* p, uint4 v) { asm volatile("st.relaxed.gpu.global.v4.u32 [%0], {%1,%2,%3,%4};" ::"l"(p), "r"(v.x), "r"(v.y), "r"(v.z), "r"(v.w) : "memory"); }
__device__ __forceinline__ void red_inc(unsigned int* p) { asm volatile("red.relaxed.gpu.global.add.u32 [%0], 1;" ::"l"(p) : "memory"); }

__device__ __forceinline__ void mbar_init(uint32_t a, int cnt) { asm volatile("mbarrier.init.shared::cta.b64 [%0], %1;" ::"r"(a), "r"(cnt) : "memory"); }
__device__ __forceinline__ void mbar_expect(uint32_t a, uint32_t bytes) { asm volatile("mbarrier.arrive.expect_tx.shared::cta.b64 _, [%0], %1;" ::"r"(a), "r"(bytes) : "memory"); }
__device__ __forceinline__ void mbar_wait(uint32_t a, uint32_t parity) {
    uint32_t ok;
    int it = 0;
    do {
        ++it;
        asm volatile("{\n.reg .pred p;\nmbarrier.try_wait.parity.shared::cta.b64 p, [%1], %2;\nselp.u32 %0, 1, 0, p;\n}" : "=r"(ok) : "r"(a), "r"(parity) : "memory");
    } while (!ok & (it < SPIN_MAX));
}
__device__ __forceinline__ bool mbar_test(uint32_t a, uint32_t parity) {
    uint32_t ok;
    asm volatile("{\n.reg .pred p;\nmbarrier.test_wait.parity.shared::cta.b64 p, [%1], %2;\nselp.u32 %0, 1, 0, p;\n}" : "=r"(ok) : "r"(a), "r"(parity) : "memory");
    return __all_sync(0xffffffffu, ok);
}
__device__ __forceinline__ void tma2d(uint32_t dst, const CUtensorMap* tm, int c0, int c1, uint32_t mbar) {
    asm volatile("cp.async.bulk.tensor.2d.shared::cluster.global.mbarrier::complete_tx::bytes [%0], [%1, {%3, %4}], [%2];"
                 ::"r"(dst), "l"(tm), "r"(mbar), "r"(c0), "r"(c1) : "memory");
}
__device__ __forceinline__ void bulk_s2g(void* dst, uint32_t src, uint32_t bytes) {
    asm volatile("cp.async.bulk.global.shared::cta.bulk_group [%0], [%1], %2;" ::"l"(dst), "r"(src), "r"(bytes) : "memory");
}
__device__ __forceinline__ uint32_t ld_acq(const unsigned int* p) { uint32_t v; asm volatile("ld.acquire.gpu.global.u32 %0, [%1];" : "=r"(v) : "l"(p) : "memory"); return v; }
__device__ __forceinline__ void bulk_pf(const void* src, uint32_t bytes) { asm volatile("cp.async.bulk.prefetch.L2.global [%0], %1;" ::"l"(src), "r"(bytes) : "memory"); }

struct cplx { float x, y; };
__device__ __forceinline__ cplx cmul(cplx a, cplx b) { cplx r; r.x = a.x * b.x - a.y * b.y; r.y = a.x * b.y + a.y * b.x; return r; }
__device__ __forceinline__ cplx csq(cplx a) { cplx r; r.x = a.x * a.x - a.y * a.y; r.y = 2.0f * a.x * a.y; return r; }
__device__ __forceinline__ uint32_t hcm(uint32_t x, uint32_t y, uint32_t yp) {
    const __half2 X = *(const __half2*)&x, Y = *(const __half2*)&y, YP = *(const __half2*)&yp;
    const __half2 r = __hfma2(__high2half2(X), YP, __hmul2(__low2half2(X), Y));
    return *(const uint32_t*)&r;
}
__device__ __forceinline__ uint32_t hcn(uint32_t x, uint32_t y, uint32_t yq) {
    const __half2 X = *(const __half2*)&x, Y = *(const __half2*)&y, YQ = *(const __half2*)&yq;
    const __half2 r = __hfma2(__hneg2(__high2half2(X)), YQ, __hmul2(__low2half2(X), Y));
    return *(const uint32_t*)&r;
}
__device__ __forceinline__ float2 hsum4(uint32_t a, uint32_t b, uint32_t c, uint32_t d) {
    return __half22float2(__hadd2(__hadd2(*(const __half2*)&a, *(const __half2*)&b), __hadd2(*(const __half2*)&c, *(const __half2*)&d)));
}
__device__ __forceinline__ uint32_t amax2(uint32_t a, uint32_t b) { uint32_t r; asm("max.xorsign.abs.bf16x2 %0, %1, %2;" : "=r"(r) : "r"(a), "r"(b)); return r; }
__device__ __forceinline__ void ln_stats(float s1, float s2, float& meanb, float& rinv) {
    const float mean = s1 * (1.0f / D_);
    const float den = bfr(fsqrt(bfr(bfr(fmaxf(fmaf(-mean, mean, s2 * (1.0f / D_)), 0.f)) + 1e-5f)));
    meanb = bfr(mean);
    rinv = frcp(den);
}

__device__ __forceinline__ int fresh_tid() { int v; asm volatile("mov.u32 %0, %tid.x;" : "=r"(v)); return v - 128; }
__device__ __forceinline__ void mma_k8(float* c, uint32_t a0, uint32_t a1, uint32_t b0) {
    asm volatile("mma.sync.aligned.m16n8k8.row.col.f32.bf16.bf16.f32 {%0,%1,%2,%3}, {%4,%5}, {%6}, {%0,%1,%2,%3};\n"
                 : "+f"(c[0]), "+f"(c[1]), "+f"(c[2]), "+f"(c[3]) : "r"(a0), "r"(a1), "r"(b0));
}
__device__ __forceinline__ void ldsm_x2(uint32_t* r, uint32_t addr) {
    asm volatile("ldmatrix.sync.aligned.m8n8.x2.shared.b16 {%0,%1}, [%2];" : "=r"(r[0]), "=r"(r[1]) : "r"(addr) : "memory");
}
__device__ __forceinline__ void ldsm_x2_t(uint32_t* r, uint32_t addr) {
    asm volatile("ldmatrix.sync.aligned.m8n8.x2.trans.shared.b16 {%0,%1}, [%2];" : "=r"(r[0]), "=r"(r[1]) : "r"(addr) : "memory");
}
__device__ __forceinline__ void stsm_x2(uint32_t addr, uint32_t r0, uint32_t r1) {
    asm volatile("stmatrix.sync.aligned.m8n8.x2.shared.b16 [%0], {%1,%2};" ::"r"(addr), "r"(r0), "r"(r1) : "memory");
}
__device__ __forceinline__ uint4 lds128(uint32_t a) { uint4 v; asm volatile("ld.shared.v4.u32 {%0,%1,%2,%3}, [%4];" : "=r"(v.x), "=r"(v.y), "=r"(v.z), "=r"(v.w) : "r"(a) : "memory"); return v; }
__device__ __forceinline__ uint32_t mapa(uint32_t a, uint32_t r) { uint32_t o; asm("mapa.shared::cluster.u32 %0, %1, %2;" : "=r"(o) : "r"(a), "r"(r)); return o; }
__device__ __forceinline__ void sta4(uint32_t dst, uint4 v, uint32_t mb) {
    asm volatile("st.async.weak.shared::cluster.mbarrier::complete_tx::bytes.v4.b32 [%0], {%1,%2,%3,%4}, [%5];" ::"r"(dst), "r"(v.x), "r"(v.y), "r"(v.z), "r"(v.w), "r"(mb) : "memory");
}
__device__ __forceinline__ void sta2(uint32_t dst, uint32_t a, uint32_t b, uint32_t mb) {
    asm volatile("st.async.weak.shared::cluster.mbarrier::complete_tx::bytes.v2.b32 [%0], {%1,%2}, [%3];" ::"r"(dst), "r"(a), "r"(b), "r"(mb) : "memory");
}
__device__ __forceinline__ void mbar_arrive(uint32_t a) { asm volatile("mbarrier.arrive.shared::cta.b64 _, [%0];" ::"r"(a) : "memory"); }
__device__ __forceinline__ void red4(float4* p, float a, float b, float c) {
    asm volatile("red.relaxed.gpu.global.add.v4.f32 [%0], {%1,%2,%3,%4};" ::"l"(p), "f"(a), "f"(b), "f"(c), "f"(1.0f) : "memory");
}
__device__ __forceinline__ void red4p(bool on, float4* p, float a, float b, float c) {
    asm volatile("{\n.reg .pred q;\nsetp.ne.u32 q, %5, 0;\n@q red.relaxed.gpu.global.add.v4.f32 [%0], {%1,%2,%3,%4};\n}" ::"l"(p), "f"(a), "f"(b), "f"(c), "f"(1.0f), "r"((uint32_t)on) : "memory");
}
__device__ __forceinline__ float4 atom4(float4* p, float a, float b, float c, float d) {
    float4 v;
    asm volatile("atom.relaxed.gpu.global.add.v4.f32 {%0,%1,%2,%3}, [%4], {%5,%6,%7,%8};" : "=f"(v.x), "=f"(v.y), "=f"(v.z), "=f"(v.w) : "l"(p), "f"(a), "f"(b), "f"(c), "f"(d) : "memory");
    return v;
}
__device__ __forceinline__ uint2 lds64(uint32_t a) { uint2 v; asm volatile("ld.shared.v2.u32 {%0,%1}, [%2];" : "=r"(v.x), "=r"(v.y) : "r"(a) : "memory"); return v; }
__device__ __forceinline__ float4 ld_rlx4f(const float4* p) { float4 v; asm volatile("ld.relaxed.gpu.global.v4.f32 {%0,%1,%2,%3}, [%4];" : "=f"(v.x), "=f"(v.y), "=f"(v.z), "=f"(v.w) : "l"(p) : "memory"); return v; }
__device__ __forceinline__ void tma5d_st(const CUtensorMap* tm, int c0, int c4, uint32_t src) {
    asm volatile("cp.async.bulk.tensor.5d.global.shared::cta.bulk_group [%0, {%2, %4, %4, %4, %3}], [%1];" ::"l"(tm), "r"(src), "r"(c0), "r"(c4), "r"(0) : "memory");
}
__device__ __forceinline__ void tma2d_pf(const CUtensorMap* tm, int c0, int c1) {
    asm volatile("cp.async.bulk.prefetch.tensor.2d.L2.global [%0, {%1, %2}];" ::"l"(tm), "r"(c0), "r"(c1) : "memory");
}
__device__ __forceinline__ void pace(int clk) {
    const long long c0 = clock64();
    int it = 0;
    while (clock64() - c0 < clk && ++it < 4096) { }
}
__device__ __forceinline__ uint32_t sign2(uint32_t a) { uint32_t r; asm("prmt.b32 %0, %1, 0, 0xBB99;" : "=r"(r) : "r"(a)); return r; }
#define MB(i) (sb + OFF_MISC + (uint32_t)offsetof(Misc, mbar) + 8 * (i))
__device__ __forceinline__ uint32_t box_tap(int i) {
    const int f = (i * 205) >> 13, l = i - 40 * f - 6 - ((0x35C36 >> (4 * f)) & 15);
    const unsigned wd = (0x16824 >> (4 * f)) & 15, one = f == 4 ? 0xFFFFu : 0x3F80u;
    return ((unsigned)l <= wd ? one : 0u) | ((unsigned)(l - 1) <= wd ? one << 16 : 0u);
}
#define SD 500
#define UF(u) ((u) < 4 ? (u) + 5 : (u) == 4 ? 13 : (u) < 10 ? (u) - 5 : (u) - 1)
template <class F>
__device__ __forceinline__ void conv_channel(unsigned char* sm, uint32_t rank, uint32_t fixa, uint32_t fixv, F& late) {
    Misc& M = *(Misc*)(sm + OFF_MISC);
    const uint32_t sb = (uint32_t)__cvta_generic_to_shared(sm);
    const int tid = fresh_tid(), lane = tid & 31, g = lane >> 2, t = lane & 3, lr = lane & 7, lm = lane >> 3;
    const int warp_ = __shfl_sync(0xffffffffu, tid >> 5, 0), wgi = warp_ >> 2, w = warp_ & 3;
    const uint32_t cb = sb + OFF_CH + wgi * CHS;
    float D[32];
    const uint32_t dlo = ((cb & 0x3FFFF) >> 4) | ((UP >> 4) << 16);
#define DS(o, z, bl) (((uint64_t)(128 >> 4) << 32) | (uint64_t)(dlo + (o) / 16 + (((z) & 1) ? 0 : UP / 8) - ((z) >> 1) * (bl)))
    const uint32_t pf = cb + XO_TF + (w >> 1) * UP + (8 + 16 * (w & 1) + g - 2 * t) * 4;
    uint32_t p[13], r9[9];
    named_bar(1 + wgi, 128);
    if (fixa) sts16(fixa, fixv);
#pragma unroll
    for (int s = 0; s < 13; s++) p[s] = lds32(pf + s * 32);
    {
        const uint32_t a8 = cb + UB + t * UP + g * 16 + w * 128, b8 = cb + XO_U8 + lm * UP + lr * 16 + w * 128;
        const uint32_t a16 = cb + UB + (2 * (lr & 1) + (lm & 1)) * UP + ((lr >> 1) + 2 * (lm & 2)) * 16 + w * 128;
        const uint32_t b16 = cb + XO_U16 + (2 * (w & 1) + (lm >> 1)) * UP + (lane & 15) * 16 + (w >> 1) * 256;
        uint32_t r[3][4];
        mbar_wait(cb + XO_MBU, 0);
        ldsm_x4_t(r[0], a8);
        ldsm_x4_t(r[1], a16);
        if (w < 2) ldsm_x4_t(r[2], a8 + 512);
        stsm_x4(b8, r[0][0], r[0][1], r[0][2], r[0][3]);
        stsm_x4(b16, r[1][0], r[1][1], r[1][2], r[1][3]);
        if (w < 2) stsm_x4(b8 + 512, r[2][0], r[2][1], r[2][2], r[2][3]);
    }
    PROXY_FENCE();
    named_bar(1 + wgi, 128);
    const uint32_t pa = cb + XO_TD + (40 + 8 * w + g - 2 * t) * 4, pq = sb + OFF_MISC + (8 * w - 18 + g - 2 * t) * 4;
    uint32_t q[3][8], k2;
    auto ld = [&](int u) {
        uint32_t* d = q[u % 3];
        const int f = UF(u);
        if (f >= 5) {
#pragma unroll
            for (int i = 0; i < 8; i++) d[i] = (f == 13 && i > 4) ? 0u : lds32(pa + (f - 5) * 256 + i * 32);
        } else {
            const int lo = f == 2, hi = f == 2 ? 3 : (f == 1 || f == 4) ? 1 : 2;
#pragma unroll
            for (int i = 0; i < 8; i++) {
                if (f < 3) d[i] = 0u;
                if (i >= lo && i <= hi + 3) {
                    asm volatile("{\n.reg .pred p;\nsetp.le.u32 p, %2, %3;\n@p ld.shared.u32 %0, [%1];\n}" : "+r"(d[i]) : "r"(pq + f * 160 + i * 32), "r"(w + i - 3 - lo), "r"(hi - lo));
                    if (f == 4) asm volatile("and.b32 %0, %0, %1;" : "+r"(d[i]) : "r"(k2));
                }
            }
        }
    };
    auto go = [&](int u) {
        const int f = UF(u);
        WG_FENCE();
#pragma unroll
        for (int z = 0; z < 2; z++) {
            const uint32_t* a = q[u % 3] + 2 * z;
#define Q4 a[1], a[5], a[0], a[4]
            if (f == 5 && z == 0) wg64z(D, Q4, DS(UB, 0, 2));
            else if (f < 2) wg48(D + 8, Q4, DS(f ? XO_ZB : XO_ZA, z, 0));
            else if (f < 5) wg32(D + 16, Q4, DS(f == 2 ? XO_ZC : f == 3 ? XO_ZD : UB, z, 0));
            else if (f < 9) wg64(D, Q4, DS(UB, 2 * (f - 5) + z, 2));
            else if (f == 13) wg48(D + 8, Q4, DS(UB, z, 0));
            else wg56(D + 4, Q4, DS(UB + 128, 2 * (f - 5) + z, 2));
        }
        WG_COMMIT();
    };
    {
        float Z8[24], Z16[16];
        uint32_t z8[12], z16[8];
        const uint32_t za = cb + ((w >> 1) ? XO_ZB : XO_ZA) + t * UP + (4 * (w & 1) + (g & 3) + 8 * (g >> 2)) * 16;
        const uint32_t zc = cb + ((w >> 1) ? XO_ZD : XO_ZC) + (2 * (lr & 1) + (lm >> 1)) * UP + (((lane & 15) >> 1) + 8 * (w & 1)) * 16;
        WG_FENCE();
#pragma unroll
        for (int e = 0; e < 6; e++) {
            if (e == 0) wg48z(Z8, TQ(p, e), DS(XO_U8, e, 8));
            else wg48(Z8, TQ(p, e), DS(XO_U8, e, 8));
        }
        WG_COMMIT();
        late();
        WG_WAIT(0);
        asm volatile("setmaxnreg.inc.sync.aligned.u32 88;");
#pragma unroll
        for (int s = 0; s < 9; s++) r9[s] = lds32(pf + 2 * UP + s * 32);
#pragma unroll
        for (int i = 0; i < 12; i++) asm volatile("cvt.rn.bf16x2.f32 %0, %1, %2;" : "=r"(z8[i]) : "f"(Z8[2 * i + 1]), "f"(Z8[2 * i]));
        WG_FENCE();
#pragma unroll
        for (int e = 0; e < 4; e++) {
            if (e == 0) wg32z(Z16, TQ(r9, e), DS(XO_U16, e, 16));
            else wg32(Z16, TQ(r9, e), DS(XO_U16, e, 16));
        }
        WG_COMMIT();
        WG_WAIT(0);
#pragma unroll
        for (int i = 0; i < 8; i++) asm volatile("cvt.rn.bf16x2.f32 %0, %1, %2;" : "=r"(z16[i]) : "f"(Z16[2 * i + 1]), "f"(Z16[2 * i]));
        named_bar(1 + wgi, 128);
#pragma unroll
        for (int i = 0; i < 3; i++) stsm_x4(za + i * 256, z8[4 * i], z8[4 * i + 1], z8[4 * i + 2], z8[4 * i + 3]);
#pragma unroll
        for (int ob = 0; ob < 2; ob++) stsm_x4(zc + ob * 256, z16[4 * ob], z16[4 * ob + 1], z16[4 * ob + 2], z16[4 * ob + 3]);
    }
    {
#define RD_(o) _Pragma("unroll") for (int i = o; i < 32; i++) { float y_; asm volatile("mov.b32 %0, %1;" : "=f"(y_) : "f"(D[i])); D[i] = y_; }
        ld(0); ld(1);
        go(0);
        ld(2);
        go(1);
        k2 = lds32(cb + XO_K1024);
#pragma unroll
        for (int u = 2; u < 14; u++) {
            WG_WAIT(1);
            if (u < 13) ld(u + 1);
            if (u == 4 || u == 7 || u == 10) { WG_WAIT(0); RD_(u == 4 ? 8 : u == 7 ? 16 : 4); }
            go(u);
            if (u == 3 && wgi == 4) { const uint32_t c0 = clock(); for (int k = 0; k < 1024 && (uint32_t)clock() - c0 < SD; k++) { } }
            if (u == 3) { PROXY_FENCE(); named_bar(1 + wgi, 128); }
        }
    }
    {
        const int tid = fresh_tid(), lane = tid & 31, lr = lane & 7, lm = lane >> 3;
        uint32_t u[2][4];
        const uint32_t ua = cb + UB + w * UP + lm * 256 + lr * 16;
        ldsm_x4_t(u[0], ua); ldsm_x4_t(u[1], ua + 128);
        const uint32_t dk2 = __byte_perm(lds32(cb + XO_DSK), 0, (rank & 1) ? 0x3232 : 0x1010);
#pragma unroll
        for (int i = 0; i < 8; i++) u[i >> 2][i & 3] = mul2(u[i >> 2][i & 3], dk2);
        mbar_wait(MB(MB_C2), 0);
        const uint32_t ga2 = M.ga[wgi];
        const int src = (lane & 28) | ((lane + 3) & 3);
        WG_WAIT(0);
        float s[8];
#pragma unroll
        for (int j = 0; j < 8; j++) s[j] = __shfl_sync(0xffffffffu, (lane & 3) < 3 ? D[4 * j + 3] : j ? D[4 * j - 1] : 0.f, src);
#pragma unroll
        for (int h = 0; h < 2; h++) {
            const uint32_t rb = mapa(sb, w + 4 * h);
#pragma unroll
            for (int j = 0; j < 4; j++) u[h][j] = mul2(ga2, add2(pack2(D[8 * j + 4 * h] + s[2 * j + h], D[8 * j + 4 * h + 1] + D[8 * j + 4 * h + 2]), u[h][j]));
            sta4(rb + OFF_V + (8 * wgi + rank) * VP + lane * 16, make_uint4(u[h][0], u[h][1], u[h][2], u[h][3]), rb + (MB(wgi < 2 ? MB_V : MB_V1 - 1 + (wgi >> 1)) - sb));
        }
    }
}
#define M2W 4
#define WS 0x3210
#define WMS(p) if (warp == 7) { if (p == 0) CL_WAIT(); if (lane == 0) { _Pragma("unroll") for (int i = 2; i < 6; i++) if (((WS >> (4 * (i - 2))) & 15) == p) tma2d(sb + (i == 5 ? OFF_WM0 + 11520 : OFF_WM2 + (i - 2) * 5760), &tm_wm, i * D_ + 40 * cl, 72 * rk, MB(MB_WM2)); } __syncwarp(); }
#define PQT 10
#define PQD 100
#define L2P 2
#define L2M 2
#define PDE 100
#define WMD 400
#define CWP 200
#define CWD 3000
#define ROW(key) (((~(key) << 2) & 0xE0u) | ((~(key) >> 6) & 24u) | ((~(key) >> 11) & 6u) | ((~(key) >> 8) & 1u))
#define RKT (((rk & 4) << 6) | ((rk & 3) << 3))
#define MINE(key) ((~(key) & 0x8C0u) == (uint32_t)(RKT << 3))
#define CE(a, b) { const uint32_t hi_ = max(a, b); b = min(a, b); a = hi_; }
#define POP(k, m) if (k.x == m) { k.x = k.y; k.y = k.z; k.z = k.w; k.w = 0u; }
#define CGT(c, a, b, n) asm volatile("{\n.reg .pred p;\nsetp.gt.u32 p, %1, %2;\n@p add.u32 %0, %0, " #n ";\n}" : "+r"(c) : "r"(a), "r"(b))
#define CL_ARRIVE() asm volatile("barrier.cluster.arrive.relaxed.aligned;" ::: "memory")
#define CL_WAIT() asm volatile("barrier.cluster.wait.aligned;" ::: "memory")
__global__ void __cluster_dims__(8, 1, 1) __launch_bounds__(NTHR, 1)
clus_kernel(const bf16* __restrict__ x, const bf16* __restrict__ logAr, const bf16* __restrict__ Aim, const bf16* __restrict__ Cr, const bf16* __restrict__ Ci,
            const bf16* __restrict__ logdt, const bf16* __restrict__ c_in, Scratch* __restrict__ S, const bf16* __restrict__ Dskip,
            const bf16* __restrict__ w_r, const bf16* __restrict__ w_mod, bf16* __restrict__ out,
            const __grid_constant__ CUtensorMap tm_wm, const __grid_constant__ CUtensorMap tm_wg,
            const __grid_constant__ CUtensorMap tm_wu, const __grid_constant__ CUtensorMap tm_wd, const __grid_constant__ CUtensorMap tm_out) {
    extern __shared__ __align__(1024) unsigned char sm[];
    Misc& M = *(Misc*)(sm + OFF_MISC);
    const uint32_t sb = (uint32_t)__cvta_generic_to_shared(sm);
    const int tid = threadIdx.x < 128 ? threadIdx.x + 640 : threadIdx.x - 128, warp = __shfl_sync(0xffffffffu, tid >> 5, 0), lane = tid & 31;
    const int g = lane >> 2, t = lane & 3, lr = lane & 7, lm = lane >> 3;
    const int wgi = warp >> 2, w = warp & 3;
    const int b = blockIdx.x, cl = b >> 3, rk = b & 7;
    auto mod_ld = [&](uint32_t (*a)[4], uint32_t s0, uint32_t s1, int i) {
        const uint32_t wa = sb + ((lm & 1) ? s1 : s0) + (lr + 8 * (lm >> 1)) * 80 + i * 16;
#pragma unroll
        for (int ks = 0; ks < 4; ks++) ldsm_x4_t(a[ks], wa + ks * 1280);
        ldsm_x2_t(a[4], wa + 5120);
    };
    auto mod_mma2 = [&](float* d, float* e, uint32_t (*a)[4], uint32_t (*c)[4], const uint32_t* bs) {
        mma_k8(d, a[4][0], a[4][1], bs[8]); mma_k8(e, c[4][0], c[4][1], bs[8]);
#pragma unroll
        for (int ks = 0; ks < 4; ks++) {
            mma_bf16(d, a[ks][0], a[ks][1], a[ks][2], a[ks][3], bs[2 * ks], bs[2 * ks + 1]);
            mma_bf16(e, c[ks][0], c[ks][1], c[ks][2], c[ks][3], bs[2 * ks], bs[2 * ks + 1]);
        }
    };
    auto mod_st = [&](const float* d, uint32_t dst, int mb) {
#pragma unroll
        for (int h = 0; h < 2; h++) {
            const uint32_t rb = mapa(sb, t + 4 * h);
            sta2(rb + dst + g * 8, __float_as_uint(d[0]), __float_as_uint(d[2]), rb + (MB(mb) - sb));
        }
    };
    auto gsum = [&](uint32_t a, int pitch) {
        float4 s = make_float4(0.f, 0.f, 0.f, 0.f);
#pragma unroll
        for (int i = 0; i < 8; i++) { const float4 q = *(const float4*)(sm + a + i * pitch); s.x += q.x; s.y += q.y; s.z += q.z; s.w += q.w; }
        return make_uint2(pack2(s.x, s.z), pack2(s.y, s.w));
    };
    auto one_plus = [&](uint32_t v) { return pack2(1.0f + lo2f(v), 1.0f + hi2f(v)); };
    auto mkc1 = [&]() {
        const int lane = fresh_tid() & 31;
        const uint2 v = gsum(OFF_MG1 + 16 * min(lane, 19), 320);
        const uint32_t c1 = one_plus(v.x);
        if (lane < 20) *(uint4*)(sm + OFF_C1 + 16 * lane) = make_uint4(__byte_perm(c1, 0, 0x1010), __byte_perm(v.y, 0, 0x1010), __byte_perm(c1, 0, 0x3232), __byte_perm(v.y, 0, 0x3232));
        __syncwarp();
        named_arrive(10, 160);
    };
    if (wgi == 5) {
        CL_ARRIVE();
        const uint32_t c_a = ld_nc((const uint32_t*)c_in + 36 * rk + lane), c_b = ld_nc((const uint32_t*)c_in + 36 * rk + 32 + t);
        {
            pace(WMD);
            const char* wp = (const char*)(w_mod + (72 * rk + 18 * w) * (6 * D_) + 40 * cl);
#pragma unroll
            for (int i = 0; i < 3; i++) {
                const uint32_t c = lane + 32 * i, row = (c * 205) >> 10;
                const char* p = wp + (row * (12 * D_ - 80) + 16 * c);
                if (c < 90) {
                    asm volatile("cp.async.cg.shared.global [%0], [%1], 16;" ::"r"(sb + OFF_WM0 + 1440 * w + 16 * c), "l"(p) : "memory");
                    asm volatile("cp.async.cg.shared.global [%0], [%1], 16;" ::"r"(sb + OFF_WM0 + 5760 + 1440 * w + 16 * c), "l"(p + 2 * D_) : "memory");
                }
            }
            if (w == 3 && lane < 20)
                asm volatile("cp.async.ca.shared.global [%0], [%1], 4, %2;" ::"r"(sb + OFF_MISC + (uint32_t)offsetof(Misc, c2) + 12 + 16 * lane), "l"((const uint32_t*)w_r + min(20 * cl + lane, D_ / 2 - 1)),
                             "r"(20 * cl + lane < D_ / 2 ? 4 : 0) : "memory");
            asm volatile("cp.async.commit_group;" ::: "memory");
        }
        {
            uint32_t bs[9], a[5][4], c[5][4];
            float d[4] = {0.f, 0.f, 0.f, 0.f}, e[4] = {0.f, 0.f, 0.f, 0.f};
            const uint32_t sc = pack2(silu(lo2f(c_a)), silu(hi2f(c_a)));
            bs[8] = pack2(silu(lo2f(c_b)), silu(hi2f(c_b)));
            if (w == 2) { sts32(sb + OFF_SC + 4 * lane, sc); sts32(sb + OFF_SC + 128 + 4 * t, bs[8]); }
#pragma unroll
            for (int ks = 0; ks < 8; ks++) bs[ks] = __shfl_sync(0xffffffffu, sc, 4 * ks + t);
            CL_WAIT();
            asm volatile("cp.async.wait_group 0;" ::: "memory");
            named_bar(10, 128);
            mod_ld(a, OFF_WM0 + 5760, OFF_WM0, w);
            mod_ld(c, OFF_WM0 + 5760, OFF_WM0, 4);
            mod_mma2(d, e, a, c, bs);
            mod_st(d, OFF_MG1 + rk * 320 + 64 * w, MB_MG1);
            if (w == 1) mod_st(e, OFF_MG1 + rk * 320 + 256, MB_MG1);
        }
        {
            const int n0 = 8 * w + 2 * (rk & 1), n1 = 8 * w + ((n0 + 4 + t) & 7);
            const float4* ap = &S->acc1[256 * rk + 8 * (n0 + t) + g];
            const float4* aq = &S->acc1[256 * rk + 8 * n1 + g];
            named_bar(9, 640);
            float4 pa = ld_rlx4f(ap), pb = ld_rlx4f(aq);
            uint32_t xq[2][5][4];
            uint2 cc[5];
            const uint32_t xa = sb + OFF_X + XI(2 * lm + (lr & 1)) + XN(n0 + (lr >> 1)), xb = sb + OFF_X + XI(2 * lm + (lr & 1)) + XN(8 * w + ((n0 + 4 + (lr >> 1)) & 7));
            const uint32_t ua = mapa(sb, g) + OFF_CH;
#pragma unroll
            for (int j = 0; j < 5; j++) ldsm_x4_t(xq[0][j], xa + 16 * j);
#pragma unroll 1
            for (int it = 0; it < SPIN_MAX && (pa.w != (float)NCL || pb.w != (float)NCL); it++) {
                pa = ld_rlx4f(ap); pb = ld_rlx4f(aq);
            }
            __syncwarp();
            float m0, r0, m1, r1;
            ln_stats(pa.x, pa.y, m0, r0);
            ln_stats(pb.x, pb.y, m1, r1);
            const uint32_t rh = pack2(r0, r1), rl = pack2(r0 - lo2f(rh), r1 - hi2f(rh));
            const uint32_t stage = sb + OFF_STG + w * 512;
            stsm_x4_t(stage + lane * 16, pack2(m0, m1), rh, rl, rl);
            __syncwarp();
            named_bar(10, 160);
            uint4 st[2][3];
#pragma unroll
            for (int q = 0; q < 2; q++)
#pragma unroll
                for (int i = 0; i < 3; i++) st[q][i] = lds128(stage + 128 * i + (2 * t + q) * 16);
#pragma unroll
            for (int j = 0; j < 5; j++) cc[j] = *(const uint2*)(sm + OFF_C1 + 64 * j + 8 * g);
            ldsm_x4_t(xq[1][0], xb);
            const uint32_t ub = ua + (rk & 3) * UP + UB + (8 * w + 8 * (rk >> 2)) * 16, u0 = ub + (n0 + t) * 16, u1 = ub + n1 * 16;
#pragma unroll
            for (int j = 0; j < 5; j++) {
                if (j >= 2 && cl == 14) break;
                if (j < 4) ldsm_x4_t(xq[1][j + 1], xb + 16 * (j + 1));
#pragma unroll
                for (int q = 0; q < 2; q++) {
                    const uint4 sm_ = st[q][0], sh = st[q][1], sl = st[q][2];
                    const uint32_t v0 = add2(mul2(norm2(xq[q][j][0], sm_.x, sh.x, sl.x), cc[j].x), cc[j].y), v1 = add2(mul2(norm2(xq[q][j][1], sm_.y, sh.y, sl.y), cc[j].x), cc[j].y);
                    const uint32_t v2 = add2(mul2(norm2(xq[q][j][2], sm_.z, sh.z, sl.z), cc[j].x), cc[j].y), v3 = add2(mul2(norm2(xq[q][j][3], sm_.w, sh.w, sl.w), cc[j].x), cc[j].y);
                    asm volatile("{\n.reg .pred p;\nsetp.ne.u32 p, %6, %7;\n"
                                 "@p st.async.weak.shared::cluster.mbarrier::complete_tx::bytes.v4.b32 [%0], {%1,%2,%3,%4}, [%5];\n"
                                 "@!p st.shared.v4.b32 [%0], {%1,%2,%3,%4};\n}"
                                 ::"r"((q ? u1 : u0) + j * CHS), "r"(v0), "r"(v1), "r"(v2), "r"(v3), "r"(ua + j * CHS + XO_MBU), "r"(g), "r"(rk) : "memory");
                }
                __syncwarp();
                if (lane == 0) mbar_arrive(sb + OFF_CH + XO_MBU + j * CHS);
            }
        }
        asm volatile("setmaxnreg.dec.sync.aligned.u32 40;");
        {
        int cl;
        asm volatile("mov.u32 %0, %clusterid.x;" : "=r"(cl));
        const int w = __shfl_sync(0xffffffffu, (fresh_tid() >> 5) & 3, 0);
        if (w) named_arrive(11, 128); else named_bar(11, 128);
        if (w == 0) {
            const int lane = fresh_tid() & 31;
            mbar_wait(MB(MB_KD), 0);
            PROXY_FENCE();
            if (lane == 0) {
                tma2d(sb + OFF_WU + 15360, &tm_wu, 40 * b, 192, MB(MB_WU));
                tma2d_pf(&tm_wu, 40 * b, 384);
                mbar_wait(MB(MB_C2), 0);
                PROXY_FENCE();
                tma2d(sb + OFF_WU + 2 * 15360, &tm_wu, 40 * b, 384, MB(MB_WU));
#pragma unroll 1
                for (int i = 0; i < 9; i++) { pace(PDE); tma2d_pf(&tm_wd, 64 * i, 40 * b); }
                mbar_wait(MB(MB_WU), 0);
            }
            __syncwarp();
        } else if (w == 2) {
            if ((fresh_tid() & 31) == 0) {
                float4 v;
                int it = 0;
                pace(CWD);
                for (;;) { v = ld_rlx4f(&S->acc1[L_]); if (++it >= SPIN_MAX || (v.z == (float)G_ && v.w == (float)NCL)) break; pace(CWP); }
                M.cws[0] = v.x; M.cws[1] = v.y;
                mbar_arrive(MB(MB_CW));
            }
            __syncwarp();
            mbar_wait(MB(MB_C2), 0);
            const int lane = fresh_tid() & 31;
            if (rk == 0 && lane < (cl < 14 ? 5 : 2)) st_rlx4(&S->h2c[136 * 72 + 5 * cl + lane], make_uint4(~M.c2[4 * lane].z, ~M.c2[4 * lane + 1].z, ~M.c2[4 * lane + 2].z, ~M.c2[4 * lane + 3].z));
        } else if (w == 3) {
            const int lane = fresh_tid() & 31, l20 = min(lane, 19);
            mbar_wait(MB(MB_MG2), 0);
            const uint2 v = gsum(OFF_MG2 + 16 * l20, 640), u = gsum(OFF_MG2 + 320 + 16 * l20, 640);
            const uint32_t wr = lane < 20 ? M.c2[lane].w : 0u, cb1 = one_plus(v.x), cw = mul2(cb1, wr);
            if (lane < 20) {
                M.c2[lane] = make_uint4(cb1, v.y, u.x, cw);
                M.wr[lane] = wr;
                unsigned e;
                asm volatile("mov.u32 %0, %cluster_ctarank;" : "=r"(e));
                if ((lane & 3) == (e >> 1)) M.ga[lane >> 2] = __byte_perm(u.y, 0, (e & 1) ? 0x3232 : 0x1010);
            }
            __syncwarp();
            if (lane == 0) mbar_arrive(MB(MB_C2));
            if (rk == 0) {
                float a = lo2f(cw) + hi2f(cw), s = lo2f(v.y) * lo2f(wr) + hi2f(v.y) * hi2f(wr);
#pragma unroll
                for (int o = 16; o; o >>= 1) { a += __shfl_xor_sync(0xffffffffu, a, o); s += __shfl_xor_sync(0xffffffffu, s, o); }
                if (lane == 0) red4(&S->acc1[L_], a, s, 0.f);
            }
        }
        {
        const int lane = fresh_tid() & 31, t = lane & 3, lr = lane & 7, lm = lane >> 3;
        __syncwarp();
        if (w >= 2) {
            uint32_t aw[5];
#pragma unroll
            for (int j = 0; j < 5; j++) aw[j] = M.wr[4 * j + t];
            const int lst = 16 * (lm & 1) + 2 * rk + (w & 1);
            const uint32_t rb = mapa(sb, lr);
            float4* p = &S->rs[8 * lst];
            float4* pr = &S->rs[8 * (16 * (t >> 1) + 2 * rk + (w & 1)) + (t & 1)];
            named_bar(6, 576);
            uint4 k = *(const uint4*)&M.key[128 * (w & 1) + 4 * lane];
            CE(k.x, k.y); CE(k.z, k.w); CE(k.x, k.z); CE(k.y, k.w); CE(k.y, k.z);
            uint32_t m[4], mine = 0;
#pragma unroll
            for (int rnd = 0; rnd < 8; rnd++) {
                const uint32_t v = __reduce_max_sync(0xffffffffu, k.x);
                POP(k, v);
                if (rnd < 4 || (lm & 1)) m[rnd & 3] = v;
                if (rnd == lr) mine = v;
            }
            const uint32_t ra = sb + OFF_H2T + ROW(mine) * 80;
            uint32_t bq[6];
            float rr[4] = {0.f, 0.f, 0.f, 0.f};
            ldsm_x4(bq, ra + 16 * lm); ldsm_x2(bq + 4, ra + 64);
            if (lane < 16) sta4(rb + OFF_MISC + (uint32_t)offsetof(Misc, cand) + lst * 16, make_uint4(m[0], m[1], m[2], m[3]), rb + (MB(MB_KEY2) - sb));
            mma_bf16(rr, aw[0], aw[0], aw[1], aw[1], bq[0], bq[1]); mma_bf16(rr, aw[2], aw[2], aw[3], aw[3], bq[2], bq[3]); mma_k8(rr, aw[4], aw[4], bq[4]);
            if (lane < 4) red4(pr, rr[0], 0.f, rr[1]);
            float4 e0 = ld_rlx4f(p), e1 = ld_rlx4f(p + 1);
#pragma unroll 1
            for (int it = 0; it < SPIN_MAX && (e0.w != (float)NCL || e1.w != (float)NCL); it++) {
                e0 = ld_rlx4f(p); e1 = ld_rlx4f(p + 1);
            }
            const uint32_t r0 = pack2(e0.x, e0.z), r1 = pack2(e1.x, e1.z);
            const uint32_t o0 = r0 ^ (sign2(r0) | 0x80008000u), o1 = r1 ^ (sign2(r1) | 0x80008000u);
            if (lane < 16) sta4(rb + OFF_EK + lst * VP, make_uint4((o0 << 16) | (m[0] & 0x3FFFu), (o0 & 0xFFFF0000u) | (m[1] & 0x3FFFu), (o1 << 16) | (m[2] & 0x3FFFu), (o1 & 0xFFFF0000u) | (m[3] & 0x3FFFu)),
                                rb + (MB(MB_EK) - sb));
        } else if (w == 0) {
            named_bar(8, 64);
            if (lane == 0) {
                PROXY_FENCE();
                tma5d_st(&tm_out, 40 * cl, RKT, sb + OFF_OUT);
                asm volatile("cp.async.bulk.commit_group;" ::: "memory");
                asm volatile("cp.async.bulk.wait_group 0;" ::: "memory");
                asm volatile("fence.acq_rel.gpu;" ::: "memory");
                mbar_arrive(MB(MB_OUT));
            }
        } else {
            uint32_t sl = 0, mine = 0;
            mbar_wait(MB(MB_KEY), 0);
            __syncwarp();
            uint4 k = *(const uint4*)&M.cand2[4 * lane];
            CE(k.x, k.z); CE(k.y, k.w); CE(k.y, k.z);
#pragma unroll
            for (int rnd = 0; rnd < 8; rnd++) {
                const uint32_t v = __reduce_max_sync(0xffffffffu, k.x);
                POP(k, v);
                if (rnd == lr) mine = v;
            }
            M.sel[lane & 15] = (lane & 8) ? (((~mine >> 2) & 62u) | ((~mine >> 5) & 64u) | (mine & 1u)) * 1152u : mine;
            __syncwarp();
            named_arrive(13, 672);
            mbar_wait(MB(MB_KEY2), 0);
            k = *(const uint4*)&M.cand[4 * lane];
#pragma unroll
            for (int s = 0; s < 8; s++) {
                const uint32_t v = M.sel[s] & ~1u;
                if (k.x == v) sl |= 8 + s;
                if (k.y == v) sl |= (8 + s) << 8;
                if (k.z == v) sl |= (8 + s) << 16;
                if (k.w == v) sl |= (8 + s) << 24;
            }
            const uint32_t found = __reduce_add_sync(0xffffffffu, __popc(sl & 0x08080808u));
            mbar_wait(MB(MB_EK), 0);
            if (b == 0 && lane == 0) st_rlx4(&S->acc1[L_], make_uint4(0, 0, 0, 0));
            if (lane < 16 || cl == 14) st_rlx4(&S->acc2[256 * rk + 16 * cl + lane], make_uint4(0, 0, 0, 0));
            k = lds128(sb + OFF_EK + lane * VP);
            const bool s0 = sl & 8u, s1 = sl & 0x800u, s2 = sl & 0x80000u, s3 = sl & 0x8000000u;
            if (s0) M.fin[sl & 7u] = k.x;
            if (s1) M.fin[(sl >> 8) & 7u] = k.y;
            if (s2) M.fin[(sl >> 16) & 7u] = k.z;
            if (s3) M.fin[(sl >> 24) & 7u] = k.w;
            const uint32_t lo = min(min(s0 ? k.x : ~0u, s1 ? k.y : ~0u), min(s2 ? k.z : ~0u, s3 ? k.w : ~0u));
            const uint32_t hi = max(max(s0 ? 0u : k.x, s1 ? 0u : k.y), max(s2 ? 0u : k.z, s3 ? 0u : k.w));
            const uint32_t hi2 = __reduce_max_sync(0xffffffffu, hi), lo2 = __reduce_min_sync(0xffffffffu, lo);
            bool redo = found != 8u;
            if (hi2 > lo2) {
                const uint32_t h = hi2 | 0xFFFFu, l = lo2 & 0xFFFF0000u;
                const uint32_t n = __reduce_add_sync(0xffffffffu, ((s0 ? k.x <= h : (k.x >= l) << 8) + (s1 ? k.y <= h : (k.y >= l) << 8)) + ((s2 ? k.z <= h : (k.z >= l) << 8) + (s3 ? k.w <= h : (k.w >= l) << 8)));
                redo = redo || (h >> 16) - (l >> 16) > 1u || ((n & 255u) > 1u && n >= 512u) || (n & 255u) + (n >> 8) > 9u;
            }
            if (redo) {
                CE(k.x, k.y); CE(k.z, k.w); CE(k.x, k.z); CE(k.y, k.w); CE(k.y, k.z);
                __syncwarp();
#pragma unroll 1
                for (int rnd = 0; rnd < 8; rnd++) {
                    const uint32_t m8 = __reduce_max_sync(0xffffffffu, k.x);
                    POP(k, m8);
                    if (lane == 0) M.fin[rnd] = m8;
                }
            }
            if (lane == 0) M.fin[8] = redo;
            __syncwarp();
            if (lane == 0) mbar_arrive(MB(MB_FIN));
        }
        }
        }
    } else {
    if (warp != 19) CL_ARRIVE();
    const int chn = 40 * cl + 8 * wgi + rk;
    const bool has_ch = chn < D_;
    const uint32_t cb = sb + OFF_CH + wgi * CHS;
    auto ldx = [&]() {
    if (warp < 16) {
        const char* xp = (const char*)(x + (512 * (warp >> 2) + 64 * (warp & 3) + RKT) * D_ + 40 * cl);
        const uint32_t dst = sb + OFF_X + XN(2 * warp) + XI(lm) + 16 * lr;
        xp += lm * (2 * D_) + 16 * lr;
#pragma unroll
        for (int i = 0; i < 4; i++)
            if (lr < 5) asm volatile("cp.async.cg.shared.global [%0], [%1], 16, %2;" ::"r"(dst + XI(4 * (i & 1)) + 80 * (i >> 1)), "l"(xp + ((i & 1) * 4 + (i >> 1) * 32) * (2 * D_)),
                                     "r"((cl < 14 || lr < 2) ? 16 : 0) : "memory");
    }
    };
    unsigned short r_ldt = 0, r_lar = 0, r_aim = 0;
    uint2 r_cr, r_ci;
    {
        const int n = min(chn, D_ - 1) * N_ + 4 * lane;
        r_ldt = ld_nc16((const unsigned short*)logdt + min(chn, D_ - 1));
        r_lar = ld_nc16((const unsigned short*)logAr + n + w);
        r_aim = ld_nc16((const unsigned short*)Aim + n + w);
        r_cr = ld_nc2(Cr + n);
        r_ci = ld_nc2(Ci + n);
    }
    if (warp == 19) {
        if (lane == 0) asm volatile("prefetch.tensormap [%0];" ::"l"(&tm_wm) : "memory");
        const uint32_t lo = 90u | (10u << 8) | (20u << 16) | (2u << 24), hi = 32u | ((rk < 4 ? 40u : 32u) << 8) | (180u << 16) | (180u << 24);
        const uint32_t tx = lane < 8 ? (((lane & 4 ? hi : lo) >> (8 * (lane & 3))) & 255u) : lane == 8 ? 180u : lane < 11 ? 2u : lane == 11 ? (hi >> 8) & 255u : lane >= MB_C2 ? 14u : cl == 14 ? 0u : lane == 12 ? 32u : 16u;
        if (lane == 0) {
#pragma unroll
            for (int i = 0; i < MB_N; i++) mbar_init(MB(i), i == MB_KD || i == MB_CD ? 20 : 1);
#pragma unroll
            for (int i = 0; i < 5; i++) mbar_init(sb + OFF_CH + XO_MBU + i * CHS, 5);
        }
        __syncwarp();
        if (lane < MB_C2 + 5) mbar_expect(lane < MB_C2 ? MB(lane) : sb + OFF_CH + XO_MBU + (lane - MB_C2) * CHS, tx << 8);
        asm volatile("fence.mbarrier_init.release.cluster;" ::: "memory");
        __syncwarp();
        CL_ARRIVE();
    }
    ldx();
    uint32_t rz[4] = {0u, 0u, 0u, 0u};
    auto rst2 = [&]() {
        if (fresh_tid() == 576) asm volatile("red.relaxed.gpu.global.add.f32 [%0], %1;" ::"l"(&S->acc1[L_].z), "f"(__uint_as_float(0x3F800000u | rz[0] | rz[1] | rz[2] | rz[3])) : "memory");
        __syncwarp();
    };
    auto rst = [&]() {
        if (warp == 18) {
            const int lane = fresh_tid() & 31;
            uint4* rp = S->h2c + NRS * b + lane;
#pragma unroll
            for (int i = 0; i < 4; i++) if (i < 3 || lane < NRS - 96) st_rlx4(rp + 32 * i, make_uint4(0, 0, 0, 0));
#pragma unroll
            for (int i = 0; i < 4; i++) asm volatile("atom.relaxed.gpu.global.or.b32 %0, [%1], 0;" : "=r"(rz[i]) : "l"((unsigned int*)(rp + (i < 3 || lane < NRS - 96 ? 32 * i : 0)) + (i & 1)) : "memory");
        }
    };
    if ((tid & 127) == 32) asm volatile("cp.async.ca.shared.global [%0], [%1], 4;" ::"r"(cb + XO_DSK), "l"((const uint32_t*)Dskip + (min(chn, D_ - 1) >> 1)) : "memory");
    asm volatile("cp.async.commit_group;" ::: "memory");
    auto mod2 = [&]() {
        if (wgi == M2W) {
            const int lane = fresh_tid() & 31, t = lane & 3;
            const uint32_t wa = sb + ((lane & 7) + ((lane >> 1) & 8)) * 80, p0 = wa + ((lane & 8) ? OFF_WM2 + 5760 : OFF_WM2 + 11520), p1 = wa + ((lane & 8) ? OFF_WM2 : OFF_WM0 + 11520);
            auto ld = [&](uint32_t (*a)[4], uint32_t p) {
#pragma unroll
                for (int ks = 0; ks < 4; ks++) ldsm_x4_t(a[ks], p + ks * 1280);
                ldsm_x2_t(a[4], p + 5120);
            };
            const uint32_t rb = mapa(sb, t), rd = mapa(sb, 4) - mapa(sb, 0), dst = rb + OFF_MG2 + rk * 640 + (lane >> 2) * 8;
            auto st = [&](const float* d, uint32_t o) {
                sta2(dst + o, __float_as_uint(d[0]), __float_as_uint(d[2]), rb + (MB(MB_MG2) - sb));
                sta2(dst + rd + o, __float_as_uint(d[0]), __float_as_uint(d[2]), rb + rd + (MB(MB_MG2) - sb));
            };
            uint32_t bs[9], a[5][4], c[5][4];
            float d[4] = {0.f, 0.f, 0.f, 0.f}, e[4] = {0.f, 0.f, 0.f, 0.f};
            mbar_wait(MB(MB_MG1), 0);
#pragma unroll
            for (int ks = 0; ks < 9; ks++) bs[ks] = lds32(sb + OFF_SC + 16 * ks + 4 * t);
            mbar_wait(MB(MB_WM2), 0);
            __syncwarp();
            ld(a, p0 + 16 * w);
            ld(c, p1 + 16 * w);
            {
                float h[6][4];
#pragma unroll
                for (int i = 0; i < 24; i++) h[i >> 2][i & 3] = 0.f;
                mma_k8(h[0], a[4][0], a[4][1], bs[8]); mma_k8(h[3], c[4][0], c[4][1], bs[8]);
#pragma unroll
                for (int ks = 0; ks < 4; ks++) {
                    mma_bf16(h[(ks + 1) % 3], a[ks][0], a[ks][1], a[ks][2], a[ks][3], bs[2 * ks], bs[2 * ks + 1]);
                    mma_bf16(h[3 + (ks + 1) % 3], c[ks][0], c[ks][1], c[ks][2], c[ks][3], bs[2 * ks], bs[2 * ks + 1]);
                }
                d[0] = h[0][0] + h[1][0] + h[2][0]; d[2] = h[0][2] + h[1][2] + h[2][2];
                e[0] = h[3][0] + h[4][0] + h[5][0]; e[2] = h[3][2] + h[4][2] + h[5][2];
                ld(a, ((w & 1) ? p1 : p0) + 64);
                st(d, 64 * w);
                st(e, 320 + 64 * w);
#pragma unroll
                for (int i = 0; i < 20; i++) h[i >> 2][i & 3] = 0.f;
                mma_k8(h[4], a[4][0], a[4][1], bs[8]);
#pragma unroll
                for (int ks = 0; ks < 4; ks++) mma_bf16(h[ks], a[ks][0], a[ks][1], a[ks][2], a[ks][3], bs[2 * ks], bs[2 * ks + 1]);
                d[0] = (h[0][0] + h[1][0]) + (h[2][0] + h[3][0]) + h[4][0]; d[2] = (h[0][2] + h[1][2]) + (h[2][2] + h[3][2]) + h[4][2];
            }
            if (w < 2) st(d, 320 * w + 256);
            __syncwarp();
        }
    };
    auto ln1 = [&]() {
        if (warp < 16) {
            uint32_t a[10];
            const uint32_t xa = sb + OFF_X + XN(2 * warp) + (lm & 1) * 80 + XI(lr) + (lm >> 1) * 16;
            asm volatile("cp.async.wait_group 0;" ::: "memory");
            __syncwarp();
            ldsm_x4(a, xa); ldsm_x4(a + 4, xa + 32); ldsm_x2(a + 8, xa + 64);
            named_arrive(9, 640);
            float c1[4] = {0.f, 0.f, 0.f, 0.f}, c2[4] = {0.f, 0.f, 0.f, 0.f}, c3[4] = {0.f, 0.f, 0.f, 0.f};
#pragma unroll
            for (int j = 0; j < 2; j++) {
                mma_bf16(c1, a[4 * j], a[4 * j + 1], a[4 * j + 2], a[4 * j + 3], 0x3F803F80u, 0x3F803F80u);
                mma_bf16(c2, a[4 * j], a[4 * j + 1], a[4 * j + 2], a[4 * j + 3], a[4 * j], a[4 * j + 2]);
                mma_bf16(c3, a[4 * j], a[4 * j + 1], a[4 * j + 2], a[4 * j + 3], a[4 * j + 1], a[4 * j + 3]);
            }
            mma_k8(c1, a[8], a[9], 0x3F803F80u); mma_k8(c2, a[8], a[9], a[8]); mma_k8(c3, a[8], a[9], a[9]);
            float4* p = &S->acc1[256 * rk + 16 * warp + g];
            red4p(t == (g >> 1), p, c1[0], (g & 1) ? c2[1] : c2[0], 0.f);
            red4p(t == (g >> 1), p + 8, c1[2], (g & 1) ? c3[3] : c3[2], 0.f);
        }
    };
    {
        unsigned char* cp = sm + OFF_CH + wgi * CHS + lane * 16;
        const uint4 z = make_uint4(0, 0, 0, 0);
        *(uint4*)(cp + w * UP + XO_TF) = z;
        *(uint4*)(cp + w * UP + (lane < 16 ? XO_U8 - 256 : XO_U16 - 512)) = z;
        if (lane < 16) *(uint4*)(cp + (lane < 8 ? w * UP + UB - 128 : XO_TD + (4 * w + (lane < 12 ? -8 : 145 - 12)) * 16)) = z;
    }
    if (tid < 200) ((uint32_t*)M.box)[tid] = box_tap(tid);
    const uint32_t scr = sb + warp * KSCR, ws = scr + lane * 4;
    uint32_t fixa = 0, fixv = 0;
    {
        uint32_t zr;
        asm volatile("ld.volatile.shared.u32 %0, [%1];" : "=r"(zr) : "r"(cb + XO_TF + w * UP + lane * 16) : "memory");
        const float p_ldt = __uint_as_float(r_ldt * 65536u + zr), p_lar = __uint_as_float(r_lar * 65536u + zr), p_aim = __uint_as_float(r_aim * 65536u + zr);
        const float p_cr = __uint_as_float((uint32_t)((((uint64_t)r_cr.y << 32) | r_cr.x) >> (16 * w)) * 65536u + zr), p_ci = __uint_as_float((uint32_t)((((uint64_t)r_ci.y << 32) | r_ci.x) >> (16 * w)) * 65536u + zr);
        float acc[5][4];
        uint32_t afr[4][4], cz[4], cq[4], bb[2][8];
        const uint32_t ba = scr + lr * 144 + lm * 16;
        auto tld = [&](int i) {
            __syncwarp();
            ldsm_x4(bb[i & 1], ba + ((i + 2) % 3) * 1152);
            ldsm_x4(bb[i & 1] + 4, ba + ((i + 2) % 3) * 1152 + 64);
        };
        auto tmm = [&](int i) {
            float* c = acc[i];
            c[0] = c[1] = c[2] = c[3] = 0.f;
#pragma unroll
            for (int s = 0; s < 4; s++) mma_f16(c, afr[s], bb[i & 1][2 * s], bb[i & 1][2 * s + 1]);
        };
#define TA(i) if (i == 1) tmm(0); WMS(i); tld(i); tmm(i);
#define PH(z) packh((z).x, (z).y)
        const float dt = bfr(expf(p_ldt));
        const float al = -bfr(expf(p_lar)) * dt * 1.4426950408889634f;
        const float th = p_aim * dt;
        const float th_ = th * 0.15915494309189535f;
        const float tl_ = fmaf(th, 0.15915494309189535f, -th_) + th * 6.4206382e-9f;
        auto anchor = [&](float s) {
            float f = th_ * s;
            f -= rintf(f);
            f = fmaf(tl_, s, f) * 6.283185307179586f;
            const float e = fex2(al * s);
            return cplx{e * __cosf(f), e * __sinf(f)};
        };
        const uint32_t cm = amax2(amax2(r_cr.x, r_cr.y), amax2(r_ci.x, r_ci.y));
        const uint32_t ex = __reduce_max_sync(0xffffffffu, __float_as_uint(fmaxf(fabsf(lo2f(cm)), fabsf(__uint_as_float(cm))))) & 0x7F800000u;
        const float scl = __uint_as_float(0x7F000000u - ex), inv = (dt + dt) * __uint_as_float(ex);
        const cplx C = cplx{p_cr * scl, p_ci * scl};
        const cplx z1 = anchor(1.f), z16 = anchor(16.f), z256 = anchor(256.f);
        {
            const cplx z32 = csq(z16), z48 = cmul(z32, z16), z64 = csq(z32), z128 = csq(z64), z192 = cmul(z128, z64);
            const uint32_t y[3] = {packh(z16.x, z16.y), packh(z32.x, z32.y), packh(z48.x, z48.y)};
            const uint32_t yp[3] = {packh(-z16.y, z16.x), packh(-z32.y, z32.x), packh(-z48.y, z48.x)};
            const uint32_t xx[3] = {packh(z64.x, z64.y), packh(z128.x, z128.y), packh(z192.x, z192.y)};
            sts32(ws, 0x00003C00u);
#pragma unroll
            for (int j = 0; j < 3; j++) sts32(ws + (1 + j) * 144, y[j]);
#pragma unroll
            for (int i = 0; i < 3; i++) {
                sts32(ws + (4 + 4 * i) * 144, xx[i]);
#pragma unroll
                for (int j = 0; j < 3; j++) sts32(ws + (5 + 4 * i + j) * 144, hcm(xx[i], y[j], yp[j]));
            }
        }
        ln1();
        WMS(0);
        const cplx z2 = csq(z1);
        {
            const cplx z3 = cmul(z2, z1), z4 = csq(z2), z8 = csq(z4);
            const cplx c4 = cmul(C, z4), c8 = cmul(C, z8), c12 = cmul(c8, z4);
            cz[0] = packh(C.x, -C.y); cz[1] = packh(c4.x, -c4.y); cz[2] = packh(c8.x, -c8.y); cz[3] = packh(c12.x, -c12.y);
            cq[0] = packh(C.y, C.x); cq[1] = packh(c4.y, c4.x); cq[2] = packh(c8.y, c8.x); cq[3] = packh(c12.y, c12.x);
            __syncwarp();
#pragma unroll
            for (int s = 0; s < 4; s++) ldsm_x4(afr[s], scr + (lr + 8 * (lm & 1)) * 144 + (lm >> 1) * 16 + 32 * s);
            const uint32_t y[3] = {PH(z1), PH(z2), PH(z3)};
#pragma unroll
            for (int tt = 0; tt < 2; tt++) {
                const int rg = tt ? 0 : 2;
#pragma unroll
                for (int i = 0; i < 2; i++) {
                    sts32(ws + rg * 1152 + (4 * i) * 144, cz[2 * tt + i]);
#pragma unroll
                    for (int j = 0; j < 3; j++) sts32(ws + rg * 1152 + (4 * i + 1 + j) * 144, hcn(y[j], cz[2 * tt + i], cq[2 * tt + i]));
                }
                if (tt == 0) tld(0);
            }
            TA(1)
        }
        const cplx z258 = cmul(z256, z2), z512 = csq(z256), z768 = cmul(z512, z256);
        {
            const uint32_t a0 = PH(z256), a1 = PH(z258);
#pragma unroll
            for (int i = 0; i < 4; i++) { sts32(ws + 1152 + (2 * i) * 144, hcn(a0, cz[i], cq[i])); sts32(ws + 1152 + (2 * i + 1) * 144, hcn(a1, cz[i], cq[i])); }
            TA(2)
        }
        {
            const uint32_t a0 = PH(z512), a1 = PH(z768);
#pragma unroll
            for (int i = 0; i < 4; i++) { sts32(ws + 2304 + i * 144, hcn(a0, cz[i], cq[i])); sts32(ws + 2304 + (4 + i) * 144, hcn(a1, cz[i], cq[i])); }
            TA(3)
        }
        const cplx z1024 = csq(z512);
        {
            const cplx zk[4] = {z1024, cmul(z1024, z256), csq(z768), cmul(z1024, z768)};
#pragma unroll
            for (int h = 0; h < 4; h++) {
                const uint32_t a0 = PH(zk[h]);
                sts32(ws + (2 * h) * 144, hcn(a0, cz[0], cq[0]));
                sts32(ws + (2 * h + 1) * 144, hcn(a0, cz[2], cq[2]));
            }
            tld(4);
            tmm(4);
        }
        const cplx z2048 = csq(z1024);
        const uint32_t last = __reduce_add_sync(0xffffffffu, __float_as_uint(fmaf(-C.y, z2048.y, fmaf(C.x, z2048.x, 12.f))));
        __syncwarp();
#pragma unroll
        for (int i = 0; i < 5; i++) *(uint2*)(sm + (scr - sb) + i * 256 + ((lane * 8) ^ (i == 1 ? 64 : 0))) = make_uint2(packh(acc[i][1], acc[i][0]), packh(acc[i][3], acc[i][2]));
        if (lane == 0) sts32(cb + XO_KLAST + 4 * w, last);
        asm volatile("cp.async.wait_group 0;" ::: "memory");
        if (warp != 7) CL_WAIT();
        named_bar(1 + wgi, 128);
        if (warp == 16) { mbar_wait(MB(MB_MG1), 0); mkc1(); }
        const uint32_t td = cb + XO_TD + 64 * 4, tf = cb + XO_TF - 32 * 4;
        auto fsum = [&](int off, uint32_t& r0, uint32_t& r1) {
            const unsigned char* p = sm + wgi * (4 * KSCR) + off;
            const uint2 a = *(const uint2*)p, b2 = *(const uint2*)(p + KSCR), c = *(const uint2*)(p + 2 * KSCR), d = *(const uint2*)(p + 3 * KSCR);
            const float2 u = hsum4(a.x, b2.x, c.x, d.x), v = hsum4(a.y, b2.y, c.y, d.y);
            r0 = pack2(u.x * inv, u.y * inv);
            r1 = pack2(v.x * inv, v.y * inv);
        };
        const int role = (w + wgi) & 3;
        const int fo = role ? (role + 1) * 256 + lane * 8 : (((g & 1) * 320) ^ (lm * 32)) + t * 8;
        uint32_t r[2];
        fsum(fo, r[0], r[1]);
        if (role == 0) {
            uint32_t q[2], v[4];
            fsum(fo + 128, q[0], q[1]);
            const uint32_t c[4] = {r[0], q[0], r[1], q[1]};
#pragma unroll
            for (int i = 0; i < 4; i++) v[i] = __shfl_sync(0xffffffffu, c[i], (lane + 31) & 31);
            if (lane == 0) mbar_arrive(MB(MB_KD));
#pragma unroll
            for (int i = 0; i < 4; i++) *(uint2*)(sm + (td - sb) + lane * 8 + i * 256) = make_uint2(__byte_perm(c[i], lane ? v[i] : i ? v[i - 1] : 0u, 0x5432), c[i]);
            if (lane == 0) { fixa = td + 256 * 4 + 2; fixv = v[3]; }
        } else if (role == 1) {
            const uint32_t v0 = __shfl_sync(0xffffffffu, r[0], (lane + 1) & 31), v1 = __shfl_sync(0xffffffffu, r[1], (lane + 1) & 31);
            if (lane == 0) mbar_arrive(MB(MB_KD));
#pragma unroll
            for (int h = 0; h < 2; h++) {
                const uint32_t dd = __byte_perm(r[h], 0, 0x3232);
                *(uint4*)(sm + (td - sb) + 1024 + lane * 16 + h * 512) = make_uint4(dd, dd, r[h], __byte_perm((h || lane == 31) ? v1 : v0, r[h], 0x5432));
            }
        } else {
            __syncwarp();
            if (lane == 0) mbar_arrive(MB(MB_KD));
            const uint32_t p = role == 2 ? tf + (64 + 32 * (t >> 1) + 2 * g + (t & 1)) * 4 : tf + 2 * UP + (64 + 16 * t + g) * 4, p1 = p + (role == 2 ? 64 : 32);
            const uint32_t k0 = r[0] >> 16, k1 = r[1] >> 16;
            sts16(p + UP, r[0]); sts16(p + UP + 6, r[0]); sts16(p1 + UP, r[1]); sts16(p1 + UP + 6, r[1]);
            sts16(p1 - 4, k1); sts16(p1 + 2, k1);
            const uint32_t dd = __byte_perm(r[0], 0, 0x3232);
            if (lane) { sts16(p - 4, k0); sts16(p + 2, k0); }
            else if (role == 2) {
                *(uint4*)(sm + (td - sb) + 512 * 4) = make_uint4(dd, dd, dd, r[0] & 0xFFFF0000u);
                fixa = td + 511 * 4; fixv = k0;
            } else {
                const uint4 kl4 = *(const uint4*)(sm + (cb - sb) + XO_KLAST);
                const uint32_t kl = f2bits((float)(int)(kl4.x + kl4.y + kl4.z + kl4.w - 128u * 0x41400000u) * 9.5367431640625e-7f * inv);
                sts16(tf + 127 * 4, dd); sts16(tf + 128 * 4 + 2, dd); sts32(cb + XO_K1024, dd);
                sts16(tf + 2 * UP + 127 * 4, kl); sts16(tf + 2 * UP + 128 * 4 + 2, kl);
            }
        }
        __syncwarp();
        rst();
        mod2();
        if (wgi == 3) {
            mbar_wait(MB(MB_KD), 0);
            mbar_wait(MB(MB_WM2), 0);
            PROXY_FENCE();
            if (lane == 0) tma2d(sb + w * 15360, w < 3 ? &tm_wg : &tm_wu, 40 * b, w < 3 ? 192 * w : 0, w < 3 ? MB(MB_WG) : MB(MB_WU));
            __syncwarp();
        }
    }
    if (has_ch) {
        conv_channel(sm, rk, fixa, fixv, rst2);
    } else {
        rst2();
        asm volatile("setmaxnreg.inc.sync.aligned.u32 88;");
        mbar_wait(MB(MB_WG), 0);
        mbar_wait(MB(MB_C2), 0);
    }
    {
    const int tid = fresh_tid(), warp = __shfl_sync(0xffffffffu, tid >> 5, 0), lane = tid & 31;
    const int g = lane >> 2, t = lane & 3, lr = lane & 7, lm = lane >> 3;
    __syncwarp();
    if (lane == 0) mbar_arrive(MB(MB_CD));
    uint32_t x1[10];
    uint32_t wf[9][4], wd[2][3][4];
    const int fmt = warp >> 2, fsl = warp & 3;
    uint32_t wa = sb + ((fmt == 4) ? (((lm & 1) ? OFF_WU : OFF_WG) + 64) : ((fmt >> 1) * OFF_WU + ((2 * (fmt & 1) + (lm & 1)) << 4))) + (144 * fsl + lr + 8 * (lm >> 1)) * 80;
    asm volatile("" : "+r"(wa));
    auto ldwf = [&]() {
#pragma unroll
        for (int ks = 0; ks < 9; ks++) ldsm_x4_t(wf[ks], wa + ks * 1280);
    };
    if (warp < 16) {
        uint32_t bw[5], v[10];
#pragma unroll
        for (int j = 0; j < 5; j++) bw[j] = (g & 1) ? M.c2[4 * j + t].w : 0x3F803F80u;
        const uint32_t xa = sb + OFF_X + XI(warp >> 1) + (2 * (warp & 1) + (lm & 1)) * XG + lr * 80 + (lm >> 1) * 16;
        uint32_t va = sb + OFF_V + (8 * (lm >> 1) + lr) * VP + 32 * warp + 16 * (lm & 1);
        uint32_t vb = cl == 14 ? xa + 32 : va + 16 * VP, vc = cl == 14 ? xa + 32 : va + 32 * VP;
        float4* p = &S->acc2[256 * rk + 16 * warp + g];
        asm volatile("" : "+r"(va), "+r"(vb), "+r"(vc), "+l"(p));
        ldsm_x4(x1, xa); ldsm_x4(x1 + 4, xa + 32); ldsm_x2(x1 + 8, xa + 64);
        float c1[4] = {0.f, 0.f, 0.f, 0.f}, c2[4] = {0.f, 0.f, 0.f, 0.f}, c3[4] = {0.f, 0.f, 0.f, 0.f};
#pragma unroll
        for (int j = 0; j < 2; j++) {
            mbar_wait(MB(j ? MB_V1 : MB_V), 0);
            ldsm_x4_t(v + 4 * j, j ? vb : va);
#pragma unroll
            for (int i = 4 * j; i < 4 * j + 4; i++) x1[i] = add2(x1[i], v[i]);
            mma_bf16(c1, x1[4 * j], x1[4 * j + 1], x1[4 * j + 2], x1[4 * j + 3], bw[2 * j], bw[2 * j + 1]);
            mma_bf16(c2, x1[4 * j], x1[4 * j + 1], x1[4 * j + 2], x1[4 * j + 3], x1[4 * j], x1[4 * j + 2]);
            mma_bf16(c3, x1[4 * j], x1[4 * j + 1], x1[4 * j + 2], x1[4 * j + 3], x1[4 * j + 1], x1[4 * j + 3]);
        }
        mbar_wait(MB(MB_V2), 0);
        ldsm_x2_t(v + 8, vc);
        x1[8] = add2(x1[8], v[8]); x1[9] = add2(x1[9], v[9]);
        mma_k8(c1, x1[8], x1[9], bw[4]); mma_k8(c2, x1[8], x1[9], x1[8]); mma_k8(c3, x1[8], x1[9], x1[9]);
        if (t == (g >> 1)) {
            red4(p, c1[0], (g & 1) ? c2[1] : c2[0], c1[1]);
            red4(p + 8, c1[2], (g & 1) ? c3[3] : c3[2], c1[3]);
        }
        __syncwarp();
    }
    if (warp >= 16) { mbar_wait(MB(MB_WG), 0); mbar_wait(MB(MB_WU), 0); ldwf(); }
    if (warp == 16) {
        const int v = min(lane, 19), vm = v >> 2, vs = v & 3, d0 = (v * 13) >> 6;
        const uint32_t r0 = mapa(sb, d0), r1 = mapa(sb, 4 + (vm & 3)), g0 = sb + OFF_FFR + (32 * v + (v < 8 ? 0 : 256)) * 4;
        uint4* tp = (uint4*)(sm + OFF_AT);
        mbar_wait(MB(MB_CD), 0);
        tp[lane] = make_uint4(lr * 128 + (((lm & 1) ^ lr) << 4) + (lm >> 1) * 1024, lr * (ROWP * 2) + lm * 16, lm * 160 + lr * 8, 0u);
        tp[32 + lane] = make_uint4(sb + OFF_ACT + lr * 112 + lm * 16, sb + OFF_ACT + lr * 112 + lm * 2, 0u, 0u);
        tp[64 + 3 * v] = make_uint4(sb + OFF_WD + vm * 5120, sb + OFF_H2S + 288 * vs, sb + OFF_FFR + (vs * 80 + 16 * vm) * 32, 32 * vs);
        tp[65 + 3 * v] = make_uint4(r0 + OFF_RS + (rk * 5 + v - 5 * d0) * 640, r1 + OFF_RS + (rk * 5 + vs) * 640, r0 + (MB(MB_RS) - sb), r1 + (MB(MB_RS) - sb));
        tp[66 + 3 * v] = make_uint4(g0, g0 + (v < 8 ? 1024 : 256), 0u, 0u);
    }
    if (warp >= 17) {
        if (warp == 17) mbar_wait(MB(MB_CD), 0);
        else if (warp == 18) named_bar(9, 64);
        else named_bar(7, 64);
        PROXY_FENCE();
        if (lane < 3) tma2d(sb + OFF_WD + (3 * (warp - 17) + lane) * 5120, &tm_wd, 64 * (3 * (warp - 17) + lane), 40 * b, MB(MB_WD));
        if (warp == 19 && (lane < 16 || cl == 14)) st_rlx4(&S->acc1[256 * rk + 16 * cl + lane], make_uint4(0, 0, 0, 0));
        __syncwarp();
    }
    uint32_t h2[10];
    uint32_t ta = sb + OFF_H2T + (16 * warp + (lane & 15)) * 80 + (lane >> 4) * 16;
    if (warp < 16) {
        const float4* ap = &S->acc2[256 * rk + 32 * (warp >> 1) + lane];
        mbar_wait(MB(MB_WG + (warp >> 3)), 0); ldwf();
        float4 s = ld_rlx4f(ap);
        const int pj = lane >= 5, pc = lane - 5 * pj;
        uint2 kp[4];
#pragma unroll
        for (int j = 0; j < 4; j++) kp[j] = *(const uint2*)&M.c2[4 * min(pc, 4) + j];
        mbar_wait(MB(MB_CW), 0);
        const float cw = M.cws[0], sbw = M.cws[1];
        uint32_t tk0 = (2047 - (((lane & 6) << 8) + ((lane & 24) << 3) + ((lane & 1) << 5) + RKT + (warp >> 1))) << 3;
        uint32_t ka = sb + OFF_MISC + (uint32_t)offsetof(Misc, key) + (32 * (warp >> 1) + lane) * 4;
        uint32_t rb = mapa(sb, 4 * (warp & 1) + t), cd = rb + OFF_MISC + (uint32_t)offsetof(Misc, cand2) + (8 * rk + (warp >> 1)) * 8;
        uint4* dst = &S->h2c[(2 * (8 * rk + (warp >> 1)) + pj) * 72 + 5 * cl + pc];
        uint32_t pa = sb + OFF_OUT + 32 * (warp >> 1) * 80 + 16 * pc, kca = sb + OFF_MISC + (uint32_t)offsetof(Misc, c2) + 16 * t;
        int wo = lane < 10 && pc < (cl < 14 ? 5 : 2) ? warp & 1 : 2;
        asm volatile("" : "+r"(tk0), "+r"(ta), "+r"(rb), "+r"(cd), "+r"(pa), "+l"(dst), "+r"(wo));
        mbar_wait(MB(MB_CD), 0);
        stsm_x4(ta + (OFF_OUT - OFF_H2T), x1[0], x1[1], x1[2], x1[3]); stsm_x4(ta + (OFF_OUT - OFF_H2T) + 32, x1[4], x1[5], x1[6], x1[7]); stsm_x2(ta + (OFF_OUT - OFF_H2T) + 64, x1[8], x1[9]);
#pragma unroll 1
        for (int it = 0; it < SPIN_MAX && s.w != (float)NCL; it++) {
            if (s.w < (float)PQT) { const uint32_t c0 = clock(); for (int k = 0; k < 1024 && (uint32_t)clock() - c0 < PQD; k++) { } }
            s = ld_rlx4f(ap);
        }
        __syncwarp();
        if (warp == 0) named_arrive(9, 64);
        float meanb, rinv;
        ln_stats(s.x, s.y, meanb, rinv);
        const uint32_t rbits = __float_as_uint(fmaf(fmaf(-meanb, cw, s.z), rinv, sbw));
        const uint32_t key = ((rbits ^ (((int)rbits >> 31) | 0x80000000u)) & 0xFFFFC000u) | tk0;
        const uint32_t m0 = __reduce_max_sync(0xffffffffu, key);
        const uint32_t mr = pack2(meanb, rinv), rl = f2bits(rinv - hi2f(mr));
        const uint32_t m1 = __reduce_max_sync(0xffffffffu, key == m0 ? 0u : key);
        if (lane < 4) sta2(cd, m0, m1 | 1u, rb + (MB(MB_KEY) - sb));
        int si = 16 * (warp & 1) + g;
        {
            const uint32_t b0 = __ballot_sync(0xffffffffu, key == m0), b1 = __ballot_sync(0xffffffffu, key == m1);
            int row;
            asm("bfind.u32 %0, %1;" : "=r"(row) : "r"(pj ? b1 : b0));
            const uint4 a = lds128(pa + 80 * row);
            const uint32_t s0 = __shfl_sync(0xffffffffu, mr, row), s1 = __shfl_sync(0xffffffffu, rl, row);
            const uint32_t qm = __byte_perm(s0, 0, 0x1010), qh = __byte_perm(s0, 0, 0x3232), ql = __byte_perm(s1, 0, 0x1010);
            const uint32_t v0 = norm2(a.x, qm, qh, ql);
            asm volatile("{\n.reg .pred p;\nsetp.eq.s32 p, %5, %6;\n@p st.relaxed.gpu.global.v4.u32 [%0], {%1,%2,%3,%4};\n}" ::"l"(dst),
                         "r"(~add2(mul2(v0, kp[0].x), kp[0].y)), "r"(~add2(mul2(norm2(a.y, qm, qh, ql), kp[1].x), kp[1].y)),
                         "r"(~add2(mul2(norm2(a.z, qm, qh, ql), kp[2].x), kp[2].y)), "r"(~add2(mul2(norm2(a.w, qm, qh, ql), kp[3].x), kp[3].y)), "r"(row >> 4), "r"(wo) : "memory");
            si |= (add2(mul2(v0, kp[0].x), kp[0].y) ^ add2(mul2(norm2(a.w, qm, qh, ql), kp[3].x), kp[3].y)) & ~31u;
        }
        if (warp == 0) named_arrive(7, 64);
        uint2 kc[5];
#pragma unroll
        for (int j = 0; j < 5; j++) kc[j] = lds64(kca + 64 * j);
        uint32_t st[2][2];
#pragma unroll
        for (int h = 0; h < 2; h++) { st[h][0] = __shfl_sync(0xffffffffu, mr, si + 8 * h); st[h][1] = __shfl_sync(0xffffffffu, rl, si + 8 * h); }
        sts32(ka, key);
#pragma unroll
        for (int i = 0; i < 10; i++)
            h2[i] = add2(mul2(norm2(x1[i], __byte_perm(st[i & 1][0], 0, 0x1010), __byte_perm(st[i & 1][0], 0, 0x3232), __byte_perm(st[i & 1][1], 0, 0x1010)), kc[i >> 1].x), kc[i >> 1].y);
        stsm_x4(ta, h2[0], h2[1], h2[2], h2[3]); stsm_x4(ta + 32, h2[4], h2[5], h2[6], h2[7]); stsm_x2(ta + 64, h2[8], h2[9]);
        __syncwarp();
        named_arrive(6, 576);
    }
    auto outt = [&]() {
        if (warp < 16) {
            uint32_t o[10];
#pragma unroll
            for (int i = 0; i < 10; i++) o[i] = add2(x1[i], mul2(M.c2[4 * (i >> 1) + t].z, h2[i]));
            stsm_x4(ta + (OFF_OUT - OFF_H2T), o[0], o[1], o[2], o[3]); stsm_x4(ta + (OFF_OUT - OFF_H2T) + 32, o[4], o[5], o[6], o[7]); stsm_x2(ta + (OFF_OUT - OFF_H2T) + 64, o[8], o[9]);
        }
    };
    outt();
    uint4 gv = make_uint4(1, 1, 1, 1);
    const unsigned char* gp;
    uint32_t gdst;
    {
        const int gi = 32 * warp + lane, kk = (gi * 911) >> 16, seg = gi - 72 * kk;
        uint32_t ca = sb + OFF_MISC + (uint32_t)offsetof(Misc, cand2), sa = ca + 544 + 4 * (kk & 7);
        gp = (const unsigned char*)&S->h2c[seg];
        gdst = sb + OFF_H2S + kk * (ROWP * 2) + seg * 16;
        if (warp == 18) {
            gp = (const unsigned char*)&S->h2c[136 * 72 + min(2 * (rk < 4 ? 5 * rk : 4 * rk + 4) + lane, 71)];
            gdst = sb + OFF_GB + 16 * lane;
            if (lane < 10) gv = ld_rlx4(gp);
        }
        asm volatile("" : "+r"(sa), "+r"(gdst), "+l"(gp));
        named_bar(13, 672);
        if (warp < 18) {
            gp += lds32(sa);
            gv = ld_rlx4(gp);
        } else if (warp == 19) named_arrive(8, 64);
    }
    uint32_t wda, ha, fo, pg, pu, pv, pa, rd[2], rm[2];
    {
        const uint32_t tl = sb + OFF_AT + 16 * lane, tw = sb + OFF_AT + 1024 + 48 * warp;
        const uint4 a = lds128(tl), c = lds128(tw), d = lds128(tw + 16);
        const uint2 e = lds64(tl + 512), f = lds64(tw + 32);
        wda = (a.x ^ c.w) + c.x; ha = a.y + c.y; fo = c.z + 8 * lane; pg = f.x + 4 * lane; pu = f.y + 4 * lane; pv = e.y + 8 * warp; pa = e.x;
        rd[0] = d.x + a.z; rd[1] = d.y + a.z; rm[0] = d.z; rm[1] = d.w;
        asm volatile("" : "+r"(wda), "+r"(ha), "+r"(fo), "+r"(pg), "+r"(pu), "+r"(pv), "+r"(pa), "+r"(rd[0]), "+r"(rd[1]), "+r"(rm[0]), "+r"(rm[1]));
    }
    const uint32_t zz = ((wda | ha | fo) | (pu | pv | pa) | (rd[0] | rd[1])) >> 31;
    auto ldwd = [&]() {
#pragma unroll
        for (int i = 0; i < 2; i++)
#pragma unroll
            for (int ks = 0; ks < 3; ks++)
                if (i == 0 || warp < 16) {
                    if (ks == 2) ldsm_x2_t(wd[i][ks], wda + ks * 2048 + i * 5 * 5120);
                    else ldsm_x4_t(wd[i][ks], wda + ks * 2048 + i * 5 * 5120);
                }
    };
    if ((gv.x | zz) == 0u) {
        int it = 0;
#pragma unroll 1
        do gv = ld_rlx4(gp); while (++it < SPIN_MAX && gv.x == 0u);
    }
    asm volatile("st.shared.v4.u32 [%0], {%1,%2,%3,%4};" ::"r"(gdst), "r"(~gv.x), "r"(~gv.y), "r"(~gv.z), "r"(~gv.w) : "memory");
    CBAR();
    auto ffn1 = [&]() {
        float acc[2][4] = {{0.f, 0.f, 0.f, 0.f}, {0.f, 0.f, 0.f, 0.f}};
        uint32_t hb[5][4];
#pragma unroll
        for (int k2 = 0; k2 < 5; k2++) if (k2 < 4) ldsm_x4(hb[k2], ha + k2 * 64); else ldsm_x2(hb[k2], ha + 256);
#pragma unroll
        for (int k2 = 0; k2 < 5; k2++) {
            mma_bf16(acc[0], wf[2 * k2][0], wf[2 * k2][1], wf[2 * k2][2], wf[2 * k2][3], hb[k2][0], hb[k2][1]);
            if (k2 < 4) mma_bf16(acc[1], wf[2 * k2 + 1][0], wf[2 * k2 + 1][1], wf[2 * k2 + 1][2], wf[2 * k2 + 1][3], hb[k2][2], hb[k2][3]);
        }
        asm volatile("st.shared.v2.f32 [%0], {%1,%2};" ::"r"(fo), "f"(acc[0][0] + acc[1][0]), "f"(acc[0][1] + acc[1][1]) : "memory");
        asm volatile("st.shared.v2.f32 [%0+256], {%1,%2};" ::"r"(fo), "f"(acc[0][2] + acc[1][2]), "f"(acc[0][3] + acc[1][3]) : "memory");
    };
    ffn1();
    auto gate = [&]() {
        if (warp < 10) {
            float a[8];
#pragma unroll
            for (int i = 0; i < 8; i++) a[i] = __uint_as_float(lds32((i & 4 ? pu : pg) + (i & 3) * 2560));
            float gg = bfr((a[0] + a[1]) + (a[2] + a[3]));
            gg = bfr(silu(gg));
            const float uu = bfr((a[4] + a[5]) + (a[6] + a[7]));
            sts16(pv, f2bits(gg * uu));
        }
    };
    if (warp < 10) { CBAR(); gate(); }
    else named_arrive(0, 640);
    mbar_wait(MB(MB_WD), 0);
    ldwd();
    named_bar(12, 640);
    auto ffn2 = [&](int pass) {
        uint32_t bq[6];
        ldsm_x4(bq, pa); ldsm_x2(bq + 4, pa + 64);
        float acc[2][4] = {{0.f, 0.f, 0.f, 0.f}, {0.f, 0.f, 0.f, 0.f}};
        uint32_t r[2][2];
#pragma unroll
        for (int ks = 0; ks < 3; ks++)
#pragma unroll
            for (int i = 0; i < 2; i++) {
                if (ks == 2) mma_k8(acc[i], wd[i][ks][0], wd[i][ks][1], bq[4]);
                else mma_bf16(acc[i], wd[i][ks][0], wd[i][ks][1], wd[i][ks][2], wd[i][ks][3], bq[2 * ks], bq[2 * ks + 1]);
            }
#pragma unroll
        for (int i = 0; i < 2; i++) { r[i][0] = movm(pack2(acc[i][0], acc[i][1])); r[i][1] = movm(pack2(acc[i][2], acc[i][3])); }
#pragma unroll
        for (int j = 0; j < 2; j++)
            if (j == 0 || warp < 16) sta2(rd[j] + 80 * pass, r[j][0], r[j][1], rm[j] + pass * 8 * (MB_RS2 - MB_RS));
    };
    ffn2(0);
    auto fin = [&](int pass) {
        const int lane = fresh_tid() & 31;
        const int fP = min(warp < 8 ? 20 * cl + lane : 8 * (rk < 4 ? 5 * rk : 4 * rk + 4) + 4 * (warp - 8) + (lane & 3), D_ / 2 - 1);
        uint32_t fgb = lds32(warp < 8 ? sb + OFF_MISC + (uint32_t)offsetof(Misc, c2) + 8 + 16 * lane : sb + OFF_GB + 16 * (warp - 8) + 4 * (lane & 3));
        const int ftok = warp < 8 ? warp : lane >> 2;
        uint32_t fkey = pass ? M.fin[ftok] : M.sel[ftok];
        const bool fon = warp < 8 ? (MINE(fkey) && lane < (cl < 14 ? 20 : 8)) : warp < (rk < 4 ? 18 : 16);
        const uint32_t hv = lds32(sb + OFF_H2S + ftok * (ROWP * 2) + 4 * fP);
        uint32_t p = sb + OFF_RS + pass * 80 + ((warp - 8) >> 1) * 640 + (lane >> 3) * 160 + (lane & 7) * 8 + 4 * (warp & 1);
        float4* ap = &S->acc3[pass * (72 * 32) + (fP >> 2) * 32 + 4 * ftok + (fP & 3)];
        bf16* op = out + ((~fkey >> 3) & 2047u) * D_ + 2 * fP;
        asm volatile("" : "+r"(p), "+l"(ap), "+l"(op));
        float s0 = 0.f, s1 = 0.f, s2 = 1.0f, s3 = 0.f;
        if (warp >= 8) {
            if (fon) {
                mbar_wait(MB(pass ? MB_RS2 : MB_RS), 0);
                uint32_t v[8];
#pragma unroll
                for (int i = 0; i < 8; i++) v[i] = lds32(p + i * 3200);
                s0 = ((lo2f(v[0]) + lo2f(v[1])) + (lo2f(v[2]) + lo2f(v[3]))) + ((lo2f(v[4]) + lo2f(v[5])) + (lo2f(v[6]) + lo2f(v[7])));
                s1 = ((hi2f(v[0]) + hi2f(v[1])) + (hi2f(v[2]) + hi2f(v[3]))) + ((hi2f(v[4]) + hi2f(v[5])) + (hi2f(v[6]) + hi2f(v[7])));
            }
        } else if (fon) {
            const uint32_t row = ROW(fkey);
            const unsigned short* vp = (const unsigned short*)(sm + OFF_V + 2 * lane * VP) + row;
            const uint32_t xv = add2(lds32(sb + OFF_X + XI(row >> 5) + ((row >> 3) & 3) * XG + (row & 7) * 80 + 4 * lane), (uint32_t)vp[0] | ((uint32_t)vp[VP / 2] << 16));
            s2 = (float)(((xv & 0xFFFFu) << 5) | 1u); s3 = (float)(xv >> 16);
            mbar_wait(MB(MB_OUT), 0);
        }
        float4 o = make_float4(0.f, 0.f, 0.f, 0.f);
        if (fon) o = atom4(ap, s0, s1, s2, s3);
        uint32_t redo = 0;
        if (!pass) {
            mbar_wait(MB(MB_FIN), 0);
            redo = M.fin[8];
            fkey = M.fin[ftok];
        }
        const float rs = sigm(hi2f(fkey ^ (((int)~fkey >> 31) | 0x80000000u)));
        uint32_t rs2 = pack2(rs, rs);
        s2 = fmaxf(s2 + 8388608.f, rs); s3 = fmaxf(s3 + 8388608.f, rs);
        if (rs > 2.f) s0 = s1 = rs;
        uint32_t msk = redo ? 0u : 16u;
        asm volatile("" : "+r"(rs2), "+r"(fgb), "+f"(s2), "+f"(s3), "+r"(msk), "+f"(s0), "+f"(s1));
        const uint32_t z = __float_as_uint(o.z + s2), zh = __float_as_uint(o.w + s3);
        const uint32_t xv = __byte_perm(z >> 5, zh, 0x5410);
        asm volatile("{\n.reg .pred q;\nsetp.ne.u32 q, %2, 0;\n@q st.global.u32 [%0], %1;\n}" ::"l"(op), "r"(add2(xv, mul2(fgb, add2(hv, mul2(pack2(o.x + s0, o.y + s1), rs2))))), "r"(z & msk) : "memory");
        return redo;
    };
    if (fin(0)) {
        const int gi = fresh_tid(), kk = (gi * 911) >> 16, seg = gi - 72 * kk;
        __syncwarp();
        if (warp < 8) {
            const uint32_t key = M.fin[warp];
            if (MINE(key) && lane < (cl < 14 ? 5 : 2)) {
                const uint4 a = lds128(sb + OFF_H2T + ROW(key) * 80 + 16 * lane);
                st_rlx4(&S->h2c[(128 + warp) * 72 + 5 * cl + lane], make_uint4(~a.x, ~a.y, ~a.z, ~a.w));
            }
            __syncwarp();
        }
        RBAR();
        if (warp < 18) {
            uint4 gv = make_uint4(0, 0, 0, 0);
#pragma unroll 1
            for (int it = 0; it < SPIN_MAX && gv.x == 0u; it++) gv = ld_rlx4(&S->h2c[128 * 72 + gi]);
            *(uint4*)(sm + OFF_H2S + kk * (ROWP * 2) + seg * 16) = make_uint4(~gv.x, ~gv.y, ~gv.z, ~gv.w);
        }
        RBAR();
        ffn1();
        ldwd();
        RBAR();
        gate();
        RBAR();
        ffn2(1);
        fin(1);
    }
    }
    }
}

typedef CUresult (*EncodeFn)(CUtensorMap*, CUtensorMapDataType, cuuint32_t, void*, const cuuint64_t*, const cuuint64_t*,
                             const cuuint32_t*, const cuuint32_t*, CUtensorMapInterleave, CUtensorMapSwizzle,
                             CUtensorMapL2promotion, CUtensorMapFloatOOBfill);

static void make_map(EncodeFn fn, CUtensorMap* m, const void* ptr, uint64_t cols, uint64_t rows, uint32_t bc, uint32_t br,
                     CUtensorMapSwizzle sw, int five) {
    cuuint64_t dims[5] = {cols, rows, 4, 4, 288};
    cuuint64_t strides[4] = {cols * 2 * (five ? 32 : 1), cols * 2 * 512, cols * 2 * 64, cols * 2};
    cuuint32_t box[5] = {bc, br, 4, 4, 8};
    cuuint32_t es[5] = {1, 1, 1, 1, 1};
    CUresult rc = fn(m, CU_TENSOR_MAP_DATA_TYPE_BFLOAT16, five ? 5 : 2, (void*)ptr, dims, strides, box, es, CU_TENSOR_MAP_INTERLEAVE_NONE,
                     sw, (CUtensorMapL2promotion)(five || sw ? 0 : br == 72 ? L2M : L2P), CU_TENSOR_MAP_FLOAT_OOB_FILL_NONE);
    (void)rc;
}

static void launch(void* const* d_in, const int* in_sizes, int n_in, void* d_out, int out_size) {
    static EncodeFn enc = nullptr;
    static CUtensorMap tmm, tmg, tmu, tmd, tmo;
    static Scratch* sp = nullptr;
    static const void* cached[6] = {nullptr, nullptr, nullptr, nullptr, nullptr, nullptr};
    if (!enc) {
        cudaDriverEntryPointQueryResult qr;
        void* fn = nullptr;
        cudaGetDriverEntryPoint("cuTensorMapEncodeTiled", &fn, cudaEnableDefault, &qr);
        enc = (EncodeFn)fn;
        cudaFuncSetAttribute(clus_kernel, cudaFuncAttributeMaxDynamicSharedMemorySize, SMEM_TOTAL);
        cudaGetSymbolAddress((void**)&sp, g_s);
    }
    if (cached[0] != d_in[13] || cached[1] != d_in[9] || cached[2] != d_in[10] || cached[3] != d_in[11] || cached[4] != d_in[0] || cached[5] != d_out) {
        make_map(enc, &tmo, d_out, D_, 2, 40, 2, CU_TENSOR_MAP_SWIZZLE_NONE, 1);
        make_map(enc, &tmm, d_in[13], 6 * D_, D_, 40, 72, CU_TENSOR_MAP_SWIZZLE_NONE, 0);
        make_map(enc, &tmg, d_in[9], F_, D_, 40, 192, CU_TENSOR_MAP_SWIZZLE_NONE, 0);
        make_map(enc, &tmu, d_in[10], F_, D_, 40, 192, CU_TENSOR_MAP_SWIZZLE_NONE, 0);
        make_map(enc, &tmd, d_in[11], D_, F_, 64, 40, CU_TENSOR_MAP_SWIZZLE_128B, 0);
        cached[0] = d_in[13]; cached[1] = d_in[9]; cached[2] = d_in[10]; cached[3] = d_in[11]; cached[4] = d_in[0]; cached[5] = d_out;
    }
    clus_kernel<<<G_, NTHR, SMEM_TOTAL>>>((const bf16*)d_in[0], (const bf16*)d_in[1], (const bf16*)d_in[2], (const bf16*)d_in[3], (const bf16*)d_in[4],
                                          (const bf16*)d_in[5], (const bf16*)d_in[12], sp, (const bf16*)d_in[6], (const bf16*)d_in[8], (const bf16*)d_in[13],
                                          (bf16*)d_out, tmm, tmg, tmu, tmd, tmo);
}


static bool fits() {
    cudaFuncSetAttribute(clus_kernel, cudaFuncAttributeMaxDynamicSharedMemorySize, SMEM_TOTAL);
    cudaLaunchConfig_t cfg = {};
    cudaLaunchAttribute at;
    at.id = cudaLaunchAttributeClusterDimension;
    at.val.clusterDim.x = 8; at.val.clusterDim.y = 1; at.val.clusterDim.z = 1;
    cfg.gridDim = dim3(G_); cfg.blockDim = dim3(NTHR); cfg.dynamicSmemBytes = SMEM_TOTAL; cfg.attrs = &at; cfg.numAttrs = 1;
    int n = 0;
    const bool ok = cudaOccupancyMaxActiveClusters(&n, clus_kernel, &cfg) == cudaSuccess && n >= NCL;
    cudaGetLastError();
    return ok;
}
}
#undef L_
#undef D_
#undef N_
#undef F_
#undef G_
#undef NCL
#undef NTHR
#undef SPIN_MAX
#undef NRS
#undef OFF_WG
#undef OFF_WU
#undef KSCR
#undef OFF_WM0
#undef OFF_STG
#undef OFF_MG2
#undef OFF_CH
#undef CHS
#undef UP
#undef UB
#undef XO_TF
#undef XO_U8
#undef XO_U16
#undef XO_ZA
#undef XO_ZB
#undef XO_ZC
#undef XO_ZD
#undef XO_TD
#undef XO_K1024
#undef XO_DSK
#undef XO_KLAST
#undef XO_MBU
#undef OFF_X
#undef XG
#undef XI
#undef XN
#undef OFF_V
#undef VP
#undef OFF_EK
#undef OFF_WM2
#undef OFF_MG1
#undef OFF_SC
#undef OFF_C1
#undef OFF_MISC
#undef OFF_WD
#undef OFF_H2T
#undef OFF_OUT
#undef OFF_GB
#undef OFF_AT
#undef ROWP
#undef OFF_H2S
#undef OFF_FFR
#undef OFF_ACT
#undef OFF_RS
#undef SMEM_TOTAL
#undef CBAR
#undef RBAR
#undef PROXY_FENCE
#undef D4
#undef O4
#undef WG_FENCE
#undef WG_COMMIT
#undef WG_WAIT
#undef TQ
#undef MB
#undef SD
#undef UF
#undef DS
#undef Q4
#undef RD_
#undef M2W
#undef WS
#undef WMS
#undef PQT
#undef PQD
#undef L2P
#undef L2M
#undef PDE
#undef WMD
#undef CWP
#undef CWD
#undef ROW
#undef RKT
#undef MINE
#undef CE
#undef POP
#undef CGT
#undef CL_ARRIVE
#undef CL_WAIT
#undef TA
#undef PH

namespace v4 {

#define L_ 2048
#define D_ 576
#define N_ 128
#define F_ 4608
#define G_ 128
#define NTHR 640
#define SPIN_MAX (1 << 18)
#define SENT 0u
#define HINT_N 182u

typedef __nv_bfloat16 bf16;

struct Scratch {
    uint4 xn[G_ * G_ * 10];
    uint4 v[G_ * D_ * 2];
    uint2 part[G_ * G_ * 9];
    uint4 h2w[L_ * 96];
    unsigned int rec[G_ * 8];
    unsigned int modw[6 * D_];
    unsigned int ticket[64];
    unsigned int cnt[64];
    unsigned int hint[64];
};
__device__ __align__(1024) Scratch g_s;

#define OFF_WG 0
#define OFF_WU 46080
#define OFF_CH 92160
#define CHS 20784
#define ULBO 656
#define XO_U8 6272
#define XO_U16 10368
#define XO_ZA 5248
#define XO_ZB 8448
#define XO_ZC 11648
#define XO_ZD 13824
#define XO_TD 16000
#define XO_TF 18624
#define XO_K1024 20672
#define KSCR 3456
#define OFF_TILE 196096
#define ROWP 584
#define OFF_MISC 214784
#define OFF_WD OFF_CH
#define OFF_H2T (OFF_CH + 3 * CHS)
#define OFF_H2S (OFF_H2T + 18688)
#define OFF_FFR (OFF_H2S + 9344)
#define OFF_FIN OFF_FFR
#define OFF_ACT (OFF_FFR + 10240)

struct Misc {
    __align__(16) uint4 sent[256];
    __align__(16) uint4 box[11 * 14];
    union {
        struct {
            __align__(16) float2 part[18][16];
            float rp[18][16];
        };
        struct {
            __align__(16) unsigned short st1[3][16];
            __align__(16) float p1[16][4], p2[16][4];
        };
    };
    __align__(16) bf16 cb1[D_], sb[D_], gb[D_];
    __align__(16) bf16 sc[D_];
    __align__(16) unsigned int cand[64], skey[16];
    __align__(16) float kinv[5][4], klast[5][4];
    unsigned int pk[4][8];
    __align__(16) uint4 st2[16];
    unsigned int wr[D_ / 2];
    float modx[32];
    unsigned int rank[16];
    volatile unsigned int flag;
    unsigned int e1cnt;
    unsigned long long mbar[5];
    unsigned int epoch;
};
#define SMEM_TOTAL (OFF_MISC + (int)sizeof(Misc))
static_assert(SMEM_TOTAL <= 232448, "smem");

__device__ __forceinline__ float lo2f(uint32_t w) { return __uint_as_float(w << 16); }
__device__ __forceinline__ float hi2f(uint32_t w) { return __uint_as_float(w & 0xFFFF0000u); }
__device__ __forceinline__ uint32_t pack2(float lo, float hi) { uint32_t r; asm("cvt.rn.bf16x2.f32 %0, %1, %2;" : "=r"(r) : "f"(hi), "f"(lo)); return r; }
__device__ __forceinline__ float bfr(float x) { return __uint_as_float(pack2(0.f, x)); }
__device__ __forceinline__ uint32_t f2bits(float x) { return pack2(x, 0.f); }
__device__ __forceinline__ uint32_t packh(float lo, float hi) { uint32_t r; asm("cvt.rn.f16x2.f32 %0, %1, %2;" : "=r"(r) : "f"(hi), "f"(lo)); return r; }
__device__ __forceinline__ float frcp(float x) { float r; asm("rcp.approx.ftz.f32 %0, %1;" : "=f"(r) : "f"(x)); return r; }
__device__ __forceinline__ float fsqrt(float x) { float r; asm("sqrt.approx.f32 %0, %1;" : "=f"(r) : "f"(x)); return r; }
__device__ __forceinline__ float fex2(float x) { float r; asm("ex2.approx.ftz.f32 %0, %1;" : "=f"(r) : "f"(x)); return r; }
__device__ __forceinline__ float silu(float x) { return __fdividef(x, 1.0f + __expf(-x)); }
__device__ __forceinline__ uint32_t add2(uint32_t a, uint32_t b) { uint32_t r; asm("add.rn.bf16x2 %0, %1, %2;" : "=r"(r) : "r"(a), "r"(b)); return r; }
__device__ __forceinline__ uint32_t sub2(uint32_t a, uint32_t b) { uint32_t r; asm("sub.rn.bf16x2 %0, %1, %2;" : "=r"(r) : "r"(a), "r"(b)); return r; }
__device__ __forceinline__ uint32_t mul2(uint32_t a, uint32_t b) { uint32_t r; asm("mul.rn.bf16x2 %0, %1, %2;" : "=r"(r) : "r"(a), "r"(b)); return r; }
__device__ __forceinline__ uint32_t fma2(uint32_t a, uint32_t b, uint32_t c) { uint32_t r; asm("fma.rn.bf16x2 %0, %1, %2, %3;" : "=r"(r) : "r"(a), "r"(b), "r"(c)); return r; }
__device__ __forceinline__ uint32_t norm2(uint32_t x, uint32_t m, uint32_t rh, uint32_t rl) { const uint32_t d = sub2(x, m); return fma2(d, rh, mul2(d, rl)); }

__device__ __forceinline__ void mma_bf16(float* c, uint32_t a0, uint32_t a1, uint32_t a2, uint32_t a3, uint32_t b0, uint32_t b1) {
    asm volatile("mma.sync.aligned.m16n8k16.row.col.f32.bf16.bf16.f32 {%0,%1,%2,%3}, {%4,%5,%6,%7}, {%8,%9}, {%0,%1,%2,%3};\n"
                 : "+f"(c[0]), "+f"(c[1]), "+f"(c[2]), "+f"(c[3]) : "r"(a0), "r"(a1), "r"(a2), "r"(a3), "r"(b0), "r"(b1));
}
__device__ __forceinline__ void mma_f16(float* c, const uint32_t* a, uint32_t b0, uint32_t b1) {
    asm volatile("mma.sync.aligned.m16n8k16.row.col.f32.f16.f16.f32 {%0,%1,%2,%3}, {%4,%5,%6,%7}, {%8,%9}, {%0,%1,%2,%3};\n"
                 : "+f"(c[0]), "+f"(c[1]), "+f"(c[2]), "+f"(c[3]) : "r"(a[0]), "r"(a[1]), "r"(a[2]), "r"(a[3]), "r"(b0), "r"(b1));
}
__device__ __forceinline__ void ldsm_x4(uint32_t* r, uint32_t addr) {
    asm volatile("ldmatrix.sync.aligned.m8n8.x4.shared.b16 {%0,%1,%2,%3}, [%4];" : "=r"(r[0]), "=r"(r[1]), "=r"(r[2]), "=r"(r[3]) : "r"(addr) : "memory");
}
__device__ __forceinline__ void ldsm_x4_t(uint32_t* r, uint32_t addr) {
    asm volatile("ldmatrix.sync.aligned.m8n8.x4.trans.shared.b16 {%0,%1,%2,%3}, [%4];" : "=r"(r[0]), "=r"(r[1]), "=r"(r[2]), "=r"(r[3]) : "r"(addr) : "memory");
}
__device__ __forceinline__ void stsm_x4(uint32_t addr, uint32_t r0, uint32_t r1, uint32_t r2, uint32_t r3) {
    asm volatile("stmatrix.sync.aligned.m8n8.x4.shared.b16 [%0], {%1,%2,%3,%4};" ::"r"(addr), "r"(r0), "r"(r1), "r"(r2), "r"(r3) : "memory");
}
__device__ __forceinline__ void stsm_x4_t(uint32_t addr, uint32_t r0, uint32_t r1, uint32_t r2, uint32_t r3) {
    asm volatile("stmatrix.sync.aligned.m8n8.x4.trans.shared.b16 [%0], {%1,%2,%3,%4};" ::"r"(addr), "r"(r0), "r"(r1), "r"(r2), "r"(r3) : "memory");
}
__device__ __forceinline__ uint32_t movm(uint32_t a) { uint32_t r; asm volatile("movmatrix.sync.aligned.m8n8.trans.b16 %0, %1;" : "=r"(r) : "r"(a)); return r; }
__device__ __forceinline__ uint32_t lds32(uint32_t a) { uint32_t v; asm volatile("ld.shared.u32 %0, [%1];" : "=r"(v) : "r"(a)); return v; }
__device__ __forceinline__ void sts32(uint32_t a, uint32_t v) { asm volatile("st.shared.u32 [%0], %1;" ::"r"(a), "r"(v) : "memory"); }
__device__ __forceinline__ void sts16(uint32_t a, uint32_t v) { asm volatile("st.shared.u16 [%0], %1;" ::"r"(a), "h"((unsigned short)v) : "memory"); }
__device__ __forceinline__ void named_bar(int id, int n) { asm volatile("bar.sync %0, %1;" ::"r"(id), "r"(n) : "memory"); }
__device__ __forceinline__ void named_arrive(int id, int n) { asm volatile("bar.arrive %0, %1;" ::"r"(id), "r"(n) : "memory"); }
#define CBAR() asm volatile("bar.sync 0, 640;" ::: "memory")
#define PROXY_FENCE() asm volatile("fence.proxy.async.shared::cta;" ::: "memory")

#define D4(d, o) "+f"(d[o]), "+f"(d[o + 1]), "+f"(d[o + 2]), "+f"(d[o + 3])
__device__ __forceinline__ void wg32(float* d, uint32_t a0, uint32_t a1, uint32_t a2, uint32_t a3, uint64_t desc) {
    asm volatile("wgmma.mma_async.sync.aligned.m64n32k16.f32.bf16.bf16 {%0,%1,%2,%3,%4,%5,%6,%7,%8,%9,%10,%11,%12,%13,%14,%15}, {%16,%17,%18,%19}, %20, 1, 1, 1, 0;"
                 : D4(d, 0), D4(d, 4), D4(d, 8), D4(d, 12) : "r"(a0), "r"(a1), "r"(a2), "r"(a3), "l"(desc));
}
__device__ __forceinline__ void wg48(float* d, uint32_t a0, uint32_t a1, uint32_t a2, uint32_t a3, uint64_t desc) {
    asm volatile("wgmma.mma_async.sync.aligned.m64n48k16.f32.bf16.bf16 {%0,%1,%2,%3,%4,%5,%6,%7,%8,%9,%10,%11,%12,%13,%14,%15,%16,%17,%18,%19,%20,%21,%22,%23}, {%24,%25,%26,%27}, %28, 1, 1, 1, 0;"
                 : D4(d, 0), D4(d, 4), D4(d, 8), D4(d, 12), D4(d, 16), D4(d, 20) : "r"(a0), "r"(a1), "r"(a2), "r"(a3), "l"(desc));
}
#define O4(d, o) "=f"(d[o]), "=f"(d[o + 1]), "=f"(d[o + 2]), "=f"(d[o + 3])
__device__ __forceinline__ void wg32z(float* d, uint32_t a0, uint32_t a1, uint32_t a2, uint32_t a3, uint64_t desc) {
    asm volatile("wgmma.mma_async.sync.aligned.m64n32k16.f32.bf16.bf16 {%0,%1,%2,%3,%4,%5,%6,%7,%8,%9,%10,%11,%12,%13,%14,%15}, {%16,%17,%18,%19}, %20, 0, 1, 1, 0;"
                 : O4(d, 0), O4(d, 4), O4(d, 8), O4(d, 12) : "r"(a0), "r"(a1), "r"(a2), "r"(a3), "l"(desc));
}
__device__ __forceinline__ void wg48z(float* d, uint32_t a0, uint32_t a1, uint32_t a2, uint32_t a3, uint64_t desc) {
    asm volatile("wgmma.mma_async.sync.aligned.m64n48k16.f32.bf16.bf16 {%0,%1,%2,%3,%4,%5,%6,%7,%8,%9,%10,%11,%12,%13,%14,%15,%16,%17,%18,%19,%20,%21,%22,%23}, {%24,%25,%26,%27}, %28, 0, 1, 1, 0;"
                 : O4(d, 0), O4(d, 4), O4(d, 8), O4(d, 12), O4(d, 16), O4(d, 20) : "r"(a0), "r"(a1), "r"(a2), "r"(a3), "l"(desc));
}
#define WG_FENCE() asm volatile("wgmma.fence.sync.aligned;" ::: "memory")
#define WG_COMMIT() asm volatile("wgmma.commit_group.sync.aligned;" ::: "memory")
#define WG_WAIT(n) asm volatile("wgmma.wait_group.sync.aligned " #n ";" ::: "memory")
#define TQ(p, k) p[2 * (k) + 1], p[2 * (k) + 2], p[2 * (k)], p[2 * (k) + 1]

__device__ __forceinline__ uint4 ld_nc4(const void* p) { uint4 v; asm volatile("ld.global.nc.v4.u32 {%0,%1,%2,%3}, [%4];" : "=r"(v.x), "=r"(v.y), "=r"(v.z), "=r"(v.w) : "l"(p)); return v; }
__device__ __forceinline__ unsigned short ld_nc16(const void* p) { unsigned short v; asm volatile("ld.global.nc.u16 %0, [%1];" : "=h"(v) : "l"(p)); return v; }
__device__ __forceinline__ uint32_t ld_nc(const void* p) { uint32_t v; asm volatile("ld.global.nc.u32 %0, [%1];" : "=r"(v) : "l"(p)); return v; }
__device__ __forceinline__ uint32_t ld_rlx(const unsigned int* p) { uint32_t v; asm volatile("ld.relaxed.gpu.global.u32 %0, [%1];" : "=r"(v) : "l"(p) : "memory"); return v; }
__device__ __forceinline__ uint2 ld_rlx2(const void* p) { uint2 v; asm volatile("ld.relaxed.gpu.global.v2.u32 {%0,%1}, [%2];" : "=r"(v.x), "=r"(v.y) : "l"(p) : "memory"); return v; }
__device__ __forceinline__ uint4 ld_rlx4(const void* p) { uint4 v; asm volatile("ld.relaxed.gpu.global.v4.u32 {%0,%1,%2,%3}, [%4];" : "=r"(v.x), "=r"(v.y), "=r"(v.z), "=r"(v.w) : "l"(p) : "memory"); return v; }
__device__ __forceinline__ void st_rlx(unsigned int* p, uint32_t v) { asm volatile("st.relaxed.gpu.global.u32 [%0], %1;" ::"l"(p), "r"(v) : "memory"); }
__device__ __forceinline__ void st_rlx2(void* p, uint32_t a, uint32_t b) { asm volatile("st.relaxed.gpu.global.v2.u32 [%0], {%1,%2};" ::"l"(p), "r"(a), "r"(b) : "memory"); }
__device__ __forceinline__ void st_rlx4(void* p, uint4 v) { asm volatile("st.relaxed.gpu.global.v4.u32 [%0], {%1,%2,%3,%4};" ::"l"(p), "r"(v.x), "r"(v.y), "r"(v.z), "r"(v.w) : "memory"); }
__device__ __forceinline__ void red_inc(unsigned int* p) { asm volatile("red.relaxed.gpu.global.add.u32 [%0], 1;" ::"l"(p) : "memory"); }

__device__ __forceinline__ void mbar_init(uint32_t a, int cnt) { asm volatile("mbarrier.init.shared::cta.b64 [%0], %1;" ::"r"(a), "r"(cnt) : "memory"); }
__device__ __forceinline__ void mbar_expect(uint32_t a, uint32_t bytes) { asm volatile("mbarrier.arrive.expect_tx.shared::cta.b64 _, [%0], %1;" ::"r"(a), "r"(bytes) : "memory"); }
__device__ __forceinline__ void mbar_wait(uint32_t a, uint32_t parity) {
    uint32_t ok = 0;
    int it = 0;
    do {
        asm volatile("{\n.reg .pred p;\nmbarrier.try_wait.parity.shared::cta.b64 p, [%1], %2;\nselp.u32 %0, 1, 0, p;\n}" : "=r"(ok) : "r"(a), "r"(parity) : "memory");
    } while (!ok && ++it < SPIN_MAX);
}
__device__ __forceinline__ void tma2d(uint32_t dst, const CUtensorMap* tm, int c0, int c1, uint32_t mbar) {
    asm volatile("cp.async.bulk.tensor.2d.shared::cluster.global.mbarrier::complete_tx::bytes [%0], [%1, {%3, %4}], [%2];"
                 ::"r"(dst), "l"(tm), "r"(mbar), "r"(c0), "r"(c1) : "memory");
}
__device__ __forceinline__ void bulk_s2g(void* dst, uint32_t src, uint32_t bytes) {
    asm volatile("cp.async.bulk.global.shared::cta.bulk_group [%0], [%1], %2;" ::"l"(dst), "r"(src), "r"(bytes) : "memory");
}
__device__ __forceinline__ uint32_t ld_acq(const unsigned int* p) { uint32_t v; asm volatile("ld.acquire.gpu.global.u32 %0, [%1];" : "=r"(v) : "l"(p) : "memory"); return v; }
__device__ __forceinline__ void bulk_pf(const void* src, uint32_t bytes) { asm volatile("cp.async.bulk.prefetch.L2.global [%0], %1;" ::"l"(src), "r"(bytes) : "memory"); }

__device__ __forceinline__ uint32_t wait_epoch(Misc& M) {
    uint32_t e = 0;
#pragma unroll 1
    for (int it = 0; it < (SPIN_MAX << 4) && e == 0; it++) e = *(volatile unsigned int*)&M.epoch;
    return e;
}
__device__ __forceinline__ void wait_reset(const unsigned int* ctr, uint32_t epoch) {
#pragma unroll 1
    for (int it = 0; it < SPIN_MAX; it++)
        if ((int)(ld_acq(ctr) - G_ * epoch) >= 0) break;
}
struct cplx { float x, y; };
__device__ __forceinline__ cplx cmul(cplx a, cplx b) { cplx r; r.x = a.x * b.x - a.y * b.y; r.y = a.x * b.y + a.y * b.x; return r; }
__device__ __forceinline__ cplx csq(cplx a) { cplx r; r.x = a.x * a.x - a.y * a.y; r.y = 2.0f * a.x * a.y; return r; }
__device__ __forceinline__ uint32_t hcm(uint32_t x, uint32_t y, uint32_t yp) {
    const __half2 X = *(const __half2*)&x, Y = *(const __half2*)&y, YP = *(const __half2*)&yp;
    const __half2 r = __hfma2(__high2half2(X), YP, __hmul2(__low2half2(X), Y));
    return *(const uint32_t*)&r;
}
__device__ __forceinline__ void ln_stats(float s1, float s2, float& meanb, float& rinv) {
    const float mean = s1 * (1.0f / D_);
    const float den = bfr(fsqrt(bfr(bfr(fmaxf(fmaf(-mean, mean, s2 * (1.0f / D_)), 0.f)) + 1e-5f)));
    meanb = bfr(mean);
    rinv = frcp(den);
}

__device__ __forceinline__ int fresh_tid() { int v; asm volatile("mov.u32 %0, %tid.x;" : "=r"(v)); return v; }
__device__ __forceinline__ void conv_channel(unsigned char* sm, Scratch* S, uint32_t gidx, uint32_t epoch, const void* pf_src,
                                             const CUtensorMap* tmu, int f0) {
    Misc& M = *(Misc*)(sm + OFF_MISC);
    const uint32_t sb = (uint32_t)__cvta_generic_to_shared(sm);
    const int tid = fresh_tid(), lane = tid & 31, g = lane >> 2, t = lane & 3, lr = lane & 7, lm = lane >> 3;
    const int warp_ = __shfl_sync(0xffffffffu, tid >> 5, 0), wgi = warp_ >> 2, w = warp_ & 3;
    const uint32_t cb = sb + OFF_CH + wgi * CHS, tag16 = (epoch % 65535u) + 1u;
    float D[16];
    uint32_t gaw, rcnt = 0;
    {
        {
            const uint32_t a8 = cb + lr * ULBO + (lm + 9) * 16 + w * 64, b8 = cb + XO_U8 + lm * 128 + lr * 16 + w * 512;
            const uint32_t a16 = cb + (((2 * lr) & 7) + (lm & 1)) * ULBO + (9 + (lr >> 2) + (lm & 2)) * 16 + w * 64;
            const uint32_t b16 = cb + XO_U16 + (lm & 1) * 512 + lr * 16 + (lm >> 1) * 128 + (w >> 1) * 1024 + (w & 1) * 256;
            uint32_t r[3][4];
            ldsm_x4_t(r[0], a8);
            ldsm_x4_t(r[1], a16);
            if (w < 2) ldsm_x4_t(r[2], a8 + 256);
            stsm_x4(b8, r[0][0], r[0][1], r[0][2], r[0][3]);
            stsm_x4(b16, r[1][0], r[1][1], r[1][2], r[1][3]);
            if (w < 2) stsm_x4(b8 + 2048, r[2][0], r[2][1], r[2][2], r[2][3]);
        }
        PROXY_FENCE();
        named_bar(1 + wgi, 128);
        {
            float Z8[24], Z16[16];
            const uint32_t pf = cb + XO_TF + (w >> 1) * 512 + (8 + 16 * (w & 1) + g - 2 * t) * 4;
            uint32_t p[13], q[9], z16[8];
#pragma unroll
            for (int s = 0; s < 9; s++) q[s] = lds32(pf + 1024 + s * 32);
            const uint32_t d8 = ((((cb + XO_U8) & 0x3FFFF) >> 4) | ((128 >> 4) << 16));
#define DZ(o) (((uint64_t)(512 >> 4) << 32) | (uint64_t)(d8 + (o)))
            WG_FENCE();
#pragma unroll
            for (int e = 0; e < 4; e++) {
                if (e == 0) wg32z(Z16, TQ(q, e), DZ(256 + 16));
                else wg32(Z16, TQ(q, e), DZ(256 - (e >> 1) * 64 + (1 - (e & 1)) * 16));
            }
            WG_COMMIT();
#pragma unroll
            for (int s = 0; s < 13; s++) p[s] = lds32(pf + s * 32);
            WG_WAIT(0);
#pragma unroll
            for (int i = 0; i < 8; i++) z16[i] = pack2(Z16[2 * i], Z16[2 * i + 1]);
            WG_FENCE();
#pragma unroll
            for (int e = 0; e < 6; e++) {
                if (e == 0) wg48z(Z8, TQ(p, e), DZ(16));
                else wg48(Z8, TQ(p, e), DZ(-(e >> 1) * 32 + (1 - (e & 1)) * 16));
            }
            WG_COMMIT();
            WG_WAIT(0);
            named_bar(1 + wgi, 128);
            const uint32_t za = cb + ((w >> 1) ? XO_ZB : XO_ZA) + lr * 400 + (1 + 2 * (w & 1) + (lm & 1) + 4 * (lm >> 1)) * 16;
#pragma unroll
            for (int i = 0; i < 3; i++)
                stsm_x4(za + i * 128, pack2(Z8[8 * i], Z8[8 * i + 1]), pack2(Z8[8 * i + 2], Z8[8 * i + 3]), pack2(Z8[8 * i + 4], Z8[8 * i + 5]), pack2(Z8[8 * i + 6], Z8[8 * i + 7]));
            const int Cz = 2 * (16 * (w & 1) + 8 * (lm & 1) + lr) + (lm >> 1);
            const uint32_t zc = cb + ((w >> 1) ? XO_ZD : XO_ZC) + (Cz & 7) * 272 + (1 + (Cz >> 3)) * 16;
#pragma unroll
            for (int ob = 0; ob < 2; ob++) stsm_x4(zc + ob * 128, z16[4 * ob], z16[4 * ob + 1], z16[4 * ob + 2], z16[4 * ob + 3]);
            if (lane < 8) *(uint4*)(sm + (cb - sb) + ((w < 2) ? (XO_ZA + w * 3200 + lane * 400) : (XO_ZC + (w - 2) * 2176 + lane * 272))) = make_uint4(0, 0, 0, 0);
        }
        gaw = ld_rlx(&S->modw[gidx]);
        if (tmu && wgi >= 2 && (tid & 127) == 96) {
            const uint32_t mbu = sb + OFF_MISC + (uint32_t)offsetof(Misc, mbar) + 24;
            if (wgi == 2) mbar_expect(mbu, 36864);
            tma2d(sb + OFF_WU + (wgi - 2) * 12288, tmu, f0, 192 * (wgi - 2), mbu);
        }
        __syncwarp();
        if ((tid & 127) == 64) rcnt = ld_rlx(S->cnt);
        {
#pragma unroll
            for (int i = 0; i < 16; i++) D[i] = 0.f;
            uint32_t pa = cb + XO_TD + (8 + 16 * w + g - 2 * t) * 4;
            uint32_t dlo = (((cb + 9 * 16) & 0x3FFFF) >> 4) | ((ULBO >> 4) << 16);
#define DS(o) (((uint64_t)(128 >> 4) << 32) | (uint64_t)(dlo + (o)))
#define KST (2 * (ULBO / 16))
            uint32_t pA[9], pB[9];
#pragma unroll
            for (int s = 0; s < 9; s++) pA[s] = lds32(pa + s * 32);
#pragma unroll 1
            for (int j = 0; j < 4; j++) {
                WG_FENCE();
#pragma unroll
                for (int q = 0; q < 4; q++) wg32(D, TQ(pA, q), DS((3 - q) * KST));
                WG_COMMIT();
                WG_WAIT(1);
#pragma unroll
                for (int s = 0; s < 9; s++) pB[s] = lds32(pa + 256 + s * 32);
                WG_FENCE();
#pragma unroll
                for (int q = 0; q < 4; q++) wg32(D, TQ(pB, q), DS((3 - q) * KST - 1));
                WG_COMMIT();
                WG_WAIT(1);
#pragma unroll
                for (int s = 0; s < 9; s++) pA[s] = lds32(pa + 512 + s * 32);
                dlo -= 2; pa += 512;
            }
            pB[1] = lds32(pa + 256 + 32); pB[2] = lds32(pa + 256 + 64);
            WG_FENCE();
#pragma unroll
            for (int q = 0; q < 4; q++) wg32(D, TQ(pA, q), DS((3 - q) * KST));
            wg32(D, pB[1], pB[2], pA[8], pB[1], DS(3 * KST - 1));
            WG_COMMIT();
        }
        if (tid == 128) bulk_pf(pf_src, 16 * D_ * 2);
        if ((tid & 127) == 64) {
#pragma unroll 1
            for (int it = 0; it < SPIN_MAX && (int)(rcnt - G_ * epoch) < 0; it++) rcnt = ld_rlx(S->cnt);
        }
    }
    {
        named_bar(1 + wgi, 128);
        {
            const uint4* pq = M.box + (6 + g - 2 * t);
#define QM(q) (q).x, (q).y, (q).z, (q).w
            uint32_t bA[2][6], bB[2][6], bC[3][4], bD[2][4], bU[2][4];
            const uint32_t k2 = lds32(cb + XO_K1024);
            uint32_t ofs[3];
#pragma unroll
            for (int d = 0; d < 3; d++) ofs[d] = cb + ((w - d) < 0 ? 0 : 16) + (lr + 8 * (lm >> 1)) * 16;
#define COL(d) (2 * ((w - (d)) & 3) + (lm & 1))
            WG_WAIT(0);
            uint4 m[4];
#pragma unroll
            for (int d = 0; d < 2; d++) {
                const uint32_t a = XO_ZA + COL(d) * 400 + ofs[d];
                ldsm_x4(bA[d], a); ldsm_x4(bB[d], a + 3200);
                uint32_t r[4];
                ldsm_x4(r, a + 256 + (lm >> 1) * (3200 - 128));
                bA[d][4] = r[0]; bA[d][5] = r[1]; bB[d][4] = r[2]; bB[d][5] = r[3];
            }
#pragma unroll
            for (int i = 0; i < 4; i++) m[i] = pq[14 * i];
#pragma unroll
            for (int d = 0; d < 2; d++)
#pragma unroll
                for (int c = 0; c < 3; c++) mma_bf16(D + 4 + 4 * c, QM(m[d]), bA[d][2 * c], bA[d][2 * c + 1]);
#pragma unroll
            for (int d = 0; d < 3; d++) ldsm_x4(bC[d], XO_ZC + COL(d) * 272 + ofs[d]);
#pragma unroll
            for (int d = 0; d < 2; d++)
#pragma unroll
                for (int c = 0; c < 3; c++) mma_bf16(D + 4 + 4 * c, QM(m[2 + d]), bB[d][2 * c], bB[d][2 * c + 1]);
#pragma unroll
            for (int i = 0; i < 3; i++) m[i] = pq[14 * (4 + i)];
#pragma unroll
            for (int d = 0; d < 2; d++) { ldsm_x4(bD[d], XO_ZD + COL(d) * 272 + ofs[d]); ldsm_x4(bU[d], COL(d) * ULBO + 128 + ofs[d]); }
#pragma unroll
            for (int d = 0; d < 3; d++)
#pragma unroll
                for (int c = 0; c < 2; c++) mma_bf16(D + 8 + 4 * c, QM(m[d]), bC[d][2 * c], bC[d][2 * c + 1]);
#pragma unroll
            for (int i = 0; i < 4; i++) m[i] = pq[14 * (7 + i)];
#pragma unroll
            for (int d = 0; d < 2; d++)
#pragma unroll
                for (int c = 0; c < 2; c++) mma_bf16(D + 8 + 4 * c, QM(m[d]), bD[d][2 * c], bD[d][2 * c + 1]);
#pragma unroll
            for (int d = 0; d < 2; d++) {
                m[2 + d].x &= k2; m[2 + d].y &= k2; m[2 + d].z &= k2; m[2 + d].w &= k2;
#pragma unroll
                for (int c = 0; c < 2; c++) mma_bf16(D + 8 + 4 * c, QM(m[2 + d]), bU[d][2 * c], bU[d][2 * c + 1]);
            }
        }
        {
#pragma unroll 1
            for (int it = 0; it < SPIN_MAX && (gaw >> 16) != tag16; it++) gaw = ld_rlx(&S->modw[gidx]);
            const uint32_t ga2 = __byte_perm(gaw, 0, 0x1010), dk2 = M.pk[3][wgi];
            const uint32_t ua = cb + (2 * w + (lm & 1)) * ULBO + (9 + lr + 8 * (lm >> 1)) * 16;
            const uint32_t ya = cb + XO_TD + w * 1024;
            const uint32_t sa = ya + (lr + 8 * (lm >> 1)) * 32 + (((lm & 1) ^ ((lane >> 2) & 1)) << 4);
#pragma unroll
            for (int cc = 0; cc < 2; cc++) {
                uint32_t u[4], v[4];
                ldsm_x4_t(u, ua + cc * 256);
#pragma unroll
                for (int m = 0; m < 4; m++) {
                    const int c = 2 * cc + (m >> 1), h = m & 1;
                    v[m] = ~mul2(ga2, add2(pack2(D[4 * c + 2 * h], D[4 * c + 2 * h + 1]), mul2(u[m], dk2)));
                }
                stsm_x4_t(sa + cc * 512, v[0], v[1], v[2], v[3]);
            }
            __syncwarp();
            const int sw = (lane >> 3) & 1;
            const uint32_t vo = (uint32_t)(((4 * (lane >> 1) + w) * D_ + gidx - 2 * D_) * 32 + (lane & 1) * 16);
            const unsigned char* yp = sm + (ya - sb) + (lane >> 1) * 32 + (lane & 1) * 8;
#pragma unroll
            for (int i = 0; i < 2; i++) {
                const uint2 A = *(const uint2*)(yp + i * 512 + (sw << 4)), B = *(const uint2*)(yp + i * 512 + ((sw ^ 1) << 4));
                st_rlx4((char*)S->v + vo + i * (64 * D_ * 32), make_uint4(A.x, B.x, A.y, B.y));
            }
        }
    }
}

__global__ void __launch_bounds__(NTHR, 1)
mega_kernel(const bf16* __restrict__ x, const bf16* __restrict__ logAr, const bf16* __restrict__ Aim,
            const bf16* __restrict__ Cr, const bf16* __restrict__ Ci, const bf16* __restrict__ logdt, const bf16* __restrict__ c_in,
            Scratch* __restrict__ S, const bf16* __restrict__ Dskip, const bf16* __restrict__ w_r, const bf16* __restrict__ w_down,
            bf16* __restrict__ out,
            const __grid_constant__ CUtensorMap tm_wm, const __grid_constant__ CUtensorMap tm_wg, const __grid_constant__ CUtensorMap tm_wu,
            const __grid_constant__ CUtensorMap tm_wd, const __grid_constant__ CUtensorMap tm_wd32,
            const __grid_constant__ CUtensorMap tm_wg32, const __grid_constant__ CUtensorMap tm_wu32) {
    extern __shared__ __align__(1024) unsigned char sm[];
    Misc& M = *(Misc*)(sm + OFF_MISC);
    const uint32_t sb = (uint32_t)__cvta_generic_to_shared(sm);
    const int tid = threadIdx.x, warp = __shfl_sync(0xffffffffu, tid >> 5, 0), lane = tid & 31;
    const int g = lane >> 2, t = lane & 3, lr = lane & 7, lm = lane >> 3;
    const int wgi = warp >> 2, w = warp & 3;
    const int b = blockIdx.x;
    const int nch = 5 - (b & 1), cs = 9 * (b >> 1) + 5 * (b & 1);
    const int f0 = 72 * (b >> 1) + 32 * (b & 1), nf = 32 + 8 * (b & 1);
    const bool has_ch = wgi < nch;
    const uint32_t mb0 = sb + OFF_MISC + offsetof(Misc, mbar), mb_wm = mb0, mb_wg = mb0 + 16, mb_wu = mb0 + 24, mb_wd = mb0 + 32;
    const uint32_t cb = sb + OFF_CH + wgi * CHS;

    if (wgi == 3) {
        M.sent[tid - 384] = make_uint4(SENT, SENT, SENT, SENT);
        M.sent[tid - 256] = make_uint4(SENT, SENT, SENT, SENT);
        if (tid == 384) {
            M.epoch = 0u; M.flag = 0u; M.e1cnt = 0u;
#pragma unroll
            for (int i = 0; i < 5; i++) mbar_init(mb0 + 8 * i, 1);
        }
        PROXY_FENCE();
        __syncwarp();
        if (warp == 12) { named_arrive(8, 160); if (b & 1) named_arrive(14, 64); }
        if (warp != 15) named_arrive(9, 128);
    }
    unsigned short r_ldt = 0, r_lar = 0, r_aim = 0, r_cr = 0, r_ci = 0;
    if (has_ch) {
        const int d = cs + wgi, n = d * N_ + (tid & 127);
        r_ldt = ld_nc16((const unsigned short*)logdt + d);
        r_lar = ld_nc16((const unsigned short*)logAr + n);
        r_aim = ld_nc16((const unsigned short*)Aim + n);
        r_cr = ld_nc16((const unsigned short*)Cr + n);
        r_ci = ld_nc16((const unsigned short*)Ci + n);
    } else {
        const unsigned short* cp = (const unsigned short*)c_in + (tid - 512);
        r_ldt = ld_nc16(cp); r_lar = ld_nc16(cp + 128); r_aim = ld_nc16(cp + 256); r_cr = ld_nc16(cp + 384);
        if (tid < 576) r_ci = ld_nc16(cp + 512);
    }
    uint4 xr[9];
    if (wgi == 4) {
        const uint4* p = (const uint4*)(x + (size_t)16 * b * D_) + (tid - 512);
#pragma unroll
        for (int i = 0; i < 9; i++) xr[i] = ld_nc4(p + 128 * i);
    }
    uint32_t wrv = 0;
    if (tid >= 128 && tid < 416) wrv = ld_nc((const uint32_t*)w_r + (tid - 128));
    if (warp == 2 && lane < nch) M.pk[3][lane] = (uint32_t)ld_nc16((const unsigned short*)Dskip + cs + lane) * 0x10001u;
    if (tid == 384) {
        const unsigned int tk = atomicAdd(S->ticket, 1u);
        *(volatile unsigned int*)&M.epoch = (tk >> 7) + 1u;
    }
    if (has_ch) {
        for (int i = tid & 127; i < 296; i += 128) *(uint4*)(sm + OFF_CH + wgi * CHS + XO_TD + i * 16) = make_uint4(0, 0, 0, 0);
    }
    if (tid < 154) {
        const int idx = (tid * 4682) >> 16, dl = tid - 14 * idx - 6;
        const int a = (0x44332221100ull >> (4 * idx)) & 7, d = (0x10102101010ull >> (4 * idx)) & 3;
        const int lo = (0x35c36 >> (4 * a)) & 15, wd = (0x16824 >> (4 * a)) & 15;
        const uint32_t one = (a == 4) ? 0xFFFFu : 0x3F80u;
        auto mk = [&](int l) { return (((unsigned)(l - lo) <= (unsigned)wd) ? one : 0u) | (((unsigned)(l - 1 - lo) <= (unsigned)wd) ? (one << 16) : 0u); };
        const int l0 = 16 * d + dl;
        M.box[tid] = make_uint4(mk(l0), mk(l0 + 8), mk(l0 - 8), mk(l0));
    }
    uint32_t xo[6];
#pragma unroll
    for (int i = 0; i < 6; i++) {
        const int ch = 16 * (warp + 16 * (i >> 1)) + 8 * (i & 1) + g;
        const int pr = (ch * 7282) >> 16, rm = ch - 9 * pr, hi = rm >= 5;
        xo[i] = (uint32_t)((((2 * pr + hi) * G_ + b) * 5 + rm - 5 * hi) * 32 + t * 8);
    }
    auto e1_store = [&]() {
        named_bar(11, 640);
        uint32_t mm[2], rhh[2], rll[2];
#pragma unroll
        for (int h = 0; h < 2; h++) {
            mm[h] = ((const uint32_t*)M.st1[0])[t + 4 * h]; rhh[h] = ((const uint32_t*)M.st1[1])[t + 4 * h]; rll[h] = ((const uint32_t*)M.st1[2])[t + 4 * h];
        }
        const uint32_t ta = sb + OFF_TILE + (lr + 8 * (lm & 1)) * (ROWP * 2) + (lm >> 1) * 16 + warp * 32;
#pragma unroll
        for (int i = 0; i < 3; i++) {
            if (i < 2 || warp < 4) {
                uint32_t r[4];
                ldsm_x4_t(r, ta + i * 512);
#pragma unroll
                for (int h = 0; h < 2; h++)
                    st_rlx2((char*)S->xn + xo[2 * i + h], ~norm2(r[2 * h], mm[0], rhh[0], rll[0]), ~norm2(r[2 * h + 1], mm[1], rhh[1], rll[1]));
            }
        }
        __syncwarp();
        if (lane == 0 && atomicAdd(&M.e1cnt, 1u) == 15u) red_inc(S->hint);
    };
    const float p_ldt = lo2f(r_ldt), p_lar = lo2f(r_lar), p_aim = lo2f(r_aim), p_cr = lo2f(r_cr), p_ci = lo2f(r_ci);
    cplx z1 = {0.f, 0.f}, z16 = z1, z256 = z1, C = z1;
    const uint32_t scr = cb + w * KSCR, ws = scr + lane * 4;
    float acc[5][4];
    uint32_t afr[4][4], cz[4];
    cplx z2 = {0.f, 0.f};
    const uint32_t ba = scr + lr * 144 + lm * 16;
    auto tile = [&](float* c, int rg) {
        __syncwarp();
        c[0] = c[1] = c[2] = c[3] = 0.f;
        uint32_t bb[2][4];
        ldsm_x4(bb[0], ba + rg * 1152);
        ldsm_x4(bb[1], ba + rg * 1152 + 64);
        mma_f16(c, afr[0], bb[0][0], bb[0][1]);
        mma_f16(c, afr[1], bb[0][2], bb[0][3]);
        mma_f16(c, afr[2], bb[1][0], bb[1][1]);
        mma_f16(c, afr[3], bb[1][2], bb[1][3]);
    };
#define CJ(z) packh((z).x, -(z).y)
#define CJP(z) packh((z).y, (z).x)
    uint32_t ex = 0;
    if (has_ch) {
        const float dt = bfr(expf(p_ldt));
        const float al = -bfr(expf(p_lar)) * dt * 1.4426950408889634f;
        const float th = p_aim * dt;
        const float th_ = th * 0.15915494309189535f;
        const float tl_ = fmaf(th, 0.15915494309189535f, -th_) + th * 6.4206382e-9f;
        auto anchor = [&](float s) {
            float f = th_ * s;
            f -= rintf(f);
            f = fmaf(tl_, s, f) * 6.283185307179586f;
            const float e = fex2(al * s);
            return cplx{e * __cosf(f), e * __sinf(f)};
        };
        const float cx = p_cr * dt * 2.0f, cy = p_ci * dt * 2.0f;
        ex = __reduce_max_sync(0xffffffffu, __float_as_uint(fmaxf(fabsf(cx), fabsf(cy)))) >> 23;
        const float scl = __uint_as_float((254u - ex) << 23);
        C = cplx{cx * scl, cy * scl};
        z1 = anchor(1.f); z16 = anchor(16.f); z256 = anchor(256.f);
            {
                const cplx z32 = csq(z16), z48 = cmul(z32, z16), z64 = csq(z32), z128 = csq(z64), z192 = cmul(z128, z64);
                const uint32_t y[3] = {packh(z16.x, z16.y), packh(z32.x, z32.y), packh(z48.x, z48.y)};
                const uint32_t yp[3] = {packh(-z16.y, z16.x), packh(-z32.y, z32.x), packh(-z48.y, z48.x)};
                const uint32_t xx[3] = {packh(z64.x, z64.y), packh(z128.x, z128.y), packh(z192.x, z192.y)};
                sts32(ws, 0x00003C00u);
#pragma unroll
                for (int j = 0; j < 3; j++) sts32(ws + (1 + j) * 144, y[j]);
#pragma unroll
                for (int i = 0; i < 3; i++) {
                    sts32(ws + (4 + 4 * i) * 144, xx[i]);
#pragma unroll
                    for (int j = 0; j < 3; j++) sts32(ws + (5 + 4 * i + j) * 144, hcm(xx[i], y[j], yp[j]));
                }
            }
    }
    if (wgi == 4) {
        if (!has_ch) {
            const int i = tid - 512;
            ((unsigned short*)M.sc)[i] = (unsigned short)f2bits(silu(lo2f(r_ldt)));
            ((unsigned short*)M.sc)[i + 128] = (unsigned short)f2bits(silu(lo2f(r_lar)));
            ((unsigned short*)M.sc)[i + 256] = (unsigned short)f2bits(silu(lo2f(r_aim)));
            ((unsigned short*)M.sc)[i + 384] = (unsigned short)f2bits(silu(lo2f(r_cr)));
            if (i < 64) ((unsigned short*)M.sc)[i + 512] = (unsigned short)f2bits(silu(lo2f(r_ci)));
            if (warp == 16) {
                named_bar(14, 64);
                if (lane == 0) {
                    mbar_expect(mb_wm, 36864);
#pragma unroll
                    for (int k = 0; k < 3; k++) tma2d(sb + OFF_WU + k * 12288, &tm_wm, 32 * (b >> 1), 192 * k, mb_wm);
                }
                __syncwarp();
            }
        }
#pragma unroll
        for (int i = 0; i < 9; i++) {
            const int c = tid - 512 + 128 * i, rr = (c * 911) >> 16;
            *(uint4*)(sm + OFF_TILE + rr * (ROWP * 2 - 1152) + c * 16) = xr[i];
        }
        named_bar(8, 160);
        {
            float c1[4] = {0.f, 0.f, 0.f, 0.f}, cl[4] = {0.f, 0.f, 0.f, 0.f}, chh[4] = {0.f, 0.f, 0.f, 0.f};
            const uint32_t a0 = sb + OFF_TILE + (lane & 15) * (ROWP * 2) + (lane >> 4) * 16 + w * 288;
            uint32_t a[9][4];
#pragma unroll
            for (int ks = 0; ks < 9; ks++) ldsm_x4(a[ks], a0 + ks * 32);
#pragma unroll
            for (int ks = 0; ks < 9; ks++) {
                mma_bf16(c1, a[ks][0], a[ks][1], a[ks][2], a[ks][3], 0x3F803F80u, 0x3F803F80u);
                mma_bf16(cl, a[ks][0], a[ks][1], a[ks][2], a[ks][3], a[ks][0], a[ks][2]);
                mma_bf16(chh, a[ks][0], a[ks][1], a[ks][2], a[ks][3], a[ks][1], a[ks][3]);
            }
            if (t == 0) { M.p1[g][w] = c1[0]; M.p1[g + 8][w] = c1[2]; }
            if (t == (g >> 1)) { M.p2[g][w] = (g & 1) ? cl[1] : cl[0]; M.p2[g + 8][w] = (g & 1) ? chh[3] : chh[2]; }
        }
        named_bar(5, 128);
        if (warp == 16) {
            const float4 q1 = *(const float4*)M.p1[lane & 15], q2 = *(const float4*)M.p2[lane & 15];
            float meanb, rinv;
            ln_stats((q1.x + q1.y) + (q1.z + q1.w), (q2.x + q2.y) + (q2.z + q2.w), meanb, rinv);
            const float rh = bfr(rinv);
            if (lane < 16) { M.st1[0][lane] = (unsigned short)f2bits(meanb); M.st1[1][lane] = (unsigned short)f2bits(rh); M.st1[2][lane] = (unsigned short)f2bits(rinv - rh); }
        }
        __syncwarp();
        named_arrive(11, 640);
    }
    auto publish_reset = [&]() {
        if (tid == 480) {
            asm volatile("cp.async.bulk.wait_group 0;" ::: "memory");
            asm volatile("fence.proxy.async;" ::: "memory");
            red_inc(S->cnt);
        }
    };
    uint32_t epoch = 0, tag16 = 0, pre = 0;
    auto mod_tile = [&](int rd) {
        const uint32_t* s2 = (const uint32_t*)M.sc + 144 * (w >> 1) + t;
        uint32_t bb[18][2];
#pragma unroll
        for (int ks = 0; ks < 18; ks++) { bb[ks][0] = (g == 0) ? s2[8 * ks] : 0u; bb[ks][1] = (g == 0) ? s2[8 * ks + 4] : 0u; }
        float acc[2][4] = {{0.f, 0.f, 0.f, 0.f}, {0.f, 0.f, 0.f, 0.f}};
        const int row = lr + 8 * (lm >> 1);
        const uint32_t wa = sb + OFF_WU + (288 * (w >> 1) + row) * 64 + ((((2 * (w & 1) + (lm & 1)) ^ (row >> 1)) & 3) << 4);
        mbar_wait(mb_wm + 8 * rd, 0);
        if (rd == 0)
#pragma unroll
        for (int kb = 0; kb < 2; kb++) {
            uint32_t a[9][4];
#pragma unroll
            for (int ks = 0; ks < 9; ks++) ldsm_x4_t(a[ks], wa + (9 * kb + ks) * 1024);
#pragma unroll
            for (int ks = 0; ks < 9; ks++) mma_bf16(acc[ks & 1], a[ks][0], a[ks][1], a[ks][2], a[ks][3], bb[9 * kb + ks][0], bb[9 * kb + ks][1]);
        }
        const float v0 = acc[0][0] + acc[1][0], v1 = acc[0][2] + acc[1][2];
        float* mx = M.modx + 16 * (w & 1) + g;
        if (w >= 2 && t == 0) { mx[0] = v0; mx[8] = v1; }
        named_bar(5, 128);
        if (w < 2 && t == 0) {
            unsigned int* mp = &S->modw[32 * ((b >> 1) + 64 * rd) + 16 * w + g];
            st_rlx(mp, f2bits(v0 + mx[0]) | (tag16 << 16));
            st_rlx(mp + 8, f2bits(v1 + mx[8]) | (tag16 << 16));
        }
        if (rd == 0 && w < 2 && b < 108) {
            named_bar(7, 64);
            if (tid == 512) red_inc(S->hint);
        }
    };
    if (has_ch) {
        {
            z2 = csq(z1);
            const cplx z3 = cmul(z2, z1), z4 = csq(z2), z8 = csq(z4);
            const cplx c4 = cmul(C, z4), c8 = cmul(C, z8), c12 = cmul(c8, z4);
            cz[0] = packh(C.x, -C.y); cz[1] = packh(c4.x, -c4.y); cz[2] = packh(c8.x, -c8.y); cz[3] = packh(c12.x, -c12.y);
            __syncwarp();
#pragma unroll
            for (int s = 0; s < 4; s++) ldsm_x4(afr[s], scr + (lr + 8 * (lm & 1)) * 144 + (2 * s + (lm >> 1)) * 16);
            {
                const uint32_t y[3] = {CJ(z1), CJ(z2), CJ(z3)}, yp[3] = {CJP(z1), CJP(z2), CJP(z3)};
#pragma unroll
                for (int tt = 0; tt < 2; tt++) {
                    const int rg = tt ? 0 : 2;
#pragma unroll
                    for (int i = 0; i < 2; i++) {
                        sts32(ws + rg * 1152 + (4 * i) * 144, cz[2 * tt + i]);
#pragma unroll
                        for (int j = 0; j < 3; j++) sts32(ws + rg * 1152 + (4 * i + 1 + j) * 144, hcm(cz[2 * tt + i], y[j], yp[j]));
                    }
                    tile(acc[tt], rg);
                }
            }
            if (tid >= 128 && tid < 416) M.wr[tid - 128] = wrv;
            if (wgi < 4) e1_store();
    if (warp == 15) {
        named_bar(9, 128);
        if (lane == 0) {
#pragma unroll 1
            for (int i = 0; i < 5; i++) {
                bulk_s2g((char*)&S->v[(size_t)b * 1152] + i * 4096, sb + OFF_MISC, i < 4 ? 4096 : 2048);
                if (i < 3) bulk_s2g((char*)&S->part[(size_t)b * 1152] + i * 4096, sb + OFF_MISC, i < 2 ? 4096 : 1024);
            }
            bulk_s2g(&S->rec[8 * b], sb + OFF_MISC, 32);
            asm volatile("cp.async.bulk.commit_group;" ::: "memory");
        }
        __syncwarp();
    }
            const cplx z258 = cmul(z256, z2), z512 = csq(z256), z768 = cmul(z512, z256);
            {
                const uint32_t a0 = CJ(z256), a0p = CJP(z256), a1 = CJ(z258), a1p = CJP(z258);
#pragma unroll
                for (int i = 0; i < 4; i++) { sts32(ws + 1152 + (2 * i) * 144, hcm(cz[i], a0, a0p)); sts32(ws + 1152 + (2 * i + 1) * 144, hcm(cz[i], a1, a1p)); }
                tile(acc[2], 1);
            }
            {
                const uint32_t a0 = CJ(z512), a0p = CJP(z512), a1 = CJ(z768), a1p = CJP(z768);
#pragma unroll
                for (int i = 0; i < 4; i++) { sts32(ws + 2304 + i * 144, hcm(cz[i], a0, a0p)); sts32(ws + 2304 + (4 + i) * 144, hcm(cz[i], a1, a1p)); }
                tile(acc[3], 2);
            }
            if (warp == 3) {
                if (lane == 15) pre = ld_rlx(S->hint);
            }
            const cplx z1024 = csq(z512);
            {
                const cplx zk[4] = {z1024, cmul(z1024, z256), csq(z768), cmul(z1024, z768)};
#pragma unroll
                for (int h = 0; h < 4; h++) {
                    const uint32_t a0 = CJ(zk[h]), a0p = CJP(zk[h]);
                    sts32(ws + (2 * h) * 144, hcm(cz[0], a0, a0p));
                    sts32(ws + (2 * h + 1) * 144, hcm(cz[2], a0, a0p));
                }
                tile(acc[4], 0);
            }
            const cplx z2048 = csq(z1024);
            float last = C.x * z2048.x - C.y * z2048.y;
#pragma unroll
            for (int o = 16; o; o >>= 1) last += __shfl_xor_sync(0xffffffffu, last, o);
            __syncwarp();
#pragma unroll
            for (int i = 0; i < 5; i++) *(float4*)(sm + (scr - sb) + i * 512 + lane * 16) = make_float4(acc[i][0], acc[i][1], acc[i][2], acc[i][3]);
            if (lane == 0) { const float inv = __uint_as_float(ex << 23); M.kinv[wgi][w] = inv; M.klast[wgi][w] = last * inv; }
        }
        if (tid == 111 && (int)(pre - HINT_N * wait_epoch(M)) >= 0) M.flag = 1u;
        named_bar(1 + wgi, 128);
        const uint32_t td = cb + XO_TD + 64 * 4, tf = cb + XO_TF - 32 * 4;
        if (tid == 111 && !M.flag) pre = ld_rlx(S->hint);
        const float4 ki = *(const float4*)M.kinv[wgi];
        auto fsum = [&](int off, uint32_t& r0, uint32_t& r1) {
            const unsigned char* p = sm + (cb - sb) + off;
            const float4 a = *(const float4*)p, b2 = *(const float4*)(p + KSCR), c = *(const float4*)(p + 2 * KSCR), d = *(const float4*)(p + 3 * KSCR);
            r0 = pack2(fmaf(a.y, ki.x, b2.y * ki.y) + fmaf(c.y, ki.z, d.y * ki.w), fmaf(a.x, ki.x, b2.x * ki.y) + fmaf(c.x, ki.z, d.x * ki.w));
            r1 = pack2(fmaf(a.w, ki.x, b2.w * ki.y) + fmaf(c.w, ki.z, d.w * ki.w), fmaf(a.z, ki.x, b2.z * ki.y) + fmaf(c.z, ki.z, d.z * ki.w));
        };
        uint32_t r[2], q[2];
        fsum(w * 512 + lane * 16, r[0], r[1]);
        fsum(2048 + w * 128 + lr * 16, q[0], q[1]);
        if (tid == 111) {
            if ((int)(pre - HINT_N * M.epoch) >= 0) M.flag = 1u;
            else pre = ld_rlx(S->hint);
        }
        __syncwarp();
        if (w < 2) {
            const uint32_t p = td + (16 * g + 8 * w + 2 * t) * 4;
#pragma unroll
            for (int h = 0; h < 2; h++) { sts16(p + h * 512, r[h] >> 16); sts32(p + h * 512 + 4, r[h]); sts16(p + h * 512 + 10, r[h]); }
        } else if (w == 2) {
            const uint32_t p = td + (256 + 16 * g + 4 * t) * 4;
#pragma unroll
            for (int h = 0; h < 2; h++) {
                const uint32_t k0 = r[h] >> 16;
                if (h || lane) { sts16(p + h * 512 - 4, k0); sts16(p + h * 512 + 2, k0); }
                sts16(p + h * 512, k0); sts32(p + h * 512 + 4, __byte_perm(r[h], 0, 0x3232)); sts32(p + h * 512 + 8, r[h]); sts16(p + h * 512 + 14, r[h]);
            }
        } else {
            const uint32_t p = tf + (64 + 32 * (t >> 1) + 2 * g + (t & 1)) * 4;
#pragma unroll
            for (int h = 0; h < 2; h++) {
                const uint32_t k0 = r[h] >> 16;
                sts16(p + h * 64 + 512, r[h]); sts16(p + h * 64 + 518, r[h]);
                if (h || lane) { sts16(p + h * 64 - 4, k0); sts16(p + h * 64 + 2, k0); }
            }
            if (lane == 0) {
                const uint32_t dd = __byte_perm(r[0], 0, 0x3232);
                sts16(td + 511 * 4, dd); sts32(td + 512 * 4, dd); sts32(td + 513 * 4, dd); sts32(td + 514 * 4, dd); sts16(td + 515 * 4 + 2, dd);
            }
        }
        if (lane < 8) {
            const uint32_t p = tf + 1024 + (64 + 16 * t + 2 * w + g) * 4;
#pragma unroll
            for (int h = 0; h < 2; h++) {
                const uint32_t k0 = q[h] >> 16;
                sts16(p + h * 32 + 512, q[h]); sts16(p + h * 32 + 518, q[h]);
                if (h || (tid & 127)) { sts16(p + h * 32 - 4, k0); sts16(p + h * 32 + 2, k0); }
            }
            if ((tid & 127) == 0) {
                const float4 kl4 = *(const float4*)M.klast[wgi];
                const uint32_t kl = f2bits((kl4.x + kl4.y) + (kl4.z + kl4.w)), dd = __byte_perm(q[0], 0, 0x3232);
                sts16(tf + 127 * 4, dd); sts16(tf + 128 * 4 + 2, dd); sts32(cb + XO_K1024, dd);
                sts16(tf + 1024 + 127 * 4, kl); sts16(tf + 1024 + 128 * 4 + 2, kl);
            }
        }
        __syncwarp();
    } else {
        const int i = tid - 512, idx = b >> 1;
        tag16 = (wait_epoch(M) % 65535u) + 1u;
        mod_tile(0);
        if (i == 0 && idx < 44) {
            PROXY_FENCE();
            mbar_expect(mb_wm + 8, 36864);
#pragma unroll
            for (int k = 0; k < 3; k++) tma2d(sb + OFF_WU + k * 12288, &tm_wm, 32 * (idx + 64), 192 * k, mb_wm + 8);
        }
        __syncwarp();
    }
    if (tid == 111) {
        epoch = wait_epoch(M);
#pragma unroll 1
        for (int it = 0; it < SPIN_MAX && (int)(pre - HINT_N * epoch) < 0; it++) pre = ld_rlx(S->hint);
        M.flag = 1u;
    }
    __syncwarp();
    const int ubp = (tid * 13108) >> 16, uloc = tid - 5 * ubp;
    const uint4* usrc = &S->xn[(size_t)b * 1280 + 2 * tid];
    uint4 ua = make_uint4(0, 0, 0, 0), uc = ua;
    uint32_t usa = 0, uca = 0;
    if (lane == 0) {
#pragma unroll 1
        for (int it = 0; it < (SPIN_MAX << 4) && !M.flag; it++) { }
    }
    __syncwarp();
    if (uloc < nch) {
 ua = ld_rlx4(usrc); uc = ld_rlx4(usrc + 1); usa = ld_rlx(&S->modw[cs + uloc]); uca = ld_rlx(&S->modw[D_ + cs + uloc]); }
    CBAR();
    epoch = M.epoch;
    tag16 = (epoch % 65535u) + 1u;
    {
        const int bp = ubp, loc = uloc;
        if (loc < nch) {
            const uint4* src = usrc;
            uint4 a = ua, c = uc;
#pragma unroll 1
            for (int it = 0; it < SPIN_MAX && (a.x == SENT || a.z == SENT || c.x == SENT || c.z == SENT || (usa >> 16) != tag16 || (uca >> 16) != tag16); it++) {
                a = ld_rlx4(src); c = ld_rlx4(src + 1); usa = ld_rlx(&S->modw[cs + loc]); uca = ld_rlx(&S->modw[D_ + cs + loc]);
            }
            const uint32_t sa = __byte_perm(usa, 0, 0x1010), ca = pack2(1.0f + lo2f(uca), 1.0f + lo2f(uca));
            unsigned char* up = sm + OFF_CH + loc * CHS + ((2 * bp) & 7) * ULBO + ((bp >> 2) + 9) * 16;
            *(uint4*)up = make_uint4(add2(mul2(~a.x, ca), sa), add2(mul2(~a.z, ca), sa), add2(mul2(~c.x, ca), sa), add2(mul2(~c.z, ca), sa));
            *(uint4*)(up + ULBO) = make_uint4(add2(mul2(~a.y, ca), sa), add2(mul2(~a.w, ca), sa), add2(mul2(~c.y, ca), sa), add2(mul2(~c.w, ca), sa));
        }
        publish_reset();
        const int i = tid & 127;
        unsigned char* cp = sm + OFF_CH + wgi * CHS;
        *(uint4*)(cp + XO_U8 - 1024 + (i >> 6) * 4096 + (i & 63) * 16) = make_uint4(0, 0, 0, 0);
        if (i < 72) { const int c = (i * 57) >> 9; *(uint4*)(cp + c * ULBO + (i - 9 * c) * 16) = make_uint4(0, 0, 0, 0); }
    }
    PROXY_FENCE();
    CBAR();
    if (w == 2 && lane == 0) {
        bulk_s2g((char*)&S->xn[(size_t)b * 1280] + wgi * 4096, sb + OFF_MISC, 4096);
        asm volatile("cp.async.bulk.commit_group;" ::: "memory");
    }
        if (tid == 416) {
            mbar_expect(mb_wg, nf * D_ * 2);
            tma2d(sb + OFF_WG, (b & 1) ? &tm_wg : &tm_wg32, f0, 0, mb_wg);
        }
    if (tid == 96 || tid == 224) tma2d(sb + OFF_WG + (1 + (tid >> 7)) * (nf * 384), (b & 1) ? &tm_wg : &tm_wg32, f0, 192 * (1 + (tid >> 7)), mb_wg);
    if (has_ch) {
        __syncwarp();
        conv_channel(sm, S, 2 * D_ + cs + wgi, epoch, w_down + (size_t)f0 * D_, (b & 1) ? nullptr : &tm_wu32, f0);
    } else {
        const int idx = b >> 1;
        if (idx < 44) mod_tile(1);
        if (tid == 512) {
            PROXY_FENCE();
            mbar_expect(mb_wu, 46080);
#pragma unroll 1
            for (int i = 0; i < 3; i++) {
                tma2d(sb + OFF_WU + i * 15360, &tm_wu, f0, 192 * i, mb_wu);
                const long long c0 = clock64();
                int it = 0;
                while (clock64() - c0 < 1200 && ++it < 4096) { }
            }
            wait_reset(S->cnt, epoch);
        }
        named_bar(5, 128);
    }
    {
    const int tid = fresh_tid(), warp = __shfl_sync(0xffffffffu, tid >> 5, 0), lane = tid & 31;
    const int g = lane >> 2, t = lane & 3, lr = lane & 7, lm = lane >> 3;
    uint32_t v3 = 0, v4 = 0, v5 = 0;
    auto load_consts = [&]() {
        if (tid < D_) { v3 = ld_rlx(&S->modw[3 * D_ + tid]); v4 = ld_rlx(&S->modw[4 * D_ + tid]); v5 = ld_rlx(&S->modw[5 * D_ + tid]); }
    };
    if (tid == 0) bulk_pf(w_down + (size_t)(f0 + 16) * D_, (nf - 16) * D_ * 2);
    uint32_t x1[2][4], wr2[2][2];
    if (warp < 18) {
        const char* vp = (const char*)S->v + ((size_t)b * D_ + 32 * warp + g) * 32 + t * 8;
        uint2 v[4];
#pragma unroll
        for (int i = 0; i < 4; i++) v[i] = ld_rlx2(vp + i * 256);
#pragma unroll
        for (int j = 0; j < 2; j++) {
            const uint32_t* wp = M.wr + 16 * warp + 8 * j + t;
            wr2[j][0] = (g == 0) ? wp[0] : 0u;
            wr2[j][1] = (g == 0) ? wp[4] : 0u;
            ldsm_x4(x1[j], sb + OFF_TILE + (lr + 8 * (lm & 1)) * (ROWP * 2) + (lm >> 1) * 16 + warp * 64 + j * 32);
        }
#pragma unroll 1
        for (int it = 0; it < SPIN_MAX && ((v3 >> 16) != tag16 || (v4 >> 16) != tag16 || (v5 >> 16) != tag16); it++) load_consts();
        ((unsigned short*)M.sb)[tid] = (unsigned short)v3;
        ((unsigned short*)M.cb1)[tid] = (unsigned short)f2bits(1.0f + lo2f(v4));
        ((unsigned short*)M.gb)[tid] = (unsigned short)v5;
#pragma unroll 1
        for (int it = 0; it < SPIN_MAX; it++) {
            bool bad = false;
#pragma unroll
            for (int i = 0; i < 4; i++) if (v[i].x == SENT) { v[i] = ld_rlx2(vp + i * 256); bad = true; }
            if (!bad) break;
        }
        __syncwarp();
        float c1[4] = {0.f, 0.f, 0.f, 0.f}, cl[4] = {0.f, 0.f, 0.f, 0.f}, chh[4] = {0.f, 0.f, 0.f, 0.f};
#pragma unroll
        for (int j = 0; j < 2; j++) {
            x1[j][0] = add2(x1[j][0], movm(~v[2 * j].x)); x1[j][1] = add2(x1[j][1], movm(~v[2 * j].y));
            x1[j][2] = add2(x1[j][2], movm(~v[2 * j + 1].x)); x1[j][3] = add2(x1[j][3], movm(~v[2 * j + 1].y));
            mma_bf16(c1, x1[j][0], x1[j][1], x1[j][2], x1[j][3], 0x3F803F80u, 0x3F803F80u);
            mma_bf16(cl, x1[j][0], x1[j][1], x1[j][2], x1[j][3], x1[j][0], x1[j][2]);
            mma_bf16(chh, x1[j][0], x1[j][1], x1[j][2], x1[j][3], x1[j][1], x1[j][3]);
        }
        float* pp = (float*)&M.part[warp][g];
        if (t == 0) { pp[0] = c1[0]; pp[16] = c1[2]; }
        if (t == (g >> 1)) { pp[1] = (g & 1) ? cl[1] : cl[0]; pp[17] = (g & 1) ? chh[3] : chh[2]; }
    }
    CBAR();
    if (warp < 18) {
        const int tok = lane & 15, hf = lane >> 4;
        uint32_t kc[2][2][2];
#pragma unroll
        for (int j = 0; j < 2; j++)
#pragma unroll
            for (int q = 0; q < 2; q++) { kc[j][q][0] = ((const uint32_t*)M.cb1)[16 * warp + 8 * j + 4 * q + t]; kc[j][q][1] = ((const uint32_t*)M.sb)[16 * warp + 8 * j + 4 * q + t]; }
        named_bar(13, 608);
        uint32_t st[2][3];
#pragma unroll
        for (int h = 0; h < 2; h++) { const uint4 q = M.st2[g + 8 * h]; st[h][0] = q.x; st[h][1] = q.y; st[h][2] = q.z; }
        float rc[4] = {0.f, 0.f, 0.f, 0.f};
        uint32_t h2[2][4];
#pragma unroll
        for (int j = 0; j < 2; j++) {
#pragma unroll
            for (int r = 0; r < 4; r++) {
                h2[j][r] = add2(mul2(norm2(x1[j][r], st[r & 1][0], st[r & 1][1], st[r & 1][2]), kc[j][r >> 1][0]), kc[j][r >> 1][1]);
            }
            mma_bf16(rc, h2[j][0], h2[j][1], h2[j][2], h2[j][3], wr2[j][0], wr2[j][1]);
        }
        if (t == 0) { M.rp[warp][g] = rc[0]; M.rp[warp][g + 8] = rc[2]; }
        if (warp == 0) {
            named_bar(12, 576);
            float r = M.rp[9 * hf][tok];
#pragma unroll
            for (int i = 1; i < 9; i++) r += M.rp[9 * hf + i][tok];
            r += __shfl_xor_sync(0xffffffffu, r, 16);
            const uint32_t rbits = f2bits(r);
            const uint32_t key = 0x80000000u | ((rbits ^ ((rbits & 0x8000u) ? 0xFFFFu : 0x8000u)) << 11) | (uint32_t)(2047 - (16 * b + tok));
            int rank = 0;
#pragma unroll
            for (int j = 1; j < 16; j++) rank += __shfl_xor_sync(0xffffffffu, key, j) > key;
            if (lane < 16) { M.skey[rank] = key; M.rank[rank] = tok; }
            __syncwarp();
            if (lane < 2) st_rlx4(&S->rec[8 * b + 4 * lane], *(const uint4*)&M.skey[4 * lane]);
        } else named_arrive(12, 576);
#pragma unroll
        for (int j = 0; j < 2; j++) {
            uint32_t o[4];
#pragma unroll
            for (int r = 0; r < 4; r++) o[r] = add2(x1[j][r], mul2(((const uint32_t*)M.gb)[16 * warp + 8 * j + 4 * (r >> 1) + t], h2[j][r]));
            const uint32_t to = (lr + 8 * (lm & 1)) * (ROWP * 2) + (lm >> 1) * 16 + warp * 64 + j * 32;
            stsm_x4(sb + OFF_H2T + to, h2[j][0], h2[j][1], h2[j][2], h2[j][3]);
            stsm_x4(sb + OFF_TILE + to, o[0], o[1], o[2], o[3]);
        }
    } else if (warp == 19) {
        const int tok = lane & 15, hf = lane >> 4;
        float2 s = M.part[9 * hf][tok];
#pragma unroll
        for (int i = 1; i < 9; i++) { const float2 q = M.part[9 * hf + i][tok]; s.x += q.x; s.y += q.y; }
        s.x += __shfl_xor_sync(0xffffffffu, s.x, 16); s.y += __shfl_xor_sync(0xffffffffu, s.y, 16);
        float meanb, rinv;
        ln_stats(s.x, s.y, meanb, rinv);
        const float rh = bfr(rinv);
        if (lane < 16) M.st2[tok] = make_uint4(pack2(meanb, meanb), pack2(rh, rh), pack2(rinv - rh, rinv - rh), 0u);
        __syncwarp();
        named_arrive(13, 608);
    } else if (lane < 9) {
        PROXY_FENCE();
        if (lane == 0) mbar_expect(mb_wd, nf * D_ * 2);
        tma2d(sb + OFF_WD + lane * 5120, (b & 1) ? &tm_wd : &tm_wd32, 64 * lane, f0, mb_wd);
    }
    CBAR();
    uint32_t wf[9][4], wd[2][3][4];
    const int fmt = warp >> 2, fsl = warp & 3;
    auto load_wf = [&]() {
        mbar_wait(mb_wg, 0);
        mbar_wait(mb_wu, 0);
        if (fmt < 4 || nf > 32) {
            const int half = lm & 1;
            const uint32_t base = (fmt == 4) ? ((half ? OFF_WU : OFF_WG) + 64)
                                             : ((fmt >> 1) * OFF_WU + (((2 * (fmt & 1) + half) ^ ((b & 1) ? 0 : (lr >> 1))) << 4));
            const uint32_t wa = sb + base + (144 * fsl + lr + 8 * (lm >> 1)) * (2 * nf);
#pragma unroll
            for (int ks = 0; ks < 9; ks++) ldsm_x4_t(wf[ks], wa + ks * (32 * nf));
        }
    mbar_wait(mb_wd, 0);
    {
#pragma unroll
        for (int i = 0; i < 2; i++) {
            const int mt = warp + 20 * i;
            const uint32_t wa = sb + OFF_WD + (mt >> 2) * 5120 + lr * 128 + (((2 * (mt & 3) + (lm & 1)) ^ lr) << 4);
#pragma unroll
            for (int ks = 0; ks < 3; ks++)
                if ((i == 0 || warp < 16) && (ks < 2 || nf > 32)) ldsm_x4_t(wd[i][ks], wa + ks * 2048 + ((ks < 2) ? (lm >> 1) * 1024 : 0));
        }
    }
    };
    if (warp >= 8) {
        if (warp < 16) {
            const int tk = M.rank[warp - 8];
            const uint32_t* hp = (const uint32_t*)(sm + OFF_H2T + tk * (ROWP * 2)) + lane;
            uint4* dst = &S->h2w[(size_t)(16 * b + tk) * 96 + lane];
#pragma unroll
            for (int j = 0; j < 3; j++) st_rlx4(dst + 32 * j, make_uint4(hp[96 * j], hp[96 * j + 32], hp[96 * j + 64], epoch));
        }
        load_wf();
    } else {
        const uint4* rp = (const uint4*)S->rec + tid;
        load_wf();
        uint4 rk = ld_rlx4(rp);
#pragma unroll 1
        for (int it = 0; it < SPIN_MAX && !rk.x; it++) rk = ld_rlx4(rp);
        __syncwarp();
        uint32_t mine = 0;
#pragma unroll
        for (int rnd = 0; rnd < 8; rnd++) {
            const uint32_t m = __reduce_max_sync(0xffffffffu, rk.x);
            if (rk.x == m) { rk.x = rk.y; rk.y = rk.z; rk.z = rk.w; rk.w = 0u; }
            if (lane == rnd) mine = m;
        }
        if (lane < 8) M.cand[8 * warp + lane] = mine;
    }
    CBAR();
    uint32_t selv = 0;
    if (warp < 12) {
        uint2 k = *(const uint2*)&M.cand[2 * lane];
#pragma unroll
        for (int rnd = 0; rnd < 8; rnd++) {
            const uint32_t m = __reduce_max_sync(0xffffffffu, k.x);
            if (k.x == m) { k.x = k.y; k.y = 0u; }
            if (lr == rnd) selv = m;
        }
        if (tid < 8) M.skey[tid] = selv;
    }
    const uint32_t seltok = 2047u - (selv & 2047u);
    const int fo = tid >> 3;
    const int fW = 9 * b + (fo >> 2), fcomp = fo & 3;
    const int fd = 16 * (fW >> 5) + ((fW >> 2) & 7) + 8 * (fcomp >> 1), fk = 2 * (fW & 3) + (fcomp & 1);
    const uint32_t fsel = __shfl_sync(0xffffffffu, selv, fk);
    uint32_t fx = 0, fv = 0;
    bf16(*h2s)[ROWP] = (bf16(*)[ROWP])(sm + OFF_H2S);
    if (warp < 12) {
        uint4 wv[2];
        const uint4* hp[2];
#pragma unroll
        for (int r = 0; r < 2; r++) {
            const int wi = warp + 12 * r, k = wi / 3, j = wi - 3 * k;
            hp[r] = &S->h2w[(size_t)__shfl_sync(0xffffffffu, seltok, k) * 96 + 32 * j + lane];
            wv[r] = ld_rlx4(hp[r]);
        }
        if (tid < 288 && (tid & 7) == 0) {
            const uint32_t ft = 2047u - (fsel & 2047u), pr = (ft & 15u) >> 1;
            fx = ((const unsigned short*)x)[(size_t)ft * D_ + fd];
            asm volatile("ld.relaxed.gpu.global.u16 %0, [%1];" : "=r"(fv)
                         : "l"((const unsigned short*)S->v + ((size_t)(ft >> 4) * D_ + fd) * 16 + ((pr & 3u) * 2 + (pr >> 2)) * 2 + (ft & 1u)) : "memory");
        }
#pragma unroll 1
        for (int it = 0; it < SPIN_MAX && (wv[0].w != epoch || wv[1].w != epoch); it++) { wv[0] = ld_rlx4(hp[0]); wv[1] = ld_rlx4(hp[1]); }
#pragma unroll
        for (int r = 0; r < 2; r++) {
            const int wi = warp + 12 * r, k = wi / 3, j = wi - 3 * k;
            uint32_t* dst = (uint32_t*)&h2s[k][0] + 96 * j + lane;
            dst[0] = wv[r].x; dst[32] = wv[r].y; dst[64] = wv[r].z;
        }
    }
    CBAR();
    float* ffr = (float*)(sm + OFF_FFR);
    if (fmt < 4 || nf > 32) {
        float acc[2][4] = {{0.f, 0.f, 0.f, 0.f}, {0.f, 0.f, 0.f, 0.f}};
        const uint32_t ha = sb + OFF_H2S + lr * (ROWP * 2) + (144 * fsl) * 2 + lm * 16;
#pragma unroll
        for (int k2 = 0; k2 < 5; k2++) {
            uint32_t hb[4];
            ldsm_x4(hb, ha + k2 * 64 - ((k2 == 4) ? (lm >> 1) * 32 : 0));
            mma_bf16(acc[0], wf[2 * k2][0], wf[2 * k2][1], wf[2 * k2][2], wf[2 * k2][3], hb[0], hb[1]);
            if (k2 < 4) mma_bf16(acc[1], wf[2 * k2 + 1][0], wf[2 * k2 + 1][1], wf[2 * k2 + 1][2], wf[2 * k2 + 1][3], hb[2], hb[3]);
        }
        float* o = ffr + ((fsl * 80 + 16 * fmt + g) * 8 + 2 * t);
        *(float2*)o = make_float2(acc[0][0] + acc[1][0], acc[0][1] + acc[1][1]);
        *(float2*)(o + 64) = make_float2(acc[0][2] + acc[1][2], acc[0][3] + acc[1][3]);
    }
    CBAR();
    bf16(*act)[56] = (bf16(*)[56])(sm + OFF_ACT);
    if (tid < 384) {
        const int f = tid >> 3, a = tid & 7;
        float v = 0.f;
        if (f < nf) {
            const int rg = (f < 32) ? f : f + 32, ru = (f < 32) ? f + 32 : f + 40;
            const float* pg = ffr + rg * 8 + a;
            const float* pu = ffr + ru * 8 + a;
            float gg = bfr((pg[0] + pg[640]) + (pg[1280] + pg[1920]));
            gg = bfr(silu(gg));
            const float uu = bfr((pu[0] + pu[640]) + (pu[1280] + pu[1920]));
            v = gg * uu;
        }
        act[a][f] = __ushort_as_bfloat16((unsigned short)f2bits(v));
    }
    CBAR();
    {
        uint32_t bq[3][2];
#pragma unroll
        for (int ks = 0; ks < 3; ks++) {
            bq[ks][0] = *(const uint32_t*)&act[g][16 * ks + 2 * t];
            bq[ks][1] = *(const uint32_t*)&act[g][16 * ks + 2 * t + 8];
        }
#pragma unroll
        for (int i = 0; i < 2; i++) {
            if (i == 0 || warp < 16) {
                float acc[4] = {0.f, 0.f, 0.f, 0.f};
#pragma unroll
                for (int ks = 0; ks < 3; ks++)
                    if (ks < 2 || nf > 32) mma_bf16(acc, wd[i][ks][0], wd[i][ks][1], wd[i][ks][2], wd[i][ks][3], bq[ks][0], bq[ks][1]);
                const int W = (warp + 20 * i) * 32 + lane, c = (W * 7282) >> 16;
                st_rlx2(&S->part[(c * G_ + b) * 9 + W - 9 * c], ~pack2(acc[0], acc[1]), ~pack2(acc[2], acc[3]));
            }
        }
    }
    if (warp >= 4) {
        const int tk = warp - 4;
        if (!__any_sync(0xffffffffu, 2047u - (M.skey[lr] & 2047u) == (uint32_t)(16 * b + tk))) {
            const uint4* src = (const uint4*)(sm + OFF_TILE + tk * (ROWP * 2));
            uint4* dst = (uint4*)(out + (size_t)(16 * b + tk) * D_);
            dst[lane] = src[lane]; dst[lane + 32] = src[lane + 32];
            if (lane < 8) dst[lane + 64] = src[lane + 64];
        }
    }
    float4* fin = (float4*)(sm + OFF_FIN);
    uint32_t rb = (fsel >> 11) & 0xFFFFu;
    rb ^= (rb & 0x8000u) ? 0x8000u : 0xFFFFu;
    const float rs = bfr(__fdividef(1.0f, 1.0f + __expf(-lo2f(rb))));
    const float fh2 = (tid < 288) ? __bfloat162float(h2s[fk][fd]) : 0.f, fgb = (tid < 288) ? __bfloat162float(M.gb[fd]) : 0.f;
    const float fx1 = bfr(lo2f(fx) + lo2f(~fv));
    if (tid < 576) {
        const uint2* src = &S->part[(size_t)b * 1152 + tid];
        uint2 a = ld_rlx2(src), c = ld_rlx2(src + 576);
#pragma unroll 1
        for (int it = 0; it < SPIN_MAX && (a.x == SENT || c.x == SENT); it++) {
            if (a.x == SENT) a = ld_rlx2(src);
            if (c.x == SENT) c = ld_rlx2(src + 576);
        }
        fin[tid] = make_float4(lo2f(~a.x) + lo2f(~c.x), hi2f(~a.x) + hi2f(~c.x), lo2f(~a.y) + lo2f(~c.y), hi2f(~a.y) + hi2f(~c.y));
    }
    CBAR();
    if (tid < 288) {
        const int part = tid & 7;
        const float* f = (const float*)fin + part * 36 + fo;
        float s = ((f[0] + f[288]) + (f[576] + f[864])) + ((f[1152] + f[1440]) + (f[1728] + f[2016]));
        s += __shfl_xor_sync(0xffffffffu, s, 1);
        s += __shfl_xor_sync(0xffffffffu, s, 2);
        s += __shfl_xor_sync(0xffffffffu, s, 4);
        const float upd = bfr(bfr(s) * rs);
        const float ov = fx1 + bfr(fgb * bfr(fh2 + upd));
        if (part == 0) out[(size_t)(2047u - (fsel & 2047u)) * D_ + fd] = __ushort_as_bfloat16((unsigned short)f2bits(ov));
    }
    if ((warp & 3) == 2 && lane == 0) asm volatile("cp.async.bulk.wait_group 0;" ::: "memory");
    }
}

typedef CUresult (*EncodeFn)(CUtensorMap*, CUtensorMapDataType, cuuint32_t, void*, const cuuint64_t*, const cuuint64_t*,
                             const cuuint32_t*, const cuuint32_t*, CUtensorMapInterleave, CUtensorMapSwizzle,
                             CUtensorMapL2promotion, CUtensorMapFloatOOBfill);

static void make_map(EncodeFn fn, CUtensorMap* m, const void* ptr, uint64_t cols, uint64_t rows, uint32_t bc, uint32_t br,
                     CUtensorMapSwizzle sw) {
    cuuint64_t dims[2] = {cols, rows};
    cuuint64_t strides[1] = {cols * 2};
    cuuint32_t box[2] = {bc, br};
    cuuint32_t es[2] = {1, 1};
    CUresult rc = fn(m, CU_TENSOR_MAP_DATA_TYPE_BFLOAT16, 2, (void*)ptr, dims, strides, box, es, CU_TENSOR_MAP_INTERLEAVE_NONE,
                     sw, CU_TENSOR_MAP_L2_PROMOTION_NONE, CU_TENSOR_MAP_FLOAT_OOB_FILL_NONE);
    (void)rc;
}

static void launch(void* const* d_in, const int* in_sizes, int n_in, void* d_out, int out_size) {
    static EncodeFn enc = nullptr;
    static CUtensorMap tmm, tmg, tmu, tmd, tmd32, tmg32, tmu32;
    static Scratch* sp = nullptr;
    static const void* cached[4] = {nullptr, nullptr, nullptr, nullptr};
    if (!enc) {
        cudaDriverEntryPointQueryResult qr;
        void* fn = nullptr;
        cudaGetDriverEntryPoint("cuTensorMapEncodeTiled", &fn, cudaEnableDefault, &qr);
        enc = (EncodeFn)fn;
        cudaFuncSetAttribute(mega_kernel, cudaFuncAttributeMaxDynamicSharedMemorySize, SMEM_TOTAL);
        cudaGetSymbolAddress((void**)&sp, g_s);
    }
    if (cached[0] != d_in[13] || cached[1] != d_in[9] || cached[2] != d_in[10] || cached[3] != d_in[11]) {
        make_map(enc, &tmm, d_in[13], 6 * D_, D_, 32, 192, CU_TENSOR_MAP_SWIZZLE_64B);
        make_map(enc, &tmg, d_in[9], F_, D_, 40, 192, CU_TENSOR_MAP_SWIZZLE_NONE);
        make_map(enc, &tmu, d_in[10], F_, D_, 40, 192, CU_TENSOR_MAP_SWIZZLE_NONE);
        make_map(enc, &tmg32, d_in[9], F_, D_, 32, 192, CU_TENSOR_MAP_SWIZZLE_64B);
        make_map(enc, &tmu32, d_in[10], F_, D_, 32, 192, CU_TENSOR_MAP_SWIZZLE_64B);
        make_map(enc, &tmd, d_in[11], D_, F_, 64, 40, CU_TENSOR_MAP_SWIZZLE_128B);
        make_map(enc, &tmd32, d_in[11], D_, F_, 64, 32, CU_TENSOR_MAP_SWIZZLE_128B);
        cached[3] = d_in[11];
        cached[0] = d_in[13]; cached[1] = d_in[9]; cached[2] = d_in[10];
    }
    mega_kernel<<<G_, NTHR, SMEM_TOTAL>>>((const bf16*)d_in[0], (const bf16*)d_in[1], (const bf16*)d_in[2], (const bf16*)d_in[3],
                                          (const bf16*)d_in[4], (const bf16*)d_in[5], (const bf16*)d_in[12], sp, (const bf16*)d_in[6],
                                          (const bf16*)d_in[8], (const bf16*)d_in[11], (bf16*)d_out, tmm, tmg, tmu, tmd, tmd32, tmg32, tmu32);
}

}

extern "C" void kernel_launch(void* const* d_in, const int* in_sizes, int n_in, void* d_out, int out_size) {
    static int mode = -1;
    if (mode < 0) mode = v5::fits() ? 1 : 0;
    if (mode) v5::launch(d_in, in_sizes, n_in, d_out, out_size);
    else v4::launch(d_in, in_sizes, n_in, d_out, out_size);
}
```
